```python
import torch

def _softmax(x, axis=-1):
    return torch.softmax(x, dim=axis)
def _gelu(x):
    return torch.nn.functional.gelu(x, approximate="tanh")
def _silu(x):
    return torch.nn.functional.silu(x)
def _sigmoid(x):
    return torch.sigmoid(x)
def _layernorm(x, axis=-1, eps=1e-5):
    m = x.mean(dim=axis, keepdim=True)
    v = x.var(dim=axis, keepdim=True, unbiased=False)
    return (x - m) / torch.sqrt(v + eps)
def _scatter_add(tgt, idx, src, axis=0):
    return tgt.clone().index_add_(axis, idx, src)
def _segment_sum(src, seg, n):
    out = torch.zeros((n,) + src.shape[1:], dtype=src.dtype)
    return out.index_add_(0, seg, src)
def _pad(x, pw):
    flat = tuple(v for pair in reversed(pw) for v in pair)
    return torch.nn.functional.pad(x, flat)

kernel_name = 'interleave_layers__sliding_local_dilated__swiglu_ffn__prompt'

def setup_inputs():

    _w = (lambda a: (lambda t: t.to(torch.bfloat16) if t.is_floating_point() else t)(torch.as_tensor(a)))
    def _A_setup():
        B, S, D = 1, 2048, 1024
        return {
            "x": _w((lambda *s: torch.randn(*s, dtype=torch.bfloat16) * 0.05)(B, S, D)),
            "wqkv": _w((lambda *s: torch.randn(*s, dtype=torch.bfloat16) * 0.05)(D, 3 * D)),
            "wo": _w((lambda *s: torch.randn(*s, dtype=torch.bfloat16) * 0.05)(D, D)),
        }
    _A_in = _A_setup()

    def _B_setup():
        B, S, D, F = 1, 2048, 1024, 3584
        return {
            "x": _w((lambda *s: torch.randn(*s, dtype=torch.bfloat16) * 0.05)(B, S, D)),
            "w_gate": _w((lambda *s: torch.randn(*s, dtype=torch.bfloat16) * 0.05)(D, F)),
            "w_up": _w((lambda *s: torch.randn(*s, dtype=torch.bfloat16) * 0.05)(D, F)),
            "w_down": _w((lambda *s: torch.randn(*s, dtype=torch.bfloat16) * 0.05)(F, D)),
        }
    _B_in = _B_setup()

    return {
        "A_x": _A_in["x"],
        "A_wqkv": _A_in["wqkv"],
        "A_wo": _A_in["wo"],
        "B_x": _B_in["x"],
        "B_w_gate": _B_in["w_gate"],
        "B_w_up": _B_in["w_up"],
        "B_w_down": _B_in["w_down"],
    }

def reference(A_x, A_wqkv, A_wo, B_x, B_w_gate, B_w_up, B_w_down):
    def _A_ref(x, wqkv, wo):
        B, S, D = x.shape
        H = 32; Dh = D // H
        W, dil = 8, 2
        qkv = (lambda x, *d: x.permute(*d))((x @ wqkv).reshape(B, S, 3, H, Dh), 2, 0, 3, 1, 4)
        q, k, v = qkv[0], qkv[1], qkv[2]
        scale = Dh ** -0.5
        pos = torch.arange(S)
        off = torch.arange(W) * dil
        idx = pos[:, None] - off[None, :]
        mask = idx >= 0
        idx_c = torch.where(mask, idx, 0).reshape(-1)
        kg = k[:, :, idx_c, :].reshape(B, H, S, W, Dh)
        vg = v[:, :, idx_c, :].reshape(B, H, S, W, Dh)
        logits = torch.einsum("bhsd,bhswd->bhsw", q, kg) * scale
        logits = torch.where(mask[None, None, :, :], logits, -1e9)
        attn = _softmax(logits, axis=-1)
        o = torch.einsum("bhsw,bhswd->bhsd", attn, vg)
        return (lambda x, *d: x.permute(*d))(o, 0, 2, 1, 3).reshape(B, S, D) @ wo

    def _B_ref(x, w_gate, w_up, w_down):
        g = _silu(x @ w_gate)
        u = x @ w_up
        return (g * u) @ w_down

    x = A_x
    x = x + _A_ref(_layernorm(x, axis=-1), A_wqkv, A_wo)
    x = x + _B_ref(_layernorm(x, axis=-1), B_w_gate, B_w_up, B_w_down)
    x = x + _A_ref(_layernorm(x, axis=-1), A_wqkv, A_wo)
    x = x + _B_ref(_layernorm(x, axis=-1), B_w_gate, B_w_up, B_w_down)
    return x
```

```cpp
#include <cuda_runtime.h>
#include <cuda_bf16.h>
#include <cuda.h>
#include <stddef.h>
#include <stdint.h>
#include <string.h>

namespace {

typedef __nv_bfloat16 bf16;
typedef unsigned long long u64;
constexpr int S = 2048, D = 1024, F = 3584;
constexpr int STAGE = 49152, NSTAGE = 4, SLOT = 16384;
constexpr int STG_OFF = NSTAGE * STAGE, BAR_OFF = STG_OFF + 2 * SLOT, AUX_OFF = BAR_OFF + 336;
constexpr int SMEM_BYTES = AUX_OFF + 2736;
constexpr int SMEM_BASE = 1024;
constexpr int NPAIR = 66, JMAX = 24, KMAX = 296;
constexpr int T_Q = 0, T_O = 1, T_G = 2, T_D = 3;
constexpr uint32_t JOB_C = 1u << 18;
constexpr uint32_t K_LAST_A = 64, K_LAST_B = 128;
constexpr uint32_t JOB_EARLY = 1u << 21;
constexpr uint32_t JOB_X = JOB_EARLY;
#define RING_SUMS 14
#define REST_AT 0
constexpr int BOOT_PIECES = 4, BOOT_STEP = RING_SUMS < 16 ? 4 : 5, ST_STEP = 9;
constexpr int PREP = 3, LAST_LEAD = 3;
constexpr int LOOK = 2, MID = 7;
constexpr int NG = 2, PIECE = 8192, DEPTH = 2;
constexpr uint32_t SPIN_LIMIT = 1u << 21;

constexpr int C_X = 0;
constexpr int C_O = C_X + 48;
constexpr int C_H = C_O + 32;
constexpr int C_RD = C_H + 32;
constexpr int C_EP = C_RD + 64;
constexpr int C_LINES = C_EP + 5;

struct Scratch {
  bf16 h[S * F];
  uint32_t cnt[256 * 32];
  bf16 o[S / 2 * D];
  u64 stats[4 * S];
  bf16 o1[S / 2 * D];
  u64 cs[60 * 128];
  ulonglong2 halo[2 * 16 * 16 * 8 * 32];
};
constexpr uint32_t O_PLANE = offsetof(Scratch, o1) - offsetof(Scratch, o);
static_assert(C_LINES <= 256, "");
constexpr size_t PAGE = 2 << 20;
__device__ __align__(1024) char g_scratch[sizeof(Scratch) + PAGE];
Scratch* scratch_base() {
  char* p;
  cudaGetSymbolAddress((void**)&p, g_scratch);
  return (Scratch*)(p + (-(size_t)p & (PAGE - 1)));
}

uint32_t kJobs[NPAIR][JMAX] = {
  {0xe44200,0xc10020,0xc44040,0xc08009,0xc10082,0x4101001a,0xc10022,0xc1800b,0x184170b3,0x46610054,0x5b610034,0x7d41000e,0xc1001e,0xc10076,0xc10096,0xc14037,0xc40000,0xc40000,0xc40000,0xc40000,0xc40000,0xc40000,0xc40000,0xc40000},
  {0xe44000,0xc10018,0xc44080,0xc08009,0xc10021,0x22010052,0xc10092,0xc100aa,0xc09013,0x16410004,0x2d61004c,0x3461002c,0x4e410086,0xc10056,0x618100ae,0xc100b6,0xc1b02f,0xc40000,0xc40000,0xc40000,0xc40000,0xc40000,0xc40000,0xc40000},
  {0xc10000,0xc44140,0xc04001,0xc10042,0x3a01004a,0xc1006a,0xc100b2,0xc1201b,0x26413033,0x6440b00d,0x681001d,0x3281002d,0xd48100a6,0xc101be,0xc1e007,0xc40000,0xc40000,0xc40000,0xc40000,0xc40000,0xc40000,0xc40000,0xc40000,0xc40000},
  {0xc10010,0xc440c0,0xc04001,0xc10002,0x3b01008a,0xc1019a,0xc101aa,0xc0800b,0x1a40d01b,0xc10014,0x66410064,0x2810006,0xc1008e,0xc10066,0xc1007e,0xc0e087,0xc1003f,0xc40000,0xc40000,0xc40000,0xc40000,0xc40000,0xc40000,0xc40000},
  {0xc10048,0xe10058,0xe10070,0xc05039,0x21010012,0x7a01b003,0xc1003a,0x29410044,0x3561001c,0x4f61005c,0x5761003c,0x7e41004e,0x6081009e,0xc100be,0xc1c00f,0xc40000,0xc40000,0xc40000,0xc40000,0xc40000,0xc40000,0xc40000,0xc40000,0xc40000},
  {0xe44240,0xc443c0,0xe10158,0xc10130,0xc040e1,0x170101ca,0x620101da,0xc101f2,0x641905b,0xc07063,0x324100c5,0x7a61016c,0x12a1013c,0x288101d6,0xc101ee,0xc10236,0xc1a04f,0xc40000,0xc40000,0xc40000,0xc40000,0xc40000,0xc40000,0xc40000},
  {0xe44280,0xc44780,0xc10228,0x1f044840,0xe10270,0xc103ca,0x5e01039a,0xc103b2,0xc1042a,0xc103ba,0x6d4180bb,0x8810506,0xc100b5,0xd2810426,0xc103be,0xc1f097,0xc40000,0xc40000,0xc40000,0xc40000,0xc40000,0xc40000,0xc40000,0xc40000},
  {0xe44380,0xc102d0,0xc040c1,0xc10091,0x1101044a,0x67010452,0xc1046a,0xc104f2,0x2c4170ab,0x5240e0bb,0x5810486,0xc104ce,0xc10466,0xc1047e,0xc1f09f,0xc40000,0xc40000,0xc40000,0xc40000,0xc40000,0xc40000,0xc40000,0xc40000,0xc40000},
  {0xe442c0,0xc10320,0xc040c1,0x1d210338,0xc1054a,0x610105e2,0x7301e0cb,0xc10344,0xc1030c,0xc040bb,0x6041036c,0x1ca1033c,0x29810596,0x6c8105a6,0xc106f6,0xc1d0df,0xc40000,0xc40000,0xc40000,0xc40000,0xc40000,0xc40000,0xc40000,0xc40000},
  {0xe443c0,0xc10390,0xc44d80,0xc100d1,0x1501060a,0x64010612,0x720180c3,0x24106ba,0xc1038c,0x404103dc,0xc103f4,0x2c80c0e5,0x4d810656,0xc1066e,0xc1069e,0xc1a0ef,0xc40000,0xc40000,0xc40000,0xc40000,0xc40000,0xc40000,0xc40000,0xc40000},
  {0xc10088,0xe100e0,0xc10011,0x270100ca,0x6c01015a,0x7c01800b,0xc0d023,0x2140f0b3,0x516100dc,0xc10106,0xc1010e,0xc10166,0xc1013e,0xc1f017,0xc40000,0xc40000,0xc40000,0xc40000,0xc40000,0xc40000,0xc40000,0xc40000,0xc40000,0xc40000},
  {0xc10198,0xc101b0,0x1b0445c0,0xc44600,0xc446c0,0xc1030a,0x5d010322,0xc102f2,0xc0e04b,0xc101c4,0xc1707b,0x79410055,0xc07065,0xb0810075,0xd0810326,0xc10336,0xc1d05f,0xc40000,0xc40000,0xc40000,0xc40000,0xc40000,0xc40000,0xc40000},
  {0xc10050,0xc10060,0xc10038,0x29210078,0x3e010062,0xc10032,0x441901b,0x2461000c,0x36610024,0x5d410074,0x228100ad,0x5b810026,0xc1006e,0xc1005e,0xc1203f,0xc40000,0xc40000,0xc40000,0xc40000,0xc40000,0xc40000,0xc40000,0xc40000,0xc40000},
  {0xe44040,0xc444c0,0xc10168,0xc10049,0x1601024a,0x63010252,0xc10262,0xc1027a,0xc18073,0x55410045,0x48101c6,0xc1034e,0xc1035e,0xc1023e,0xc1e04f,0xc40000,0xc40000,0xc40000,0xc40000,0xc40000,0xc40000,0xc40000,0xc40000,0xc40000},
  {0xe44080,0xc44700,0xe10220,0xc09089,0xc103c2,0x5a010412,0xc10512,0xc103f2,0x1e41c0a3,0x4961021c,0x58410234,0x36a1027c,0x4881041e,0x7281051e,0xc10436,0xc1909f,0xc40000,0xc40000,0xc40000,0xc40000,0xc40000,0xc40000,0xc40000,0xc40000},
  {0xe44180,0xc44880,0xe102a0,0xc04081,0x1c2102f8,0xc104ca,0x66010462,0xc104ea,0xc104ba,0xc104fa,0xc102d4,0xc102ac,0x1d8104c6,0xc104d6,0x6d8104a6,0xc1053e,0xc0f087,0xc0c0b7,0xc40000,0xc40000,0xc40000,0xc40000,0xc40000,0xc40000},
  {0xe440c0,0xc44ac0,0xc10328,0xc07041,0xc080c9,0xc0c0e1,0xb2010592,0xc105aa,0xc106e2,0x1d4130db,0xc090e3,0x484100fb,0xc810546,0x3f81054e,0x5d810566,0xc1057e,0xc200c7,0xc40000,0xc40000,0xc40000,0xc40000,0xc40000,0xc40000,0xc40000},
  {0xe441c0,0xc44c40,0xc10398,0xc44d40,0xe103f0,0xc100f1,0xd0010692,0xc10632,0xc10672,0xc1067a,0x6f6103cc,0x736103a4,0x13810606,0xc1064e,0xc10626,0xc1067e,0xc0f0e7,0xc0e0ff,0xc40000,0xc40000,0xc40000,0xc40000,0xc40000,0xc40000},
  {0xe44300,0xc100a0,0xc04001,0xc100c2,0x3c010112,0x7b01d003,0x741013a,0x234100c4,0x374100d4,0xc100ac,0x39a100fc,0xc10156,0x6981012e,0xc1019e,0xc1b01f,0xc40000,0xc40000,0xc40000,0xc40000,0xc40000,0xc40000,0xc40000,0xc40000,0xc40000},
  {0xe44340,0xc101d8,0xc09041,0xc10051,0x24010352,0xc1032a,0xc1b053,0x12410073,0xe101dc,0xe101ac,0xc10286,0x40810296,0x758102a6,0xc102e6,0xc19057,0xc40000,0xc40000,0xc40000,0xc40000,0xc40000,0xc40000,0xc40000,0xc40000,0xc40000},
  {0xc10008,0xc44000,0xc44100,0xe10068,0xc10029,0x3601009a,0xc1002a,0xc100a2,0xc1007a,0x3041803b,0xc0b095,0x10810046,0x41810016,0x7881002e,0xc1003e,0xc19037,0xc40000,0xc40000,0xc40000,0xc40000,0xc40000,0xc40000,0xc40000,0xc40000},
  {0xc10110,0xc44440,0xe10160,0xc101c2,0x4201021a,0xc10222,0xc10272,0xc101fa,0x3f410104,0x5e610114,0xc100dd,0x2081024e,0x5c8101e6,0xc101fe,0xc10047,0xc1007f,0xc40000,0xc40000,0xc40000,0xc40000,0xc40000,0xc40000,0xc40000,0xc40000},
  {0xc10200,0xc44a00,0xc10260,0x3010402,0x4301050a,0xc10422,0xc0808b,0xc10432,0xc10244,0xe10214,0xc0b08d,0x7810386,0xc1050e,0x5f8103e6,0xc103fe,0xc1f0a7,0xc40000,0xc40000,0xc40000,0xc40000,0xc40000,0xc40000,0xc40000,0xc40000},
  {0xc102c0,0xc44900,0xc102b0,0x40449c0,0x120100b1,0x3801045a,0xc10472,0xa41a093,0x3d8102c4,0x4fa10294,0xe102e4,0xe102bc,0xc10516,0xc104e6,0xc104fe,0xc1b08f,0xc40000,0xc40000,0xc40000,0xc40000,0xc40000,0xc40000,0xc40000,0xc40000},
  {0xc10308,0xe10350,0xc44b00,0xe10378,0xc070f9,0x3f01059a,0xc105f2,0xc105ba,0x134105fa,0xe1034c,0xe10364,0xc106c6,0xc10556,0xc1055e,0xc105f6,0xc1e0ef,0xc40000,0xc40000,0xc40000,0xc40000,0xc40000,0xc40000,0xc40000,0xc40000},
  {0xc10388,0xe103e0,0xc44d00,0xc10682,0x5801065a,0xc106aa,0xc41b0d3,0xc110eb,0x4a4130fb,0x3810686,0xc106ce,0xc106ee,0xc106a6,0xc1e0d7,0xc40000,0xc40000,0xc40000,0xc40000,0xc40000,0xc40000,0xc40000,0xc40000,0xc40000,0xc40000},
  {0xe44100,0xc44180,0xe100d8,0xc44280,0xc10019,0x1001010a,0xc0b039,0xc10172,0xc1016a,0x1441a02b,0x4241009c,0xb8100f4,0x24810146,0x5981003d,0xf08100f6,0xc19017,0xc0c03f,0xc40000,0xc40000,0xc40000,0xc40000,0xc40000,0xc40000,0xc40000},
  {0xe44140,0xc101a0,0xc44640,0xc10059,0x1301028a,0x6501029a,0xc08079,0x71014053,0xc180e3,0xc0e07b,0xc101b4,0x37a101bc,0x4981007d,0x668102b6,0xc1033e,0xc1806f,0xc40000,0xc40000,0xc40000,0xc40000,0xc40000,0xc40000,0xc40000,0xc40000},
  {0x2e010040,0xe10028,0xe10030,0xc1000a,0x6801005a,0xc10072,0x40f013,0x104100ba,0x56410005,0x7161006c,0x14a1007c,0x2a810035,0x68810036,0xc1018e,0xc18027,0xc40000,0xc40000,0xc40000,0xc40000,0xc40000,0xc40000,0xc40000,0xc40000,0xc40000},
  {0xc10150,0xe10118,0xc44680,0xc10069,0x2f0101d2,0x7701c043,0x541023a,0x2241006b,0x4741011c,0xc10174,0x2f81020e,0xc1025e,0x7a8101f6,0xc10256,0xc0c05f,0xc0a077,0xc40000,0xc40000,0xc40000,0xc40000,0xc40000,0xc40000,0xc40000,0xc40000},
  {0xc10208,0xc44740,0xc447c0,0xc04081,0xc07089,0x100a9,0xb00103da,0x7501d083,0x34103fa,0xe1020c,0xe10254,0xe1022c,0xc1038e,0xc1039e,0x768103b6,0xc1d08f,0xc0a0bf,0xc40000,0xc40000,0xc40000,0xc40000,0xc40000,0xc40000,0xc40000},
  {0xc10290,0xc44940,0xc102f0,0x5010099,0x200080b9,0xd201049a,0xc104a2,0xc1047a,0xc0e09b,0x3e6102cc,0x5f40707b,0xc102f4,0x2b81048e,0xc1049e,0x7b8104b6,0xc104de,0xc160b7,0xc40000,0xc40000,0xc40000,0xc40000,0xc40000,0xc40000,0xc40000},
  {0xc10318,0xc10358,0xc44b80,0xc10542,0x59010552,0xc1056a,0xc10572,0xc1c0eb,0x4b610314,0x59610374,0x7f61037c,0x158100fd,0x648105ae,0xc105e6,0xc180c7,0xc40000,0xc40000,0xc40000,0xc40000,0xc40000,0xc40000,0xc40000,0xc40000,0xc40000},
  {0xc103c0,0xc44c00,0xc103e8,0x6010602,0x4401061a,0xc090f9,0x7401a0cb,0xc170e3,0xc0d0fb,0xc103ec,0xc040e5,0x2e81068e,0xc1065e,0x7e8106b6,0xc1b0df,0xc0a0ff,0xc40000,0xc40000,0xc40000,0xc40000,0xc40000,0xc40000,0xc40000,0xc40000},
  {0xc100c8,0xc44240,0xc100b0,0x7010102,0x450100da,0xc1012a,0xc100f2,0xc100fa,0xe1008c,0xe10094,0xc0500d,0x1810186,0xc10196,0x6781016e,0xc100fe,0xc1d02f,0xc40000,0xc40000,0xc40000,0xc40000,0xc40000,0xc40000,0xc40000,0xc40000},
  {0xc101d0,0xe101e0,0xc100a1,0x250102ca,0x6e01031a,0x7e0102b2,0xc102ba,0xc0a06b,0x3161018c,0x676101ec,0x744102c6,0xc102d6,0x6f8102ae,0xc1032e,0xc1b067,0xc40000,0xc40000,0xc40000,0xc40000,0xc40000,0xc40000,0xc40000,0xc40000,0xc40000},
  {0xc10108,0xe10170,0xe10138,0xc08079,0x3701025a,0xc10232,0xc1404b,0x1b410144,0x2e610154,0x38610164,0x68410206,0xc101ce,0xc10226,0xc1037e,0xc1d067,0xc40000,0xc40000,0xc40000,0xc40000,0xc40000,0xc40000,0xc40000,0xc40000,0xc40000},
  {0xc10218,0xc10258,0xc10278,0x2a01040a,0xc080b9,0xc103ea,0xc1308b,0x1f41053a,0xc10085,0x7c61026c,0x16810406,0x478103d6,0x738103ae,0xc1042e,0xc19097,0xc40000,0xc40000,0xc40000,0xc40000,0xc40000,0xc40000,0xc40000,0xc40000,0xc40000},
  {0xc102c8,0xe102a8,0xc04081,0x1010482,0x5b010492,0x7601b083,0x941809b,0xe1028c,0xe102a4,0xc05095,0x11810446,0x42810496,0xc1046e,0xc104be,0xc190a7,0xc40000,0xc40000,0xc40000,0xc40000,0xc40000,0xc40000,0xc40000,0xc40000,0xc40000},
  {0xc10348,0xc44bc0,0xc10370,0x80105c2,0x4601058a,0x790200c3,0x14160db,0x3c410354,0x61610324,0x754105c6,0xc105d6,0x658106e6,0xc105fe,0xc1d0cf,0xc40000,0xc40000,0xc40000,0xc40000,0xc40000,0xc40000,0xc40000,0xc40000,0xc40000,0xc40000},
  {0xc103d0,0xc103a8,0xc103f8,0x2b01064a,0x6901062a,0xc1069a,0xc106b2,0x27410384,0x394103d4,0x7b6103e4,0x17810646,0x448106d6,0xc106ae,0xc106be,0xc1a0e7,0xc40000,0xc40000,0xc40000,0xc40000,0xc40000,0xc40000,0xc40000,0xc40000,0xc40000},
  {0xc100d0,0xe100a8,0xc100d9,0x2801018a,0x6d010132,0x7d010162,0xc1017a,0xc1102b,0x4140d03b,0xfa100ec,0x1b8100ce,0xc1015e,0x7d810136,0xc1a007,0xc0b037,0xc40000,0xc40000,0xc40000,0xc40000,0xc40000,0xc40000,0xc40000,0xc40000,0xc40000},
  {0xc10190,0xc44580,0xc101f0,0x9010282,0x47010292,0xc102da,0xc102e2,0xc1033a,0xc10073,0x536101e4,0xc10306,0xc10356,0xc1029e,0xc102be,0xc1f057,0xc40000,0xc40000,0xc40000,0xc40000,0xc40000,0xc40000,0xc40000,0xc40000,0xc40000},
  {0xc10148,0xc44400,0xc10128,0xa010202,0x4801020a,0xc101ea,0xc1604b,0x1c41037a,0x6e61010c,0x76610124,0x18810246,0xc10216,0x63810266,0xc1027e,0xc13047,0xc0a0bf,0xc40000,0xc40000,0xc40000,0xc40000,0xc40000,0xc40000,0xc40000,0xc40000},
  {0xc10248,0xc44a40,0xc10268,0xb010382,0x490103d2,0xc103aa,0xc10532,0xc1043a,0xc120b3,0x50410264,0x8103c6,0xc10396,0xc103a6,0xc1043e,0xc1e0af,0xc40000,0xc40000,0xc40000,0xc40000,0xc40000,0xc40000,0xc40000,0xc40000,0xc40000},
  {0xc10288,0x2c2102d8,0xe102b8,0xc1048a,0x6a0104d2,0xc104aa,0xc1052a,0x284150ab,0x5440e0bb,0xa81009d,0x34a102fc,0x4a81045e,0xc10476,0xc104ee,0xc110bf,0xc40000,0xc40000,0xc40000,0xc40000,0xc40000,0xc40000,0xc40000,0xc40000,0xc40000},
  {0xc10340,0xc44a80,0xc10368,0xc010582,0x4a0106da,0xc105d2,0xc105ea,0xc106fa,0xc130f3,0x654100cd,0x1f810586,0xc105ce,0x6e8105ee,0xc105be,0xc0f0e7,0xc0c0f7,0xc40000,0xc40000,0xc40000,0xc40000,0xc40000,0xc40000,0xc40000,0xc40000},
  {0xc103d8,0xc44cc0,0xc040c1,0xc103b8,0x140106ca,0x5f010662,0xc106a2,0xc106ea,0xc1d0f3,0xc080fb,0xe8100d5,0x2381060e,0x5881061e,0xc10636,0xc106fe,0xc120ff,0xc40000,0xc40000,0xc40000,0xc40000,0xc40000,0xc40000,0xc40000,0xc40000},
  {0xc10080,0xc441c0,0xc04001,0xc10142,0x3d0100d2,0xc101a2,0xc101ba,0xc12023,0x2540d02b,0x4340c03b,0x72410015,0x2681014e,0xc1011e,0xc100ee,0xc101a6,0xc0a027,0xc0a03f,0xc40000,0xc40000,0xc40000,0xc40000,0xc40000,0xc40000,0xc40000},
  {0xc10180,0xc44500,0xc101f8,0xd010302,0x4b0102d2,0x7801c043,0x8420063,0xc080f3,0x6241004d,0x1e809065,0x218100f5,0xd6810366,0xc102f6,0xc2006f,0xc40000,0xc40000,0xc40000,0xc40000,0xc40000,0xc40000,0xc40000,0xc40000,0xc40000,0xc40000},
  {0xc10140,0xc44380,0xc10120,0xe010342,0x4c01035a,0xc1022a,0xc1026a,0xc1e06b,0x4540c07b,0xc10134,0x3581006d,0x458101de,0x7c810276,0xc10376,0xc15077,0xc40000,0xc40000,0xc40000,0xc40000,0xc40000,0xc40000,0xc40000,0xc40000,0xc40000},
  {0xc10240,0xc44800,0xe10230,0xc10502,0x4d010392,0xc1041a,0xc103a2,0xc1209b,0x2040c0ab,0x4441025c,0xd810274,0x2581040e,0xc103de,0x7f8103f6,0xc10526,0xc130bf,0xc40000,0xc40000,0xc40000,0xc40000,0xc40000,0xc40000,0xc40000,0xc40000},
  {0xc10298,0xc448c0,0xc102e8,0xf010442,0x4e0104da,0xc10522,0xc104b2,0xc1c0a3,0x4c41029c,0x706102b4,0x1981044e,0x5a8100bd,0x6a810536,0xc1052e,0xc160b7,0xc40000,0xc40000,0xc40000,0xc40000,0xc40000,0xc40000,0xc40000,0xc40000,0xc40000},
  {0xc10300,0xe10330,0xc44dc0,0xc100e9,0xb401055a,0xc105a2,0xc105b2,0xc106f2,0xc0b0eb,0x4d61035c,0x5a61032c,0xc1058e,0xc1059e,0x7781056e,0xc105de,0xc170f7,0xc40000,0xc40000,0xc40000,0xc40000,0xc40000,0xc40000,0xc40000,0xc40000},
  {0xc103c8,0xe103a0,0xc04081,0x2010642,0x5c010652,0xc10622,0xb41d0d3,0x3c8103c4,0x4ba1039c,0xe103b4,0xe103bc,0xc10616,0xc1062e,0xc1063e,0xc1a0d7,0xc40000,0xc40000,0xc40000,0xc40000,0xc40000,0xc40000,0xc40000,0xc40000,0xc40000},
  {0xc100c0,0xc442c0,0xc100b8,0x192100f8,0x2301014a,0xc100e2,0xc100ea,0xc19023,0x336100cc,0x694100e4,0x3aa100bc,0xc10116,0xc101ae,0xc1017e,0xc1d01f,0xc40000,0xc40000,0xc40000,0xc40000,0xc40000,0xc40000,0xc40000,0xc40000,0xc40000},
  {0xc10188,0xe101a8,0xc080c9,0x18010071,0x400102a2,0xc102ea,0xc10332,0x11410184,0x2f6101d4,0x3a6101a4,0x6a410346,0xc102ce,0xc102de,0xc1036e,0xc15047,0xc0a07f,0xc40000,0xc40000,0xc40000,0xc40000,0xc40000,0xc40000,0xc40000,0xc40000},
  {0xc10100,0xc44480,0xc10178,0xc10242,0x4f010212,0xc101e2,0xe41f05b,0x2b61014c,0x3b61015c,0x6b61012c,0x7761017c,0x1a81021e,0x7481022e,0xc1026e,0xc19077,0xc40000,0xc40000,0xc40000,0xc40000,0xc40000,0xc40000,0xc40000,0xc40000,0xc40000},
  {0xc10210,0x2d210250,0xe10238,0xc1038a,0x6b0103e2,0x7001d08b,0x19410204,0xe1024c,0xe10224,0xe1023c,0xc040a5,0x4e8103ce,0xc103ee,0xc10416,0xc1a0af,0xc40000,0xc40000,0xc40000,0xc40000,0xc40000,0xc40000,0xc40000,0xc40000,0xc40000},
  {0xc10280,0xc44980,0xc102e0,0xc104c2,0x5401051a,0xc104e2,0xd41e093,0xc10284,0xc102dc,0xc102ec,0xc0c0a5,0x3e810456,0x6b8104ae,0xc104f6,0xc1b087,0xc40000,0xc40000,0xc40000,0xc40000,0xc40000,0xc40000,0xc40000,0xc40000,0xc40000},
  {0xc10310,0xc44b40,0xc10360,0xc106c2,0x550105ca,0xc10562,0xc105da,0xc1057a,0xc10304,0xc1031c,0xc10334,0x278100ed,0x438106de,0xc10576,0xc105b6,0xc150f7,0xc40000,0xc40000,0xc40000,0xc40000,0xc40000,0xc40000,0xc40000,0xc40000},
  {0xc10380,0xc44c80,0xc040c1,0x1e2103b0,0xc1068a,0x600106d2,0xc1066a,0xc1063a,0xc0f0db,0x3d610394,0x6c4103ac,0x3ba103fc,0xc10696,0xc10666,0xc10676,0xc0f0cf,0xc0e0ff,0xc40000,0xc40000,0xc40000,0xc40000,0xc40000,0xc40000,0xc40000},
  {0xc10090,0xc44200,0xc100e8,0x1a044340,0xc10031,0x39010152,0xc10122,0xc101b2,0x17410084,0xc11033,0x5c40703b,0xc100b4,0x2d810025,0x468100de,0x79810176,0xc101b6,0xc16027,0xc40000,0xc40000,0xc40000,0xc40000,0xc40000,0xc40000,0xc40000},
  {0xc101c8,0xc101e8,0xc10061,0x2601034a,0x6f0102aa,0x7f01036a,0xc102fa,0xe101cc,0xc1019c,0xc101f4,0x38a101fc,0x4c810316,0xc102ee,0xc1030e,0xc0c0cf,0xc0e07f,0xc40000,0xc40000,0xc40000,0xc40000,0xc40000,0xc40000,0xc40000,0xc40000},
  {0xc10098,0xc44300,0xc100f0,0xc10182,0x56010192,0xc1011a,0xf420013,0x2a414033,0x636100a4,0x784100c6,0xc100d6,0x628100e6,0xc10126,0xc1c00f,0xc40000,0xc40000,0xc40000,0xc40000,0xc40000,0xc40000,0xc40000,0xc40000,0xc40000,0xc40000},
  {0xc101c0,0xc44540,0xc101b8,0xc102c2,0x57010312,0xc10362,0xc10372,0xc09053,0x15411063,0xc10194,0xc0508d,0x981005d,0x3381028e,0x5e81031e,0xc102fe,0xc0f05f,0xc1007f,0xc40000,0xc40000,0xc40000,0xc40000,0xc40000,0xc40000,0xc40000},
};
uint8_t kSeq[NPAIR][KMAX] = {
  {0,1,2,3,0,1,2,3,4,5,6,7,8,9,10,11,12,13,14,15,0,1,2,3,64,67,72,78,76,70,66,74,64,66,76,78,65,67,77,79,68,70,69,71,72,74,73,75,4,6,0,2,5,7,1,3,12,14,8,10,13,15,9,11,4,6,8,10,0,2,5,7,9,11,12,14,1,3,13,15,88,89,94,95,116,117,118,119,106,107,78,79,82,83,112,113,84,85,102,103,98,99,72,73,72,73,80,81,98,99,74,75,110,111,112,113,86,87,92,93,78,79,64,65,66,67,84,68,70,69,71,76,78,72,74,64,66,77,79,73,75,65,67,68,70,72,74,69,71,64,66,76,78,73,75,65,67,77,79,8,10,0,2,9,11,12,14,1,3,4,6,13,15,5,7,12,14,8,10,4,6,0,2,13,15,9,11,5,7,1,3,12,14,8,10,13,15,4,6,9,11,5,7,0,2,1,3,200,202,73,75,196,198,192,194,204,206,197,199,193,195,205,207,71,66,67,112,113,98,99,86,87,110,111,114,115,88,89,118,119,196,197,230,0,0,0,0,0,0,0,0,0,0,0,0,0,0,0,0,0,0,0,0,0,0,0,0,0,0,0,0,0,0,0,0,0,0,0,0,0,0,0,0,0,0,0,0,0,0,0,0,0,0,0,0,0},
  {0,1,2,3,0,1,2,3,4,5,6,7,8,9,10,11,12,13,14,15,0,1,2,3,77,69,73,79,65,68,75,71,70,64,76,66,74,72,79,71,78,67,69,65,75,77,68,73,12,14,8,10,13,15,9,11,0,2,4,6,1,3,5,7,76,78,72,74,77,79,73,75,64,66,68,70,65,67,69,71,4,6,12,14,8,10,0,2,5,7,13,15,9,11,1,3,114,115,100,101,74,75,116,117,118,0,2,4,6,8,10,1,3,5,7,12,14,9,11,13,15,76,78,68,70,77,79,64,66,72,74,69,71,65,67,73,75,12,14,4,6,0,2,13,15,5,7,8,10,1,3,9,11,8,10,12,14,0,2,9,11,13,15,1,3,4,6,5,7,8,10,9,11,4,6,0,2,12,14,5,7,1,3,13,15,4,6,12,14,8,10,5,7,13,15,9,11,0,2,1,3,12,14,8,10,13,15,4,6,9,11,5,7,128,130,1,3,99,64,65,80,81,92,93,108,109,106,107,70,71,66,67,90,91,88,89,82,83,224,225,232,233,230,231,0,0,0,0,0,0,0,0,0,0,0,0,0,0,0,0,0,0,0,0,0,0,0,0,0,0,0,0,0,0,0,0,0,0,0,0,0,0,0,0,0,0,0,0,0,0,0,0,0,0,0,0},
  {64,65,66,67,68,69,70,71,72,73,74,75,76,77,78,79,0,1,2,3,79,75,77,73,0,2,12,14,1,3,13,15,4,6,5,7,8,10,9,11,64,66,72,74,65,67,73,75,76,78,68,70,77,79,69,71,4,6,12,14,8,10,0,2,5,7,13,15,9,11,1,3,0,2,8,10,4,6,12,14,1,3,9,11,5,7,13,15,83,98,99,108,109,92,93,78,79,84,85,100,101,66,67,74,75,88,66,67,84,85,68,69,90,91,104,105,70,71,210,211,228,229,106,107,222,71,72,69,66,64,78,74,77,76,75,73,64,71,78,77,69,72,75,70,74,79,76,73,68,67,66,65,64,71,78,74,77,70,73,69,66,72,76,79,68,65,67,75,4,6,5,7,8,10,12,14,9,11,13,15,0,2,1,3,4,6,12,14,8,10,5,7,13,15,0,2,9,11,1,3,106,107,104,105,92,93,88,89,72,73,90,91,100,101,78,79,116,117,64,65,118,119,208,209,94,95,76,77,240,241,0,0,0,0,0,0,0,0,0,0,0,0,0,0,0,0,0,0,0,0,0,0,0,0,0,0,0,0,0,0,0,0,0,0,0,0,0,0,0,0,0,0,0,0,0,0,0,0,0,0,0,0,0,0,0,0,0,0,0,0,0,0,0,0,0,0},
  {0,1,2,3,4,5,6,7,8,9,10,11,12,13,14,15,0,1,2,3,66,74,68,64,0,2,12,14,1,3,13,15,4,6,5,7,8,10,9,11,64,66,72,74,65,67,73,75,76,78,68,70,77,79,69,71,4,6,0,2,5,7,1,3,12,14,8,10,13,15,9,11,4,6,12,14,8,10,0,2,5,7,13,15,9,11,1,3,92,93,64,65,100,101,96,97,89,76,77,96,97,86,87,72,73,116,117,110,111,4,6,5,7,12,14,8,10,0,2,13,15,9,11,1,3,0,2,1,3,4,6,8,10,12,14,5,7,9,11,13,15,8,10,12,14,0,2,9,11,13,15,1,3,4,6,5,7,8,10,0,2,9,11,12,14,1,3,4,6,13,15,5,7,4,6,5,7,8,10,12,14,9,11,13,15,0,2,1,3,4,6,12,14,8,10,5,7,13,15,0,2,9,11,1,3,77,112,113,110,111,82,83,70,71,68,69,102,103,108,80,81,66,67,90,91,96,97,242,243,202,203,70,199,238,239,0,0,0,0,0,0,0,0,0,0,0,0,0,0,0,0,0,0,0,0,0,0,0,0,0,0,0,0,0,0,0,0,0,0,0,0,0,0,0,0,0,0,0,0,0,0,0,0,0,0,0,0,0,0,0,0,0,0,0,0,0},
  {64,65,66,67,68,69,70,71,72,73,74,75,76,77,78,79,64,65,66,67,68,69,70,71,72,73,74,75,76,77,78,79,64,65,66,67,68,69,70,71,72,73,74,75,76,77,78,79,198,69,194,199,204,12,14,8,10,13,15,9,11,0,2,4,6,1,3,5,7,70,71,64,65,98,99,92,93,78,79,112,113,94,95,72,73,80,81,84,85,114,115,116,117,106,107,66,8,10,0,2,9,11,1,3,12,14,13,15,4,6,5,7,0,2,4,6,8,10,1,3,5,7,12,14,9,11,13,15,4,6,5,7,0,2,8,10,12,14,1,3,9,11,13,15,68,70,69,71,64,66,72,74,76,78,65,67,73,75,77,79,132,134,128,130,133,135,129,131,136,138,140,142,137,139,141,143,8,10,0,2,9,11,12,14,1,3,4,6,13,15,5,7,12,14,8,10,4,6,0,2,13,15,9,11,5,7,1,3,4,6,12,14,8,10,5,7,13,15,0,2,137,139,1,3,92,93,108,109,98,99,80,81,100,101,70,71,116,117,96,97,74,75,64,65,112,113,82,83,234,235,212,213,0,0,0,0,0,0,0,0,0,0,0,0,0,0,0,0,0,0,0,0,0,0,0,0,0,0,0,0,0,0,0,0,0,0,0,0,0,0,0,0,0,0,0,0},
  {0,1,2,3,0,1,2,3,0,1,2,3,4,5,6,7,8,9,10,11,12,13,14,15,0,1,2,3,4,5,6,7,8,9,10,11,12,13,14,15,70,64,76,66,0,2,8,10,1,3,9,11,12,14,4,6,13,15,5,7,4,6,0,2,5,7,1,3,12,14,8,10,13,15,9,11,0,2,8,10,4,6,12,14,1,3,9,11,5,7,13,15,93,78,79,84,85,100,101,66,67,74,75,88,89,76,77,96,97,86,87,72,73,116,117,110,111,84,85,88,89,114,115,110,66,71,70,77,69,73,72,64,65,78,67,75,79,74,76,68,12,14,4,6,0,2,13,15,5,7,8,10,1,3,9,11,132,134,128,130,133,135,129,131,136,138,140,142,137,139,141,143,8,10,9,11,4,6,0,2,12,14,5,7,1,3,13,15,4,6,12,14,8,10,5,7,13,15,9,11,0,2,1,3,140,142,136,138,141,143,132,134,137,139,133,135,128,130,129,131,72,73,86,87,102,103,90,91,118,119,68,69,206,207,114,115,66,67,110,111,94,95,88,217,204,205,0,0,0,0,0,0,0,0,0,0,0,0,0,0,0,0,0,0,0,0,0,0,0,0,0,0,0,0,0,0,0,0,0,0,0,0,0,0,0,0,0,0,0,0,0,0,0,0,0,0},
  {0,1,2,3,0,1,2,3,0,1,2,3,4,5,6,7,8,9,10,11,12,13,14,15,0,1,2,3,0,1,2,3,4,5,6,7,8,9,10,11,12,13,14,15,0,2,8,10,1,3,9,11,12,14,4,6,13,15,5,7,4,6,0,2,5,7,1,3,12,14,8,10,13,15,9,11,0,2,8,10,4,6,12,14,1,3,9,11,5,7,13,15,4,6,12,14,8,10,0,2,5,7,13,15,9,11,1,3,8,10,0,2,9,11,1,3,12,14,13,15,4,6,5,7,204,205,236,237,240,241,210,211,226,227,228,229,192,193,200,201,208,209,202,203,212,213,214,215,8,10,12,14,0,2,9,11,13,15,1,3,4,6,5,7,78,74,77,71,70,64,66,69,79,200,75,68,204,73,195,65,4,6,5,7,8,10,12,14,9,11,13,15,0,2,1,3,132,134,140,142,136,138,133,135,141,143,128,130,137,139,129,131,99,102,103,86,87,104,105,78,79,118,119,114,115,88,89,112,113,100,101,64,65,84,85,94,95,224,225,82,83,196,197,0,0,0,0,0,0,0,0,0,0,0,0,0,0,0,0,0,0,0,0,0,0,0,0,0,0,0,0,0,0,0,0,0,0,0,0,0,0,0,0,0,0,0,0,0,0,0,0,0,0,0,0,0},
  {0,1,2,3,0,1,2,3,4,5,6,7,8,9,10,11,12,13,14,15,66,74,68,64,64,74,76,66,68,70,65,72,79,67,69,71,78,75,77,73,0,2,8,10,1,3,9,11,12,14,4,6,13,15,5,7,12,14,8,10,13,15,9,11,0,2,4,6,1,3,5,7,4,6,12,14,8,10,0,2,5,7,13,15,9,11,1,3,0,2,8,10,4,6,12,14,1,3,9,11,5,7,13,15,99,100,101,90,91,70,71,76,77,68,69,110,111,82,83,74,75,96,97,118,119,104,105,238,239,242,243,232,233,218,219,220,221,230,231,196,197,8,10,12,14,0,2,9,11,13,15,1,3,4,6,5,7,8,10,0,2,9,11,12,14,1,3,4,6,13,15,5,7,4,6,5,7,8,10,12,14,9,11,13,15,0,2,1,3,4,6,140,142,136,138,133,135,141,143,128,130,137,139,129,131,80,81,96,97,92,93,108,109,70,71,82,83,100,101,78,79,74,75,114,115,94,95,118,119,200,201,192,193,240,241,226,0,0,0,0,0,0,0,0,0,0,0,0,0,0,0,0,0,0,0,0,0,0,0,0,0,0,0,0,0,0,0,0,0,0,0,0,0,0,0,0,0,0,0,0,0,0,0,0,0,0,0,0,0,0,0,0,0,0,0,0},
  {0,1,2,3,0,1,2,3,4,5,6,7,8,9,10,11,12,13,14,15,69,76,67,65,128,129,130,131,132,133,134,135,136,137,138,139,140,141,142,143,0,2,8,10,1,3,9,11,12,14,4,6,13,15,5,7,4,6,8,10,0,2,5,7,9,11,12,14,1,3,13,15,88,89,94,95,116,117,118,119,106,107,78,79,82,83,112,113,84,85,102,103,98,99,72,73,92,93,64,65,100,101,0,2,4,6,8,10,1,3,5,7,12,14,9,11,13,15,12,14,4,6,13,15,0,2,8,10,5,7,1,3,9,11,222,223,244,245,12,14,4,6,0,2,13,15,5,7,8,10,1,3,9,11,132,134,128,130,133,135,129,131,136,138,140,142,137,139,141,143,8,10,9,11,4,6,0,2,12,14,5,7,1,3,13,15,4,6,5,7,8,10,12,14,9,11,13,15,0,2,1,3,12,14,8,10,13,15,4,6,9,11,5,7,0,2,1,3,65,112,113,98,99,88,89,86,87,84,85,90,91,106,235,68,69,104,105,76,77,116,117,110,111,102,103,194,195,0,0,0,0,0,0,0,0,0,0,0,0,0,0,0,0,0,0,0,0,0,0,0,0,0,0,0,0,0,0,0,0,0,0,0,0,0,0,0,0,0,0,0,0,0,0,0,0,0},
  {0,1,2,3,0,1,2,3,4,5,6,7,8,9,10,11,12,13,14,15,0,1,2,3,64,74,76,66,68,70,65,72,79,67,69,71,78,75,77,73,0,2,8,10,1,3,9,11,12,14,4,6,13,15,5,7,12,14,8,10,13,15,9,11,0,2,4,6,1,3,5,7,96,97,82,83,74,75,110,111,76,77,88,89,118,119,68,69,100,101,104,105,102,103,90,91,8,10,0,2,9,11,1,3,12,14,13,15,4,6,5,7,12,14,4,6,13,15,0,2,8,10,5,7,1,3,9,11,4,6,5,7,0,2,8,10,12,14,1,3,9,11,13,15,4,6,8,10,5,7,0,2,12,14,9,11,1,3,13,15,77,69,78,72,76,68,66,73,79,67,75,65,8,10,9,11,4,6,0,2,12,14,5,7,1,3,13,15,4,6,12,14,8,10,5,7,13,15,9,11,0,2,1,3,12,14,8,10,132,134,0,2,141,143,9,11,133,135,129,131,64,65,80,81,92,93,108,109,106,107,70,71,66,67,90,91,88,89,82,83,96,97,232,233,230,231,0,0,0,0,0,0,0,0,0,0,0,0,0,0,0,0,0,0,0,0,0,0,0,0,0,0,0,0,0,0,0,0,0,0,0,0,0,0,0,0,0,0,0,0,0,0,0,0,0,0},
  {64,65,66,67,68,69,70,71,72,73,74,75,76,77,78,79,0,1,2,3,4,5,6,7,8,9,10,11,12,13,14,15,64,74,76,66,68,70,65,72,79,67,69,71,78,75,77,73,0,2,8,10,1,3,9,11,12,14,4,6,13,15,5,7,4,6,0,2,5,7,1,3,12,14,8,10,13,15,9,11,114,115,76,77,70,71,86,87,90,91,74,75,66,67,68,69,80,81,108,109,110,111,104,105,84,85,88,89,114,115,110,111,98,99,66,67,94,85,68,69,90,91,104,105,70,71,210,211,100,101,234,235,4,6,5,7,0,2,8,10,12,14,1,3,9,11,13,15,8,10,12,14,0,2,9,11,13,15,1,3,4,6,5,7,8,10,0,2,9,11,12,14,1,3,4,6,13,15,5,7,4,6,5,7,8,10,12,14,9,11,13,15,0,2,1,3,4,6,12,14,8,10,133,135,13,15,0,2,137,139,1,3,99,102,103,86,87,104,105,78,79,118,119,114,115,88,89,112,113,100,101,64,65,84,85,94,95,224,225,210,211,196,197,0,0,0,0,0,0,0,0,0,0,0,0,0,0,0,0,0,0,0,0,0,0,0,0,0,0,0,0,0,0,0,0,0,0,0,0,0,0,0,0,0,0,0,0,0,0,0,0,0,0,0,0,0},
  {0,1,2,3,4,5,6,7,8,9,10,11,12,13,14,15,0,1,2,3,4,5,6,7,8,9,10,11,12,13,14,15,0,1,2,3,0,1,2,3,0,1,2,3,0,2,8,10,1,3,9,11,12,14,4,6,13,15,5,7,4,6,8,10,0,2,5,7,9,11,12,14,1,3,13,15,0,2,8,10,4,6,12,14,1,3,9,11,5,7,13,15,72,73,92,93,64,65,100,101,96,97,114,115,76,77,0,2,4,6,8,10,1,3,5,7,12,14,9,11,13,15,204,205,108,109,112,113,210,211,226,227,228,229,192,193,200,201,208,209,202,203,212,213,214,71,69,72,78,64,77,75,74,79,73,67,76,70,68,66,65,68,66,73,79,67,75,65,78,74,77,71,70,64,194,69,207,200,75,196,204,73,195,65,4,6,5,7,8,10,12,14,9,11,13,15,0,2,1,3,12,14,8,10,13,15,4,6,9,11,5,7,0,2,1,3,65,112,113,98,99,88,89,86,87,84,85,90,91,106,107,68,69,104,105,76,77,116,117,238,239,102,103,194,195,0,0,0,0,0,0,0,0,0,0,0,0,0,0,0,0,0,0,0,0,0,0,0,0,0,0,0,0,0,0,0,0,0,0,0,0,0,0,0,0,0,0,0,0,0,0,0,0,0,0,0},
  {0,1,2,3,4,5,6,7,8,9,10,11,12,13,14,15,0,1,2,3,4,5,6,7,8,9,10,11,12,13,14,15,128,129,130,131,132,133,134,135,136,137,138,139,140,141,142,143,192,193,194,195,196,197,198,199,200,201,202,203,204,205,206,207,4,6,8,10,0,2,5,7,9,11,12,14,1,3,13,15,0,2,8,10,4,6,12,14,1,3,9,11,5,7,13,15,64,65,70,71,80,81,112,113,90,91,102,103,118,119,104,105,114,115,106,107,94,95,68,69,82,12,14,4,6,13,15,0,2,8,10,5,7,1,3,9,11,0,2,1,3,4,6,8,10,12,14,5,7,9,11,13,15,68,70,72,74,69,71,64,66,76,78,73,75,65,67,77,79,64,71,78,74,77,70,73,69,66,72,76,79,68,65,67,75,4,6,5,7,8,10,12,14,9,11,13,15,0,2,1,3,4,6,12,14,8,10,5,7,13,15,9,11,0,2,1,3,204,206,200,202,196,198,192,194,205,207,201,203,197,199,193,195,78,79,106,107,86,87,94,95,76,77,220,221,72,73,98,227,212,213,0,0,0,0,0,0,0,0,0,0,0,0,0,0,0,0,0,0,0,0,0,0,0,0,0,0,0,0,0,0,0,0,0,0,0,0,0,0,0,0,0,0,0,0,0},
  {0,1,2,3,0,1,2,3,0,1,2,3,4,5,6,7,8,9,10,11,12,13,14,15,64,67,72,77,69,73,78,76,70,66,74,79,65,68,75,71,0,2,8,10,1,3,9,11,12,14,4,6,13,15,5,7,12,14,8,10,13,15,9,11,0,2,4,6,1,3,5,7,4,6,8,10,0,2,5,7,9,11,12,14,1,3,13,15,8,10,0,2,9,11,1,3,12,14,13,15,4,6,5,7,78,79,64,65,66,67,84,85,68,69,90,91,104,105,70,71,210,211,100,101,106,107,222,223,66,71,70,77,69,73,72,64,65,78,67,75,79,74,76,68,8,10,12,14,0,2,9,11,13,15,1,3,4,6,5,7,8,10,0,2,9,11,12,14,1,3,4,6,13,15,5,7,12,14,8,10,4,6,0,2,13,15,9,11,5,7,1,3,4,6,12,14,8,10,5,7,141,143,0,2,137,139,1,3,92,93,108,109,98,99,80,81,100,101,70,71,116,117,96,97,74,75,64,65,112,113,82,83,106,107,212,213,232,233,0,0,0,0,0,0,0,0,0,0,0,0,0,0,0,0,0,0,0,0,0,0,0,0,0,0,0,0,0,0,0,0,0,0,0,0,0,0,0,0,0,0,0,0,0,0,0,0,0,0,0,0,0,0,0,0,0,0},
  {0,1,2,3,0,1,2,3,0,1,2,3,4,5,6,7,8,9,10,11,12,13,14,15,64,67,72,77,69,73,78,76,70,64,66,76,78,65,67,77,79,68,70,69,71,72,74,73,75,12,14,8,10,13,15,9,11,0,2,4,6,1,3,5,7,76,78,72,74,77,79,73,75,64,66,68,70,65,67,69,71,0,2,8,10,4,6,12,14,1,3,9,11,5,7,13,15,84,85,88,89,114,115,110,111,98,99,66,67,94,95,70,71,76,77,106,107,96,97,64,65,78,79,90,91,4,6,5,7,0,2,8,10,12,14,1,3,9,11,13,15,4,6,8,10,5,7,0,2,12,14,9,11,1,3,13,15,132,134,128,130,133,135,129,131,136,138,140,142,137,139,141,143,12,14,8,10,4,6,0,2,13,15,9,11,5,7,1,3,12,14,8,10,4,6,0,2,13,15,9,11,5,7,1,3,12,14,8,10,13,15,132,134,9,11,133,135,128,130,129,131,99,88,89,86,87,84,85,90,91,234,235,68,69,104,105,76,77,116,117,110,111,102,103,194,195,0,0,0,0,0,0,0,0,0,0,0,0,0,0,0,0,0,0,0,0,0,0,0,0,0,0,0,0,0,0,0,0,0,0,0,0,0,0,0,0,0,0,0,0,0,0,0,0,0,0},
  {0,1,2,3,0,1,2,3,0,1,2,3,4,5,6,7,8,9,10,11,12,13,14,15,79,75,77,73,128,129,130,131,132,133,134,135,136,137,138,139,140,141,142,143,0,2,8,10,1,3,9,11,12,14,4,6,13,15,5,7,4,6,8,10,0,2,5,7,9,11,12,14,1,3,13,15,4,6,12,14,8,10,0,2,5,7,13,15,9,11,1,3,8,10,0,2,9,11,1,3,12,14,13,15,4,6,5,7,8,10,0,2,9,11,1,3,12,14,13,15,4,6,5,7,4,6,5,7,12,14,8,10,0,2,13,15,9,11,1,3,12,14,4,6,0,2,13,15,5,7,8,10,1,3,9,11,8,10,12,14,0,2,9,11,13,15,1,3,4,6,5,7,8,10,9,11,4,6,0,2,12,14,5,7,1,3,13,15,4,6,5,7,8,10,12,14,9,11,13,15,0,2,1,3,4,6,12,14,8,10,5,7,13,15,0,2,9,11,1,3,109,86,87,114,115,98,99,66,67,84,85,96,97,74,75,102,103,80,81,96,97,76,77,218,219,236,237,0,0,0,0,0,0,0,0,0,0,0,0,0,0,0,0,0,0,0,0,0,0,0,0,0,0,0,0,0,0,0,0,0,0,0,0,0,0,0,0,0,0,0,0,0,0,0,0,0},
  {0,1,2,3,0,1,2,3,0,1,2,3,4,5,6,7,8,9,10,11,12,13,14,15,72,78,70,71,66,74,68,70,66,74,79,65,68,75,71,74,72,79,71,78,67,69,65,75,77,68,73,12,14,8,10,13,15,9,11,0,2,4,6,1,3,5,7,4,6,12,14,8,10,0,2,5,7,13,15,9,11,1,3,4,6,8,10,0,2,5,7,9,11,12,14,1,3,13,15,68,69,82,83,98,99,108,109,92,93,78,79,84,85,100,101,66,67,74,75,86,87,92,93,118,119,68,69,216,217,198,199,206,207,246,247,194,195,238,239,242,243,232,233,8,10,12,14,0,2,9,11,13,15,1,3,4,6,5,7,8,10,0,2,9,11,12,14,1,3,4,6,13,15,5,7,4,6,5,7,8,10,12,14,9,11,13,15,0,2,1,3,132,134,140,142,136,138,133,135,141,143,128,130,137,139,129,131,106,107,104,105,92,93,88,89,72,73,90,91,100,101,78,79,116,117,64,65,118,119,208,209,94,95,76,77,240,241,238,239,0,0,0,0,0,0,0,0,0,0,0,0,0,0,0,0,0,0,0,0,0,0,0,0,0,0,0,0,0,0,0,0,0,0,0,0,0,0,0,0,0,0,0,0,0,0,0,0,0,0,0,0,0,0,0,0,0},
  {0,1,2,3,0,1,2,3,0,1,2,3,4,5,6,7,8,9,10,11,12,13,14,15,0,1,2,3,0,1,2,3,4,5,6,7,8,9,10,11,12,13,14,15,76,69,70,72,74,66,71,75,67,77,68,73,79,206,64,65,12,14,8,10,13,15,9,11,0,2,4,6,1,3,5,7,0,2,8,10,4,6,12,14,1,3,9,11,5,7,13,15,0,2,8,10,4,6,12,14,1,3,9,11,5,7,13,15,8,10,0,2,9,11,1,3,12,14,13,15,4,6,5,7,12,14,4,6,13,15,0,2,8,10,5,7,1,3,9,11,0,2,1,3,4,6,8,10,12,14,5,7,9,11,13,15,8,10,12,14,0,2,9,11,13,15,1,3,4,6,5,7,8,10,0,2,9,11,12,14,1,3,4,6,13,15,5,7,4,6,5,7,8,10,12,14,9,11,13,15,0,2,1,3,4,6,140,142,136,138,5,7,141,143,0,2,137,139,129,131,75,98,99,66,67,80,81,92,93,114,115,112,113,88,89,110,111,82,83,68,69,104,105,108,109,102,103,244,245,0,0,0,0,0,0,0,0,0,0,0,0,0,0,0,0,0,0,0,0,0,0,0,0,0,0,0,0,0,0,0,0,0,0,0,0,0,0,0,0,0,0,0,0,0,0,0},
  {0,1,2,3,0,1,2,3,4,5,6,7,8,9,10,11,12,13,14,15,69,76,67,65,0,2,12,14,1,3,13,15,4,6,5,7,8,10,9,11,12,14,8,10,13,15,9,11,0,2,4,6,1,3,5,7,67,108,109,86,87,96,97,82,83,74,75,110,111,76,77,88,89,118,119,68,69,100,101,104,105,102,103,90,91,8,10,0,2,9,11,1,3,12,14,13,15,4,6,5,7,0,2,4,6,8,10,1,3,5,7,12,14,9,11,13,15,4,6,5,7,12,14,8,10,0,2,13,15,9,11,1,3,12,14,4,6,0,2,13,15,5,7,8,10,1,3,9,11,132,134,128,130,133,135,129,131,136,138,140,142,137,139,141,143,8,10,9,11,4,6,0,2,12,14,5,7,1,3,13,15,4,6,12,14,8,10,5,7,13,15,9,11,0,2,1,3,12,14,8,10,4,6,0,2,13,15,9,11,5,7,1,3,80,81,96,97,92,93,108,109,70,71,82,83,100,101,206,207,74,75,114,115,94,95,118,119,200,201,192,0,0,0,0,0,0,0,0,0,0,0,0,0,0,0,0,0,0,0,0,0,0,0,0,0,0,0,0,0,0,0,0,0,0,0,0,0,0,0,0,0,0,0,0,0,0,0,0,0,0,0,0,0,0,0,0},
  {0,1,2,3,0,1,2,3,4,5,6,7,8,9,10,11,12,13,14,15,64,79,75,77,73,69,76,67,65,64,74,76,66,68,70,65,72,79,67,69,71,78,75,77,73,12,14,8,10,13,15,9,11,0,2,4,6,1,3,5,7,4,6,12,14,8,10,0,2,5,7,13,15,9,11,1,3,76,77,88,89,106,107,78,79,96,97,108,109,114,115,100,101,74,75,116,117,118,119,82,83,112,113,98,72,73,80,81,98,99,74,75,110,111,112,113,86,87,92,93,4,6,5,7,0,2,8,10,12,14,1,3,9,11,13,15,12,14,4,6,0,2,13,15,5,7,8,10,1,3,9,11,8,10,12,14,0,2,9,11,13,15,1,3,4,6,5,7,8,10,9,11,4,6,0,2,12,14,5,7,1,3,13,15,4,6,5,7,8,10,12,14,9,11,13,15,0,2,1,3,132,134,133,135,136,138,140,142,137,139,141,143,128,130,129,131,90,91,106,107,92,93,116,117,72,73,76,77,108,109,110,111,208,209,70,71,66,67,202,203,226,0,0,0,0,0,0,0,0,0,0,0,0,0,0,0,0,0,0,0,0,0,0,0,0,0,0,0,0,0,0,0,0,0,0,0,0,0,0,0,0,0,0,0,0,0,0,0,0,0,0,0,0,0,0,0},
  {64,65,66,67,68,69,70,71,72,73,74,75,76,77,78,79,0,1,2,3,0,1,2,3,64,65,66,67,68,69,70,71,72,73,74,75,76,77,78,79,72,76,64,70,66,74,71,78,67,79,65,197,75,68,73,77,4,6,0,2,5,7,1,3,12,14,8,10,13,15,9,11,4,6,12,14,8,10,0,2,5,7,13,15,9,11,1,3,68,70,72,74,64,66,69,71,73,75,76,78,65,67,77,79,8,10,0,2,9,11,1,3,12,14,13,15,4,6,5,7,76,77,108,109,112,113,82,83,226,227,100,101,64,65,200,201,208,209,202,203,212,213,214,215,71,69,72,78,64,77,75,74,79,73,67,8,10,12,14,0,2,9,11,13,15,1,3,4,6,5,7,8,10,9,11,4,6,0,2,12,14,5,7,1,3,13,15,4,6,12,14,8,10,5,7,13,15,9,11,0,2,1,3,132,134,140,142,136,138,133,135,141,143,128,130,137,139,129,131,64,65,84,85,92,93,104,105,74,75,78,79,100,101,82,83,72,73,116,117,222,223,234,235,198,0,0,0,0,0,0,0,0,0,0,0,0,0,0,0,0,0,0,0,0,0,0,0,0,0,0,0,0,0,0,0,0,0,0,0,0,0,0,0,0,0,0,0,0,0,0,0,0,0,0,0,0},
  {0,1,2,3,4,5,6,7,8,9,10,11,12,13,14,15,0,1,2,3,192,193,194,195,196,197,198,199,200,201,202,203,204,205,206,207,64,66,76,78,65,67,77,79,68,70,69,71,72,74,73,75,4,6,0,2,5,7,1,3,12,14,8,10,13,15,9,11,4,6,8,10,0,2,5,7,9,11,12,14,1,3,13,15,0,2,8,10,4,6,12,14,1,3,9,11,5,7,13,15,8,10,0,2,9,11,1,3,12,14,13,15,4,6,5,7,64,66,68,70,72,74,65,67,69,71,76,78,73,75,77,79,68,70,69,71,76,78,72,74,64,66,77,79,73,75,65,67,64,71,78,77,69,72,75,70,74,79,76,73,68,67,66,65,8,10,0,2,9,11,12,14,1,3,4,6,13,15,5,7,4,6,5,7,8,10,12,14,9,11,13,15,0,2,1,3,132,134,140,142,136,138,133,135,141,143,128,130,137,139,129,131,106,107,104,105,92,93,88,89,72,73,90,91,100,101,78,79,84,85,80,81,66,67,90,91,96,97,242,243,202,203,198,199,0,0,0,0,0,0,0,0,0,0,0,0,0,0,0,0,0,0,0,0,0,0,0,0,0,0,0,0,0,0,0,0,0,0,0,0,0,0,0,0,0,0,0,0,0,0,0,0,0,0,0,0},
  {64,65,66,67,68,69,70,71,72,73,74,75,76,77,78,79,0,1,2,3,64,65,66,67,68,69,70,71,72,73,74,75,76,77,78,79,64,66,76,78,65,67,77,79,68,70,69,71,72,74,73,75,64,66,72,74,65,67,73,75,76,78,68,70,77,79,69,71,4,6,8,10,0,2,5,7,9,11,12,14,1,3,13,15,80,81,108,109,110,111,104,105,0,2,8,10,4,6,12,14,1,3,9,11,5,7,13,15,0,2,4,6,8,10,1,3,5,7,12,14,9,11,13,15,4,6,5,7,12,14,8,10,0,2,13,15,9,11,1,3,71,72,69,66,64,78,74,77,76,75,73,8,10,12,14,0,2,9,11,13,15,1,3,4,6,5,7,8,10,0,2,9,11,12,14,1,3,4,6,13,15,5,7,4,6,5,7,8,10,12,14,9,11,13,15,0,2,1,3,132,134,140,142,136,138,133,135,141,143,128,130,137,139,129,131,64,65,78,79,90,91,106,107,94,95,68,69,96,97,74,75,98,99,66,67,80,81,220,221,242,243,112,113,216,217,236,0,0,0,0,0,0,0,0,0,0,0,0,0,0,0,0,0,0,0,0,0,0,0,0,0,0,0,0,0,0,0,0,0,0,0,0,0,0,0,0,0,0,0,0,0,0,0,0,0,0},
  {64,65,66,67,68,69,70,71,72,73,74,75,76,77,78,79,0,1,2,3,0,1,2,3,4,5,6,7,8,9,10,11,12,13,14,15,0,1,2,3,76,69,70,72,74,66,71,75,67,77,68,73,79,78,64,65,4,6,0,2,5,7,1,3,12,14,8,10,13,15,9,11,0,2,8,10,4,6,12,14,1,3,9,11,5,7,13,15,108,109,114,115,100,101,74,75,116,117,118,119,82,83,112,113,98,99,102,103,68,69,110,111,104,105,0,2,4,6,8,10,1,3,5,7,12,14,9,11,13,15,4,6,5,7,12,14,8,10,0,2,13,15,9,11,1,3,64,66,65,67,68,70,72,74,76,78,69,71,73,75,77,79,132,134,128,130,133,135,129,131,136,138,140,142,137,139,141,143,8,10,9,11,4,6,0,2,12,14,5,7,1,3,13,15,4,6,5,7,8,10,12,14,9,11,13,15,0,2,1,3,4,6,12,14,8,10,5,7,13,15,0,2,9,11,1,3,105,72,73,86,87,102,103,90,91,118,119,68,69,78,79,114,115,66,67,110,111,94,95,216,217,204,205,0,0,0,0,0,0,0,0,0,0,0,0,0,0,0,0,0,0,0,0,0,0,0,0,0,0,0,0,0,0,0,0,0,0,0,0,0,0,0,0,0,0,0},
  {64,65,66,67,68,69,70,71,72,73,74,75,76,77,78,79,64,65,66,67,68,69,70,71,72,73,74,75,76,77,78,79,0,1,2,3,128,129,130,131,132,133,134,135,136,137,138,139,140,141,142,143,198,197,194,199,204,203,206,4,6,0,2,5,7,1,3,12,14,8,10,13,15,9,11,0,2,8,10,4,6,12,14,1,3,9,11,5,7,13,15,8,10,0,2,9,11,1,3,12,14,13,15,4,6,5,7,8,10,0,2,9,11,1,3,12,14,13,15,4,6,5,7,12,14,4,6,13,15,0,2,8,10,5,7,1,3,9,11,0,2,1,3,4,6,8,10,12,14,5,7,9,11,13,15,8,10,12,14,0,2,9,11,13,15,1,3,4,6,5,7,8,10,9,11,4,6,0,2,12,14,5,7,1,3,13,15,12,14,8,10,4,6,0,2,13,15,9,11,5,7,1,3,12,14,8,10,13,15,4,6,9,11,5,7,0,2,1,3,118,119,76,77,74,75,68,69,72,73,100,101,110,111,84,85,206,207,116,117,94,95,242,243,86,87,240,241,226,227,0,0,0,0,0,0,0,0,0,0,0,0,0,0,0,0,0,0,0,0,0,0,0,0,0,0,0,0,0,0,0,0,0,0,0,0,0,0,0,0,0,0,0,0,0,0,0},
  {64,65,66,67,68,69,70,71,72,73,74,75,76,77,78,79,0,1,2,3,4,5,6,7,8,9,10,11,12,13,14,15,0,1,2,3,64,66,76,78,65,67,77,79,68,70,69,71,72,74,73,75,4,6,0,2,5,7,1,3,12,14,8,10,13,15,9,11,4,6,12,14,8,10,0,2,5,7,13,15,9,11,1,3,97,108,109,114,115,100,101,74,75,116,117,118,119,82,83,112,113,98,99,102,103,68,69,110,111,104,105,114,115,102,103,98,99,100,101,90,91,70,71,76,77,68,69,110,193,200,201,208,209,202,203,212,213,214,215,222,223,244,245,234,235,224,225,8,10,12,14,0,2,9,11,13,15,1,3,4,6,5,7,8,10,0,2,9,11,12,14,1,3,4,6,13,15,5,7,4,6,12,14,8,10,5,7,13,15,9,11,0,2,1,3,4,6,5,7,8,10,140,142,9,11,13,15,0,2,1,3,90,91,106,107,92,93,116,117,72,73,76,77,108,109,110,111,80,81,70,71,66,67,74,75,98,99,102,103,214,215,0,0,0,0,0,0,0,0,0,0,0,0,0,0,0,0,0,0,0,0,0,0,0,0,0,0,0,0,0,0,0,0,0,0,0,0,0,0,0,0,0,0,0,0,0,0,0,0,0,0,0,0,0,0,0},
  {0,1,2,3,0,1,2,3,0,1,2,3,4,5,6,7,8,9,10,11,12,13,14,15,0,1,2,3,74,66,76,79,70,72,64,67,71,69,78,68,75,65,77,73,0,2,8,10,1,3,9,11,12,14,4,6,13,15,5,7,203,206,200,202,196,201,207,205,195,192,193,0,2,8,10,4,6,12,14,1,3,9,11,5,7,13,15,4,6,12,14,8,10,0,2,5,7,13,15,9,11,1,3,112,113,84,85,88,89,66,67,78,79,92,93,72,73,80,81,106,107,116,117,236,237,64,65,94,95,4,6,5,7,0,2,8,10,12,14,1,3,9,11,13,15,4,6,8,10,5,7,0,2,12,14,9,11,1,3,13,15,72,74,76,78,64,66,73,75,77,79,65,67,68,70,69,71,72,79,194,76,192,67,202,196,199,206,198,197,205,201,193,203,12,14,8,10,13,15,4,6,9,11,5,7,0,2,1,3,90,91,106,107,92,93,116,117,72,73,76,77,108,109,110,111,80,81,70,71,66,67,74,75,98,82,83,68,69,104,105,108,109,102,103,244,245,0,0,0,0,0,0,0,0,0,0,0,0,0,0,0,0,0,0,0,0,0,0,0,0,0,0,0,0,0,0,0,0,0,0,0,0,0,0,0,0,0,0,0,0,0,0,0,0,0,0},
  {0,1,2,3,0,1,2,3,4,5,6,7,8,9,10,11,12,13,14,15,0,1,2,3,74,66,76,79,70,72,64,67,71,69,78,68,75,65,77,73,0,2,8,10,1,3,9,11,12,14,4,6,13,15,5,7,4,6,0,2,5,7,1,3,12,14,8,10,13,15,9,11,202,196,201,207,205,195,192,193,90,91,70,71,72,73,66,67,64,65,84,85,92,93,80,81,86,87,94,95,84,85,88,89,114,115,110,111,98,99,66,67,94,95,70,71,76,77,106,107,96,97,64,65,215,222,223,244,245,234,235,224,225,216,217,198,199,206,4,6,8,10,5,7,0,2,12,14,9,11,1,3,13,15,132,134,128,130,133,135,129,131,136,138,140,142,137,139,141,143,72,79,194,76,192,67,202,196,199,206,198,197,205,201,193,203,12,14,8,10,13,15,4,6,9,11,5,7,0,2,1,3,4,6,12,14,136,138,5,7,13,15,128,130,137,139,129,131,80,81,92,93,108,109,106,107,70,71,66,67,90,91,88,89,82,83,224,225,232,233,230,231,0,0,0,0,0,0,0,0,0,0,0,0,0,0,0,0,0,0,0,0,0,0,0,0,0,0,0,0,0,0,0,0,0,0,0,0,0,0,0,0,0,0,0,0,0,0,0,0,0,0,0,0,0,0},
  {64,65,66,67,68,69,70,71,72,73,74,75,76,77,78,79,0,1,2,3,4,5,6,7,8,9,10,11,12,13,14,15,192,193,194,195,196,197,198,199,200,201,202,203,204,205,206,207,0,2,8,10,1,3,9,11,12,14,4,6,13,15,5,7,4,6,0,2,5,7,1,3,12,14,8,10,13,15,9,11,0,2,8,10,4,6,12,14,1,3,9,11,5,7,13,15,119,82,83,112,113,98,99,102,103,68,69,110,111,104,105,72,74,64,66,73,75,65,67,76,78,77,79,68,70,69,71,66,71,70,77,69,73,72,64,65,78,67,75,79,74,76,68,76,78,68,70,64,66,77,79,69,71,72,74,65,67,73,75,132,134,128,130,133,135,129,131,136,138,140,142,137,139,141,143,78,74,77,71,70,64,194,69,207,200,75,196,204,73,195,65,12,14,8,10,13,15,4,6,9,11,5,7,0,2,1,3,72,74,64,66,73,75,76,78,65,67,196,198,77,79,197,199,68,69,96,97,74,75,98,99,66,67,80,81,92,93,114,115,112,113,88,89,108,109,246,247,0,0,0,0,0,0,0,0,0,0,0,0,0,0,0,0,0,0,0,0,0,0,0,0,0,0,0,0,0,0,0,0,0,0,0,0,0,0,0,0,0,0,0,0,0,0,0,0,0},
  {0,1,2,3,4,5,6,7,8,9,10,11,12,13,14,15,64,65,66,67,68,69,70,71,72,73,74,75,76,77,78,79,0,1,2,3,72,76,64,70,66,74,71,78,67,79,65,197,75,68,73,77,12,14,8,10,13,15,9,11,0,2,4,6,1,3,5,7,108,109,86,87,96,97,82,83,74,75,110,111,76,77,88,89,118,119,68,69,100,101,104,105,102,103,90,91,8,10,0,2,9,11,1,3,12,14,13,15,4,6,5,7,76,77,68,69,110,111,82,83,74,75,96,97,118,119,104,105,4,6,5,7,0,2,8,10,12,14,1,3,9,11,13,15,4,6,8,10,5,7,0,2,12,14,9,11,1,3,13,15,8,10,0,2,9,11,12,14,1,3,4,6,13,15,5,7,12,14,8,10,4,6,0,2,13,15,9,11,5,7,1,3,12,14,8,10,13,15,132,134,9,11,5,7,0,2,1,3,136,138,9,11,132,134,0,2,140,142,133,135,129,131,141,143,79,74,75,114,115,94,95,118,119,72,73,64,208,209,96,97,76,77,218,219,236,237,0,0,0,0,0,0,0,0,0,0,0,0,0,0,0,0,0,0,0,0,0,0,0,0,0,0,0,0,0,0,0,0,0,0,0,0,0,0,0,0,0,0,0,0,0,0,0,0,0,0},
  {64,65,66,67,68,69,70,71,72,73,74,75,76,77,78,79,0,1,2,3,0,1,2,3,66,74,68,64,66,74,79,65,68,75,71,72,76,64,70,66,74,71,78,67,79,65,69,75,68,73,77,4,6,0,2,5,7,1,3,12,14,8,10,13,15,9,11,70,71,64,65,98,99,92,93,78,79,112,113,94,95,72,73,80,81,84,85,114,115,116,117,106,107,66,67,108,8,10,0,2,9,11,1,3,12,14,13,15,4,6,5,7,12,14,4,6,13,15,0,2,8,10,5,7,1,3,9,11,4,6,5,7,12,14,8,10,0,2,13,15,9,11,1,3,76,78,4,6,0,2,13,15,5,7,8,10,1,3,9,11,8,10,0,2,9,11,12,14,1,3,4,6,13,15,5,7,12,14,8,10,4,6,0,2,13,15,9,11,5,7,1,3,12,14,8,10,13,15,4,6,9,11,5,7,0,2,1,3,92,93,108,109,98,99,80,81,100,101,70,71,116,117,96,97,74,75,64,65,112,113,82,83,234,235,84,85,104,112,113,228,229,192,193,216,217,246,247,0,0,0,0,0,0,0,0,0,0,0,0,0,0,0,0,0,0,0,0,0,0,0,0,0,0,0,0,0,0,0,0,0,0,0,0,0,0,0,0,0,0,0,0,0,0,0,0,0},
  {0,1,2,3,4,5,6,7,8,9,10,11,12,13,14,15,0,1,2,3,0,1,2,3,4,5,6,7,8,9,10,11,12,13,14,15,74,66,76,79,70,72,64,67,71,69,78,68,75,65,77,73,198,194,204,206,200,202,196,192,4,6,0,2,5,7,1,3,12,14,8,10,13,15,9,11,4,6,8,10,0,2,5,7,9,11,12,14,1,3,13,15,8,10,0,2,9,11,1,3,12,14,13,15,4,6,5,7,88,89,76,77,96,97,86,87,72,73,116,117,110,111,12,14,4,6,13,15,0,2,8,10,5,7,1,3,9,11,219,220,221,230,231,196,197,4,6,8,10,5,7,0,2,12,14,9,11,1,3,13,15,8,10,0,2,9,11,12,14,1,3,4,6,13,15,5,7,12,14,8,10,4,6,0,2,13,15,9,11,5,7,1,3,12,14,8,10,13,15,4,6,9,11,5,7,0,2,1,3,12,14,8,10,132,134,0,2,13,15,9,11,133,135,1,3,64,65,84,85,92,93,104,105,74,75,206,207,100,101,82,83,200,201,116,117,222,223,0,0,0,0,0,0,0,0,0,0,0,0,0,0,0,0,0,0,0,0,0,0,0,0,0,0,0,0,0,0,0,0,0,0,0,0,0,0,0,0,0,0,0,0,0,0,0,0,0},
  {0,1,2,3,4,5,6,7,8,9,10,11,12,13,14,15,64,65,66,67,68,69,70,71,72,73,74,75,76,77,78,79,0,1,2,3,64,66,76,78,65,67,77,79,68,70,69,71,72,74,73,75,12,14,8,10,13,15,9,11,0,2,4,6,1,3,5,7,4,6,12,14,8,10,0,2,5,7,13,15,9,11,1,3,0,2,8,10,4,6,12,14,1,3,9,11,5,7,13,15,112,113,84,85,88,89,66,67,78,79,92,93,72,73,80,81,106,107,116,117,108,109,64,65,94,95,86,87,4,6,5,7,12,14,8,10,0,2,13,15,9,11,1,3,4,6,8,10,5,7,0,2,12,14,9,11,1,3,13,15,132,134,128,130,133,135,129,131,136,138,140,142,137,139,141,143,200,207,194,204,192,195,202,196,199,206,198,197,205,201,193,203,4,6,12,14,8,10,5,7,13,15,9,11,0,2,1,3,4,6,5,7,136,138,140,142,9,11,141,143,128,130,129,131,82,83,70,71,68,69,102,103,108,109,86,87,114,115,98,99,66,67,84,85,224,225,202,203,0,0,0,0,0,0,0,0,0,0,0,0,0,0,0,0,0,0,0,0,0,0,0,0,0,0,0,0,0,0,0,0,0,0,0,0,0,0,0,0,0,0,0,0,0,0,0,0},
  {64,65,66,67,68,69,70,71,72,73,74,75,76,77,78,79,0,1,2,3,0,1,2,3,4,5,6,7,8,9,10,11,12,13,14,15,64,66,76,78,65,67,77,79,68,70,69,71,72,74,73,75,4,6,0,2,5,7,1,3,12,14,8,10,13,15,9,11,200,202,196,201,207,205,195,192,193,96,97,114,115,76,77,70,71,86,87,90,91,74,75,66,67,68,69,80,81,108,109,110,111,104,105,78,79,90,91,80,81,102,103,104,105,108,109,112,113,72,73,116,117,82,83,100,101,74,204,205,236,237,240,241,210,211,226,227,228,229,192,12,14,4,6,0,2,13,15,5,7,8,10,1,3,9,11,64,71,70,74,8,10,0,2,9,11,12,14,1,3,4,6,13,15,5,7,12,14,8,10,4,6,0,2,13,15,9,11,5,7,1,3,12,14,8,10,13,15,4,6,9,11,5,7,0,2,1,3,80,81,96,97,92,93,108,109,70,71,82,83,100,101,78,79,74,75,114,115,94,95,118,119,72,73,64,112,113,228,229,192,193,216,217,246,247,0,0,0,0,0,0,0,0,0,0,0,0,0,0,0,0,0,0,0,0,0,0,0,0,0,0,0,0,0,0,0,0,0,0,0,0,0,0,0,0,0,0,0,0,0,0,0,0,0,0,0,0},
  {64,65,66,67,68,69,70,71,72,73,74,75,76,77,78,79,0,1,2,3,128,129,130,131,132,133,134,135,136,137,138,139,140,141,142,143,64,66,76,78,65,67,77,79,68,70,69,71,72,74,73,75,4,6,0,2,5,7,1,3,12,14,8,10,13,15,9,11,4,6,12,14,8,10,0,2,5,7,13,15,9,11,1,3,0,2,8,10,4,6,12,14,1,3,9,11,5,7,13,15,8,10,0,2,9,11,1,3,12,14,13,15,4,6,5,7,12,14,4,6,13,15,0,2,8,10,5,7,1,3,9,11,68,70,69,71,76,78,72,74,64,66,77,79,73,75,65,67,79,68,65,67,70,8,10,12,14,0,2,9,11,13,15,1,3,4,6,5,7,8,10,9,11,4,6,0,2,12,14,5,7,1,3,13,15,4,6,12,14,8,10,5,7,13,15,9,11,0,2,1,3,132,134,140,142,136,138,133,135,141,143,128,130,137,139,129,131,118,119,76,77,74,75,68,69,72,73,100,101,110,111,84,85,206,207,116,117,94,95,242,243,214,215,240,241,226,0,0,0,0,0,0,0,0,0,0,0,0,0,0,0,0,0,0,0,0,0,0,0,0,0,0,0,0,0,0,0,0,0,0,0,0,0,0,0,0,0,0,0,0,0,0,0,0,0,0},
  {0,1,2,3,4,5,6,7,8,9,10,11,12,13,14,15,0,1,2,3,4,5,6,7,8,9,10,11,12,13,14,15,70,64,76,66,74,72,79,71,78,67,69,65,75,77,68,73,0,2,8,10,1,3,9,11,12,14,4,6,13,15,5,7,4,6,0,2,5,7,1,3,12,14,8,10,13,15,9,11,0,2,8,10,4,6,12,14,1,3,9,11,5,7,13,15,8,10,0,2,9,11,1,3,12,14,13,15,4,6,5,7,112,113,84,85,88,89,66,67,78,79,76,78,68,70,77,79,64,66,72,74,69,71,65,67,73,75,12,14,4,6,0,2,13,15,5,7,8,10,1,3,9,11,8,10,12,14,0,2,9,11,13,15,1,3,4,6,5,7,8,10,9,11,4,6,0,2,12,14,5,7,1,3,13,15,4,6,12,14,8,10,5,7,13,15,9,11,0,2,1,3,4,6,12,14,8,10,5,7,13,15,9,11,128,130,1,3,89,108,109,118,119,82,83,70,71,100,101,102,103,84,85,116,117,72,73,214,215,238,239,232,233,204,205,0,0,0,0,0,0,0,0,0,0,0,0,0,0,0,0,0,0,0,0,0,0,0,0,0,0,0,0,0,0,0,0,0,0,0,0,0,0,0,0,0,0,0,0,0,0,0,0,0,0,0},
  {64,65,66,67,68,69,70,71,72,73,74,75,76,77,78,79,0,1,2,3,4,5,6,7,8,9,10,11,12,13,14,15,128,129,130,131,132,133,134,135,136,137,138,139,140,141,142,143,198,197,194,199,204,203,206,200,4,6,0,2,5,7,1,3,12,14,8,10,13,15,9,11,0,2,8,10,4,6,12,14,1,3,9,11,5,7,13,15,70,71,86,87,90,91,74,75,66,67,68,69,80,81,108,109,110,111,104,105,0,2,4,6,8,10,1,3,5,7,12,14,9,11,13,15,4,6,5,7,12,14,8,10,0,2,13,15,9,11,1,3,0,2,1,3,4,6,8,10,12,14,5,7,9,11,13,15,8,10,12,14,0,2,9,11,13,15,1,3,4,6,5,7,8,10,0,2,9,11,12,14,1,3,4,6,13,15,5,7,4,6,5,7,8,10,12,14,9,11,13,15,0,2,1,3,4,6,12,14,8,10,5,7,13,15,0,2,9,11,1,3,64,65,78,79,90,91,106,107,94,95,68,69,96,97,74,75,98,99,66,67,208,209,92,93,242,243,240,241,216,0,0,0,0,0,0,0,0,0,0,0,0,0,0,0,0,0,0,0,0,0,0,0,0,0,0,0,0,0,0,0,0,0,0,0,0,0,0,0,0,0,0,0,0,0,0,0},
  {0,1,2,3,4,5,6,7,8,9,10,11,12,13,14,15,64,65,66,67,68,69,70,71,72,73,74,75,76,77,78,79,128,129,130,131,132,133,134,135,136,137,138,139,140,141,142,143,0,2,8,10,1,3,9,11,12,14,4,6,13,15,5,7,197,199,203,201,207,205,195,193,4,6,12,14,8,10,0,2,5,7,13,15,9,11,1,3,88,89,94,95,116,117,118,119,106,107,78,79,82,83,112,113,84,85,102,8,10,0,2,9,11,1,3,12,14,13,15,4,6,5,7,66,71,70,77,69,73,72,64,65,78,67,75,79,74,76,68,12,14,4,6,0,2,13,15,5,7,8,10,1,3,9,11,8,10,12,14,0,2,9,11,13,15,1,3,4,6,5,7,8,10,9,11,4,6,0,2,12,14,5,7,1,3,13,15,4,6,12,14,8,10,5,7,13,15,9,11,0,2,1,3,4,6,12,14,136,138,5,7,13,15,137,139,128,130,129,131,90,91,106,107,92,93,116,117,72,73,76,77,108,109,110,111,80,81,198,199,66,67,202,203,226,0,0,0,0,0,0,0,0,0,0,0,0,0,0,0,0,0,0,0,0,0,0,0,0,0,0,0,0,0,0,0,0,0,0,0,0,0,0,0,0,0,0,0,0,0,0,0,0,0,0,0,0},
  {64,65,66,67,68,69,70,71,72,73,74,75,76,77,78,79,0,1,2,3,4,5,6,7,8,9,10,11,12,13,14,15,72,78,70,71,64,66,76,78,65,67,77,79,68,70,69,71,72,74,73,75,12,14,8,10,13,15,9,11,0,2,4,6,1,3,5,7,109,86,87,96,97,82,83,74,75,110,111,76,77,88,89,118,119,68,69,100,101,104,105,102,103,90,91,64,65,70,71,80,81,112,113,90,91,102,103,118,119,104,105,114,115,106,107,94,95,68,69,12,14,4,6,13,15,0,2,8,10,5,7,1,3,9,11,0,2,1,3,4,6,8,10,12,14,5,7,9,11,13,15,76,70,68,66,65,8,10,12,14,0,2,9,11,13,15,1,3,4,6,5,7,8,10,9,11,4,6,0,2,12,14,5,7,1,3,13,15,4,6,12,14,8,10,5,7,13,15,9,11,0,2,1,3,132,134,140,142,136,138,133,135,141,143,128,130,137,139,129,131,109,118,119,82,83,70,71,100,101,102,103,84,85,116,117,72,73,86,87,110,111,232,233,204,205,0,0,0,0,0,0,0,0,0,0,0,0,0,0,0,0,0,0,0,0,0,0,0,0,0,0,0,0,0,0,0,0,0,0,0,0,0,0,0,0,0,0,0,0,0,0,0,0,0,0,0},
  {64,65,66,67,68,69,70,71,72,73,74,75,76,77,78,79,0,1,2,3,0,1,2,3,4,5,6,7,8,9,10,11,12,13,14,15,64,66,76,78,65,67,77,79,68,70,69,71,72,74,73,75,64,66,72,74,65,67,73,75,76,78,68,70,77,79,69,71,70,71,64,65,98,99,92,93,78,79,112,113,94,95,72,73,80,81,84,85,114,115,116,117,106,107,66,67,108,109,86,87,64,65,70,71,80,81,112,113,90,91,102,103,118,119,104,105,114,115,106,107,94,95,4,6,5,7,12,14,8,10,0,2,13,15,9,11,1,3,0,2,1,3,4,6,8,10,12,14,5,7,9,11,13,15,8,10,12,14,0,2,9,11,13,15,1,3,4,6,5,7,8,10,9,11,4,6,0,2,12,14,5,7,1,3,13,15,4,6,5,7,8,10,12,14,9,11,13,15,0,2,1,3,4,6,12,14,8,10,5,7,13,15,0,2,9,11,1,3,85,104,105,72,73,86,87,102,103,90,91,118,119,68,69,206,207,114,115,66,67,110,111,94,95,216,217,204,205,0,0,0,0,0,0,0,0,0,0,0,0,0,0,0,0,0,0,0,0,0,0,0,0,0,0,0,0,0,0,0,0,0,0,0,0,0,0,0,0,0,0,0,0,0,0,0,0,0},
  {0,1,2,3,4,5,6,7,8,9,10,11,12,13,14,15,0,1,2,3,4,5,6,7,8,9,10,11,12,13,14,15,128,129,130,131,132,133,134,135,136,137,138,139,140,141,142,143,0,2,8,10,1,3,9,11,12,14,4,6,13,15,5,7,4,6,12,14,8,10,0,2,5,7,13,15,9,11,1,3,4,6,0,2,5,7,1,3,12,14,8,10,13,15,9,11,0,2,8,10,4,6,12,14,1,3,9,11,5,7,13,15,0,2,4,6,8,10,1,3,5,7,12,14,9,11,13,15,4,6,5,7,12,14,8,10,0,2,13,15,9,11,1,3,0,2,1,3,4,6,8,10,12,14,5,7,9,11,13,15,8,10,12,14,0,2,9,11,13,15,1,3,4,6,5,7,8,10,9,11,4,6,0,2,12,14,5,7,1,3,13,15,4,6,12,14,8,10,5,7,13,15,9,11,0,2,1,3,4,6,140,142,136,138,5,7,141,143,128,130,137,139,129,131,108,109,118,119,82,83,70,71,100,101,102,103,84,85,116,117,72,73,86,87,110,111,232,233,204,205,0,0,0,0,0,0,0,0,0,0,0,0,0,0,0,0,0,0,0,0,0,0,0,0,0,0,0,0,0,0,0,0,0,0,0,0,0,0,0,0,0,0,0,0,0,0},
  {0,1,2,3,4,5,6,7,8,9,10,11,12,13,14,15,0,1,2,3,4,5,6,7,8,9,10,11,12,13,14,15,74,66,76,79,70,72,64,67,71,69,78,68,75,65,77,73,0,2,8,10,1,3,9,11,12,14,4,6,13,15,5,7,0,2,8,10,4,6,12,14,1,3,9,11,5,7,13,15,4,6,8,10,0,2,5,7,9,11,12,14,1,3,13,15,8,10,0,2,9,11,1,3,12,14,13,15,4,6,5,7,86,87,114,115,102,103,98,99,100,101,90,91,70,71,204,205,68,206,207,246,247,194,195,238,239,242,243,232,233,218,76,78,68,70,64,66,77,79,69,71,72,74,65,67,73,75,8,10,0,2,9,11,12,14,1,3,4,6,13,15,5,7,12,14,8,10,4,6,0,2,13,15,9,11,5,7,1,3,12,14,8,10,13,15,4,6,9,11,5,7,0,2,1,3,110,111,82,83,70,71,68,69,102,103,108,109,86,87,114,115,98,99,66,67,84,85,96,97,74,75,103,208,209,96,97,76,77,218,219,236,237,0,0,0,0,0,0,0,0,0,0,0,0,0,0,0,0,0,0,0,0,0,0,0,0,0,0,0,0,0,0,0,0,0,0,0,0,0,0,0,0,0,0,0,0,0,0,0,0,0,0,0,0,0},
  {0,1,2,3,4,5,6,7,8,9,10,11,12,13,14,15,0,1,2,3,128,129,130,131,132,133,134,135,136,137,138,139,140,141,142,143,64,66,76,78,65,67,77,79,68,70,69,71,72,74,73,75,12,14,8,10,13,15,9,11,0,2,4,6,1,3,5,7,4,6,0,2,5,7,1,3,12,14,8,10,13,15,9,11,4,6,8,10,0,2,5,7,9,11,12,14,1,3,13,15,8,10,0,2,9,11,1,3,12,14,13,15,4,6,5,7,108,109,204,205,88,89,114,115,96,97,102,103,116,117,246,247,0,2,1,3,4,6,8,10,12,14,5,7,9,11,13,15,8,10,12,14,0,2,9,11,13,15,1,3,4,6,5,7,8,10,9,11,4,6,0,2,12,14,5,7,1,3,13,15,12,14,8,10,4,6,0,2,13,15,9,11,5,7,1,3,132,134,140,142,136,138,133,135,141,143,128,130,137,139,129,131,99,102,103,86,87,104,105,78,79,118,119,114,115,88,89,112,113,100,101,64,65,84,85,94,95,224,225,210,211,196,197,0,0,0,0,0,0,0,0,0,0,0,0,0,0,0,0,0,0,0,0,0,0,0,0,0,0,0,0,0,0,0,0,0,0,0,0,0,0,0,0,0,0,0,0,0,0,0,0,0,0,0,0,0},
  {64,65,66,67,68,69,70,71,72,73,74,75,76,77,78,79,0,1,2,3,0,1,2,3,4,5,6,7,8,9,10,11,12,13,14,15,64,66,76,78,65,67,77,79,68,70,69,71,72,74,73,75,64,66,72,74,65,67,73,75,76,78,68,70,77,79,69,71,4,6,12,14,8,10,0,2,5,7,13,15,9,11,1,3,88,89,94,95,116,117,118,119,106,107,78,79,82,83,112,113,84,85,102,103,98,99,8,10,0,2,9,11,1,3,12,14,13,15,4,6,5,7,12,14,4,6,13,15,0,2,8,10,5,7,1,3,9,11,0,2,1,3,4,6,8,10,12,14,5,7,9,11,13,15,8,10,12,14,0,2,9,11,13,15,1,3,4,6,5,7,8,10,9,11,4,6,0,2,12,14,5,7,1,3,13,15,4,6,5,7,8,10,12,14,9,11,13,15,0,2,1,3,4,6,12,14,8,10,5,7,13,15,0,2,9,11,1,3,69,102,103,108,109,86,87,114,115,98,99,66,67,84,85,96,97,74,75,68,69,104,105,108,109,102,103,244,245,0,0,0,0,0,0,0,0,0,0,0,0,0,0,0,0,0,0,0,0,0,0,0,0,0,0,0,0,0,0,0,0,0,0,0,0,0,0,0,0,0,0,0,0,0,0,0,0,0},
  {64,65,66,67,68,69,70,71,72,73,74,75,76,77,78,79,0,1,2,3,0,1,2,3,4,5,6,7,8,9,10,11,12,13,14,15,64,66,76,78,65,67,77,79,68,70,69,71,72,74,73,75,12,14,8,10,13,15,9,11,0,2,4,6,1,3,5,7,4,6,12,14,8,10,0,2,5,7,13,15,9,11,1,3,0,2,8,10,4,6,12,14,1,3,9,11,5,7,13,15,8,10,0,2,9,11,1,3,12,14,13,15,4,6,5,7,94,95,108,109,76,77,88,89,114,115,96,97,102,103,116,117,118,119,0,2,1,3,4,6,8,10,12,14,5,7,9,11,13,15,8,10,12,14,0,2,9,11,13,15,1,3,4,6,5,7,8,10,9,11,4,6,0,2,12,14,5,7,1,3,13,15,4,6,5,7,8,10,12,14,9,11,13,15,0,2,1,3,4,6,12,14,8,10,5,7,13,15,0,2,9,11,1,3,118,119,76,77,74,75,68,69,72,73,100,101,110,111,84,85,78,79,116,117,94,95,242,243,214,215,240,241,226,227,0,0,0,0,0,0,0,0,0,0,0,0,0,0,0,0,0,0,0,0,0,0,0,0,0,0,0,0,0,0,0,0,0,0,0,0,0,0,0,0,0,0,0,0,0,0,0,0,0,0,0,0},
  {64,65,66,67,68,69,70,71,72,73,74,75,76,77,78,79,64,65,66,67,68,69,70,71,72,73,74,75,76,77,78,79,128,129,130,131,132,133,134,135,136,137,138,139,140,141,142,143,0,2,8,10,1,3,9,11,12,14,4,6,13,15,5,7,12,14,8,10,13,15,9,11,0,2,4,6,1,3,5,7,4,6,12,14,8,10,0,2,5,7,13,15,9,11,1,3,68,70,76,78,72,74,64,66,69,71,77,79,73,75,65,67,72,73,80,81,106,107,116,117,108,109,64,65,94,95,86,87,114,115,102,103,226,234,235,224,225,216,217,198,199,206,207,246,247,194,195,64,71,78,77,69,72,75,70,74,79,76,73,68,67,66,65,196,198,192,194,197,199,193,195,200,202,204,206,201,203,205,207,12,14,8,10,4,6,0,2,13,15,9,11,5,7,1,3,12,14,8,10,13,15,132,134,9,11,133,135,128,130,1,3,196,198,204,206,200,202,69,71,205,207,201,203,192,194,193,195,81,66,67,90,91,96,97,114,115,74,75,198,199,238,239,210,211,0,0,0,0,0,0,0,0,0,0,0,0,0,0,0,0,0,0,0,0,0,0,0,0,0,0,0,0,0,0,0,0,0,0,0,0,0,0,0,0,0,0,0,0,0,0,0,0,0,0,0,0},
  {64,65,66,67,68,69,70,71,72,73,74,75,76,77,78,79,0,1,2,3,0,1,2,3,4,5,6,7,8,9,10,11,12,13,14,15,64,66,76,78,65,67,77,79,68,70,69,71,72,74,73,75,4,6,0,2,5,7,1,3,12,14,8,10,13,15,9,11,76,78,72,74,77,79,73,75,64,66,68,70,65,67,69,71,4,6,12,14,8,10,0,2,5,7,13,15,9,11,1,3,8,10,0,2,9,11,1,3,12,14,13,15,4,6,5,7,107,94,95,108,109,76,77,88,89,114,115,96,97,102,103,116,117,118,119,71,72,69,66,64,78,74,77,76,75,73,79,68,65,67,70,8,10,12,14,0,2,9,11,13,15,1,3,4,6,5,7,8,10,0,2,9,11,12,14,1,3,4,6,13,15,5,7,4,6,12,14,8,10,5,7,13,15,9,11,0,2,1,3,4,6,12,14,8,10,5,7,13,15,0,2,9,11,1,3,64,65,78,79,90,91,106,107,94,95,68,69,96,97,74,102,103,208,209,96,97,76,77,218,219,236,237,0,0,0,0,0,0,0,0,0,0,0,0,0,0,0,0,0,0,0,0,0,0,0,0,0,0,0,0,0,0,0,0,0,0,0,0,0,0,0,0,0,0,0,0,0,0,0,0,0,0,0,0,0,0},
  {0,1,2,3,4,5,6,7,8,9,10,11,12,13,14,15,0,1,2,3,79,75,77,73,128,129,130,131,132,133,134,135,136,137,138,139,140,141,142,143,0,2,8,10,1,3,9,11,12,14,4,6,13,15,5,7,4,6,8,10,0,2,5,7,9,11,12,14,1,3,13,15,4,6,8,10,0,2,5,7,9,11,12,14,1,3,13,15,4,6,12,14,8,10,0,2,5,7,13,15,9,11,1,3,72,73,80,81,98,99,74,75,110,111,112,113,86,87,92,93,78,79,64,65,66,67,84,85,68,69,90,91,104,218,219,220,221,230,231,196,197,71,69,72,78,64,77,75,74,79,73,67,76,70,68,66,65,8,10,0,2,9,11,12,14,1,3,4,6,13,15,5,7,12,14,8,10,4,6,0,2,13,15,9,11,5,7,1,3,12,14,8,10,13,15,4,6,9,11,5,7,0,2,1,3,196,198,204,206,200,202,197,199,205,207,192,194,201,203,193,195,78,79,106,235,86,87,94,95,76,77,220,221,200,201,98,99,212,213,0,0,0,0,0,0,0,0,0,0,0,0,0,0,0,0,0,0,0,0,0,0,0,0,0,0,0,0,0,0,0,0,0,0,0,0,0,0,0,0,0,0,0,0,0,0,0,0,0,0,0,0,0,0,0,0,0},
  {64,65,66,67,68,69,70,71,72,73,74,75,76,77,78,79,0,1,2,3,72,78,70,71,0,2,12,14,1,3,13,15,4,6,5,7,8,10,9,11,12,14,8,10,13,15,9,11,0,2,4,6,1,3,5,7,4,6,8,10,0,2,5,7,9,11,12,14,1,3,13,15,8,10,0,2,9,11,1,3,12,14,13,15,4,6,5,7,95,70,71,76,77,106,107,96,97,64,65,78,79,90,91,80,81,102,69,110,111,82,83,74,75,96,97,118,119,104,105,94,223,244,245,234,235,224,225,216,217,198,199,71,69,72,78,64,77,75,74,79,73,67,76,70,68,66,65,8,10,0,2,9,11,12,14,1,3,4,6,13,15,5,7,12,14,8,10,4,6,0,2,13,15,9,11,5,7,1,3,4,6,12,14,8,10,5,7,13,15,9,11,0,2,1,3,68,70,69,71,200,202,204,206,201,203,205,207,192,194,193,195,64,65,78,79,90,91,106,107,94,95,112,113,228,229,64,193,216,217,246,247,0,0,0,0,0,0,0,0,0,0,0,0,0,0,0,0,0,0,0,0,0,0,0,0,0,0,0,0,0,0,0,0,0,0,0,0,0,0,0,0,0,0,0,0,0,0,0,0,0,0,0,0,0,0,0,0,0,0,0,0,0,0,0,0,0},
  {64,65,66,67,68,69,70,71,72,73,74,75,76,77,78,79,0,1,2,3,128,129,130,131,132,133,134,135,136,137,138,139,140,141,142,143,64,66,76,78,65,67,77,79,68,70,69,71,72,74,73,75,12,14,8,10,13,15,9,11,0,2,4,6,1,3,5,7,70,71,64,65,98,99,92,93,78,79,112,113,94,95,72,73,80,81,84,85,114,115,116,117,106,107,66,67,111,98,99,66,67,94,95,70,71,76,77,106,107,96,97,64,65,78,79,90,91,80,81,102,103,104,105,236,237,240,241,72,105,70,71,210,211,100,101,106,71,72,69,66,64,78,74,77,76,75,73,79,68,65,67,70,64,71,70,74,77,69,78,72,76,78,74,77,71,70,64,66,69,207,200,75,68,204,73,195,65,4,6,5,7,8,10,12,14,9,11,13,15,0,2,1,3,12,14,8,10,13,15,132,134,9,11,133,135,0,2,1,3,118,119,76,77,74,75,68,69,72,73,100,101,110,111,84,85,206,207,116,117,94,95,114,115,214,215,112,113,98,99,192,193,0,0,0,0,0,0,0,0,0,0,0,0,0,0,0,0,0,0,0,0,0,0,0,0,0,0,0,0,0,0,0,0,0,0,0,0,0,0,0,0,0,0,0,0,0,0,0,0,0,0,0,0,0,0,0},
  {64,65,66,67,68,69,70,71,72,73,74,75,76,77,78,79,0,1,2,3,64,65,66,67,68,69,70,71,72,73,74,75,76,77,78,79,64,66,76,78,65,67,77,79,68,70,69,71,72,74,73,75,4,6,0,2,5,7,1,3,12,14,8,10,13,15,9,11,4,6,12,14,8,10,0,2,5,7,13,15,9,11,1,3,4,6,12,14,8,10,0,2,5,7,13,15,9,11,1,3,92,93,72,73,80,81,106,107,116,117,108,109,64,65,94,95,86,87,114,115,102,103,98,99,100,101,90,91,70,71,207,246,247,194,195,238,239,242,243,232,233,218,4,6,8,10,5,7,0,2,12,14,9,11,1,3,13,15,64,71,78,74,77,70,73,69,66,72,76,79,68,65,67,75,12,14,8,10,4,6,0,2,13,15,9,11,5,7,1,3,12,14,8,10,13,15,4,6,9,11,5,7,0,2,1,3,204,206,200,202,205,207,196,198,201,203,197,199,192,194,193,195,71,66,67,112,113,98,99,86,87,110,111,114,115,88,89,118,119,68,69,230,231,0,0,0,0,0,0,0,0,0,0,0,0,0,0,0,0,0,0,0,0,0,0,0,0,0,0,0,0,0,0,0,0,0,0,0,0,0,0,0,0,0,0,0,0,0,0,0,0,0,0,0,0,0},
  {64,65,66,67,68,69,70,71,72,73,74,75,76,77,78,79,0,1,2,3,0,1,2,3,4,5,6,7,8,9,10,11,12,13,14,15,64,66,76,78,65,67,77,79,68,70,69,71,72,74,73,75,12,14,8,10,13,15,9,11,0,2,4,6,1,3,5,7,4,6,0,2,5,7,1,3,12,14,8,10,13,15,9,11,4,6,8,10,0,2,5,7,9,11,12,14,1,3,13,15,82,83,98,99,108,109,92,93,78,79,84,85,100,101,66,67,74,75,112,113,84,85,88,89,66,67,78,79,92,93,4,6,5,7,0,2,8,10,12,14,1,3,9,11,13,15,4,6,8,10,5,7,0,2,12,14,9,11,1,3,13,15,8,10,0,2,9,11,12,14,1,3,4,6,13,15,5,7,12,14,8,10,4,6,0,2,13,15,9,11,5,7,1,3,12,14,8,10,13,15,132,134,9,11,5,7,0,2,1,3,196,198,69,71,200,202,204,206,201,203,205,207,192,194,193,195,78,79,106,107,86,87,94,95,76,77,220,221,200,201,98,99,212,213,208,0,0,0,0,0,0,0,0,0,0,0,0,0,0,0,0,0,0,0,0,0,0,0,0,0,0,0,0,0,0,0,0,0,0,0,0,0,0,0,0,0,0,0,0,0,0,0,0,0,0,0},
  {0,1,2,3,4,5,6,7,8,9,10,11,12,13,14,15,0,1,2,3,0,1,2,3,4,5,6,7,8,9,10,11,12,13,14,15,64,66,76,78,65,67,77,79,68,70,69,71,72,74,73,75,4,6,0,2,5,7,1,3,12,14,8,10,13,15,9,11,4,6,8,10,0,2,5,7,9,11,12,14,1,3,13,15,0,2,8,10,4,6,12,14,1,3,9,11,5,7,13,15,80,81,102,103,104,105,108,109,112,113,72,73,116,117,82,83,100,101,74,75,86,87,92,93,118,119,68,69,4,6,5,7,0,2,8,10,12,14,1,3,9,11,13,15,4,6,8,10,5,7,0,2,12,14,9,11,1,3,13,15,8,10,0,2,9,11,12,14,1,3,4,6,13,15,5,7,200,207,194,204,192,195,202,196,199,206,198,197,205,201,193,203,12,14,8,10,13,15,4,6,9,11,5,7,0,2,1,3,132,134,12,14,136,138,133,135,13,15,137,139,128,130,129,131,106,107,70,71,66,67,112,113,98,99,86,87,110,111,242,243,88,89,118,119,196,197,0,0,0,0,0,0,0,0,0,0,0,0,0,0,0,0,0,0,0,0,0,0,0,0,0,0,0,0,0,0,0,0,0,0,0,0,0,0,0,0,0,0,0,0,0,0,0,0,0,0},
  {64,65,66,67,68,69,70,71,72,73,74,75,76,77,78,79,0,1,2,3,4,5,6,7,8,9,10,11,12,13,14,15,0,1,2,3,72,76,64,70,66,74,71,78,67,79,65,69,75,68,73,77,4,6,0,2,5,7,1,3,12,14,8,10,13,15,9,11,4,6,8,10,0,2,5,7,9,11,12,14,1,3,13,15,0,2,8,10,4,6,12,14,1,3,9,11,5,7,13,15,64,66,72,74,68,70,76,78,65,67,73,75,69,71,77,79,111,82,83,74,75,96,97,118,119,104,105,4,6,5,7,0,2,8,10,12,14,1,3,9,11,13,15,76,78,68,70,0,2,13,15,5,7,8,10,1,3,9,11,8,10,0,2,9,11,12,14,1,3,4,6,13,15,5,7,12,14,8,10,4,6,0,2,13,15,9,11,5,7,1,3,4,6,12,14,8,10,5,7,13,15,9,11,0,2,1,3,12,14,136,138,132,134,0,2,141,143,137,139,133,135,129,131,64,65,84,85,92,93,104,105,74,75,206,207,100,101,82,83,200,201,116,117,222,223,234,0,0,0,0,0,0,0,0,0,0,0,0,0,0,0,0,0,0,0,0,0,0,0,0,0,0,0,0,0,0,0,0,0,0,0,0,0,0,0,0,0,0,0,0,0,0,0,0,0,0},
  {64,65,66,67,68,69,70,71,72,73,74,75,76,77,78,79,0,1,2,3,4,5,6,7,8,9,10,11,12,13,14,15,69,76,67,65,64,66,76,78,65,67,77,79,68,70,69,71,72,74,73,75,12,14,8,10,13,15,9,11,0,2,4,6,1,3,5,7,4,6,8,10,0,2,5,7,9,11,12,14,1,3,13,15,90,91,70,71,72,73,66,67,64,65,84,85,92,93,80,81,86,87,94,95,76,77,88,89,106,107,78,79,96,0,2,4,6,8,10,1,3,5,7,12,14,9,11,13,15,4,6,5,7,0,2,8,10,12,14,1,3,9,11,13,15,4,6,8,10,5,7,0,2,12,14,9,11,1,3,13,15,132,134,128,130,133,135,129,131,136,138,140,142,137,139,141,143,8,10,9,11,4,6,0,2,12,14,5,7,1,3,13,15,4,6,12,14,8,10,5,7,13,15,9,11,0,2,1,3,132,134,140,142,136,138,133,135,141,143,128,130,137,139,129,131,104,105,78,79,118,119,114,115,88,89,112,113,100,101,64,65,84,85,94,95,96,97,210,211,196,197,0,0,0,0,0,0,0,0,0,0,0,0,0,0,0,0,0,0,0,0,0,0,0,0,0,0,0,0,0,0,0,0,0,0,0,0,0,0,0,0,0,0,0,0,0},
  {64,65,66,67,68,69,70,71,72,73,74,75,76,77,78,79,0,1,2,3,128,129,130,131,132,133,134,135,136,137,138,139,140,141,142,143,128,129,130,131,132,133,134,135,136,137,138,139,140,141,142,143,0,2,8,10,1,3,9,11,12,14,4,6,13,15,5,7,4,6,8,10,0,2,5,7,9,11,12,14,1,3,13,15,4,6,12,14,8,10,0,2,5,7,13,15,9,11,1,3,103,104,105,108,109,112,113,72,73,116,117,82,83,100,101,74,75,86,87,92,93,118,119,68,69,76,78,68,70,77,79,64,66,72,74,69,71,65,67,73,75,0,2,1,3,4,6,8,10,12,14,5,7,9,11,13,15,132,134,128,130,133,135,129,131,136,138,140,142,137,139,141,143,8,10,9,11,4,6,0,2,12,14,5,7,1,3,13,15,4,6,12,14,8,10,5,7,13,15,9,11,0,2,1,3,132,134,140,142,136,138,133,135,141,143,128,130,137,139,129,131,65,112,113,98,99,88,89,86,87,84,85,90,91,106,107,68,69,104,105,76,77,116,117,110,111,102,103,194,195,0,0,0,0,0,0,0,0,0,0,0,0,0,0,0,0,0,0,0,0,0,0,0,0,0,0,0,0,0,0,0,0,0,0,0,0,0,0,0,0,0,0,0,0,0,0},
  {64,65,66,67,68,69,70,71,72,73,74,75,76,77,78,79,0,1,2,3,4,5,6,7,8,9,10,11,12,13,14,15,64,67,72,77,69,73,78,76,76,69,70,72,74,66,71,75,67,77,68,73,79,206,64,65,4,6,8,10,0,2,5,7,9,11,12,14,1,3,13,15,4,6,12,14,8,10,0,2,5,7,13,15,9,11,1,3,0,2,8,10,4,6,12,14,1,3,9,11,5,7,13,15,0,2,4,6,8,10,1,3,5,7,12,14,9,11,13,15,4,6,5,7,12,14,8,10,0,2,13,15,9,11,1,3,0,2,1,3,4,6,8,10,12,14,5,7,9,11,13,15,8,10,12,14,0,2,9,11,13,15,1,3,4,6,5,7,8,10,0,2,9,11,12,14,1,3,4,6,13,15,5,7,12,14,8,10,4,6,0,2,13,15,9,11,5,7,1,3,4,6,12,14,8,10,5,7,13,15,9,11,0,2,1,3,116,117,64,65,118,119,80,81,94,95,76,77,112,113,110,111,82,83,70,71,68,112,113,228,229,64,65,88,217,246,247,0,0,0,0,0,0,0,0,0,0,0,0,0,0,0,0,0,0,0,0,0,0,0,0,0,0,0,0,0,0,0,0,0,0,0,0,0,0,0,0,0,0,0,0,0,0,0,0,0},
  {64,65,66,67,68,69,70,71,72,73,74,75,76,77,78,79,0,1,2,3,128,129,130,131,132,133,134,135,136,137,138,139,140,141,142,143,64,66,76,78,65,67,77,79,68,70,69,71,72,74,73,75,12,14,8,10,13,15,9,11,0,2,4,6,1,3,5,7,4,6,8,10,0,2,5,7,9,11,12,14,1,3,13,15,64,65,70,71,80,81,112,113,90,91,102,103,118,119,104,105,114,115,106,107,94,95,68,69,82,83,98,99,108,109,92,12,14,4,6,13,15,0,2,8,10,5,7,1,3,9,11,4,6,5,7,0,2,8,10,12,14,1,3,9,11,13,15,76,78,68,70,64,66,77,79,69,71,72,74,65,67,73,75,132,134,128,130,133,135,129,131,136,138,140,142,137,139,141,143,12,14,8,10,4,6,0,2,13,15,9,11,5,7,1,3,4,6,12,14,8,10,5,7,13,15,9,11,0,2,1,3,4,6,12,14,136,138,5,7,13,15,137,139,128,130,129,131,64,65,84,85,92,93,104,105,74,75,206,207,100,101,82,83,72,73,116,117,222,223,234,235,198,0,0,0,0,0,0,0,0,0,0,0,0,0,0,0,0,0,0,0,0,0,0,0,0,0,0,0,0,0,0,0,0,0,0,0,0,0,0,0,0,0,0,0,0},
  {0,1,2,3,4,5,6,7,8,9,10,11,12,13,14,15,64,65,66,67,68,69,70,71,72,73,74,75,76,77,78,79,128,129,130,131,132,133,134,135,136,137,138,139,140,141,142,143,0,2,8,10,1,3,9,11,12,14,4,6,13,15,5,7,4,6,8,10,0,2,5,7,9,11,12,14,1,3,13,15,103,98,99,72,73,92,93,64,65,100,101,96,97,114,115,76,77,70,71,86,87,90,91,74,75,66,67,68,69,0,2,4,6,8,10,1,3,5,7,12,14,9,11,13,15,12,14,4,6,13,15,0,2,8,10,5,7,1,3,9,11,0,2,1,3,4,6,8,10,12,14,5,7,9,11,13,15,132,134,128,130,133,135,129,131,136,138,140,142,137,139,141,143,79,67,75,65,8,10,0,2,9,11,12,14,1,3,4,6,13,15,5,7,4,6,12,14,8,10,5,7,13,15,9,11,0,2,1,3,8,10,9,11,4,6,0,2,140,142,133,135,1,3,141,143,64,65,80,81,92,93,108,109,106,107,70,71,66,67,90,91,88,89,82,83,224,225,232,233,230,231,0,0,0,0,0,0,0,0,0,0,0,0,0,0,0,0,0,0,0,0,0,0,0,0,0,0,0,0,0,0,0,0,0,0,0,0,0,0,0,0,0,0,0,0,0},
  {64,65,66,67,68,69,70,71,72,73,74,75,76,77,78,79,0,1,2,3,64,65,66,67,68,69,70,71,72,73,74,75,76,77,78,79,64,66,76,78,65,67,77,79,68,70,69,71,72,74,73,75,4,6,0,2,5,7,1,3,12,14,8,10,13,15,9,11,4,6,8,10,0,2,5,7,9,11,12,14,1,3,13,15,90,91,70,71,72,73,66,67,64,65,84,85,92,93,80,81,86,87,94,95,76,77,88,89,106,107,78,79,96,97,0,2,4,6,8,10,1,3,5,7,12,14,9,11,13,15,4,6,5,7,0,2,8,10,12,14,1,3,9,11,13,15,12,14,4,6,0,2,13,15,5,7,8,10,1,3,9,11,64,71,70,74,77,69,78,72,76,68,66,73,8,10,9,11,4,6,0,2,12,14,5,7,1,3,13,15,4,6,12,14,8,10,5,7,13,15,9,11,0,2,1,3,12,14,8,10,13,15,4,6,9,11,5,7,0,2,1,3,106,107,104,105,92,93,88,89,72,73,90,91,100,101,206,207,116,117,64,65,118,119,80,209,222,223,204,0,0,0,0,0,0,0,0,0,0,0,0,0,0,0,0,0,0,0,0,0,0,0,0,0,0,0,0,0,0,0,0,0,0,0,0,0,0,0,0,0,0,0,0,0,0,0},
  {0,1,2,3,4,5,6,7,8,9,10,11,12,13,14,15,0,1,2,3,64,65,66,67,68,69,70,71,72,73,74,75,76,77,78,79,64,66,76,78,65,67,77,79,68,70,69,71,72,74,73,75,64,66,72,74,65,67,73,75,76,78,68,70,77,79,69,71,4,6,8,10,0,2,5,7,9,11,12,14,1,3,13,15,68,70,64,66,69,71,65,67,76,78,72,74,77,79,73,75,8,10,0,2,9,11,1,3,12,14,13,15,4,6,5,7,64,66,68,70,72,74,65,67,69,71,76,78,73,75,77,79,4,6,5,7,0,2,8,10,12,14,1,3,9,11,13,15,4,6,8,10,5,7,0,2,12,14,9,11,1,3,13,15,64,71,78,74,77,70,73,69,66,72,76,79,68,65,67,75,12,14,8,10,4,6,0,2,13,15,9,11,5,7,1,3,12,14,8,10,13,15,132,134,9,11,133,135,0,2,1,3,204,206,200,202,205,207,196,198,201,203,197,199,192,194,193,195,107,70,71,66,67,112,113,98,99,86,87,110,111,242,243,88,89,118,119,196,197,0,0,0,0,0,0,0,0,0,0,0,0,0,0,0,0,0,0,0,0,0,0,0,0,0,0,0,0,0,0,0,0,0,0,0,0,0,0,0,0,0,0,0,0,0,0,0},
  {64,65,66,67,68,69,70,71,72,73,74,75,76,77,78,79,0,1,2,3,72,78,70,71,128,129,130,131,132,133,134,135,136,137,138,139,140,141,142,143,0,2,8,10,1,3,9,11,12,14,4,6,13,15,5,7,12,14,8,10,13,15,9,11,0,2,4,6,1,3,5,7,4,6,12,14,8,10,0,2,5,7,13,15,9,11,1,3,8,10,0,2,9,11,1,3,12,14,13,15,4,6,5,7,75,88,89,76,77,96,97,86,87,72,73,116,117,110,111,4,6,5,7,12,14,8,10,0,2,13,15,9,11,1,3,12,14,4,6,0,2,13,15,5,7,8,10,1,3,9,11,132,134,128,130,133,135,129,131,136,138,140,142,137,139,141,143,8,10,9,11,4,6,0,2,12,14,5,7,1,3,13,15,4,6,5,7,8,10,12,14,9,11,13,15,0,2,1,3,12,14,8,10,13,15,132,134,9,11,133,135,128,130,129,131,116,117,96,97,74,75,64,65,112,113,82,83,106,107,84,80,81,66,67,90,91,96,97,242,243,74,75,198,199,0,0,0,0,0,0,0,0,0,0,0,0,0,0,0,0,0,0,0,0,0,0,0,0,0,0,0,0,0,0,0,0,0,0,0,0,0,0,0,0,0,0,0,0,0,0,0,0,0,0,0,0},
  {0,1,2,3,4,5,6,7,8,9,10,11,12,13,14,15,0,1,2,3,0,1,2,3,4,5,6,7,8,9,10,11,12,13,14,15,0,1,2,3,76,69,70,72,74,66,71,75,67,77,68,73,79,78,64,65,12,14,8,10,13,15,9,11,0,2,4,6,1,3,5,7,4,6,8,10,0,2,5,7,9,11,12,14,1,3,13,15,0,2,8,10,4,6,12,14,1,3,9,11,5,7,13,15,0,2,4,6,8,10,1,3,5,7,12,14,9,11,13,15,95,108,109,76,77,88,89,114,115,96,97,102,103,244,245,246,247,219,220,221,230,231,196,197,4,6,8,10,5,7,0,2,12,14,9,11,1,3,13,15,64,71,70,74,77,69,78,72,76,68,66,73,79,67,75,65,12,14,8,10,4,6,0,2,13,15,9,11,5,7,1,3,12,14,8,10,13,15,4,6,9,11,5,7,0,2,1,3,76,78,72,74,77,79,68,70,73,75,69,71,64,66,65,67,82,83,70,71,100,101,102,103,84,85,116,117,72,73,86,87,110,111,232,233,204,205,0,0,0,0,0,0,0,0,0,0,0,0,0,0,0,0,0,0,0,0,0,0,0,0,0,0,0,0,0,0,0,0,0,0,0,0,0,0,0,0,0,0,0,0,0,0,0,0,0,0},
  {64,65,66,67,68,69,70,71,72,73,74,75,76,77,78,79,0,1,2,3,4,5,6,7,8,9,10,11,12,13,14,15,70,64,76,66,74,72,79,71,78,67,69,65,75,77,68,73,0,2,8,10,1,3,9,11,12,14,4,6,13,15,5,7,4,6,12,14,8,10,0,2,5,7,13,15,9,11,1,3,4,6,12,14,8,10,0,2,5,7,13,15,9,11,1,3,8,10,0,2,9,11,1,3,12,14,13,15,4,6,5,7,12,14,4,6,13,15,0,2,8,10,5,7,1,3,9,11,4,6,5,7,0,2,8,10,12,14,1,3,9,11,13,15,4,6,8,10,5,7,0,2,12,14,9,11,1,3,13,15,132,134,128,130,133,135,129,131,136,138,140,142,137,139,141,143,8,10,9,11,4,6,0,2,12,14,5,7,1,3,13,15,4,6,12,14,8,10,5,7,13,15,9,11,0,2,1,3,8,10,0,2,9,11,140,142,1,3,132,134,141,143,133,135,92,93,108,109,98,99,80,81,100,101,70,71,110,111,82,83,68,69,104,105,108,109,102,103,244,245,0,0,0,0,0,0,0,0,0,0,0,0,0,0,0,0,0,0,0,0,0,0,0,0,0,0,0,0,0,0,0,0,0,0,0,0,0,0,0,0,0,0,0,0,0,0},
  {0,1,2,3,4,5,6,7,8,9,10,11,12,13,14,15,0,1,2,3,0,1,2,3,4,5,6,7,8,9,10,11,12,13,14,15,64,66,76,78,65,67,77,79,68,70,69,71,72,74,73,75,12,14,8,10,13,15,9,11,0,2,4,6,1,3,5,7,4,6,0,2,5,7,1,3,12,14,8,10,13,15,9,11,90,91,70,71,72,73,66,67,64,65,84,85,92,93,80,81,86,87,94,95,76,77,88,89,106,107,78,79,96,97,108,109,72,73,80,81,98,99,74,75,110,111,240,241,86,87,92,93,206,207,192,193,0,2,1,3,4,6,8,10,12,14,5,7,9,11,13,15,8,10,12,14,0,2,9,11,13,15,1,3,4,6,5,7,8,10,9,11,4,6,0,2,12,14,5,7,1,3,13,15,4,6,5,7,8,10,12,14,9,11,13,15,0,2,1,3,132,134,5,7,136,138,140,142,9,11,141,143,128,130,129,131,104,105,72,73,86,87,102,103,90,91,118,119,68,69,206,207,114,115,66,67,110,111,222,223,216,217,204,205,0,0,0,0,0,0,0,0,0,0,0,0,0,0,0,0,0,0,0,0,0,0,0,0,0,0,0,0,0,0,0,0,0,0,0,0,0,0,0,0,0,0,0,0,0,0,0,0,0,0,0,0},
  {64,65,66,67,68,69,70,71,72,73,74,75,76,77,78,79,0,1,2,3,128,129,130,131,132,133,134,135,136,137,138,139,140,141,142,143,64,66,76,78,65,67,77,79,68,70,69,71,72,74,73,75,12,14,8,10,13,15,9,11,0,2,4,6,1,3,5,7,4,6,8,10,0,2,5,7,9,11,12,14,1,3,13,15,0,2,8,10,4,6,12,14,1,3,9,11,5,7,13,15,99,102,103,68,69,110,111,104,105,73,116,117,82,83,100,101,74,75,86,87,92,93,118,119,68,69,4,6,5,7,12,14,8,10,0,2,13,15,9,11,1,3,79,68,65,67,70,64,71,78,77,69,72,75,70,74,79,76,73,68,67,66,65,8,10,0,2,9,11,12,14,1,3,4,6,13,15,5,7,12,14,8,10,4,6,0,2,13,15,9,11,5,7,1,3,4,6,12,14,8,10,5,7,13,15,0,2,9,11,1,3,80,81,96,97,92,93,108,109,70,71,82,83,100,101,78,206,207,106,107,86,87,94,95,76,77,220,221,200,201,226,227,0,0,0,0,0,0,0,0,0,0,0,0,0,0,0,0,0,0,0,0,0,0,0,0,0,0,0,0,0,0,0,0,0,0,0,0,0,0,0,0,0,0,0,0,0,0,0,0,0,0,0,0,0,0},
};

struct alignas(64) Params {
  CUtensorMap a[6];
  CUtensorMap w[4];
  CUtensorMap ow;
  CUtensorMap xr;
  const bf16 *x0, *wqkv;
  bf16* out;
  uint32_t swap;
  uint32_t jobs[NPAIR][JMAX];
  uint8_t kseq[NPAIR][KMAX];
};

template <class T> __device__ __forceinline__ T* at(T* base, uint32_t bytes) {
  T* r;
  asm("{\n.reg .u32 lo, hi;\nmov.b64 {lo, hi}, %1;\nadd.cc.u32 lo, lo, %2;\naddc.u32 hi, hi, 0;\nmov.b64 %0, {lo, hi};\n}" : "=l"(r) : "l"(base), "r"(bytes));
  return r;
}
#define SCR(sm, member, bytes) reinterpret_cast<decltype(&scratch_base()->member[0])>(at((sm).scratch, offsetof(Scratch, member) + (bytes)))
#define counter(line, word) SCR(sm, cnt, (line) * 128 + (word) * 4)
#define TRS(st, slot) do {} while (0)
#define TRX(cond, job, bit, slot, reg) do {} while (0)
#define TR(job, slot) do {} while (0)
#define TRI(cond, job, slot) do {} while (0)
#define TRK(cond, job, slot) do {} while (0)
#define TRC(job, slot) do {} while (0)

__device__ __forceinline__ uint32_t smem_u32(const void* p) { return (uint32_t)__cvta_generic_to_shared(p); }
__device__ __forceinline__ void mbar_init(uint32_t bar, uint32_t cnt) { asm volatile("mbarrier.init.shared::cta.b64 [%0], %1;" ::"r"(bar), "r"(cnt) : "memory"); }
__device__ __forceinline__ void mbar_expect_tx(uint32_t bar, uint32_t bytes) { asm volatile("mbarrier.arrive.expect_tx.shared::cta.b64 _, [%0], %1;" ::"r"(bar), "r"(bytes) : "memory"); }
__device__ __forceinline__ void mbar_arrive_n(uint32_t bar, uint32_t cnt) { asm volatile("mbarrier.arrive.shared::cta.b64 _, [%0], %1;" ::"r"(bar), "r"(cnt) : "memory"); }
__device__ __forceinline__ void mbar_arrive_cl_if(uint32_t cond, uint32_t bar) {
  asm volatile("{\n.reg .pred p;\nsetp.ne.u32 p, %1, 0;\n@p mbarrier.arrive.shared::cluster.b64 _, [%0];\n}" ::"r"(bar), "r"(cond) : "memory");
}
__device__ __forceinline__ void mbar_arrive_warp(uint32_t bar) {
  asm volatile("{\n.reg .pred p;\nbar.warp.sync -1;\nelect.sync _|p, -1;\n@p mbarrier.arrive.shared::cta.b64 _, [%0];\n}" ::"r"(bar) : "memory");
}
__device__ __forceinline__ uint32_t mapa(uint32_t addr, uint32_t cta) { uint32_t r; asm("mapa.shared::cluster.u32 %0, %1, %2;" : "=r"(r) : "r"(addr), "r"(cta)); return r; }
__device__ __forceinline__ bool mbar_test(uint32_t bar, uint32_t parity) {
  uint32_t ok;
  asm volatile("{\n.reg .pred p;\nmbarrier.test_wait.parity.shared::cta.b64 p, [%1], %2;\nselp.u32 %0, 1, 0, p;\n}\n" : "=r"(ok) : "r"(bar), "r"(parity) : "memory");
  return ok;
}
__device__ __forceinline__ void mbar_wait(uint32_t bar, uint32_t parity) {
  asm volatile(
      "{\n.reg .pred p;\n.reg .u32 n;\nmov.u32 n, 0;\n"
      "WAIT:\nmbarrier.try_wait.parity.shared::cta.b64 p, [%0], %1;\n@p bra DONE;\n"
      "add.u32 n, n, 1;\nsetp.lt.u32 p, n, %2;\n@p bra WAIT;\ntrap;\nDONE:\n}\n" ::"r"(bar), "r"(parity), "n"(SPIN_LIMIT) : "memory");
}
template <int ID, int N> __device__ __forceinline__ void bar_sync() { asm volatile("bar.sync %0, %1;" ::"n"(ID), "n"(N) : "memory"); }
template <int ID, int N> __device__ __forceinline__ void bar_arrive() { asm volatile("bar.arrive %0, %1;" ::"n"(ID), "n"(N) : "memory"); }
__device__ __forceinline__ uint32_t ld_relaxed(const uint32_t* p) { uint32_t v; asm volatile("ld.relaxed.gpu.global.u32 %0, [%1];" : "=r"(v) : "l"(p) : "memory"); return v; }
__device__ __forceinline__ void red_relaxed(uint32_t* p, uint32_t v) { asm volatile("red.relaxed.gpu.global.add.u32 [%0], %1;" ::"l"(p), "r"(v) : "memory"); }
__device__ __forceinline__ void red_release(uint32_t* p, uint32_t v) {
  asm volatile("fence.release.gpu;\nred.relaxed.gpu.global.add.u32 [%0], %1;" ::"l"(p), "r"(v) : "memory");
}
__device__ __forceinline__ bool elect() {
  uint32_t p;
  asm volatile("{\n.reg .pred P;\nelect.sync _|P, 0xffffffff;\nselp.u32 %0, 1, 0, P;\n}\n" : "=r"(p));
  return p;
}
__device__ __forceinline__ void fence_acquire() { asm volatile("fence.acquire.gpu;" ::: "memory"); }
__device__ __forceinline__ void wait_count(const uint32_t* p, uint32_t target) {
  for (uint32_t n = 0; !__all_sync(~0u, (int)(ld_relaxed(p) - target) >= 0); n++) {
    __nanosleep(200);
    if (n > SPIN_LIMIT) __trap();
  }
  fence_acquire();
}
__device__ __forceinline__ void fence_proxy_async() { asm volatile("fence.proxy.async.global;" ::: "memory"); }
__device__ __forceinline__ void fence_proxy_async_smem() { asm volatile("fence.proxy.async.shared::cta;" ::: "memory"); }
__device__ __forceinline__ void tma4d_mc(uint32_t dst, const CUtensorMap* tm, int c1, int c2, uint32_t bar, uint64_t pol) {
  asm volatile("cp.async.bulk.tensor.4d.shared::cluster.global.mbarrier::complete_tx::bytes.multicast::cluster.L2::cache_hint [%0], [%1, {%3, %4, %5, %3}], [%2], %6, %7;"
               ::"r"(dst), "l"(tm), "r"(bar), "r"(0), "r"(c1), "r"(c2), "h"((uint16_t)3), "l"(pol) : "memory");
}
__device__ __forceinline__ void tma3d(uint32_t dst, const CUtensorMap* tm, int c0, int c1, int c2, uint32_t bar, uint64_t pol) {
  asm volatile("cp.async.bulk.tensor.3d.shared::cluster.global.mbarrier::complete_tx::bytes.L2::cache_hint [%0], [%1, {%3, %4, %5}], [%2], %6;"
               ::"r"(dst), "l"(tm), "r"(bar), "r"(c0), "r"(c1), "r"(c2), "l"(pol) : "memory");
}
__device__ __forceinline__ void tma3d_reduce_add(const CUtensorMap* tm, int c0, int c1, int c2, uint32_t src) {
  asm volatile("cp.reduce.async.bulk.tensor.3d.global.shared::cta.add.tile.bulk_group [%0, {%2, %3, %4}], [%1];"
               ::"l"(tm), "r"(src), "r"(c0), "r"(c1), "r"(c2) : "memory");
}
__device__ __forceinline__ void tma3d_store(const CUtensorMap* tm, int c0, int c1, int c2, uint32_t src) {
  asm volatile("cp.async.bulk.tensor.3d.global.shared::cta.tile.bulk_group [%0, {%2, %3, %4}], [%1];"
               ::"l"(tm), "r"(src), "r"(c0), "r"(c1), "r"(c2) : "memory");
}
__device__ __forceinline__ void bulk_commit() { asm volatile("cp.async.bulk.commit_group;" ::: "memory"); }
template <int N> __device__ __forceinline__ void bulk_wait_read() { asm volatile("cp.async.bulk.wait_group.read %0;" ::"n"(N) : "memory"); }
__device__ __forceinline__ void bulk_wait() { asm volatile("cp.async.bulk.wait_group 0;" ::: "memory"); }
__device__ __forceinline__ uint2 lds64(uint32_t a) { uint2 v; asm volatile("ld.shared.v2.u32 {%0,%1}, [%2];" : "=r"(v.x), "=r"(v.y) : "r"(a) : "memory"); return v; }
__device__ __forceinline__ float lds32f(uint32_t a) { float v; asm volatile("ld.shared.f32 %0, [%1];" : "=f"(v) : "r"(a) : "memory"); return v; }
__device__ __forceinline__ uint4 lds128(uint32_t a) { uint4 v; asm volatile("ld.shared.v4.u32 {%0,%1,%2,%3}, [%4];" : "=r"(v.x), "=r"(v.y), "=r"(v.z), "=r"(v.w) : "r"(a) : "memory"); return v; }
__device__ __forceinline__ uint2 lds64v(uint32_t a) { uint2 v; asm volatile("ld.volatile.shared.v2.u32 {%0,%1}, [%2];" : "=r"(v.x), "=r"(v.y) : "r"(a) : "memory"); return v; }
__device__ __forceinline__ uint4 lds128v(uint32_t a) { uint4 v; asm volatile("ld.volatile.shared.v4.u32 {%0,%1,%2,%3}, [%4];" : "=r"(v.x), "=r"(v.y), "=r"(v.z), "=r"(v.w) : "r"(a) : "memory"); return v; }
__device__ __forceinline__ void sts32(uint32_t a, uint32_t v) { asm volatile("st.shared.u32 [%0], %1;" ::"r"(a), "r"(v) : "memory"); }
__device__ __forceinline__ void sts64(uint32_t a, uint2 v) { asm volatile("st.shared.v2.u32 [%0], {%1,%2};" ::"r"(a), "r"(v.x), "r"(v.y) : "memory"); }
__device__ __forceinline__ void stg128(void* p, uint4 v) { asm volatile("st.global.L1::no_allocate.v4.u32 [%0], {%1,%2,%3,%4};" ::"l"(p), "r"(v.x), "r"(v.y), "r"(v.z), "r"(v.w) : "memory"); }
__device__ __forceinline__ uint4 ldg128(const void* p) { uint4 v; asm volatile("ld.relaxed.gpu.global.v4.u32 {%0,%1,%2,%3}, [%4];" : "=r"(v.x), "=r"(v.y), "=r"(v.z), "=r"(v.w) : "l"(p) : "memory"); return v; }
__device__ __forceinline__ void prefetch_tm(const CUtensorMap* tm) { asm volatile("prefetch.tensormap [%0];" ::"l"(tm) : "memory"); }
template <int N> __device__ __forceinline__ void wg_wait() { asm volatile("wgmma.wait_group.sync.aligned %0;" ::"n"(N) : "memory"); }
__device__ __forceinline__ void cluster_arrive() { asm volatile("barrier.cluster.arrive.relaxed.aligned;" ::: "memory"); }
__device__ __forceinline__ void cluster_wait() { asm volatile("barrier.cluster.wait.acquire.aligned;" ::: "memory"); }
__device__ __forceinline__ uint32_t pack_bf16(float lo, float hi) { uint32_t r; asm("cvt.rn.bf16x2.f32 %0, %1, %2;" : "=r"(r) : "f"(hi), "f"(lo)); return r; }
__device__ __forceinline__ float bf_lo(uint32_t v) { return __uint_as_float(v << 16); }
__device__ __forceinline__ float bf_hi(uint32_t v) { return __uint_as_float(v & 0xffff0000u); }
__device__ __forceinline__ uint32_t dup_hi(uint32_t v) { return __byte_perm(v, 0, 0x3232); }
__device__ __forceinline__ float bf_round(float x) { return __bfloat162float(__float2bfloat16_rn(x)); }
__device__ __forceinline__ uint32_t bf2_add(uint32_t a, uint32_t b) { uint32_t r; asm("add.rn.bf16x2 %0, %1, %2;" : "=r"(r) : "r"(a), "r"(b)); return r; }
__device__ __forceinline__ uint32_t bf2_mul(uint32_t a, uint32_t b) { uint32_t r; asm("mul.rn.bf16x2 %0, %1, %2;" : "=r"(r) : "r"(a), "r"(b)); return r; }
__device__ __forceinline__ uint32_t bf2_fma(uint32_t a, uint32_t b, uint32_t c) { uint32_t r; asm("fma.rn.bf16x2 %0, %1, %2, %3;" : "=r"(r) : "r"(a), "r"(b), "r"(c)); return r; }
__device__ __forceinline__ uint4 add8(uint4 a, uint4 b) { return make_uint4(bf2_add(a.x, b.x), bf2_add(a.y, b.y), bf2_add(a.z, b.z), bf2_add(a.w, b.w)); }
__device__ __forceinline__ uint4 fma8(uint32_t a, uint4 b, uint4 c) { return make_uint4(bf2_fma(a, b.x, c.x), bf2_fma(a, b.y, c.y), bf2_fma(a, b.z, c.z), bf2_fma(a, b.w, c.w)); }
__device__ __forceinline__ void stsm4(uint32_t a, uint32_t r0, uint32_t r1, uint32_t r2, uint32_t r3) {
  asm volatile("stmatrix.sync.aligned.m8n8.x4.shared.b16 [%0], {%1,%2,%3,%4};" ::"r"(a), "r"(r0), "r"(r1), "r"(r2), "r"(r3) : "memory");
}
__device__ __forceinline__ void ldsm4(uint32_t a, uint32_t (&r)[4]) {
  asm volatile("ldmatrix.sync.aligned.m8n8.x4.shared.b16 {%0,%1,%2,%3}, [%4];" : "=r"(r[0]), "=r"(r[1]), "=r"(r[2]), "=r"(r[3]) : "r"(a) : "memory");
}
__device__ __forceinline__ void ldsm4t(uint32_t a, uint32_t (&r)[4]) {
  asm volatile("ldmatrix.sync.aligned.m8n8.x4.trans.shared.b16 {%0,%1,%2,%3}, [%4];" : "=r"(r[0]), "=r"(r[1]), "=r"(r[2]), "=r"(r[3]) : "r"(a) : "memory");
}
__device__ __forceinline__ void mma16816(float (&c)[4], uint32_t a0, uint32_t a1, uint32_t a2, uint32_t a3, uint32_t b0, uint32_t b1) {
  asm volatile("mma.sync.aligned.m16n8k16.row.col.f32.bf16.bf16.f32 {%0,%1,%2,%3}, {%4,%5,%6,%7}, {%8,%9}, {%0,%1,%2,%3};"
               : "+f"(c[0]), "+f"(c[1]), "+f"(c[2]), "+f"(c[3]) : "r"(a0), "r"(a1), "r"(a2), "r"(a3), "r"(b0), "r"(b1));
}
__device__ __forceinline__ void mma1688(float (&c)[4], uint32_t a0, uint32_t a1, uint32_t b0) {
  asm volatile("mma.sync.aligned.m16n8k8.row.col.f32.bf16.bf16.f32 {%0,%1,%2,%3}, {%4,%5}, {%6}, {%0,%1,%2,%3};"
               : "+f"(c[0]), "+f"(c[1]), "+f"(c[2]), "+f"(c[3]) : "r"(a0), "r"(a1), "r"(b0));
}
__device__ __forceinline__ float ex2(float x) { float y; asm("ex2.approx.ftz.f32 %0, %1;" : "=f"(y) : "f"(x)); return y; }
__device__ __forceinline__ float sqrt_fast(float x) { float y; asm("sqrt.approx.f32 %0, %1;" : "=f"(y) : "f"(x)); return y; }
__device__ __forceinline__ float tanh_fast(float x) { float y; asm("tanh.approx.f32 %0, %1;" : "=f"(y) : "f"(x)); return y; }
__device__ __forceinline__ float rcp(float x) { float y; asm("rcp.approx.ftz.f32 %0, %1;" : "=f"(y) : "f"(x)); return y; }
__device__ __forceinline__ uint32_t opaque_zero() { uint32_t z; asm volatile("mov.u32 %0, %%ctaid.y;" : "=r"(z)); return z; }
__device__ __forceinline__ int fresh_tid() { int t; asm volatile("mov.u32 %0, %%tid.x;" : "=r"(t)); return t; }

__device__ __forceinline__ void first_kstep(float (&d)[128], uint32_t a, uint32_t b) {
  asm volatile("{\n.reg .u32 t;\n.reg .u64 da, db;\nwgmma.fence.sync.aligned;\n"
    "add.u32 t, %128, 0;\nmov.b64 da, {t, %130};\nadd.u32 t, %129, 0;\nmov.b64 db, {t, %130};\n"
    "wgmma.mma_async.sync.aligned.m64n256k16.f32.bf16.bf16 {%0, %1, %2, %3, %4, %5, %6, %7, %8, %9, %10, %11, %12, %13, %14, %15, %16, %17, %18, %19, %20, %21, %22, %23, %24, %25, %26, %27, %28, %29, %30, %31, %32, %33, %34, %35, %36, %37, %38, %39, %40, %41, %42, %43, %44, %45, %46, %47, %48, %49, %50, %51, %52, %53, %54, %55, %56, %57, %58, %59, %60, %61, %62, %63, %64, %65, %66, %67, %68, %69, %70, %71, %72, %73, %74, %75, %76, %77, %78, %79, %80, %81, %82, %83, %84, %85, %86, %87, %88, %89, %90, %91, %92, %93, %94, %95, %96, %97, %98, %99, %100, %101, %102, %103, %104, %105, %106, %107, %108, %109, %110, %111, %112, %113, %114, %115, %116, %117, %118, %119, %120, %121, %122, %123, %124, %125, %126, %127}, da, db, 0, 1, 1, 0, 1;\nwgmma.commit_group.sync.aligned;\n"
    "add.u32 t, %128, 2;\nmov.b64 da, {t, %130};\nadd.u32 t, %129, 128;\nmov.b64 db, {t, %130};\n"
    "wgmma.mma_async.sync.aligned.m64n256k16.f32.bf16.bf16 {%0, %1, %2, %3, %4, %5, %6, %7, %8, %9, %10, %11, %12, %13, %14, %15, %16, %17, %18, %19, %20, %21, %22, %23, %24, %25, %26, %27, %28, %29, %30, %31, %32, %33, %34, %35, %36, %37, %38, %39, %40, %41, %42, %43, %44, %45, %46, %47, %48, %49, %50, %51, %52, %53, %54, %55, %56, %57, %58, %59, %60, %61, %62, %63, %64, %65, %66, %67, %68, %69, %70, %71, %72, %73, %74, %75, %76, %77, %78, %79, %80, %81, %82, %83, %84, %85, %86, %87, %88, %89, %90, %91, %92, %93, %94, %95, %96, %97, %98, %99, %100, %101, %102, %103, %104, %105, %106, %107, %108, %109, %110, %111, %112, %113, %114, %115, %116, %117, %118, %119, %120, %121, %122, %123, %124, %125, %126, %127}, da, db, 1, 1, 1, 0, 1;\n"
    "add.u32 t, %128, 4;\nmov.b64 da, {t, %130};\nadd.u32 t, %129, 1024;\nmov.b64 db, {t, %130};\n"
    "wgmma.mma_async.sync.aligned.m64n256k16.f32.bf16.bf16 {%0, %1, %2, %3, %4, %5, %6, %7, %8, %9, %10, %11, %12, %13, %14, %15, %16, %17, %18, %19, %20, %21, %22, %23, %24, %25, %26, %27, %28, %29, %30, %31, %32, %33, %34, %35, %36, %37, %38, %39, %40, %41, %42, %43, %44, %45, %46, %47, %48, %49, %50, %51, %52, %53, %54, %55, %56, %57, %58, %59, %60, %61, %62, %63, %64, %65, %66, %67, %68, %69, %70, %71, %72, %73, %74, %75, %76, %77, %78, %79, %80, %81, %82, %83, %84, %85, %86, %87, %88, %89, %90, %91, %92, %93, %94, %95, %96, %97, %98, %99, %100, %101, %102, %103, %104, %105, %106, %107, %108, %109, %110, %111, %112, %113, %114, %115, %116, %117, %118, %119, %120, %121, %122, %123, %124, %125, %126, %127}, da, db, 1, 1, 1, 0, 1;\n"
    "add.u32 t, %128, 6;\nmov.b64 da, {t, %130};\nadd.u32 t, %129, 1152;\nmov.b64 db, {t, %130};\n"
    "wgmma.mma_async.sync.aligned.m64n256k16.f32.bf16.bf16 {%0, %1, %2, %3, %4, %5, %6, %7, %8, %9, %10, %11, %12, %13, %14, %15, %16, %17, %18, %19, %20, %21, %22, %23, %24, %25, %26, %27, %28, %29, %30, %31, %32, %33, %34, %35, %36, %37, %38, %39, %40, %41, %42, %43, %44, %45, %46, %47, %48, %49, %50, %51, %52, %53, %54, %55, %56, %57, %58, %59, %60, %61, %62, %63, %64, %65, %66, %67, %68, %69, %70, %71, %72, %73, %74, %75, %76, %77, %78, %79, %80, %81, %82, %83, %84, %85, %86, %87, %88, %89, %90, %91, %92, %93, %94, %95, %96, %97, %98, %99, %100, %101, %102, %103, %104, %105, %106, %107, %108, %109, %110, %111, %112, %113, %114, %115, %116, %117, %118, %119, %120, %121, %122, %123, %124, %125, %126, %127}, da, db, 1, 1, 1, 0, 1;\nwgmma.commit_group.sync.aligned;\n"
    "}\n"
    : "=f"(d[0]), "=f"(d[1]), "=f"(d[2]), "=f"(d[3]), "=f"(d[4]), "=f"(d[5]), "=f"(d[6]), "=f"(d[7]), "=f"(d[8]), "=f"(d[9]), "=f"(d[10]), "=f"(d[11]), "=f"(d[12]), "=f"(d[13]), "=f"(d[14]), "=f"(d[15]), "=f"(d[16]), "=f"(d[17]), "=f"(d[18]), "=f"(d[19]), "=f"(d[20]), "=f"(d[21]), "=f"(d[22]), "=f"(d[23]), "=f"(d[24]), "=f"(d[25]), "=f"(d[26]), "=f"(d[27]), "=f"(d[28]), "=f"(d[29]), "=f"(d[30]), "=f"(d[31]), "=f"(d[32]), "=f"(d[33]), "=f"(d[34]), "=f"(d[35]), "=f"(d[36]), "=f"(d[37]), "=f"(d[38]), "=f"(d[39]), "=f"(d[40]), "=f"(d[41]), "=f"(d[42]), "=f"(d[43]), "=f"(d[44]), "=f"(d[45]), "=f"(d[46]), "=f"(d[47]), "=f"(d[48]), "=f"(d[49]), "=f"(d[50]), "=f"(d[51]), "=f"(d[52]), "=f"(d[53]), "=f"(d[54]), "=f"(d[55]), "=f"(d[56]), "=f"(d[57]), "=f"(d[58]), "=f"(d[59]), "=f"(d[60]), "=f"(d[61]), "=f"(d[62]), "=f"(d[63]), "=f"(d[64]), "=f"(d[65]), "=f"(d[66]), "=f"(d[67]), "=f"(d[68]), "=f"(d[69]), "=f"(d[70]), "=f"(d[71]), "=f"(d[72]), "=f"(d[73]), "=f"(d[74]), "=f"(d[75]), "=f"(d[76]), "=f"(d[77]), "=f"(d[78]), "=f"(d[79]), "=f"(d[80]), "=f"(d[81]), "=f"(d[82]), "=f"(d[83]), "=f"(d[84]), "=f"(d[85]), "=f"(d[86]), "=f"(d[87]), "=f"(d[88]), "=f"(d[89]), "=f"(d[90]), "=f"(d[91]), "=f"(d[92]), "=f"(d[93]), "=f"(d[94]), "=f"(d[95]), "=f"(d[96]), "=f"(d[97]), "=f"(d[98]), "=f"(d[99]), "=f"(d[100]), "=f"(d[101]), "=f"(d[102]), "=f"(d[103]), "=f"(d[104]), "=f"(d[105]), "=f"(d[106]), "=f"(d[107]), "=f"(d[108]), "=f"(d[109]), "=f"(d[110]), "=f"(d[111]), "=f"(d[112]), "=f"(d[113]), "=f"(d[114]), "=f"(d[115]), "=f"(d[116]), "=f"(d[117]), "=f"(d[118]), "=f"(d[119]), "=f"(d[120]), "=f"(d[121]), "=f"(d[122]), "=f"(d[123]), "=f"(d[124]), "=f"(d[125]), "=f"(d[126]), "=f"(d[127])
    : "r"(a), "r"(b), "n"(0x40000040) : "memory");
}
__device__ __forceinline__ void kstep(float (&d)[128], uint32_t a, uint32_t b) {
  asm volatile("{\n.reg .u32 t;\n.reg .u64 da, db;\nwgmma.fence.sync.aligned;\n"
    "add.u32 t, %128, 0;\nmov.b64 da, {t, %130};\nadd.u32 t, %129, 0;\nmov.b64 db, {t, %130};\n"
    "wgmma.mma_async.sync.aligned.m64n256k16.f32.bf16.bf16 {%0, %1, %2, %3, %4, %5, %6, %7, %8, %9, %10, %11, %12, %13, %14, %15, %16, %17, %18, %19, %20, %21, %22, %23, %24, %25, %26, %27, %28, %29, %30, %31, %32, %33, %34, %35, %36, %37, %38, %39, %40, %41, %42, %43, %44, %45, %46, %47, %48, %49, %50, %51, %52, %53, %54, %55, %56, %57, %58, %59, %60, %61, %62, %63, %64, %65, %66, %67, %68, %69, %70, %71, %72, %73, %74, %75, %76, %77, %78, %79, %80, %81, %82, %83, %84, %85, %86, %87, %88, %89, %90, %91, %92, %93, %94, %95, %96, %97, %98, %99, %100, %101, %102, %103, %104, %105, %106, %107, %108, %109, %110, %111, %112, %113, %114, %115, %116, %117, %118, %119, %120, %121, %122, %123, %124, %125, %126, %127}, da, db, 1, 1, 1, 0, 1;\nwgmma.commit_group.sync.aligned;\n"
    "add.u32 t, %128, 2;\nmov.b64 da, {t, %130};\nadd.u32 t, %129, 128;\nmov.b64 db, {t, %130};\n"
    "wgmma.mma_async.sync.aligned.m64n256k16.f32.bf16.bf16 {%0, %1, %2, %3, %4, %5, %6, %7, %8, %9, %10, %11, %12, %13, %14, %15, %16, %17, %18, %19, %20, %21, %22, %23, %24, %25, %26, %27, %28, %29, %30, %31, %32, %33, %34, %35, %36, %37, %38, %39, %40, %41, %42, %43, %44, %45, %46, %47, %48, %49, %50, %51, %52, %53, %54, %55, %56, %57, %58, %59, %60, %61, %62, %63, %64, %65, %66, %67, %68, %69, %70, %71, %72, %73, %74, %75, %76, %77, %78, %79, %80, %81, %82, %83, %84, %85, %86, %87, %88, %89, %90, %91, %92, %93, %94, %95, %96, %97, %98, %99, %100, %101, %102, %103, %104, %105, %106, %107, %108, %109, %110, %111, %112, %113, %114, %115, %116, %117, %118, %119, %120, %121, %122, %123, %124, %125, %126, %127}, da, db, 1, 1, 1, 0, 1;\n"
    "add.u32 t, %128, 4;\nmov.b64 da, {t, %130};\nadd.u32 t, %129, 1024;\nmov.b64 db, {t, %130};\n"
    "wgmma.mma_async.sync.aligned.m64n256k16.f32.bf16.bf16 {%0, %1, %2, %3, %4, %5, %6, %7, %8, %9, %10, %11, %12, %13, %14, %15, %16, %17, %18, %19, %20, %21, %22, %23, %24, %25, %26, %27, %28, %29, %30, %31, %32, %33, %34, %35, %36, %37, %38, %39, %40, %41, %42, %43, %44, %45, %46, %47, %48, %49, %50, %51, %52, %53, %54, %55, %56, %57, %58, %59, %60, %61, %62, %63, %64, %65, %66, %67, %68, %69, %70, %71, %72, %73, %74, %75, %76, %77, %78, %79, %80, %81, %82, %83, %84, %85, %86, %87, %88, %89, %90, %91, %92, %93, %94, %95, %96, %97, %98, %99, %100, %101, %102, %103, %104, %105, %106, %107, %108, %109, %110, %111, %112, %113, %114, %115, %116, %117, %118, %119, %120, %121, %122, %123, %124, %125, %126, %127}, da, db, 1, 1, 1, 0, 1;\n"
    "add.u32 t, %128, 6;\nmov.b64 da, {t, %130};\nadd.u32 t, %129, 1152;\nmov.b64 db, {t, %130};\n"
    "wgmma.mma_async.sync.aligned.m64n256k16.f32.bf16.bf16 {%0, %1, %2, %3, %4, %5, %6, %7, %8, %9, %10, %11, %12, %13, %14, %15, %16, %17, %18, %19, %20, %21, %22, %23, %24, %25, %26, %27, %28, %29, %30, %31, %32, %33, %34, %35, %36, %37, %38, %39, %40, %41, %42, %43, %44, %45, %46, %47, %48, %49, %50, %51, %52, %53, %54, %55, %56, %57, %58, %59, %60, %61, %62, %63, %64, %65, %66, %67, %68, %69, %70, %71, %72, %73, %74, %75, %76, %77, %78, %79, %80, %81, %82, %83, %84, %85, %86, %87, %88, %89, %90, %91, %92, %93, %94, %95, %96, %97, %98, %99, %100, %101, %102, %103, %104, %105, %106, %107, %108, %109, %110, %111, %112, %113, %114, %115, %116, %117, %118, %119, %120, %121, %122, %123, %124, %125, %126, %127}, da, db, 1, 1, 1, 0, 1;\nwgmma.commit_group.sync.aligned;\n"
    "}\n"
    : "+f"(d[0]), "+f"(d[1]), "+f"(d[2]), "+f"(d[3]), "+f"(d[4]), "+f"(d[5]), "+f"(d[6]), "+f"(d[7]), "+f"(d[8]), "+f"(d[9]), "+f"(d[10]), "+f"(d[11]), "+f"(d[12]), "+f"(d[13]), "+f"(d[14]), "+f"(d[15]), "+f"(d[16]), "+f"(d[17]), "+f"(d[18]), "+f"(d[19]), "+f"(d[20]), "+f"(d[21]), "+f"(d[22]), "+f"(d[23]), "+f"(d[24]), "+f"(d[25]), "+f"(d[26]), "+f"(d[27]), "+f"(d[28]), "+f"(d[29]), "+f"(d[30]), "+f"(d[31]), "+f"(d[32]), "+f"(d[33]), "+f"(d[34]), "+f"(d[35]), "+f"(d[36]), "+f"(d[37]), "+f"(d[38]), "+f"(d[39]), "+f"(d[40]), "+f"(d[41]), "+f"(d[42]), "+f"(d[43]), "+f"(d[44]), "+f"(d[45]), "+f"(d[46]), "+f"(d[47]), "+f"(d[48]), "+f"(d[49]), "+f"(d[50]), "+f"(d[51]), "+f"(d[52]), "+f"(d[53]), "+f"(d[54]), "+f"(d[55]), "+f"(d[56]), "+f"(d[57]), "+f"(d[58]), "+f"(d[59]), "+f"(d[60]), "+f"(d[61]), "+f"(d[62]), "+f"(d[63]), "+f"(d[64]), "+f"(d[65]), "+f"(d[66]), "+f"(d[67]), "+f"(d[68]), "+f"(d[69]), "+f"(d[70]), "+f"(d[71]), "+f"(d[72]), "+f"(d[73]), "+f"(d[74]), "+f"(d[75]), "+f"(d[76]), "+f"(d[77]), "+f"(d[78]), "+f"(d[79]), "+f"(d[80]), "+f"(d[81]), "+f"(d[82]), "+f"(d[83]), "+f"(d[84]), "+f"(d[85]), "+f"(d[86]), "+f"(d[87]), "+f"(d[88]), "+f"(d[89]), "+f"(d[90]), "+f"(d[91]), "+f"(d[92]), "+f"(d[93]), "+f"(d[94]), "+f"(d[95]), "+f"(d[96]), "+f"(d[97]), "+f"(d[98]), "+f"(d[99]), "+f"(d[100]), "+f"(d[101]), "+f"(d[102]), "+f"(d[103]), "+f"(d[104]), "+f"(d[105]), "+f"(d[106]), "+f"(d[107]), "+f"(d[108]), "+f"(d[109]), "+f"(d[110]), "+f"(d[111]), "+f"(d[112]), "+f"(d[113]), "+f"(d[114]), "+f"(d[115]), "+f"(d[116]), "+f"(d[117]), "+f"(d[118]), "+f"(d[119]), "+f"(d[120]), "+f"(d[121]), "+f"(d[122]), "+f"(d[123]), "+f"(d[124]), "+f"(d[125]), "+f"(d[126]), "+f"(d[127])
    : "r"(a), "r"(b), "n"(0x40000040) : "memory");
}
__device__ __forceinline__ void first_kstep(float (&d)[96], uint32_t a, uint32_t b) {
  asm volatile("{\n.reg .u32 t;\n.reg .u64 da, db;\nwgmma.fence.sync.aligned;\n"
    "add.u32 t, %96, 0;\nmov.b64 da, {t, %98};\nadd.u32 t, %97, 0;\nmov.b64 db, {t, %98};\n"
    "wgmma.mma_async.sync.aligned.m64n192k16.f32.bf16.bf16 {%0, %1, %2, %3, %4, %5, %6, %7, %8, %9, %10, %11, %12, %13, %14, %15, %16, %17, %18, %19, %20, %21, %22, %23, %24, %25, %26, %27, %28, %29, %30, %31, %32, %33, %34, %35, %36, %37, %38, %39, %40, %41, %42, %43, %44, %45, %46, %47, %48, %49, %50, %51, %52, %53, %54, %55, %56, %57, %58, %59, %60, %61, %62, %63, %64, %65, %66, %67, %68, %69, %70, %71, %72, %73, %74, %75, %76, %77, %78, %79, %80, %81, %82, %83, %84, %85, %86, %87, %88, %89, %90, %91, %92, %93, %94, %95}, da, db, 0, 1, 1, 0, 1;\nwgmma.commit_group.sync.aligned;\n"
    "add.u32 t, %96, 2;\nmov.b64 da, {t, %98};\nadd.u32 t, %97, 128;\nmov.b64 db, {t, %98};\n"
    "wgmma.mma_async.sync.aligned.m64n192k16.f32.bf16.bf16 {%0, %1, %2, %3, %4, %5, %6, %7, %8, %9, %10, %11, %12, %13, %14, %15, %16, %17, %18, %19, %20, %21, %22, %23, %24, %25, %26, %27, %28, %29, %30, %31, %32, %33, %34, %35, %36, %37, %38, %39, %40, %41, %42, %43, %44, %45, %46, %47, %48, %49, %50, %51, %52, %53, %54, %55, %56, %57, %58, %59, %60, %61, %62, %63, %64, %65, %66, %67, %68, %69, %70, %71, %72, %73, %74, %75, %76, %77, %78, %79, %80, %81, %82, %83, %84, %85, %86, %87, %88, %89, %90, %91, %92, %93, %94, %95}, da, db, 1, 1, 1, 0, 1;\n"
    "add.u32 t, %96, 4;\nmov.b64 da, {t, %98};\nadd.u32 t, %97, 1024;\nmov.b64 db, {t, %98};\n"
    "wgmma.mma_async.sync.aligned.m64n192k16.f32.bf16.bf16 {%0, %1, %2, %3, %4, %5, %6, %7, %8, %9, %10, %11, %12, %13, %14, %15, %16, %17, %18, %19, %20, %21, %22, %23, %24, %25, %26, %27, %28, %29, %30, %31, %32, %33, %34, %35, %36, %37, %38, %39, %40, %41, %42, %43, %44, %45, %46, %47, %48, %49, %50, %51, %52, %53, %54, %55, %56, %57, %58, %59, %60, %61, %62, %63, %64, %65, %66, %67, %68, %69, %70, %71, %72, %73, %74, %75, %76, %77, %78, %79, %80, %81, %82, %83, %84, %85, %86, %87, %88, %89, %90, %91, %92, %93, %94, %95}, da, db, 1, 1, 1, 0, 1;\n"
    "add.u32 t, %96, 6;\nmov.b64 da, {t, %98};\nadd.u32 t, %97, 1152;\nmov.b64 db, {t, %98};\n"
    "wgmma.mma_async.sync.aligned.m64n192k16.f32.bf16.bf16 {%0, %1, %2, %3, %4, %5, %6, %7, %8, %9, %10, %11, %12, %13, %14, %15, %16, %17, %18, %19, %20, %21, %22, %23, %24, %25, %26, %27, %28, %29, %30, %31, %32, %33, %34, %35, %36, %37, %38, %39, %40, %41, %42, %43, %44, %45, %46, %47, %48, %49, %50, %51, %52, %53, %54, %55, %56, %57, %58, %59, %60, %61, %62, %63, %64, %65, %66, %67, %68, %69, %70, %71, %72, %73, %74, %75, %76, %77, %78, %79, %80, %81, %82, %83, %84, %85, %86, %87, %88, %89, %90, %91, %92, %93, %94, %95}, da, db, 1, 1, 1, 0, 1;\nwgmma.commit_group.sync.aligned;\n"
    "}\n"
    : "=f"(d[0]), "=f"(d[1]), "=f"(d[2]), "=f"(d[3]), "=f"(d[4]), "=f"(d[5]), "=f"(d[6]), "=f"(d[7]), "=f"(d[8]), "=f"(d[9]), "=f"(d[10]), "=f"(d[11]), "=f"(d[12]), "=f"(d[13]), "=f"(d[14]), "=f"(d[15]), "=f"(d[16]), "=f"(d[17]), "=f"(d[18]), "=f"(d[19]), "=f"(d[20]), "=f"(d[21]), "=f"(d[22]), "=f"(d[23]), "=f"(d[24]), "=f"(d[25]), "=f"(d[26]), "=f"(d[27]), "=f"(d[28]), "=f"(d[29]), "=f"(d[30]), "=f"(d[31]), "=f"(d[32]), "=f"(d[33]), "=f"(d[34]), "=f"(d[35]), "=f"(d[36]), "=f"(d[37]), "=f"(d[38]), "=f"(d[39]), "=f"(d[40]), "=f"(d[41]), "=f"(d[42]), "=f"(d[43]), "=f"(d[44]), "=f"(d[45]), "=f"(d[46]), "=f"(d[47]), "=f"(d[48]), "=f"(d[49]), "=f"(d[50]), "=f"(d[51]), "=f"(d[52]), "=f"(d[53]), "=f"(d[54]), "=f"(d[55]), "=f"(d[56]), "=f"(d[57]), "=f"(d[58]), "=f"(d[59]), "=f"(d[60]), "=f"(d[61]), "=f"(d[62]), "=f"(d[63]), "=f"(d[64]), "=f"(d[65]), "=f"(d[66]), "=f"(d[67]), "=f"(d[68]), "=f"(d[69]), "=f"(d[70]), "=f"(d[71]), "=f"(d[72]), "=f"(d[73]), "=f"(d[74]), "=f"(d[75]), "=f"(d[76]), "=f"(d[77]), "=f"(d[78]), "=f"(d[79]), "=f"(d[80]), "=f"(d[81]), "=f"(d[82]), "=f"(d[83]), "=f"(d[84]), "=f"(d[85]), "=f"(d[86]), "=f"(d[87]), "=f"(d[88]), "=f"(d[89]), "=f"(d[90]), "=f"(d[91]), "=f"(d[92]), "=f"(d[93]), "=f"(d[94]), "=f"(d[95])
    : "r"(a), "r"(b), "n"(0x40000040) : "memory");
}
__device__ __forceinline__ void kstep(float (&d)[96], uint32_t a, uint32_t b) {
  asm volatile("{\n.reg .u32 t;\n.reg .u64 da, db;\nwgmma.fence.sync.aligned;\n"
    "add.u32 t, %96, 0;\nmov.b64 da, {t, %98};\nadd.u32 t, %97, 0;\nmov.b64 db, {t, %98};\n"
    "wgmma.mma_async.sync.aligned.m64n192k16.f32.bf16.bf16 {%0, %1, %2, %3, %4, %5, %6, %7, %8, %9, %10, %11, %12, %13, %14, %15, %16, %17, %18, %19, %20, %21, %22, %23, %24, %25, %26, %27, %28, %29, %30, %31, %32, %33, %34, %35, %36, %37, %38, %39, %40, %41, %42, %43, %44, %45, %46, %47, %48, %49, %50, %51, %52, %53, %54, %55, %56, %57, %58, %59, %60, %61, %62, %63, %64, %65, %66, %67, %68, %69, %70, %71, %72, %73, %74, %75, %76, %77, %78, %79, %80, %81, %82, %83, %84, %85, %86, %87, %88, %89, %90, %91, %92, %93, %94, %95}, da, db, 1, 1, 1, 0, 1;\nwgmma.commit_group.sync.aligned;\n"
    "add.u32 t, %96, 2;\nmov.b64 da, {t, %98};\nadd.u32 t, %97, 128;\nmov.b64 db, {t, %98};\n"
    "wgmma.mma_async.sync.aligned.m64n192k16.f32.bf16.bf16 {%0, %1, %2, %3, %4, %5, %6, %7, %8, %9, %10, %11, %12, %13, %14, %15, %16, %17, %18, %19, %20, %21, %22, %23, %24, %25, %26, %27, %28, %29, %30, %31, %32, %33, %34, %35, %36, %37, %38, %39, %40, %41, %42, %43, %44, %45, %46, %47, %48, %49, %50, %51, %52, %53, %54, %55, %56, %57, %58, %59, %60, %61, %62, %63, %64, %65, %66, %67, %68, %69, %70, %71, %72, %73, %74, %75, %76, %77, %78, %79, %80, %81, %82, %83, %84, %85, %86, %87, %88, %89, %90, %91, %92, %93, %94, %95}, da, db, 1, 1, 1, 0, 1;\n"
    "add.u32 t, %96, 4;\nmov.b64 da, {t, %98};\nadd.u32 t, %97, 1024;\nmov.b64 db, {t, %98};\n"
    "wgmma.mma_async.sync.aligned.m64n192k16.f32.bf16.bf16 {%0, %1, %2, %3, %4, %5, %6, %7, %8, %9, %10, %11, %12, %13, %14, %15, %16, %17, %18, %19, %20, %21, %22, %23, %24, %25, %26, %27, %28, %29, %30, %31, %32, %33, %34, %35, %36, %37, %38, %39, %40, %41, %42, %43, %44, %45, %46, %47, %48, %49, %50, %51, %52, %53, %54, %55, %56, %57, %58, %59, %60, %61, %62, %63, %64, %65, %66, %67, %68, %69, %70, %71, %72, %73, %74, %75, %76, %77, %78, %79, %80, %81, %82, %83, %84, %85, %86, %87, %88, %89, %90, %91, %92, %93, %94, %95}, da, db, 1, 1, 1, 0, 1;\n"
    "add.u32 t, %96, 6;\nmov.b64 da, {t, %98};\nadd.u32 t, %97, 1152;\nmov.b64 db, {t, %98};\n"
    "wgmma.mma_async.sync.aligned.m64n192k16.f32.bf16.bf16 {%0, %1, %2, %3, %4, %5, %6, %7, %8, %9, %10, %11, %12, %13, %14, %15, %16, %17, %18, %19, %20, %21, %22, %23, %24, %25, %26, %27, %28, %29, %30, %31, %32, %33, %34, %35, %36, %37, %38, %39, %40, %41, %42, %43, %44, %45, %46, %47, %48, %49, %50, %51, %52, %53, %54, %55, %56, %57, %58, %59, %60, %61, %62, %63, %64, %65, %66, %67, %68, %69, %70, %71, %72, %73, %74, %75, %76, %77, %78, %79, %80, %81, %82, %83, %84, %85, %86, %87, %88, %89, %90, %91, %92, %93, %94, %95}, da, db, 1, 1, 1, 0, 1;\nwgmma.commit_group.sync.aligned;\n"
    "}\n"
    : "+f"(d[0]), "+f"(d[1]), "+f"(d[2]), "+f"(d[3]), "+f"(d[4]), "+f"(d[5]), "+f"(d[6]), "+f"(d[7]), "+f"(d[8]), "+f"(d[9]), "+f"(d[10]), "+f"(d[11]), "+f"(d[12]), "+f"(d[13]), "+f"(d[14]), "+f"(d[15]), "+f"(d[16]), "+f"(d[17]), "+f"(d[18]), "+f"(d[19]), "+f"(d[20]), "+f"(d[21]), "+f"(d[22]), "+f"(d[23]), "+f"(d[24]), "+f"(d[25]), "+f"(d[26]), "+f"(d[27]), "+f"(d[28]), "+f"(d[29]), "+f"(d[30]), "+f"(d[31]), "+f"(d[32]), "+f"(d[33]), "+f"(d[34]), "+f"(d[35]), "+f"(d[36]), "+f"(d[37]), "+f"(d[38]), "+f"(d[39]), "+f"(d[40]), "+f"(d[41]), "+f"(d[42]), "+f"(d[43]), "+f"(d[44]), "+f"(d[45]), "+f"(d[46]), "+f"(d[47]), "+f"(d[48]), "+f"(d[49]), "+f"(d[50]), "+f"(d[51]), "+f"(d[52]), "+f"(d[53]), "+f"(d[54]), "+f"(d[55]), "+f"(d[56]), "+f"(d[57]), "+f"(d[58]), "+f"(d[59]), "+f"(d[60]), "+f"(d[61]), "+f"(d[62]), "+f"(d[63]), "+f"(d[64]), "+f"(d[65]), "+f"(d[66]), "+f"(d[67]), "+f"(d[68]), "+f"(d[69]), "+f"(d[70]), "+f"(d[71]), "+f"(d[72]), "+f"(d[73]), "+f"(d[74]), "+f"(d[75]), "+f"(d[76]), "+f"(d[77]), "+f"(d[78]), "+f"(d[79]), "+f"(d[80]), "+f"(d[81]), "+f"(d[82]), "+f"(d[83]), "+f"(d[84]), "+f"(d[85]), "+f"(d[86]), "+f"(d[87]), "+f"(d[88]), "+f"(d[89]), "+f"(d[90]), "+f"(d[91]), "+f"(d[92]), "+f"(d[93]), "+f"(d[94]), "+f"(d[95])
    : "r"(a), "r"(b), "n"(0x40000040) : "memory");
}

__device__ __forceinline__ void sum_columns(float (&d)[4], uint32_t a, uint32_t b) {
  asm volatile("{\n.reg .u32 t;\n.reg .u64 da, db;\nmov.b64 db, {%5, 0};\nwgmma.fence.sync.aligned;\n"
               "add.u32 t, %4, 0;\nmov.b64 da, {t, %6};\nwgmma.mma_async.sync.aligned.m64n8k16.f32.bf16.bf16 {%0, %1, %2, %3}, da, db, 1, 1, 1, 1, 0;\n"
               "add.u32 t, %4, 128;\nmov.b64 da, {t, %6};\nwgmma.mma_async.sync.aligned.m64n8k16.f32.bf16.bf16 {%0, %1, %2, %3}, da, db, 1, 1, 1, 1, 0;\n"
               "add.u32 t, %4, 256;\nmov.b64 da, {t, %6};\nwgmma.mma_async.sync.aligned.m64n8k16.f32.bf16.bf16 {%0, %1, %2, %3}, da, db, 1, 1, 1, 1, 0;\n"
               "add.u32 t, %4, 384;\nmov.b64 da, {t, %6};\nwgmma.mma_async.sync.aligned.m64n8k16.f32.bf16.bf16 {%0, %1, %2, %3}, da, db, 1, 1, 1, 1, 0;\n"
               "add.u32 t, %4, 512;\nmov.b64 da, {t, %6};\nwgmma.mma_async.sync.aligned.m64n8k16.f32.bf16.bf16 {%0, %1, %2, %3}, da, db, 1, 1, 1, 1, 0;\n"
               "add.u32 t, %4, 640;\nmov.b64 da, {t, %6};\nwgmma.mma_async.sync.aligned.m64n8k16.f32.bf16.bf16 {%0, %1, %2, %3}, da, db, 1, 1, 1, 1, 0;\n"
               "add.u32 t, %4, 768;\nmov.b64 da, {t, %6};\nwgmma.mma_async.sync.aligned.m64n8k16.f32.bf16.bf16 {%0, %1, %2, %3}, da, db, 1, 1, 1, 1, 0;\n"
               "add.u32 t, %4, 896;\nmov.b64 da, {t, %6};\nwgmma.mma_async.sync.aligned.m64n8k16.f32.bf16.bf16 {%0, %1, %2, %3}, da, db, 1, 1, 1, 1, 0;\n"
               "add.u32 t, %4, 1024;\nmov.b64 da, {t, %6};\nwgmma.mma_async.sync.aligned.m64n8k16.f32.bf16.bf16 {%0, %1, %2, %3}, da, db, 1, 1, 1, 1, 0;\n"
               "add.u32 t, %4, 1152;\nmov.b64 da, {t, %6};\nwgmma.mma_async.sync.aligned.m64n8k16.f32.bf16.bf16 {%0, %1, %2, %3}, da, db, 1, 1, 1, 1, 0;\n"
               "add.u32 t, %4, 1280;\nmov.b64 da, {t, %6};\nwgmma.mma_async.sync.aligned.m64n8k16.f32.bf16.bf16 {%0, %1, %2, %3}, da, db, 1, 1, 1, 1, 0;\n"
               "add.u32 t, %4, 1408;\nmov.b64 da, {t, %6};\nwgmma.mma_async.sync.aligned.m64n8k16.f32.bf16.bf16 {%0, %1, %2, %3}, da, db, 1, 1, 1, 1, 0;\n"
               "add.u32 t, %4, 1536;\nmov.b64 da, {t, %6};\nwgmma.mma_async.sync.aligned.m64n8k16.f32.bf16.bf16 {%0, %1, %2, %3}, da, db, 1, 1, 1, 1, 0;\n"
               "add.u32 t, %4, 1664;\nmov.b64 da, {t, %6};\nwgmma.mma_async.sync.aligned.m64n8k16.f32.bf16.bf16 {%0, %1, %2, %3}, da, db, 1, 1, 1, 1, 0;\n"
               "add.u32 t, %4, 1792;\nmov.b64 da, {t, %6};\nwgmma.mma_async.sync.aligned.m64n8k16.f32.bf16.bf16 {%0, %1, %2, %3}, da, db, 1, 1, 1, 1, 0;\n"
               "add.u32 t, %4, 1920;\nmov.b64 da, {t, %6};\nwgmma.mma_async.sync.aligned.m64n8k16.f32.bf16.bf16 {%0, %1, %2, %3}, da, db, 1, 1, 1, 1, 0;\n"
               "wgmma.commit_group.sync.aligned;\nwgmma.wait_group.sync.aligned 0;\n}"
               : "+f"(d[0]), "+f"(d[1]), "+f"(d[2]), "+f"(d[3]) : "r"(a), "r"(b), "n"(0x40000040) : "memory");
}
struct Job {
  uint32_t type, layer, R, col, nk;
  __device__ __forceinline__ explicit Job(uint32_t j) : type(j & 3), layer((j >> 2) & 1), R((j >> 3) & 7), col((j >> 6) & 63), nk((j >> 12) & 63) {}
  __device__ __forceinline__ uint32_t inst() const { return layer * 2 + (type >> 1); }
};
struct Smem {
  char* scratch;
  uint32_t base;
  __device__ __forceinline__ uint32_t stage(uint32_t s) const { return base + (s & (NSTAGE - 1)) * STAGE; }
  __device__ __forceinline__ uint32_t slot(uint32_t c) const { return base + STG_OFF + c * SLOT; }
  __device__ __forceinline__ uint32_t full(uint32_t s) const { return base + BAR_OFF + (s & (NSTAGE - 1)) * 8; }
  __device__ __forceinline__ uint32_t empty(uint32_t s) const { return base + BAR_OFF + 32 + (s & (NSTAGE - 1)) * 8; }
  __device__ __forceinline__ uint32_t filled(uint32_t u) const { return base + BAR_OFF + 64 + u * 8; }
  __device__ __forceinline__ uint32_t vacant(uint32_t u) const { return base + BAR_OFF + 96 + u * 8; }
  __device__ __forceinline__ uint32_t summed(uint32_t s) const { return base + BAR_OFF + 128 + (s & (NSTAGE - 1)) * 8; }
  __device__ __forceinline__ uint32_t aux_full() const { return base + BAR_OFF + 160; }
  __device__ __forceinline__ uint32_t boot() const { return base + BAR_OFF + 168; }
  __device__ __forceinline__ uint32_t xchg_full() const { return base + BAR_OFF + 176; }
  __device__ __forceinline__ uint32_t wgmma_done() const { return base + BAR_OFF + 184; }
  __device__ __forceinline__ uint32_t mma_done() const { return base + BAR_OFF + 192; }
  __device__ __forceinline__ uint32_t kv_ready(int w) const { return base + BAR_OFF + 208 + w * 8; }
  __device__ __forceinline__ uint32_t pair_id() const { return base + BAR_OFF + 280; }
  __device__ __forceinline__ uint32_t stats() const { return base + AUX_OFF; }
  __device__ __forceinline__ uint32_t sums() const { return base + AUX_OFF + 1088; }
  __device__ __forceinline__ uint32_t xchg() const { return base + AUX_OFF + 1600; }
};
__device__ __forceinline__ uint32_t par(uint32_t s) { return (s / NSTAGE) & 1; }

__device__ __forceinline__ void st_word(u64* p, uint32_t lo, uint32_t hi) {
  asm volatile("st.relaxed.gpu.global.u64 [%0], %1;" ::"l"(p), "l"(((u64)hi << 32) | lo) : "memory");
}
__device__ __forceinline__ uint2 ld_word(const u64* p) {
  u64 v;
  asm volatile("ld.relaxed.gpu.global.u64 %0, [%1];" : "=l"(v) : "l"(p) : "memory");
  return make_uint2((uint32_t)v, (uint32_t)(v >> 32));
}
__device__ __forceinline__ void add_moments(uint4 v, float (&m)[4]) {
  const uint32_t w[4] = {v.x, v.y, v.z, v.w};
#pragma unroll
  for (int c = 0; c < 4; c++) {
    const float lo = bf_lo(w[c]), hi = bf_hi(w[c]);
    m[0] += lo; m[1] += hi; m[2] = fmaf(lo, lo, m[2]); m[3] = fmaf(hi, hi, m[3]);
  }
}
__device__ __forceinline__ void publish_stats(const Smem& sm, float s, float q, uint32_t idx, bool valid, uint32_t e1) {
  const float mean = s * (1.f / D), var = fmaxf(q * (1.f / D) - mean * mean, 0.f);
  const u64 word = ((u64)((__float_as_uint(-bf_round(mean)) & 0xffff0000u) | (e1 & 0xffff)) << 32) | __float_as_uint(rcp(bf_round(sqrt_fast(bf_round(bf_round(var) + 1e-5f)))));
  asm volatile("{\n.reg .pred p;\nsetp.ne.u32 p, %2, 0;\n@p st.relaxed.gpu.global.u64 [%0], %1;\n}" ::"l"(SCR(sm, stats, idx * 8)), "l"(word), "r"((uint32_t)valid) : "memory");
}
__device__ __forceinline__ void stats_task(const Smem& sm, uint32_t jw, int rank, int w, uint32_t e1, const bf16* x) {
  const uint32_t inst = (jw >> 22) & 3, lane = fresh_tid() & 31, steps = (jw >> 31) * 2 + 2;
  uint32_t row = ((jw >> 24) & 127) * 8 + (w - 1) * 4 + (lane >> 3);
  wait_count(counter(C_X + inst * 16 + (row >> 7) * 2 + rank, lane & 7), e1 * (inst & 1 ? 56 : 16));
  const uint4* p = at(reinterpret_cast<const uint4*>(x), (row * 2 + rank) * (D * 2) + (lane & 7) * 16);
  uint4 v[8];
  float m[4] = {0.f, 0.f, 0.f, 0.f};
#pragma unroll
  for (int i = 0; i < 8; i++) v[i] = ldg128(p + i * 8);
#pragma unroll 1
  for (uint32_t it = 1; it <= steps; it++) {
    p = at(p, it & 1 ? 1024 : 8 * D * 4 - 1024);
#pragma unroll
    for (int i = 0; i < 8; i++) {
      add_moments(v[i], m);
      if (it < steps) v[i] = ldg128(p + i * 8);
    }
    if (!(it & 1)) {
      m[0] += m[1]; m[2] += m[3];
#pragma unroll
      for (int o = 1; o <= 4; o <<= 1) { m[0] += __shfl_xor_sync(~0u, m[0], o); m[2] += __shfl_xor_sync(~0u, m[2], o); }
      publish_stats(sm, m[0], m[2], (inst + 1) * S + rank * (S / 2) + row, (lane & 7) == 0, e1);
      m[0] = m[1] = m[2] = m[3] = 0.f;
      row += 8;
    }
  }
}
struct Stager {
  uint2 st[5], cs[4];
  __device__ __forceinline__ void load(const Smem& sm, const Job& J, int rank, int lane, bool sums) {
#pragma unroll
    for (int i = 0; i < 5; i++) st[i] = ld_word(SCR(sm, stats, (J.inst() * S + rank * (S / 2) + J.R * 128 + min(max(lane - 8 + 32 * i, J.R && J.type == T_Q ? -8 : 0), 127)) * 8));
#pragma unroll
    for (int i = 0; i < 4; i++)
      if (sums && (i < 3 || J.type == T_G)) cs[i] = ld_word(SCR(sm, cs, ((J.col + J.type * 8) * 128 + lane) * 8) + i * 32);
  }
  __device__ __forceinline__ void store(const Smem& sm, const Job& J, int rank, int lane, bool sums, uint32_t e1) {
    for (uint32_t n = 0;; n++) {
      uint32_t bad = (st[1].y ^ e1) | (st[2].y ^ e1) | (st[3].y ^ e1);
      bad |= (st[0].y ^ e1) | (st[4].y ^ e1);
      if (sums) bad |= (cs[0].y ^ e1) | (cs[1].y ^ e1) | (cs[2].y ^ e1);
      if (J.type == T_G) bad |= cs[3].y ^ e1;
      if (__all_sync(~0u, (bad & 0xffff) == 0)) break;
      __nanosleep(300);
      if (n > SPIN_LIMIT) __trap();
      load(sm, J, rank, lane, sums);
    }
#pragma unroll
    for (int i = 0; i < 5; i++) {
      if (i < 4 || lane < 8) sts64(sm.stats() + (lane + 32 * i) * 8, st[i]);
      if (i < 4 && sums && (i < 3 || J.type == T_G)) sts32(sm.sums() + (lane + 32 * i) * 4, cs[i].x);
    }
  }
};
__device__ __forceinline__ void add_cols(float (&a)[8], uint4 x, uint4 y) {
  const uint4 t = add8(x, y);
  a[0] += bf_lo(t.x); a[1] += bf_hi(t.x); a[2] += bf_lo(t.y); a[3] += bf_hi(t.y);
  a[4] += bf_lo(t.z); a[5] += bf_hi(t.z); a[6] += bf_lo(t.w); a[7] += bf_hi(t.w);
}
__device__ __forceinline__ void reduce_cols(float (&a)[8], int lane) {
#pragma unroll
  for (int i = 0; i < 4; i++) { const bool up = lane & 16; const float o = __shfl_xor_sync(~0u, up ? a[i] : a[i + 4], 16); a[i] = (up ? a[i + 4] : a[i]) + o; }
#pragma unroll
  for (int i = 0; i < 2; i++) { const bool up = lane & 8; const float o = __shfl_xor_sync(~0u, up ? a[i] : a[i + 2], 8); a[i] = (up ? a[i + 2] : a[i]) + o; }
}
template <class Fn>
__device__ __forceinline__ uint32_t qkv_col_sums(const Smem& sm, int rank, int w, int lane, const uint32_t& rest, Fn between) {
  float a[8] = {0.f, 0.f, 0.f, 0.f, 0.f, 0.f, 0.f, 0.f};
#pragma unroll 1
  for (int s = 0; s < RING_SUMS; s++) {
    between(s);
    const uint32_t p = sm.stage(s) + SLOT + rank * SLOT + w * 4096 + (lane >> 3) * 128 + (((lane & 7) ^ (lane >> 3)) << 4);
    uint4 v[8];
    mbar_wait(sm.full(s), par(s));
#pragma unroll
    for (int j = 0; j < 8; j++) v[j] = lds128((p ^ ((j & 1) * 64)) + j * 512);
    __syncwarp();
    mbar_arrive_cl_if(lane < 2, mapa(sm.summed(s), lane & 1));
    add_cols(a, add8(v[0], v[1]), add8(v[2], v[3]));
    add_cols(a, add8(v[4], v[5]), add8(v[6], v[7]));
  }
  reduce_cols(a, lane);
  const uint32_t slot = sm.xchg() + (w * 32 + lane) * 8;
  asm volatile("st.async.weak.shared::cluster.mbarrier::complete_tx::bytes.v2.b32 [%0], {%1, %2}, [%3];"
               ::"r"(mapa(slot, rank ^ 1)), "r"(__float_as_uint(a[0])), "r"(__float_as_uint(a[1])), "r"(mapa(sm.xchg_full(), rank ^ 1)) : "memory");
  mbar_wait(sm.xchg_full(), 0);
  const uint2 o = lds64(slot);
  return pack_bf16(a[0] + __uint_as_float(o.x) + bf_lo(rest), a[1] + __uint_as_float(o.y) + bf_hi(rest));
}

constexpr float LOGIT_SCALE = 0.17677669529663687f * 1.4426950408889634f;
constexpr float MASKED = -1e30f;
enum { A_CS = 16, A_NM = 40, A_KT = 42, A_KU = 44, A_CT = 46, A_CU = 48, A_BIAS = 50, A_MASK = 52, A_ZERO = 53 };
__device__ __forceinline__ void attention_prepare(uint32_t (&r)[64], const Smem& sm, int W, int lane, bool first) {
  const int i = lane >> 2, c = (lane & 3) * 2;
  r[A_ZERO] = opaque_zero();
  r[A_MASK] = (c > i ? 0xffffu : 0u) | (c + 1 > i ? 0xffff0000u : 0u);
  const uint32_t a = sm.stats() + W * 128;
  const uint2 r0 = lds64(a + 64 + i * 8), r1 = lds64(a + 128 + i * 8);
#pragma unroll
  for (int y = 0; y < 2; y++) {
    const uint32_t k = a + (c + y + (c + y > i ? 0 : 8)) * 8;
    const float kt = lds32f(k), ku = lds32f(k + 64);
    r[A_KT + y] = __float_as_uint(kt); r[A_CT + y] = __float_as_uint(__uint_as_float(r0.x) * LOGIT_SCALE * kt);
    r[A_KU + y] = __float_as_uint(ku); r[A_CU + y] = __float_as_uint(__uint_as_float(r1.x) * LOGIT_SCALE * ku);
    r[A_BIAS + y] = __float_as_uint(first && W == 0 && c + y > i ? MASKED : 0.f);
  }
#pragma unroll
  for (int j = 0; j < 6; j++) {
    const uint4 v = lds128(sm.sums() + c * 48 + j * 16);
    r[A_CS + 4 * j] = v.x; r[A_CS + 4 * j + 1] = v.y; r[A_CS + 4 * j + 2] = v.z; r[A_CS + 4 * j + 3] = v.w;
  }
  r[A_NM] = dup_hi(r0.y); r[A_NM + 1] = dup_hi(r1.y);
}
__device__ __forceinline__ bool attention(const float (&acc)[96], uint32_t (&r)[64], const Smem& sm, int W, int lane, uint32_t t8, uint32_t t16,
                                          bool halo, uint32_t block, uint32_t tag, uint32_t parity, uint32_t next_bar, uint32_t next_parity, int ji) {
#define TRW W
  const uint32_t own = (W >> 2) * SLOT;
  const uint32_t pk = W == 0 ? (halo ? 4096 : 1024) : W == 4 ? 7168 : own - 1024;
  const uint32_t pv = W == 0 && halo ? 6144 : pk + 8192;
  uint32_t x[48];
  auto pack = [&](int j0, int step, int count) {
#pragma unroll
    for (int j = j0; j < j0 + step * count; j += step) x[j] = bf2_fma(r[A_NM + j % 2], r[A_CS + j / 2], pack_bf16(acc[2 * j], acc[2 * j + 1]));
  };
  auto put8 = [&](uint32_t a, int j) {
    stsm4(t8 + a, x[j], x[j + 2], x[j + 4], x[j + 6]);
    stsm4((t8 ^ 64) + a, x[j + 8], x[j + 10], x[j + 12], x[j + 14]);
  };
  uint32_t k0[2][4], v0[2][4], v12[4][4];
  pack(17, 2, 8);
  put8(own + 1024, 17);
  pack(32, 1, 16);
#pragma unroll
  for (int j = 0; j < 4; j++) stsm4((t16 ^ (j << 5)) + (own + 8192), x[32 + 4 * j], x[33 + 4 * j], x[34 + 4 * j], x[35 + 4 * j]);
  mbar_arrive_warp(sm.kv_ready(W));
  pack(16, 2, 8);
  pack(0, 1, 16);
  if (W == 0) {
    put8(0, 16);
#pragma unroll
    for (int j = 0; j < 4; j++) stsm4(lane & 8 ? sm.xchg() : (t16 ^ (j << 5)) + 2048, x[4 * j], x[4 * j + 1], x[4 * j + 2], x[4 * j + 3]);
  }
  mbar_wait(sm.kv_ready(W - 1), parity);
#pragma unroll
  for (int h = 0; h < 2; h++) ldsm4((t8 ^ (h * 64)) + pk, k0[h]);
#pragma unroll
  for (int j = 0; j < 4; j++) ldsm4t((t16 ^ (j << 5)) + (own + 8192), v12[j]);
#pragma unroll
  for (int h = 0; h < 2; h++) ldsm4t((t8 ^ (h * 64)) + pv, v0[h]);
  if (W < 4) mbar_wait(sm.wgmma_done(), parity);
  const bool next_full = mbar_test(next_bar, next_parity);
  TRC(ji, 20);
  float s0[2][4], s1[2][4], s2[2][4];
#pragma unroll
  for (int h = 0; h < 2; h++) {
#pragma unroll
    for (int y = 0; y < 4; y++) s0[h][y] = s1[h][y] = s2[h][y] = 0.f;
  }
#pragma unroll
  for (int ks = 0; ks < 2; ks++)
#pragma unroll
    for (int h = 0; h < 2; h++) {
      const int n = 8 * h + 4 * ks;
      mma16816(s1[h], x[n], x[n + 1], x[n + 2], x[n + 3], x[16 + n], x[18 + n]);
      mma16816(s2[h], x[n], x[n + 1], x[n + 2], x[n + 3], x[17 + n], x[19 + n]);
      mma16816(s0[h], x[n], x[n + 1], x[n + 2], x[n + 3], k0[h][2 * ks], k0[h][2 * ks + 1]);
    }
  const uint32_t mask = r[A_MASK];
  const bool after[2] = {(mask & 1) != 0, (int)mask < 0};
  float lt[2][2], lu[2][2], mt[2], mu[2];
#pragma unroll
  for (int h = 0; h < 2; h++) {
#pragma unroll
    for (int y = 0; y < 2; y++) {
      lt[h][y] = fmaf(after[y] ? s0[h][y] : s1[h][y], __uint_as_float(r[A_CT + y]), __uint_as_float(r[A_BIAS + y]));
      lu[h][y] = (after[y] ? s1[h][2 + y] : s2[h][2 + y]) * __uint_as_float(r[A_CU + y]);
    }
    mt[h] = fmaxf(lt[h][0], lt[h][1]);
    mu[h] = fmaxf(lu[h][0], lu[h][1]);
  }
#pragma unroll
  for (int d = 1; d <= 2; d++)
#pragma unroll
    for (int h = 0; h < 2; h++) {
      mt[h] = fmaxf(mt[h], __shfl_xor_sync(~0u, mt[h], d));
      mu[h] = fmaxf(mu[h], __shfl_xor_sync(~0u, mu[h], d));
    }
  float o[2][4][4];
#pragma unroll
  for (int h = 0; h < 2; h++) {
#pragma unroll
    for (int y = 0; y < 2; y++) { lt[h][y] = ex2(lt[h][y] - mt[h]); lu[h][y] = ex2(lu[h][y] - mu[h]); }
    const uint32_t pt = pack_bf16(lt[h][0] * __uint_as_float(r[A_KT]), lt[h][1] * __uint_as_float(r[A_KT + 1]));
    const uint32_t pu = pack_bf16(lu[h][0] * __uint_as_float(r[A_KU]), lu[h][1] * __uint_as_float(r[A_KU + 1]));
#pragma unroll
    for (int n = 0; n < 4; n++) {
      o[h][n][0] = o[h][n][1] = o[h][n][2] = o[h][n][3] = 0.f;
      mma16816(o[h][n], pt & ~mask, pu & mask, 0u, pu & ~mask, v12[2 * h + n / 2][n % 2 * 2], v12[2 * h + n / 2][n % 2 * 2 + 1]);
    }
#pragma unroll
    for (int n = 0; n < 4; n++) mma1688(o[h][n], pt & mask, 0u, v0[h][n]);
    mt[h] = lt[h][0] + lt[h][1];
    mu[h] = lu[h][0] + lu[h][1];
  }
#pragma unroll
  for (int d = 1; d <= 2; d++)
#pragma unroll
    for (int h = 0; h < 2; h++) {
      mt[h] += __shfl_xor_sync(~0u, mt[h], d);
      mu[h] += __shfl_xor_sync(~0u, mu[h], d);
    }
  uint32_t dep = 0;
#pragma unroll
  for (int n = 0; n < 3; n++) dep |= __float_as_uint(o[n % 2][n / 2][0]);
  mbar_arrive_warp(sm.mma_done() + (dep & r[A_ZERO]));
  TRC(ji, 22);
  if (W == 7) {
    ulonglong2* exp = SCR(sm, halo, (block * 256 + lane) * 16);
#pragma unroll
    for (int m = 0; m < 8; m++)
      asm volatile("st.relaxed.gpu.global.v2.u64 [%0], {%1,%2};" ::"l"(exp + m * 32), "l"(((u64)tag << 32) | x[17 + 4 * m]), "l"(((u64)tag << 32) | x[19 + 4 * m]) : "memory");
  }
#pragma unroll
  for (int h = 0; h < 2; h++) {
    const float rt = rcp(mt[h]), ru = rcp(mu[h]);
#pragma unroll
    for (int n = 0; n < 4; n++) {
      r[8 * h + 2 * n] = pack_bf16(o[h][n][0] * rt, o[h][n][1] * rt);
      r[8 * h + 2 * n + 1] = pack_bf16(o[h][n][2] * ru, o[h][n][3] * ru);
    }
  }
  return next_full;
}
__device__ __forceinline__ void import_halo(const Smem& sm, const ulonglong2* halo, uint32_t tag, int lane) {
  u64 x[16];
  for (uint32_t n = 0;; n++) {
#pragma unroll
    for (int m = 0; m < 8; m++)
      asm volatile("ld.relaxed.gpu.global.v2.u64 {%0,%1}, [%2];" : "=l"(x[2 * m]), "=l"(x[2 * m + 1]) : "l"(halo + m * 32) : "memory");
    uint32_t bad = 0;
#pragma unroll
    for (int m = 0; m < 16; m++) bad |= (uint32_t)(x[m] >> 32) ^ tag;
    if (__all_sync(~0u, bad == 0)) break;
    __nanosleep(300);
    if (n > SPIN_LIMIT) __trap();
  }
  const uint32_t a = sm.slot(0) + 4096 + (lane & 7) * 128 + (((lane >> 3) ^ (lane & 7)) << 4);
#pragma unroll
  for (int m = 0; m < 4; m++) stsm4((a ^ ((m & 1) * 64)) + (m >> 1) * 2048, (uint32_t)x[4 * m], (uint32_t)x[4 * m + 1], (uint32_t)x[4 * m + 2], (uint32_t)x[4 * m + 3]);
}
__device__ __forceinline__ void unpack8(uint4 v, float* f) {
  f[0] = bf_lo(v.x); f[1] = bf_hi(v.x); f[2] = bf_lo(v.y); f[3] = bf_hi(v.y);
  f[4] = bf_lo(v.z); f[5] = bf_hi(v.z); f[6] = bf_lo(v.w); f[7] = bf_hi(v.w);
}
__device__ __forceinline__ void boundary_rows(const Smem& sm, int h, int lane, uint32_t out) {
  const int i = lane >> 2, u = h * 4 + (lane & 3);
  uint4 r[8];
  float x[8], l[8], ik[8];
  unpack8(lds128(sm.slot(0) + 2048 + i * 128 + ((u ^ i) << 4)), x);
#pragma unroll
  for (int j = 0; j < 8; j++) {
    r[j] = lds128(sm.slot(0) + j * 128 + (j > i ? 4096 : 0) + ((u ^ j) << 4));
    ik[j] = lds32f(sm.stats() + j * 8 + (j > i ? 0 : 64));
  }
  const float cq = lds32f(sm.stats() + 64 + i * 8) * LOGIT_SCALE;
#pragma unroll
  for (int j = 0; j < 8; j++) {
    float kf[8];
    unpack8(r[j], kf);
    r[j] = lds128(sm.slot(0) + j * 128 + (j > i ? 6144 : 8192) + ((u ^ j) << 4));
    l[j] = 0.f;
#pragma unroll
    for (int d = 0; d < 8; d++) l[j] = fmaf(x[d], kf[d], l[j]);
  }
#pragma unroll
  for (int d = 1; d <= 2; d++)
#pragma unroll
    for (int j = 0; j < 8; j++) l[j] += __shfl_xor_sync(~0u, l[j], d);
  float m = MASKED, sum = 0.f;
#pragma unroll
  for (int j = 0; j < 8; j++) { l[j] *= cq * ik[j]; m = fmaxf(m, l[j]); }
#pragma unroll
  for (int j = 0; j < 8; j++) { l[j] = ex2(l[j] - m); sum += l[j]; }
  const float rs = rcp(sum);
#pragma unroll
  for (int d = 0; d < 8; d++) x[d] = 0.f;
#pragma unroll
  for (int j = 0; j < 8; j++) {
    const float pw = l[j] * ik[j] * rs;
    float vf[8];
    unpack8(r[j], vf);
#pragma unroll
    for (int d = 0; d < 8; d++) x[d] = fmaf(pw, vf[d], x[d]);
  }
  stg128(SCR(sm, o, out + i * (2 * D) + u * 16), make_uint4(pack_bf16(x[0], x[1]), pack_bf16(x[2], x[3]), pack_bf16(x[4], x[5]), pack_bf16(x[6], x[7])));
}
__device__ __forceinline__ uint32_t swiglu2(uint32_t g, uint32_t u, float hinv, float hinv2) {
  const float a = bf_lo(g) * hinv, b = bf_hi(g) * hinv, a2 = bf_lo(g) * hinv2, b2 = bf_hi(g) * hinv2;
  return bf2_mul(pack_bf16(fmaf(a2, tanh_fast(a), a2), fmaf(b2, tanh_fast(b), b2)), u);
}

__device__ __forceinline__ const uint32_t* dep_counter(const Smem& sm, uint32_t jw, int rank, uint32_t k) {
  const Job J(jw);
  const uint32_t b = J.R * 2 + rank;
  const uint32_t line = J.type == T_O ? C_O + J.layer * 16 + b : J.type == T_D ? C_H + J.layer * 16 + b : C_X + max((int)J.inst() - 1, 0) * 16 + b;
  return counter(line, J.type & 1 ? k >> (J.type >> 1) : (k >> 2) * 2 + (k & 1));
}
__device__ __forceinline__ void producer(const Params& P, const Smem& sm, const uint32_t* jobs, const uint8_t* kseq, int rank, int lane, uint32_t e1) {
  uint32_t s = (jobs[0] & JOB_C) ? 0 : NSTAGE;
  uint32_t end = 0, poll = 0;
  uint64_t keep, stream;
  asm("createpolicy.fractional.L2::evict_unchanged.b64 %0, 1.0;" : "=l"(keep));
  asm("createpolicy.fractional.L2::evict_first.b64 %0, 1.0;" : "=l"(stream));
  const uint32_t* dep = counter(0, 0);
  const uint32_t summed_end = (jobs[0] & JOB_C) ? 0 : RING_SUMS + NSTAGE;
  for (int ji = 0;; ji++) {
    const uint32_t jw = jobs[ji];
    const Job J(jw);
    if (J.nk == 0) break;
    const bool isC = jw & JOB_C, isX = isC && (jw & JOB_X);
    const uint32_t target = (jw & 7) == 0 ? 0 : e1 * (J.type == T_Q ? 56 : J.type == T_G ? 16 : 1);
    const uint32_t g = J.col * 2 + rank;
    const CUtensorMap* tmA = &P.a[isC ? 4 + isX : (jw & 7) == 4 ? 2 : J.type];
    const CUtensorMap* tmB = &P.w[J.type];
    const uint32_t bytes = isC ? 32768 : J.type == T_Q ? 40960 : STAGE, bcol = J.col << (J.type == T_Q ? 0 : J.type == T_G ? 1 : 2);
    const uint32_t a0 = isX ? 0 : (g >> 2) * 128 + (g & 1) * 64, a1 = isX ? g * 64 : J.R * 128, ak = isX ? 0 : 256, a2 = isC ? (g >> 1) & 1 : rank;
    end += J.nk;
    uint32_t sa = s, spins = 0;
    auto issue_a = [&](uint32_t k) { TRS(sa, 1); tma3d(sm.stage(sa), tmA, isC ? a0 : (k & 63) * 64, isC ? a1 + k * ak : a1, isX ? k * 4 : a2, sm.full(sa), (k & K_LAST_A) ? stream : keep); };
    auto issue_b = [&](uint32_t k) {
      mbar_expect_tx(sm.full(s), bytes);
      TRS(s, 0);
      if (!isC) tma4d_mc(sm.stage(s) + SLOT + rank * SLOT, tmB, (k & 63) * 64 + rank * 32, bcol, sm.full(s), (k & K_LAST_B) ? stream : keep);
    };
    TRI(lane == 0, ji, 6);
    TRK(lane == 0, ji, 24);
    while (true) {
      const uint32_t missing = __ballot_sync(~0u, (int)(poll - target) < 0 && lane < J.nk);
      uint32_t lim = end;
      if (missing) lim += __ffs(missing) - 1 - J.nk;
      if (lim > sa) {
        fence_acquire();
        fence_proxy_async();
        TRI(sa == end - J.nk && lane == 0, ji, 7);
#pragma unroll 1
        for (; sa < min(lim, s); sa++) {
          const uint32_t k = kseq[sa];
          if (elect()) issue_a(k);
        }
#pragma unroll 1
        for (int phase = 0;; phase++) {
          const uint32_t upto = phase == 2 ? lim : phase == 1 ? lim - LOOK : min((int)lim - LOOK, (int)sa + MID);
#pragma unroll 1
          for (; (int)sa < (int)upto; sa++, s++) {
            const uint32_t k = kseq[s];
            uint32_t stage = sm.stage(s), bar = sm.full(s), c0 = isC ? a0 : (k & 63) * 64, c1 = isC ? a1 + k * ak : a1, kb = (k & 63) * 64 + rank * 32, c2 = isX ? k * 4 : a2;
            uint64_t pa = (k & K_LAST_A) ? stream : keep, pb = (k & K_LAST_B) ? stream : keep;
            asm volatile("" : "+r"(stage), "+r"(bar), "+r"(c0), "+r"(c1), "+r"(kb), "+r"(c2), "+l"(pa), "+l"(pb));
            if (s < summed_end) mbar_wait(sm.summed(s), par(s) ^ 1);
            mbar_wait(bar + 32, par(s) ^ 1);
            TRS(s, 0);
            asm volatile("{\n.reg .pred p, q;\nelect.sync _|p, -1;\nsetp.eq.and.u32 q, %14, 0, p;\n"
                         "@q cp.async.bulk.tensor.4d.shared::cluster.global.mbarrier::complete_tx::bytes.multicast::cluster.L2::cache_hint [%3], [%4, {%5, %6, %7, %5}], [%0], %8, %9;\n"
                         "@p cp.async.bulk.tensor.3d.shared::cluster.global.mbarrier::complete_tx::bytes.L2::cache_hint [%2], [%10, {%11, %12, %13}], [%0], %15;\n"
                         "@p mbarrier.arrive.expect_tx.shared::cta.b64 _, [%0], %1;\n}"
                         ::"r"(bar), "r"(bytes), "r"(stage), "r"(stage + SLOT + rank * SLOT), "l"(tmB), "r"(0), "r"(kb), "r"(bcol), "h"((uint16_t)3), "l"(pb),
                           "l"(tmA), "r"(c0), "r"(c1), "r"(c2), "r"((uint32_t)isC), "l"(pa) : "memory");
            TRS(s, 1);
          }
          if (phase == 2) break;
          if (phase == 1) poll = ld_relaxed(dep);
          else if (lim == end) dep = dep_counter(sm, jobs[ji + 1], rank, (reinterpret_cast<const uint32_t*>(kseq)[(end + lane) >> 2] >> ((end + lane) % 4 * 8)) & 63);
        }
        if (lim == end) break;
      } else {
        if (s < min(end, sa + NSTAGE) && __all_sync(~0u, mbar_test(sm.empty(s), par(s) ^ 1))) {
          const uint32_t k = kseq[s];
          if (s < summed_end) mbar_wait(sm.summed(s), par(s) ^ 1);
          if (elect()) issue_b(k);
          s++;
        }
        poll = ld_relaxed(dep);
        if (++spins > SPIN_LIMIT) __trap();
      }
    }
    TRI(lane == 0, ji, 8);
  }
}

__global__ void __cluster_dims__(2, 1, 1) __launch_bounds__(384, 1) mega_kernel(char* scratch, uint32_t by_place, const __grid_constant__ Params P) {
#undef TRW
#define TRW warp
  extern __shared__ __align__(1024) uint8_t smem_raw[];
  TRX(threadIdx.x == 320, JMAX - 1, 0, 1, "%%globaltimer_lo");
  TRX(threadIdx.x == 320, JMAX - 1, 0, 25, "%%clock");
  TRX(threadIdx.x == 320, JMAX - 1, 0, 28, "%%smid");
  Smem sm;
  sm.scratch = scratch;
  sm.base = smem_u32(smem_raw);
  if ((sm.base & 0x3FFFF) != SMEM_BASE) __trap();
  const int warp = __shfl_sync(~0u, threadIdx.x >> 5, 0);
  const int rank = blockIdx.x & 1;
  uint32_t smid;
  asm("mov.u32 %0, %%smid;" : "=r"(smid));
  const uint32_t pair = !by_place ? blockIdx.x >> 1 : smid < 2 * NPAIR - 8 ? (smid >> 1) + 4 : (smid >> 1) + 4 - NPAIR;
  const uint32_t* jobs = P.jobs[pair];
  const uint32_t launches = ld_relaxed(counter(C_EP, blockIdx.x + threadIdx.y));
  if (warp == 10) {
    if (elect()) {
      for (int i = 0; i < NSTAGE; i++) mbar_init(sm.full(i), 1);
      mbar_init(sm.boot(), 1);
      asm volatile("fence.mbarrier_init.release.cluster;" ::: "memory");
    }
    cluster_arrive();
    const uint32_t first = jobs[0];
    const bool isC = first & JOB_C;
    if (elect()) {
      prefetch_tm(&P.a[0]);
      prefetch_tm(&P.w[0]);
    }
    uint64_t keep;
    asm("createpolicy.fractional.L2::evict_unchanged.b64 %0, 1.0;" : "=l"(keep));
    const Job J(first);
    if (!isC) {
      if (elect()) {
        mbar_expect_tx(sm.full(0), 40960);
        tma3d(sm.stage(0), &P.a[0], 0, J.R * 128, rank, sm.full(0), keep);
        TRS(0, 1);
      }
      TRX(threadIdx.x == 320, JMAX - 1, 0, 26, "%%clock");
      cluster_wait();
      TRX(threadIdx.x == 320, JMAX - 1, 0, 27, "%%clock");
      if (elect()) {
        tma4d_mc(sm.stage(0) + SLOT + rank * SLOT, &P.w[0], rank * 32, J.col, sm.full(0), keep);
        TRS(0, 0);
      }
#pragma unroll 1
      for (int k = 1; k < NSTAGE; k++) {
        if (elect()) {
          tma4d_mc(sm.stage(k) + SLOT + rank * SLOT, &P.w[0], k * 64 + rank * 32, J.col, sm.full(k), keep);
          TRS(k, 0);
          mbar_expect_tx(sm.full(k), 40960);
          tma3d(sm.stage(k), &P.a[0], k * 64, J.R * 128, rank, sm.full(k), keep);
          TRS(k, 1);
        }
      }
    } else {
      cluster_wait();
      if (!(first & JOB_X)) mbar_wait(sm.boot(), 0);
    }
  } else {
    if (warp < 8 && elect()) {
      mbar_init(sm.kv_ready(warp), 1);
      if (warp == 3) {
        mbar_init(sm.aux_full(), 3); mbar_init(sm.wgmma_done(), 4); mbar_init(sm.mma_done(), 8); mbar_init(sm.xchg_full(), 1); mbar_init(sm.kv_ready(-1), 1);
        mbar_expect_tx(sm.xchg_full(), 768);
      } else if (warp > 3) {
        mbar_init(sm.empty(warp), 4); mbar_init(sm.summed(warp), 6); mbar_init(sm.filled(warp - 4), 4); mbar_init(sm.vacant(warp - 4), 3);
      }
      asm volatile("fence.mbarrier_init.release.cluster;" ::: "memory");
    }
    cluster_arrive();
  }
  TRI(threadIdx.x == 0, JMAX - 1, 0);

  if (warp < 8) {
    asm volatile("setmaxnreg.inc.sync.aligned.u32 208;");
    const uint32_t e1 = launches + 1;
    cluster_wait();
    const uint32_t wg = warp >> 2;
    uint32_t rel = (threadIdx.x & 95) == 0 ? mapa(sm.empty(0), (threadIdx.x & 32) ? rank ^ 1 : rank) : 0;
    uint32_t dst = sm.slot(0) + (warp & 3) * 2048 + (threadIdx.x & 15) * 128 + ((((threadIdx.x >> 4) & 1) ^ (threadIdx.x & 7)) << 4);
    uint32_t t8 = sm.slot(0) + (warp & 3) * 2048 + (threadIdx.x & 7) * 128 + ((((threadIdx.x >> 3) & 3) ^ (threadIdx.x & 7)) << 4);
    rel = __shfl_sync(~0u, rel, threadIdx.x);
    dst = __shfl_sync(~0u, dst, threadIdx.x);
    t8 = __shfl_sync(~0u, t8, threadIdx.x);
    const uint32_t da0 = ((SMEM_BASE >> 4) | (1 << 16)) + wg * 512, dba = (255 << 16) + 1024 - wg * 512;
    uint32_t pend[64], todo = 0, pbar = 0, vbar = sm.vacant(0), ppar = 0, poff = 0, direct = 0;
    uint32_t s = 0, na = 0, nb = 0, ready = 0;
    auto release = [&](uint32_t st) { mbar_arrive_cl_if(rel, rel + (st & (NSTAGE - 1)) * 8); };
    auto flush = [&](bool vacant) {
      if (__all_sync(~0u, vacant)) {
        const uint32_t a = dst + poff;
        if (todo & 2) {
#pragma unroll
          for (int j = 0; j < 4; j++) stsm4(a ^ (j << 5), pend[4 * j], pend[4 * j + 1], pend[4 * j + 2], pend[4 * j + 3]);
          if (todo == 2) {
#pragma unroll
            for (int j = 0; j < 4; j++) stsm4((a ^ (j << 5)) + 8192, pend[16 + 4 * j], pend[17 + 4 * j], pend[18 + 4 * j], pend[19 + 4 * j]);
          }
        } else {
#pragma unroll
          for (int j = 0; j < 8; j++) stsm4((a ^ ((j & 3) << 5)) + (j >> 2) * 8192, pend[32 + 4 * j], pend[33 + 4 * j], pend[34 + 4 * j], pend[35 + 4 * j]);
        }
        mbar_arrive_warp(pbar);
        pbar += 16; vbar += 16; ppar = ~nb & 1;
        todo = todo == 2;
      }
    };
    uint32_t jw = jobs[0];
#pragma unroll
    for (int i = 0; i < 64; i++) pend[i] = 0;
    for (int ji = 0;; ji++) {
      const uint32_t cur = jw, nk = (jw >> 12) & 63, isQ = (jw & 3) == T_Q;
      jw = jobs[ji + 1];
      if (__builtin_expect((cur & JOB_C) || !ready, 0)) {
        for (uint32_t spins = 0; todo && ((cur & JOB_C) || !ready);) {
          if (direct && todo == 1) {
            vbar = sm.empty(s); ppar = par(s) ^ 1; poff = sm.stage(s) - sm.slot(0) + wg * SLOT;
          }
          flush(mbar_test(vbar, ppar));
          ready = __all_sync(~0u, mbar_test(sm.full(s), par(s)));
          if (++spins > SPIN_LIMIT) __trap();
        }
        if (cur & JOB_C) {
          if (nk == 0) break;
          TRC(ji, 16);
          constexpr uint32_t ONES = 0x3f803f80;
          const uint32_t lane = fresh_tid() & 31, g = ((cur >> 6) & 63) * 2 + rank;
          if (!(cur & JOB_X)) {
            float d[4] = {0.f, 0.f, 0.f, 0.f};
            sts32(sm.xchg() + 128 + lane * 4, ONES);
            fence_proxy_async_smem();
            bar_sync<9, 256>();
#pragma unroll 1
            for (int i = 0; i < 4; i++, s++) {
              mbar_wait(sm.full(s), par(s));
              if (!wg) sum_columns(d, da0 + (s & (NSTAGE - 1)) * (STAGE / 16), (SMEM_BASE + AUX_OFF + 1600 + 128) >> 4);
              release(s);
            }
            const float c = lane & 1 ? d[2] : d[0], c1 = __shfl_down_sync(~0u, c, 4);
            asm volatile("{\n.reg .pred p;\nsetp.eq.u32 p, %2, 0;\n@p st.relaxed.gpu.global.u64 [%0], %1;\n}"
                         ::"l"(SCR(sm, cs, (16 * 128 + g * 32 + (warp & 3) * 8 + (lane & 1) * 4 + (lane >> 3)) * 8)), "l"(((u64)e1 << 32) | pack_bf16(c, c1)), "r"((lane & 6) | wg) : "memory");
          } else {
            float a[6][4];
#pragma unroll
            for (int n = 0; n < 24; n++) pend[n] = 0;
#pragma unroll 1
            for (int i = 0;; i++) {
              const uint32_t p = dst - sm.slot(0) + sm.stage(s) + wg * SLOT;
              mbar_wait(sm.full(s), par(s));
              uint32_t v[8][4];
#pragma unroll
              for (int n = 0; n < 24; n++) a[n / 4][n % 4] = __uint_as_float(pend[n]);
#pragma unroll
              for (int j = 0; j < 8; j++) ldsm4((p ^ ((j & 3) << 5)) + (j >> 2) * 8192, v[j]);
#pragma unroll
              for (int j = 0; j < 8; j++) {
                mma16816(a[4 + (j & 1)], v[j][0], v[j][1], v[j][2], v[j][3], ONES, ONES);
#pragma unroll
                for (int n = 0; n < 4; n++) mma1688(a[n], v[j][n & 2], v[j][(n & 2) + 1], v[j][n]);
              }
#pragma unroll
              for (int n = 0; n < 24; n++) pend[n] = __float_as_uint(a[n / 4][n % 4]);
              if (i == 3) break;
              bar_sync<9, 256>();
              release(s++);
            }
            const uint32_t part = sm.stage(s) + 2 * SLOT + lane * 8, row = g * 64 + (warp & 3) * 16 + wg * 8 + (lane >> 2);
            const bool odd = lane & 4;
            const float s0 = a[4][0] + a[5][0], q0 = odd ? a[0][1] + a[2][1] : a[0][0] + a[2][0];
            const float s1 = a[4][2] + a[5][2], q1 = odd ? a[1][3] + a[3][3] : a[1][2] + a[3][2];
            sts64(part + warp * 256, make_uint2(__float_as_uint(wg ? s0 : s1), __float_as_uint(wg ? q0 : q1)));
            bar_sync<9, 256>();
            const uint2 o = lds64(part + (warp ^ 4) * 256);
            fence_proxy_async_smem();
            bar_sync<9, 256>();
            release(s++);
            publish_stats(sm, (wg ? s1 : s0) + __uint_as_float(o.x), (wg ? q1 : q0) + __uint_as_float(o.y), (row & 1) * (S / 2) + (row >> 1), (lane & 3) == lane >> 3, e1);
          }
          ready = 0;
          TRC(ji, 18);
          continue;
        }
        if (!ready) mbar_wait(sm.full(s), par(s));
      }
      auto mainloop = [&](auto& acc, auto near_end) {
        const uint32_t lead = (jw >> 12) % 64 == 0 ? min(LAST_LEAD, nk - 2) : 2, turn = wg ? lead : nk - 2, hurry = nk - lead - wg;
        uint32_t owed = 0;
        uint32_t da = da0 + (s & (NSTAGE - 1)) * (STAGE / 16);
        if (todo == 3) mbar_wait(vbar, ppar);
        if (wg) bar_sync<13, 256>();
        TRC(ji, 16);
        first_kstep(acc, da, da + dba);
        if (!wg) bar_arrive<13, 256>();
        constexpr uint32_t CLEAR = sizeof(acc) == 96 * 4 ? PREP + 2 : 3;
        for (uint32_t left = nk - 1;; left--) {
          for (uint32_t spins = 0;; spins++) {
            const bool vacant = mbar_test(vbar, ppar), next_full = mbar_test(sm.full(s + 1), par(s + 1));
            wg_wait<2>();
            mbar_arrive_cl_if(owed, owed + ((s - 1) & (NSTAGE - 1)) * 8);
            owed = 0;
            ready = __all_sync(~0u, next_full);
            if (!todo) {
              near_end(left, vacant);
              break;
            }
            const bool go = ready && left >= max(CLEAR, lead + 1);
            if (!(go && spins)) flush(vacant);
            if (go) break;
            if (spins > SPIN_LIMIT) __trap();
          }
          if (left == 0) break;
          if (!ready) mbar_wait(sm.full(s + 1), par(s + 1));
          owed = rel;
          if (left == turn) {
            wg_wait<0>();
            release(s);
            owed = 0;
            if (wg) bar_sync<1, 256>();
          }
          if (left - lead < hurry) wg_wait<1>();
          s++;
          da = da0 + (s & (NSTAGE - 1)) * (STAGE / 16);
          kstep(acc, da, da + dba);
          if (left == 1 + wg * 64) bar_arrive<1, 256>();
        }
      };
      if (isQ) {
        float acc[96];
        const uint32_t lane = (((dst - SMEM_BASE) >> 7) & 15) | ((dst ^ (dst >> 3)) & 16), qpar = (na ^ nb) & 1;
        uint32_t prepare_at = PREP;
        mainloop(acc, [&](uint32_t left, bool aux_full) {
          if (left == PREP + 1) {
            vbar = sm.aux_full(); ppar = qpar;
          } else if (left == prepare_at) {
            if (left == 0) mbar_wait(vbar, ppar);
            if (left == 0 || __all_sync(~0u, aux_full)) attention_prepare(pend, sm, warp, lane, !(cur & 0x38));
            else prepare_at--;
          }
        });
        wg_wait<0>();
        release(s);
        u64 token = 0;
        asm volatile("{\n.reg .pred p;\nsetp.eq.u32 p, %2, 0;\n@p mbarrier.arrive.shared::cta.b64 %0, [%1];\n}" : "+l"(token) : "r"(sm.wgmma_done()), "r"(lane + 1 - wg) : "memory");
        pend[A_NM + 1] |= (uint32_t)token & pend[A_ZERO];
        TRC(ji, 18);
        ready = __all_sync(~0u, attention(acc, pend, sm, warp, lane, t8, dst, cur & JOB_EARLY, (((cur >> 2) & 1) * 16 + ((cur >> 3) & 7) * 2 + rank) * 16 + ((cur >> 6) & 15), e1, qpar,
                                          sm.full(s + 1), par(s + 1), ji));
        todo = 3; pbar = sm.filled(wg); vbar = sm.mma_done(); ppar = qpar; poff = SLOT + wg * 8192;
      } else {
        float acc[128];
        mainloop(acc, [](uint32_t, bool) {});
        pbar = sm.filled(wg); vbar = pbar + 32; ppar = na & 1; poff = wg * SLOT;
        direct = (cur & 1) && (jw >> 12) % 64 == 0;
        nb++;
        todo = 2;
        wg_wait<0>();
        release(s);
        const bool next_full = mbar_test(sm.full(s + 1), par(s + 1));
        TRC(ji, 18);
#pragma unroll
        for (int i = 0; i < 64; i++) {
          const int j = (i & 15) + (i & 16) * 2 + (i >> 5) * 16;
          pend[i] = pack_bf16(acc[2 * j], acc[2 * j + 1]);
        }
        ready = __all_sync(~0u, next_full);
      }
      na++;
      s++;
    }
  } else {
    asm volatile("setmaxnreg.dec.sync.aligned.u32 88;");
    if (warp == 10) {
      producer(P, sm, jobs, P.kseq[pair], rank, threadIdx.x & 31, __shfl_sync(~0u, launches, 0) + 1);
    } else {
      const uint32_t e1 = __shfl_sync(~0u, launches, 0) + 1;
      const int w = min(warp - 8, 2);
      cluster_wait();
      if (w == 1) asm volatile("st.shared::cluster.u32 [%0], %1;" ::"r"(mapa(sm.pair_id(), rank ^ 1)), "r"(pair) : "memory");
      auto copy_rows = [&](uint32_t step) {
        constexpr int IN = 2 * SLOT / BOOT_PIECES;
        if (step == BOOT_STEP) mbar_wait(sm.boot(), 0);
        if (elect()) {
          if (step == 0) mbar_expect_tx(sm.boot(), blockIdx.x < S / 16 ? 2 * SLOT : 0);
          if (step < BOOT_PIECES && blockIdx.x < S / 16)
            asm volatile("cp.async.bulk.shared::cluster.global.mbarrier::complete_tx::bytes [%0], [%1], %2, [%3];"
                         ::"r"(sm.slot(0) + step * IN), "l"(at(P.x0, blockIdx.x * 32768 + step * IN)), "n"(IN), "r"(sm.boot()) : "memory");
          if (step - BOOT_STEP < 8 && blockIdx.x < S / 16) {
            asm volatile("cp.async.bulk.global.shared::cta.bulk_group [%0], [%1], %2;"
                         ::"l"(at(P.out, blockIdx.x * 32768 + (step - BOOT_STEP) * 4096)), "r"(sm.slot(0) + (step - BOOT_STEP) * 4096), "n"(4096) : "memory");
            bulk_commit();
          }
        }
        if (step == BOOT_STEP + 8) {
          bulk_wait();
          if (elect()) {
            mbar_arrive_n(sm.vacant(0), 3);
            mbar_arrive_n(sm.vacant(1), 3);
          }
        }
      };
      if (jobs[0] & JOB_C) {
        const uint32_t u = (((jobs[0] >> 6) & 63) * 2 + rank) * 2 + w, lane = threadIdx.x & 31;
        if (RING_SUMS < 16 && (jobs[0] & JOB_X) && w < 2 && u < 48) {
          const uint32_t part = u & 3 ? (u & 3) - 1 : u >> 4, c = u & 3 ? u >> 2 : 12 + ((u >> 2) & 3);
          const uint4* p = at(reinterpret_cast<const uint4*>(P.wqkv), (RING_SUMS * 64 + (lane >> 3)) * (6 * D) + part * (2 * D) + c * 128 + (lane & 7) * 16);
          float a[8] = {0.f, 0.f, 0.f, 0.f, 0.f, 0.f, 0.f, 0.f};
          mbar_wait(sm.full(REST_AT), 0);
#pragma unroll 1
          for (int i = RING_SUMS * 2; i < 32; i++, p = at(p, 32 * 6 * D)) {
            uint4 v[8];
#pragma unroll
            for (int j = 0; j < 8; j++) v[j] = __ldg(p + j * (4 * 6 * D / 16));
            add_cols(a, add8(v[0], v[1]), add8(v[2], v[3]));
            add_cols(a, add8(v[4], v[5]), add8(v[6], v[7]));
          }
          reduce_cols(a, lane);
          st_word(SCR(sm, cs, ((44 + c) * 128 + (lane >> 3) * 24 + part * 8 + (lane & 7)) * 8), pack_bf16(a[0], a[1]), e1);
        }
        if (w == 2) {
          if (jobs[0] & JOB_X) mbar_wait(sm.full(3), 0);
#pragma unroll 1
          for (int i = 0; i <= BOOT_STEP + 8; i++) {
            copy_rows(i);
            bulk_wait_read<0>();
          }
        }
      } else {
        const int lane = threadIdx.x & 31, word = (lane >> 3) * 24 + w * 8 + (lane & 7);
        Stager st;
        uint2 rest = make_uint2(0, 0);
        const u64* rp = SCR(sm, cs, ((44 + ((jobs[0] >> 6) & 15)) * 128 + word) * 8);
        const uint32_t cs = qkv_col_sums(sm, rank, w, lane, rest.x, [&](int s) {
          if (RING_SUMS < 16 && s == RING_SUMS - 3) rest = ld_word(rp);
          if (RING_SUMS < 16 && s == RING_SUMS - 1) {
            for (uint32_t n = 0; !__all_sync(~0u, rest.y == e1); n++) {
              rest = ld_word(rp);
              if (n > SPIN_LIMIT) __trap();
            }
          }
          if (w == 2) copy_rows(s - (RING_SUMS > 13));
          if (w == 0 && s == ST_STEP) st.load(sm, Job(jobs[0]), rank, lane, false);
          if (w == 0 && s == ST_STEP + 2) st.store(sm, Job(jobs[0]), rank, lane, false, e1);
        });
        sts32(sm.sums() + word * 4, cs);
        mbar_arrive_warp(sm.aux_full());
        if ((jobs[0] & 0x38) == 0 && rank == 0) st_word(SCR(sm, cs, (((jobs[0] >> 6) & 15) * 128 + word) * 8), cs, e1);
      }
      bar_sync<2, 96>();
      if (w == 2 && blockIdx.x < S / 16 && elect()) {
        red_release(counter(C_RD + (blockIdx.x >> 4) * 2, 0), 1);
        red_relaxed(counter(C_RD + (blockIdx.x >> 4) * 2 + 1, 0), 1);
      }
      uint32_t na = 0, nb = 0, stages = 0;
      for (int ji = 0;; ji++) {
        const uint32_t jw = jobs[ji];
        const Job J(jw);
        if (J.nk == 0) break;
        stages += J.nk;
        if (w != 0 && ((jw >> 22) & 3) != 3) {
          stats_task(sm, jw, rank, w, e1, P.out);
          TRI(threadIdx.x == 11 * 32, ji, 10);
        }
        if (jw & JOB_C) continue;
        const int lane = fresh_tid() & 31;
        const uint32_t b = J.R * 2 + rank;
        if (w == 0 && !(J.type & 1) && ji != 0) {
          Stager st;
          st.load(sm, J, rank, lane, true);
          st.store(sm, J, rank, lane, true, e1);
          TRI(lane == 0, ji, 9);
        }
        if (J.type == T_G) {
          bar_sync<2, 96>();
          constexpr int PER = 16 / NG;
          const uint32_t swap = P.swap, never = jw, ac = sm.sums() + (lane & 7) * 16;
          uint32_t ag[NG], au[NG], as = sm.stats() + 64 + w * NG * 32 + (lane >> 3) * 8;
          uint32_t ho = (rank * (S / 2) + J.R * 128 + w * NG * 4 + (lane >> 3)) * (F * 2) + J.col * 256 + (lane & 7) * 16;
          uint4 cg = lds128(ac + (swap >> 5)), cu = lds128(ac + 256 - (swap >> 5)), g4[NG], u4[NG];
          uint2 st[NG];
          auto load = [&] {
#pragma unroll
            for (int i = 0; i < NG; i++) { st[i] = lds64v(as + i * 32); g4[i] = lds128v(ag[i]); u4[i] = lds128v(au[i]); }
          };
#pragma unroll
          for (int i = 0; i < NG; i++) {
            const uint32_t a = (sm.slot(0) + (w * NG + i) * 512 + (lane >> 3) * 128 + (((lane & 7) ^ (lane >> 3)) << 4)) ^ (((w * NG + i) & 1) << 6);
            ag[i] = a + swap; au[i] = a + (swap ^ 8192);
          }
          mbar_wait(sm.filled(0), na & 1);
          mbar_wait(sm.filled(1), na & 1);
          load();
          if (w == 2 && elect()) red_relaxed(counter(C_RD + J.inst() * 16 + b, 0), 1);
          TRI(threadIdx.x == 11 * 32, ji, 3);
#pragma unroll 1
          for (uint32_t g = w; g < 4 * PER; g += 3) {
            float hinv[NG], hinv2[NG];
            uint4 gc[NG], uc[NG];
            const bool turn = ((g + 3) ^ g) & PER, half = ((g + 3) ^ g) & (2 * PER);
#pragma unroll
            for (int i = 0; i < NG; i++) {
              hinv[i] = 0.5f * __uint_as_float(st[i].x);
              hinv2[i] = hinv[i] * __uint_as_float(st[i].x);
              asm volatile("" : "+f"(hinv[i]), "+f"(hinv2[i]));
              gc[i] = fma8(dup_hi(st[i].y), cg, g4[i]);
              uc[i] = fma8(dup_hi(st[i].y), cu, u4[i]);
              ag[i] = (ag[i] + NG * 1536) ^ ((NG & 1) << 6);
              au[i] = (au[i] + NG * 1536) ^ ((NG & 1) << 6);
            }
            as += NG * 96;
            if (turn) {
              mbar_arrive_warp(sm.vacant((g / PER) ^ 2));
              if (half) {
                cg = lds128(ac + (swap >> 5) + 128); cu = lds128(ac + 384 - (swap >> 5));
                as -= 1024;
              }
#pragma unroll
              for (int i = 0; i < NG; i++) { ag[i] += half ? -3 * 8192 : 8192; au[i] += half ? -3 * 8192 : 8192; }
              TRX(threadIdx.x == 11 * 32 && g < 3 * PER, ji, 25, 25 + g / PER * 2, "%%clock");
              if (g < 3 * PER) mbar_wait(sm.filled(g / PER + 1), (g < PER ? na : nb) & 1);
              TRX(threadIdx.x == 11 * 32 && g < 3 * PER, ji, 25, 26 + g / PER * 2, "%%clock");
            }
            load();
            if (g == never) mbar_wait(sm.boot(), 0);
            bf16* out = SCR(sm, h, ho);
#pragma unroll
            for (int i = 0; i < NG; i++)
              stg128(out + i * 4 * F, make_uint4(swiglu2(gc[i].x, uc[i].x, hinv[i], hinv2[i]), swiglu2(gc[i].y, uc[i].y, hinv[i], hinv2[i]),
                                                 swiglu2(gc[i].z, uc[i].z, hinv[i], hinv2[i]), swiglu2(gc[i].w, uc[i].w, hinv[i], hinv2[i])));
            ho += NG * 12 * F * 2 - (half ? 128 * F * 2 - 128 : 0);
          }
          bar_sync<2, 96>();
          TRI(threadIdx.x == 11 * 32, ji, 4);
          if (w == 2 && elect()) red_release(counter(C_H + J.layer * 16 + b, J.col), 1);
          TRI(threadIdx.x == 11 * 32, ji, 5);
        } else if (J.type == T_Q) {
          const bool late = J.R > 0 && !(jw & JOB_EARLY);
          if (w == 0) {
            __syncwarp();
            if (ji != 0 && elect()) mbar_arrive_n(sm.aux_full(), 3);
#pragma unroll 1
            for (int phase = 0; phase < 2; phase++) {
              if (J.R > 0 && phase == late) import_halo(sm, SCR(sm, halo, (((J.layer * 16 + b - 2) * 16 + J.col) * 256 + lane) * 16), e1, lane);
              if (phase == 0) {
                mbar_arrive_warp(sm.kv_ready(-1));
                TRI(lane == 0, ji, 11);
#pragma unroll 1
                for (int h = 0; h < 2; h++) {
                  mbar_wait(sm.filled(h), na & 1);
                  TRI(lane == 0, ji, 3);
                  fence_proxy_async_smem();
                  bulk_wait_read<0>();
                  if (elect()) {
                    tma3d_store(&P.ow, J.col * 64, J.R * 128 + h * 64, rank, sm.slot(1) + h * 8192);
                    bulk_commit();
                  }
                }
                if (J.layer && elect()) red_relaxed(counter(C_RD + 32 + b, 0), 1);
              }
            }
            bulk_wait();
          }
          if (late && w < 2) {
            bar_sync<7, 64>();
            boundary_rows(sm, w, lane, rank * O_PLANE + J.R * 128 * (D * 2) + J.col * 128);
            bar_sync<7, 64>();
          }
          TRI(threadIdx.x == 256, ji, 4);
          if (w == 0 && elect()) {
            mbar_arrive_n(sm.vacant(0), 3);
            mbar_arrive_n(sm.vacant(1), 3);
            red_release(counter(C_O + J.layer * 16 + b, J.col), 1);
          }
          TRI(threadIdx.x == 256, ji, 5);
        } else if (w == 0) {
          wait_count(counter(C_RD + J.inst() * 16 + b, 0), e1 * (J.type == T_D ? 28 : 16));
          fence_proxy_async();
          const bool last = Job(jobs[ji + 1]).nk == 0;
#pragma unroll 1
          for (uint32_t v = 0; v < 4; v++) {
            const uint32_t u = last ? (v >> 1) + (v & 1) * 2 : v;
            mbar_wait(sm.filled(u), (u & 2 ? nb : na) & 1);
            TRI(u == 0 && lane == 0, ji, 3);
            fence_proxy_async_smem();
            const uint32_t src = (last && (u & 2) ? sm.stage(stages) : sm.slot(0)) + (u & 1) * SLOT;
#pragma unroll 1
            for (uint32_t p = 0; p < 16384 / PIECE; p++) {
              if (elect()) {
                tma3d_reduce_add(&P.xr, J.col * 256 + (u & 2) * 32 + p * PIECE / 8192 * 128, J.R * 128 + (u & 1) * 64 + p * PIECE % 8192 / 128, rank, src + p * PIECE);
                bulk_commit();
              }
              if (!last) bulk_wait_read<DEPTH - 1>();
            }
            if (!last) {
              bulk_wait();
              if (elect()) mbar_arrive_n(sm.vacant(u ^ 2), 3);
            }
            if (u == 1 && J.inst() != 3) bar_arrive<8, 64>();
          }
          bulk_wait();
        }
        if ((J.type & 1) && J.inst() != 3 && w < 2) {
          if (w == 1) bar_sync<8, 64>();
          TRX(lane == 0, ji, 4, w ? 12 : 4, "%%globaltimer_lo");
          if (elect()) red_release(counter(C_X + J.inst() * 16 + b, J.col * 2 + 1 - w), J.nk);
          TRX(lane == 0, ji, 5, w ? 13 : 5, "%%globaltimer_lo");
          if (w == 1) bar_arrive<10, 64>(); else bar_sync<10, 64>();
        }
        na++;
        nb += J.type != T_Q;
      }
      TRI(threadIdx.x == 8 * 32, JMAX - 1, 6);
      TRK(threadIdx.x == 8 * 32, JMAX - 1, 24);
      if (w == 0 && elect()) red_relaxed(counter(C_EP, blockIdx.x), 1);
      if (w == 2 && __float_as_uint(lds32f(sm.pair_id())) != pair) __trap();
    }
  }
  cluster_arrive();
  cluster_wait();
}

typedef CUresult (*EncodeFn)(CUtensorMap*, CUtensorMapDataType, cuuint32_t, void*, const cuuint64_t*, const cuuint64_t*, const cuuint32_t*,
                             const cuuint32_t*, CUtensorMapInterleave, CUtensorMapSwizzle, CUtensorMapL2promotion, CUtensorMapFloatOOBfill);
struct Dim { cuuint64_t size, stride; cuuint32_t box; };
template <int N> void encode(EncodeFn fn, CUtensorMap* m, const void* ptr, const Dim (&d)[N]) {
  cuuint64_t dims[N], strides[N];
  cuuint32_t box[N], es[N];
  for (int i = 0; i < N; i++) { dims[i] = d[i].size; strides[i] = d[i].stride; box[i] = d[i].box; es[i] = 1; }
  fn(m, CU_TENSOR_MAP_DATA_TYPE_BFLOAT16, N, const_cast<void*>(ptr), dims, strides + 1, box, es, CU_TENSOR_MAP_INTERLEAVE_NONE,
     CU_TENSOR_MAP_SWIZZLE_128B, CU_TENSOR_MAP_L2_PROMOTION_L2_128B, CU_TENSOR_MAP_FLOAT_OOB_FILL_NONE);
}

}

extern "C" void kernel_launch(void* const* d_in, const int* in_sizes, int n_in, void* d_out, int out_size) {
  (void)in_sizes; (void)n_in; (void)out_size;
  static EncodeFn fn = nullptr;
  static Scratch* scr;
  static int sms;
  if (!fn) {
    void* p = nullptr;
    cudaDriverEntryPointQueryResult q;
    cudaGetDriverEntryPoint("cuTensorMapEncodeTiled", &p, cudaEnableDefault, &q);
    fn = (EncodeFn)p;
    scr = scratch_base();
    int device = 0;
    cudaGetDevice(&device);
    cudaDeviceGetAttribute(&sms, cudaDevAttrMultiProcessorCount, device);
    cudaFuncSetAttribute(mega_kernel, cudaFuncAttributeMaxDynamicSharedMemorySize, SMEM_BYTES);
  }
  static Params P;
  const char *wg = (const char*)d_in[4], *wu = (const char*)d_in[5], *w0 = wg < wu ? wg : wu;
  const cuuint64_t plane = wg < wu ? wu - wg : wg - wu;
  P.swap = wg < wu ? 0 : 8192;
  encode(fn, &P.a[0], d_in[0], {{D, 2, 64}, {S / 2, D * 4, 128}, {2, D * 2, 1}});
  encode(fn, &P.a[1], scr->o, {{D, 2, 64}, {S / 2, D * 2, 128}, {2, O_PLANE, 1}});
  encode(fn, &P.ow, scr->o, {{D, 2, 64}, {S / 2, D * 2, 64}, {2, O_PLANE, 1}});
  encode(fn, &P.a[2], d_out, {{D, 2, 64}, {S / 2, D * 4, 128}, {2, D * 2, 1}});
  encode(fn, &P.a[3], scr->h, {{F, 2, 64}, {S / 2, F * 2, 128}, {2, (cuuint64_t)F * S, 1}});
  encode(fn, &P.a[4], w0, {{F, 2, 64}, {D, F * 2, 256}, {2, plane, 1}});
  encode(fn, &P.a[5], d_in[0], {{64, 2, 64}, {S, D * 2, 64}, {16, 128, 4}});
  encode(fn, &P.w[T_Q], d_in[1], {{64, 2, 64}, {D, 3 * D * 2, 32}, {16, 128, 1}, {3, D * 2, 3}});
  encode(fn, &P.w[T_O], d_in[2], {{64, 2, 64}, {D, D * 2, 32}, {16, 128, 4}, {1, (cuuint64_t)D * D * 2, 1}});
  encode(fn, &P.w[T_G], w0, {{64, 2, 64}, {D, F * 2, 32}, {F / 64, 128, 2}, {2, plane, 2}});
  encode(fn, &P.w[T_D], d_in[6], {{64, 2, 64}, {F, D * 2, 32}, {16, 128, 4}, {1, (cuuint64_t)F * D * 2, 1}});
  encode(fn, &P.xr, d_out, {{D, 2, 64}, {S / 2, D * 4, PIECE / 128}, {2, D * 2, 1}});
  memcpy(P.jobs, kJobs, sizeof(kJobs));
  memcpy(P.kseq, kSeq, sizeof(kSeq));
  P.x0 = (const bf16*)d_in[0];
  P.wqkv = (const bf16*)d_in[1];
  P.out = (bf16*)d_out;
  mega_kernel<<<2 * NPAIR, 384, SMEM_BYTES>>>((char*)scr, sms == 2 * NPAIR, P);
}
```

```cpp
#include <cuda_runtime.h>
#include <cuda_bf16.h>
#include <cuda.h>
#include <stddef.h>
#include <stdint.h>
#include <string.h>

namespace {

typedef __nv_bfloat16 bf16;
typedef unsigned long long u64;
constexpr int S = 2048, D = 1024, F = 3584;
constexpr int STAGE = 49152, NSTAGE = 4, SLOT = 16384;
constexpr int STG_OFF = NSTAGE * STAGE, BAR_OFF = STG_OFF + 2 * SLOT, AUX_OFF = BAR_OFF + 336;
constexpr int SMEM_BYTES = AUX_OFF + 2736;
constexpr int SMEM_BASE = 1024;
constexpr int NPAIR = 66, JMAX = 24, KMAX = 296;
constexpr int T_Q = 0, T_O = 1, T_G = 2, T_D = 3;
constexpr uint32_t JOB_C = 1u << 18;
constexpr uint32_t K_LAST_A = 64, K_LAST_B = 128;
constexpr uint32_t JOB_EARLY = 1u << 21;
constexpr uint32_t JOB_X = JOB_EARLY;
#define RING_SUMS 14
#define REST_AT 0
constexpr int BOOT_PIECES = 4, BOOT_STEP = RING_SUMS < 16 ? 4 : 5, ST_STEP = 9;
constexpr int SPLIT_MIN = 6;
constexpr int PREP = 3, LAST_LEAD = 3;
constexpr int LOOK = 2, MID = 7;
constexpr int NG = 2, PIECE = 8192, DEPTH = 2;
constexpr uint32_t SPIN_LIMIT = 1u << 21;

constexpr int C_X = 0;
constexpr int C_O = C_X + 48;
constexpr int C_H = C_O + 32;
constexpr int C_RD = C_H + 32;
constexpr int C_EP = C_RD + 64;
constexpr int C_LINES = C_EP + 5;

struct Scratch {
  bf16 h[S * F];
  uint32_t cnt[256 * 32];
  bf16 o[S / 2 * D];
  u64 stats[4 * S];
  bf16 o1[S / 2 * D];
  u64 cs[60 * 128];
  ulonglong2 halo[2 * 16 * 16 * 8 * 32];
};
constexpr uint32_t O_PLANE = offsetof(Scratch, o1) - offsetof(Scratch, o);
static_assert(C_LINES <= 256, "");
constexpr size_t PAGE = 2 << 20;
__device__ __align__(1024) char g_scratch[sizeof(Scratch) + PAGE];
Scratch* scratch_base() {
  char* p;
  cudaGetSymbolAddress((void**)&p, g_scratch);
  return (Scratch*)(p + (-(size_t)p & (PAGE - 1)));
}

uint32_t kJobs[NPAIR][JMAX] = {
  {0xe44200,0xc10020,0xc44040,0xc08009,0xc10082,0x4101001a,0xc10022,0xc1800b,0x184170b3,0x46610054,0x5b610034,0x7d41000e,0xc1001e,0xc10076,0xc10096,0xc14037,0xc40000,0xc40000,0xc40000,0xc40000,0xc40000,0xc40000,0xc40000,0xc40000},
  {0xe44000,0xc10018,0xc44080,0xc08009,0xc10021,0x22010052,0xc10092,0xc100aa,0xc09013,0x16410004,0x2d61004c,0x3461002c,0x4e410086,0xc10056,0x618100ae,0xc100b6,0xc1b02f,0xc40000,0xc40000,0xc40000,0xc40000,0xc40000,0xc40000,0xc40000},
  {0xc10000,0xc44140,0xc04001,0xc10042,0x3a01004a,0xc1006a,0xc100b2,0xc1201b,0x26413033,0x6440b00d,0x681001d,0x3281002d,0xd48100a6,0xc101be,0xc1e007,0xc40000,0xc40000,0xc40000,0xc40000,0xc40000,0xc40000,0xc40000,0xc40000,0xc40000},
  {0xc10010,0xc440c0,0xc04001,0xc10002,0x3b01008a,0xc1019a,0xc101aa,0xc0800b,0x1a40d01b,0xc10014,0x66410064,0x2810006,0xc1008e,0xc10066,0xc1007e,0xc0e087,0xc1003f,0xc40000,0xc40000,0xc40000,0xc40000,0xc40000,0xc40000,0xc40000},
  {0xc10048,0xe10058,0xe10070,0xc05039,0x21010012,0x7a01b003,0xc1003a,0x29410044,0x3561001c,0x4f61005c,0x5761003c,0x7e41004e,0x6081009e,0xc100be,0xc1c00f,0xc40000,0xc40000,0xc40000,0xc40000,0xc40000,0xc40000,0xc40000,0xc40000,0xc40000},
  {0xe44240,0xc443c0,0xe10158,0xc10130,0xc040e1,0x170101ca,0x620101da,0xc101f2,0x641905b,0xc07063,0x324100c5,0x7a61016c,0x12a1013c,0x288101d6,0xc101ee,0xc10236,0xc1a04f,0xc40000,0xc40000,0xc40000,0xc40000,0xc40000,0xc40000,0xc40000},
  {0xe44280,0xc44780,0xc10228,0x1f044840,0xe10270,0xc103ca,0x5e01039a,0xc103b2,0xc1042a,0xc103ba,0x6d4180bb,0x8810506,0xc100b5,0xd2810426,0xc103be,0xc1f097,0xc40000,0xc40000,0xc40000,0xc40000,0xc40000,0xc40000,0xc40000,0xc40000},
  {0xe44380,0xc102d0,0xc040c1,0xc10091,0x1101044a,0x67010452,0xc1046a,0xc104f2,0x2c4170ab,0x5240e0bb,0x5810486,0xc104ce,0xc10466,0xc1047e,0xc1f09f,0xc40000,0xc40000,0xc40000,0xc40000,0xc40000,0xc40000,0xc40000,0xc40000,0xc40000},
  {0xe442c0,0xc10320,0xc040c1,0x1d210338,0xc1054a,0x610105e2,0x7301e0cb,0xc10344,0xc1030c,0xc040bb,0x6041036c,0x1ca1033c,0x29810596,0x6c8105a6,0xc106f6,0xc1d0df,0xc40000,0xc40000,0xc40000,0xc40000,0xc40000,0xc40000,0xc40000,0xc40000},
  {0xe443c0,0xc10390,0xc44d80,0xc100d1,0x1501060a,0x64010612,0x720180c3,0x24106ba,0xc1038c,0x404103dc,0xc103f4,0x2c80c0e5,0x4d810656,0xc1066e,0xc1069e,0xc1a0ef,0xc40000,0xc40000,0xc40000,0xc40000,0xc40000,0xc40000,0xc40000,0xc40000},
  {0xc10088,0xe100e0,0xc10011,0x270100ca,0x6c01015a,0x7c01800b,0xc0d023,0x2140f0b3,0x516100dc,0xc10106,0xc1010e,0xc10166,0xc1013e,0xc1f017,0xc40000,0xc40000,0xc40000,0xc40000,0xc40000,0xc40000,0xc40000,0xc40000,0xc40000,0xc40000},
  {0xc10198,0xc101b0,0x1b0445c0,0xc44600,0xc446c0,0xc1030a,0x5d010322,0xc102f2,0xc0e04b,0xc101c4,0xc1707b,0x79410055,0xc07065,0xb0810075,0xd0810326,0xc10336,0xc1d05f,0xc40000,0xc40000,0xc40000,0xc40000,0xc40000,0xc40000,0xc40000},
  {0xc10050,0xc10060,0xc10038,0x29210078,0x3e010062,0xc10032,0x441901b,0x2461000c,0x36610024,0x5d410074,0x228100ad,0x5b810026,0xc1006e,0xc1005e,0xc1203f,0xc40000,0xc40000,0xc40000,0xc40000,0xc40000,0xc40000,0xc40000,0xc40000,0xc40000},
  {0xe44040,0xc444c0,0xc10168,0xc10049,0x1601024a,0x63010252,0xc10262,0xc1027a,0xc18073,0x55410045,0x48101c6,0xc1034e,0xc1035e,0xc1023e,0xc1e04f,0xc40000,0xc40000,0xc40000,0xc40000,0xc40000,0xc40000,0xc40000,0xc40000,0xc40000},
  {0xe44080,0xc44700,0xe10220,0xc09089,0xc103c2,0x5a010412,0xc10512,0xc103f2,0x1e41c0a3,0x4961021c,0x58410234,0x36a1027c,0x4881041e,0x7281051e,0xc10436,0xc1909f,0xc40000,0xc40000,0xc40000,0xc40000,0xc40000,0xc40000,0xc40000,0xc40000},
  {0xe44180,0xc44880,0xe102a0,0xc04081,0x1c2102f8,0xc104ca,0x66010462,0xc104ea,0xc104ba,0xc104fa,0xc102d4,0xc102ac,0x1d8104c6,0xc104d6,0x6d8104a6,0xc1053e,0xc0f087,0xc0c0b7,0xc40000,0xc40000,0xc40000,0xc40000,0xc40000,0xc40000},
  {0xe440c0,0xc44ac0,0xc10328,0xc07041,0xc080c9,0xc0c0e1,0xb2010592,0xc105aa,0xc106e2,0x1d4130db,0xc090e3,0x484100fb,0xc810546,0x3f81054e,0x5d810566,0xc1057e,0xc200c7,0xc40000,0xc40000,0xc40000,0xc40000,0xc40000,0xc40000,0xc40000},
  {0xe441c0,0xc44c40,0xc10398,0xc44d40,0xe103f0,0xc100f1,0xd0010692,0xc10632,0xc10672,0xc1067a,0x6f6103cc,0x736103a4,0x13810606,0xc1064e,0xc10626,0xc1067e,0xc0f0e7,0xc0e0ff,0xc40000,0xc40000,0xc40000,0xc40000,0xc40000,0xc40000},
  {0xe44300,0xc100a0,0xc04001,0xc100c2,0x3c010112,0x7b01d003,0x741013a,0x234100c4,0x374100d4,0xc100ac,0x39a100fc,0xc10156,0x6981012e,0xc1019e,0xc1b01f,0xc40000,0xc40000,0xc40000,0xc40000,0xc40000,0xc40000,0xc40000,0xc40000,0xc40000},
  {0xe44340,0xc101d8,0xc09041,0xc10051,0x24010352,0xc1032a,0xc1b053,0x12410073,0xe101dc,0xe101ac,0xc10286,0x40810296,0x758102a6,0xc102e6,0xc19057,0xc40000,0xc40000,0xc40000,0xc40000,0xc40000,0xc40000,0xc40000,0xc40000,0xc40000},
  {0xc10008,0xc44000,0xc44100,0xe10068,0xc10029,0x3601009a,0xc1002a,0xc100a2,0xc1007a,0x3041803b,0xc0b095,0x10810046,0x41810016,0x7881002e,0xc1003e,0xc19037,0xc40000,0xc40000,0xc40000,0xc40000,0xc40000,0xc40000,0xc40000,0xc40000},
  {0xc10110,0xc44440,0xe10160,0xc101c2,0x4201021a,0xc10222,0xc10272,0xc101fa,0x3f410104,0x5e610114,0xc100dd,0x2081024e,0x5c8101e6,0xc101fe,0xc10047,0xc1007f,0xc40000,0xc40000,0xc40000,0xc40000,0xc40000,0xc40000,0xc40000,0xc40000},
  {0xc10200,0xc44a00,0xc10260,0x3010402,0x4301050a,0xc10422,0xc0808b,0xc10432,0xc10244,0xe10214,0xc0b08d,0x7810386,0xc1050e,0x5f8103e6,0xc103fe,0xc1f0a7,0xc40000,0xc40000,0xc40000,0xc40000,0xc40000,0xc40000,0xc40000,0xc40000},
  {0xc102c0,0xc44900,0xc102b0,0x40449c0,0x120100b1,0x3801045a,0xc10472,0xa41a093,0x3d8102c4,0x4fa10294,0xe102e4,0xe102bc,0xc10516,0xc104e6,0xc104fe,0xc1b08f,0xc40000,0xc40000,0xc40000,0xc40000,0xc40000,0xc40000,0xc40000,0xc40000},
  {0xc10308,0xe10350,0xc44b00,0xe10378,0xc070f9,0x3f01059a,0xc105f2,0xc105ba,0x134105fa,0xe1034c,0xe10364,0xc106c6,0xc10556,0xc1055e,0xc105f6,0xc1e0ef,0xc40000,0xc40000,0xc40000,0xc40000,0xc40000,0xc40000,0xc40000,0xc40000},
  {0xc10388,0xe103e0,0xc44d00,0xc10682,0x5801065a,0xc106aa,0xc41b0d3,0xc110eb,0x4a4130fb,0x3810686,0xc106ce,0xc106ee,0xc106a6,0xc1e0d7,0xc40000,0xc40000,0xc40000,0xc40000,0xc40000,0xc40000,0xc40000,0xc40000,0xc40000,0xc40000},
  {0xe44100,0xc44180,0xe100d8,0xc44280,0xc10019,0x1001010a,0xc0b039,0xc10172,0xc1016a,0x1441a02b,0x4241009c,0xb8100f4,0x24810146,0x5981003d,0xf08100f6,0xc19017,0xc0c03f,0xc40000,0xc40000,0xc40000,0xc40000,0xc40000,0xc40000,0xc40000},
  {0xe44140,0xc101a0,0xc44640,0xc10059,0x1301028a,0x6501029a,0xc08079,0x71014053,0xc180e3,0xc0e07b,0xc101b4,0x37a101bc,0x4981007d,0x668102b6,0xc1033e,0xc1806f,0xc40000,0xc40000,0xc40000,0xc40000,0xc40000,0xc40000,0xc40000,0xc40000},
  {0x2e010040,0xe10028,0xe10030,0xc1000a,0x6801005a,0xc10072,0x40f013,0x104100ba,0x56410005,0x7161006c,0x14a1007c,0x2a810035,0x68810036,0xc1018e,0xc18027,0xc40000,0xc40000,0xc40000,0xc40000,0xc40000,0xc40000,0xc40000,0xc40000,0xc40000},
  {0xc10150,0xe10118,0xc44680,0xc10069,0x2f0101d2,0x7701c043,0x541023a,0x2241006b,0x4741011c,0xc10174,0x2f81020e,0xc1025e,0x7a8101f6,0xc10256,0xc0c05f,0xc0a077,0xc40000,0xc40000,0xc40000,0xc40000,0xc40000,0xc40000,0xc40000,0xc40000},
  {0xc10208,0xc44740,0xc447c0,0xc04081,0xc07089,0x100a9,0xb00103da,0x7501d083,0x34103fa,0xe1020c,0xe10254,0xe1022c,0xc1038e,0xc1039e,0x768103b6,0xc1d08f,0xc0a0bf,0xc40000,0xc40000,0xc40000,0xc40000,0xc40000,0xc40000,0xc40000},
  {0xc10290,0xc44940,0xc102f0,0x5010099,0x200080b9,0xd201049a,0xc104a2,0xc1047a,0xc0e09b,0x3e6102cc,0x5f40707b,0xc102f4,0x2b81048e,0xc1049e,0x7b8104b6,0xc104de,0xc160b7,0xc40000,0xc40000,0xc40000,0xc40000,0xc40000,0xc40000,0xc40000},
  {0xc10318,0xc10358,0xc44b80,0xc10542,0x59010552,0xc1056a,0xc10572,0xc1c0eb,0x4b610314,0x59610374,0x7f61037c,0x158100fd,0x648105ae,0xc105e6,0xc180c7,0xc40000,0xc40000,0xc40000,0xc40000,0xc40000,0xc40000,0xc40000,0xc40000,0xc40000},
  {0xc103c0,0xc44c00,0xc103e8,0x6010602,0x4401061a,0xc090f9,0x7401a0cb,0xc170e3,0xc0d0fb,0xc103ec,0xc040e5,0x2e81068e,0xc1065e,0x7e8106b6,0xc1b0df,0xc0a0ff,0xc40000,0xc40000,0xc40000,0xc40000,0xc40000,0xc40000,0xc40000,0xc40000},
  {0xc100c8,0xc44240,0xc100b0,0x7010102,0x450100da,0xc1012a,0xc100f2,0xc100fa,0xe1008c,0xe10094,0xc0500d,0x1810186,0xc10196,0x6781016e,0xc100fe,0xc1d02f,0xc40000,0xc40000,0xc40000,0xc40000,0xc40000,0xc40000,0xc40000,0xc40000},
  {0xc101d0,0xe101e0,0xc100a1,0x250102ca,0x6e01031a,0x7e0102b2,0xc102ba,0xc0a06b,0x3161018c,0x676101ec,0x744102c6,0xc102d6,0x6f8102ae,0xc1032e,0xc1b067,0xc40000,0xc40000,0xc40000,0xc40000,0xc40000,0xc40000,0xc40000,0xc40000,0xc40000},
  {0xc10108,0xe10170,0xe10138,0xc08079,0x3701025a,0xc10232,0xc1404b,0x1b410144,0x2e610154,0x38610164,0x68410206,0xc101ce,0xc10226,0xc1037e,0xc1d067,0xc40000,0xc40000,0xc40000,0xc40000,0xc40000,0xc40000,0xc40000,0xc40000,0xc40000},
  {0xc10218,0xc10258,0xc10278,0x2a01040a,0xc080b9,0xc103ea,0xc1308b,0x1f41053a,0xc10085,0x7c61026c,0x16810406,0x478103d6,0x738103ae,0xc1042e,0xc19097,0xc40000,0xc40000,0xc40000,0xc40000,0xc40000,0xc40000,0xc40000,0xc40000,0xc40000},
  {0xc102c8,0xe102a8,0xc04081,0x1010482,0x5b010492,0x7601b083,0x941809b,0xe1028c,0xe102a4,0xc05095,0x11810446,0x42810496,0xc1046e,0xc104be,0xc190a7,0xc40000,0xc40000,0xc40000,0xc40000,0xc40000,0xc40000,0xc40000,0xc40000,0xc40000},
  {0xc10348,0xc44bc0,0xc10370,0x80105c2,0x4601058a,0x790200c3,0x14160db,0x3c410354,0x61610324,0x754105c6,0xc105d6,0x658106e6,0xc105fe,0xc1d0cf,0xc40000,0xc40000,0xc40000,0xc40000,0xc40000,0xc40000,0xc40000,0xc40000,0xc40000,0xc40000},
  {0xc103d0,0xc103a8,0xc103f8,0x2b01064a,0x6901062a,0xc1069a,0xc106b2,0x27410384,0x394103d4,0x7b6103e4,0x17810646,0x448106d6,0xc106ae,0xc106be,0xc1a0e7,0xc40000,0xc40000,0xc40000,0xc40000,0xc40000,0xc40000,0xc40000,0xc40000,0xc40000},
  {0xc100d0,0xe100a8,0xc100d9,0x2801018a,0x6d010132,0x7d010162,0xc1017a,0xc1102b,0x4140d03b,0xfa100ec,0x1b8100ce,0xc1015e,0x7d810136,0xc1a007,0xc0b037,0xc40000,0xc40000,0xc40000,0xc40000,0xc40000,0xc40000,0xc40000,0xc40000,0xc40000},
  {0xc10190,0xc44580,0xc101f0,0x9010282,0x47010292,0xc102da,0xc102e2,0xc1033a,0xc10073,0x536101e4,0xc10306,0xc10356,0xc1029e,0xc102be,0xc1f057,0xc40000,0xc40000,0xc40000,0xc40000,0xc40000,0xc40000,0xc40000,0xc40000,0xc40000},
  {0xc10148,0xc44400,0xc10128,0xa010202,0x4801020a,0xc101ea,0xc1604b,0x1c41037a,0x6e61010c,0x76610124,0x18810246,0xc10216,0x63810266,0xc1027e,0xc13047,0xc0a0bf,0xc40000,0xc40000,0xc40000,0xc40000,0xc40000,0xc40000,0xc40000,0xc40000},
  {0xc10248,0xc44a40,0xc10268,0xb010382,0x490103d2,0xc103aa,0xc10532,0xc1043a,0xc120b3,0x50410264,0x8103c6,0xc10396,0xc103a6,0xc1043e,0xc1e0af,0xc40000,0xc40000,0xc40000,0xc40000,0xc40000,0xc40000,0xc40000,0xc40000,0xc40000},
  {0xc10288,0x2c2102d8,0xe102b8,0xc1048a,0x6a0104d2,0xc104aa,0xc1052a,0x284150ab,0x5440e0bb,0xa81009d,0x34a102fc,0x4a81045e,0xc10476,0xc104ee,0xc110bf,0xc40000,0xc40000,0xc40000,0xc40000,0xc40000,0xc40000,0xc40000,0xc40000,0xc40000},
  {0xc10340,0xc44a80,0xc10368,0xc010582,0x4a0106da,0xc105d2,0xc105ea,0xc106fa,0xc130f3,0x654100cd,0x1f810586,0xc105ce,0x6e8105ee,0xc105be,0xc0f0e7,0xc0c0f7,0xc40000,0xc40000,0xc40000,0xc40000,0xc40000,0xc40000,0xc40000,0xc40000},
  {0xc103d8,0xc44cc0,0xc040c1,0xc103b8,0x140106ca,0x5f010662,0xc106a2,0xc106ea,0xc1d0f3,0xc080fb,0xe8100d5,0x2381060e,0x5881061e,0xc10636,0xc106fe,0xc120ff,0xc40000,0xc40000,0xc40000,0xc40000,0xc40000,0xc40000,0xc40000,0xc40000},
  {0xc10080,0xc441c0,0xc04001,0xc10142,0x3d0100d2,0xc101a2,0xc101ba,0xc12023,0x2540d02b,0x4340c03b,0x72410015,0x2681014e,0xc1011e,0xc100ee,0xc101a6,0xc0a027,0xc0a03f,0xc40000,0xc40000,0xc40000,0xc40000,0xc40000,0xc40000,0xc40000},
  {0xc10180,0xc44500,0xc101f8,0xd010302,0x4b0102d2,0x7801c043,0x8420063,0xc080f3,0x6241004d,0x1e809065,0x218100f5,0xd6810366,0xc102f6,0xc2006f,0xc40000,0xc40000,0xc40000,0xc40000,0xc40000,0xc40000,0xc40000,0xc40000,0xc40000,0xc40000},
  {0xc10140,0xc44380,0xc10120,0xe010342,0x4c01035a,0xc1022a,0xc1026a,0xc1e06b,0x4540c07b,0xc10134,0x3581006d,0x458101de,0x7c810276,0xc10376,0xc15077,0xc40000,0xc40000,0xc40000,0xc40000,0xc40000,0xc40000,0xc40000,0xc40000,0xc40000},
  {0xc10240,0xc44800,0xe10230,0xc10502,0x4d010392,0xc1041a,0xc103a2,0xc1209b,0x2040c0ab,0x4441025c,0xd810274,0x2581040e,0xc103de,0x7f8103f6,0xc10526,0xc130bf,0xc40000,0xc40000,0xc40000,0xc40000,0xc40000,0xc40000,0xc40000,0xc40000},
  {0xc10298,0xc448c0,0xc102e8,0xf010442,0x4e0104da,0xc10522,0xc104b2,0xc1c0a3,0x4c41029c,0x706102b4,0x1981044e,0x5a8100bd,0x6a810536,0xc1052e,0xc160b7,0xc40000,0xc40000,0xc40000,0xc40000,0xc40000,0xc40000,0xc40000,0xc40000,0xc40000},
  {0xc10300,0xe10330,0xc44dc0,0xc100e9,0xb401055a,0xc105a2,0xc105b2,0xc106f2,0xc0b0eb,0x4d61035c,0x5a61032c,0xc1058e,0xc1059e,0x7781056e,0xc105de,0xc170f7,0xc40000,0xc40000,0xc40000,0xc40000,0xc40000,0xc40000,0xc40000,0xc40000},
  {0xc103c8,0xe103a0,0xc04081,0x2010642,0x5c010652,0xc10622,0xb41d0d3,0x3c8103c4,0x4ba1039c,0xe103b4,0xe103bc,0xc10616,0xc1062e,0xc1063e,0xc1a0d7,0xc40000,0xc40000,0xc40000,0xc40000,0xc40000,0xc40000,0xc40000,0xc40000,0xc40000},
  {0xc100c0,0xc442c0,0xc100b8,0x192100f8,0x2301014a,0xc100e2,0xc100ea,0xc19023,0x336100cc,0x694100e4,0x3aa100bc,0xc10116,0xc101ae,0xc1017e,0xc1d01f,0xc40000,0xc40000,0xc40000,0xc40000,0xc40000,0xc40000,0xc40000,0xc40000,0xc40000},
  {0xc10188,0xe101a8,0xc080c9,0x18010071,0x400102a2,0xc102ea,0xc10332,0x11410184,0x2f6101d4,0x3a6101a4,0x6a410346,0xc102ce,0xc102de,0xc1036e,0xc15047,0xc0a07f,0xc40000,0xc40000,0xc40000,0xc40000,0xc40000,0xc40000,0xc40000,0xc40000},
  {0xc10100,0xc44480,0xc10178,0xc10242,0x4f010212,0xc101e2,0xe41f05b,0x2b61014c,0x3b61015c,0x6b61012c,0x7761017c,0x1a81021e,0x7481022e,0xc1026e,0xc19077,0xc40000,0xc40000,0xc40000,0xc40000,0xc40000,0xc40000,0xc40000,0xc40000,0xc40000},
  {0xc10210,0x2d210250,0xe10238,0xc1038a,0x6b0103e2,0x7001d08b,0x19410204,0xe1024c,0xe10224,0xe1023c,0xc040a5,0x4e8103ce,0xc103ee,0xc10416,0xc1a0af,0xc40000,0xc40000,0xc40000,0xc40000,0xc40000,0xc40000,0xc40000,0xc40000,0xc40000},
  {0xc10280,0xc44980,0xc102e0,0xc104c2,0x5401051a,0xc104e2,0xd41e093,0xc10284,0xc102dc,0xc102ec,0xc0c0a5,0x3e810456,0x6b8104ae,0xc104f6,0xc1b087,0xc40000,0xc40000,0xc40000,0xc40000,0xc40000,0xc40000,0xc40000,0xc40000,0xc40000},
  {0xc10310,0xc44b40,0xc10360,0xc106c2,0x550105ca,0xc10562,0xc105da,0xc1057a,0xc10304,0xc1031c,0xc10334,0x278100ed,0x438106de,0xc10576,0xc105b6,0xc150f7,0xc40000,0xc40000,0xc40000,0xc40000,0xc40000,0xc40000,0xc40000,0xc40000},
  {0xc10380,0xc44c80,0xc040c1,0x1e2103b0,0xc1068a,0x600106d2,0xc1066a,0xc1063a,0xc0f0db,0x3d610394,0x6c4103ac,0x3ba103fc,0xc10696,0xc10666,0xc10676,0xc0f0cf,0xc0e0ff,0xc40000,0xc40000,0xc40000,0xc40000,0xc40000,0xc40000,0xc40000},
  {0xc10090,0xc44200,0xc100e8,0x1a044340,0xc10031,0x39010152,0xc10122,0xc101b2,0x17410084,0xc11033,0x5c40703b,0xc100b4,0x2d810025,0x468100de,0x79810176,0xc101b6,0xc16027,0xc40000,0xc40000,0xc40000,0xc40000,0xc40000,0xc40000,0xc40000},
  {0xc101c8,0xc101e8,0xc10061,0x2601034a,0x6f0102aa,0x7f01036a,0xc102fa,0xe101cc,0xc1019c,0xc101f4,0x38a101fc,0x4c810316,0xc102ee,0xc1030e,0xc0c0cf,0xc0e07f,0xc40000,0xc40000,0xc40000,0xc40000,0xc40000,0xc40000,0xc40000,0xc40000},
  {0xc10098,0xc44300,0xc100f0,0xc10182,0x56010192,0xc1011a,0xf420013,0x2a414033,0x636100a4,0x784100c6,0xc100d6,0x628100e6,0xc10126,0xc1c00f,0xc40000,0xc40000,0xc40000,0xc40000,0xc40000,0xc40000,0xc40000,0xc40000,0xc40000,0xc40000},
  {0xc101c0,0xc44540,0xc101b8,0xc102c2,0x57010312,0xc10362,0xc10372,0xc09053,0x15411063,0xc10194,0xc0508d,0x981005d,0x3381028e,0x5e81031e,0xc102fe,0xc0f05f,0xc1007f,0xc40000,0xc40000,0xc40000,0xc40000,0xc40000,0xc40000,0xc40000},
};
uint8_t kSeq[NPAIR][KMAX] = {
  {0,1,2,3,0,1,2,3,4,5,6,7,8,9,10,11,12,13,14,15,0,1,2,3,64,67,72,78,76,70,66,74,64,66,76,78,65,67,77,79,68,70,69,71,72,74,73,75,4,6,0,2,5,7,1,3,12,14,8,10,13,15,9,11,4,6,8,10,0,2,5,7,9,11,12,14,1,3,13,15,88,89,94,95,116,117,118,119,106,107,78,79,82,83,112,113,84,85,102,103,98,99,72,73,72,73,80,81,98,99,74,75,110,111,112,113,86,87,92,93,78,79,64,65,66,67,84,68,70,69,71,76,78,72,74,64,66,77,79,73,75,65,67,68,70,72,74,69,71,64,66,76,78,73,75,65,67,77,79,8,10,0,2,9,11,12,14,1,3,4,6,13,15,5,7,12,14,8,10,4,6,0,2,13,15,9,11,5,7,1,3,12,14,8,10,13,15,4,6,9,11,5,7,0,2,1,3,200,202,73,75,196,198,192,194,204,206,197,199,193,195,205,207,71,66,67,112,113,98,99,86,87,110,111,114,115,88,89,118,119,196,197,230,0,0,0,0,0,0,0,0,0,0,0,0,0,0,0,0,0,0,0,0,0,0,0,0,0,0,0,0,0,0,0,0,0,0,0,0,0,0,0,0,0,0,0,0,0,0,0,0,0,0,0,0,0},
  {0,1,2,3,0,1,2,3,4,5,6,7,8,9,10,11,12,13,14,15,0,1,2,3,77,69,73,79,65,68,75,71,70,64,76,66,74,72,79,71,78,67,69,65,75,77,68,73,12,14,8,10,13,15,9,11,0,2,4,6,1,3,5,7,76,78,72,74,77,79,73,75,64,66,68,70,65,67,69,71,4,6,12,14,8,10,0,2,5,7,13,15,9,11,1,3,114,115,100,101,74,75,116,117,118,0,2,4,6,8,10,1,3,5,7,12,14,9,11,13,15,76,78,68,70,77,79,64,66,72,74,69,71,65,67,73,75,12,14,4,6,0,2,13,15,5,7,8,10,1,3,9,11,8,10,12,14,0,2,9,11,13,15,1,3,4,6,5,7,8,10,9,11,4,6,0,2,12,14,5,7,1,3,13,15,4,6,12,14,8,10,5,7,13,15,9,11,0,2,1,3,12,14,8,10,13,15,4,6,9,11,5,7,128,130,1,3,99,64,65,80,81,92,93,108,109,106,107,70,71,66,67,90,91,88,89,82,83,224,225,232,233,230,231,0,0,0,0,0,0,0,0,0,0,0,0,0,0,0,0,0,0,0,0,0,0,0,0,0,0,0,0,0,0,0,0,0,0,0,0,0,0,0,0,0,0,0,0,0,0,0,0,0,0,0,0},
  {64,65,66,67,68,69,70,71,72,73,74,75,76,77,78,79,0,1,2,3,79,75,77,73,0,2,12,14,1,3,13,15,4,6,5,7,8,10,9,11,64,66,72,74,65,67,73,75,76,78,68,70,77,79,69,71,4,6,12,14,8,10,0,2,5,7,13,15,9,11,1,3,0,2,8,10,4,6,12,14,1,3,9,11,5,7,13,15,83,98,99,108,109,92,93,78,79,84,85,100,101,66,67,74,75,88,66,67,84,85,68,69,90,91,104,105,70,71,210,211,228,229,106,107,222,71,72,69,66,64,78,74,77,76,75,73,64,71,78,77,69,72,75,70,74,79,76,73,68,67,66,65,64,71,78,74,77,70,73,69,66,72,76,79,68,65,67,75,4,6,5,7,8,10,12,14,9,11,13,15,0,2,1,3,4,6,12,14,8,10,5,7,13,15,0,2,9,11,1,3,106,107,104,105,92,93,88,89,72,73,90,91,100,101,78,79,116,117,64,65,118,119,208,209,94,95,76,77,240,241,0,0,0,0,0,0,0,0,0,0,0,0,0,0,0,0,0,0,0,0,0,0,0,0,0,0,0,0,0,0,0,0,0,0,0,0,0,0,0,0,0,0,0,0,0,0,0,0,0,0,0,0,0,0,0,0,0,0,0,0,0,0,0,0,0,0},
  {0,1,2,3,4,5,6,7,8,9,10,11,12,13,14,15,0,1,2,3,66,74,68,64,0,2,12,14,1,3,13,15,4,6,5,7,8,10,9,11,64,66,72,74,65,67,73,75,76,78,68,70,77,79,69,71,4,6,0,2,5,7,1,3,12,14,8,10,13,15,9,11,4,6,12,14,8,10,0,2,5,7,13,15,9,11,1,3,92,93,64,65,100,101,96,97,89,76,77,96,97,86,87,72,73,116,117,110,111,4,6,5,7,12,14,8,10,0,2,13,15,9,11,1,3,0,2,1,3,4,6,8,10,12,14,5,7,9,11,13,15,8,10,12,14,0,2,9,11,13,15,1,3,4,6,5,7,8,10,0,2,9,11,12,14,1,3,4,6,13,15,5,7,4,6,5,7,8,10,12,14,9,11,13,15,0,2,1,3,4,6,12,14,8,10,5,7,13,15,0,2,9,11,1,3,77,112,113,110,111,82,83,70,71,68,69,102,103,108,80,81,66,67,90,91,96,97,242,243,202,203,70,199,238,239,0,0,0,0,0,0,0,0,0,0,0,0,0,0,0,0,0,0,0,0,0,0,0,0,0,0,0,0,0,0,0,0,0,0,0,0,0,0,0,0,0,0,0,0,0,0,0,0,0,0,0,0,0,0,0,0,0,0,0,0,0},
  {64,65,66,67,68,69,70,71,72,73,74,75,76,77,78,79,64,65,66,67,68,69,70,71,72,73,74,75,76,77,78,79,64,65,66,67,68,69,70,71,72,73,74,75,76,77,78,79,198,69,194,199,204,12,14,8,10,13,15,9,11,0,2,4,6,1,3,5,7,70,71,64,65,98,99,92,93,78,79,112,113,94,95,72,73,80,81,84,85,114,115,116,117,106,107,66,8,10,0,2,9,11,1,3,12,14,13,15,4,6,5,7,0,2,4,6,8,10,1,3,5,7,12,14,9,11,13,15,4,6,5,7,0,2,8,10,12,14,1,3,9,11,13,15,68,70,69,71,64,66,72,74,76,78,65,67,73,75,77,79,132,134,128,130,133,135,129,131,136,138,140,142,137,139,141,143,8,10,0,2,9,11,12,14,1,3,4,6,13,15,5,7,12,14,8,10,4,6,0,2,13,15,9,11,5,7,1,3,4,6,12,14,8,10,5,7,13,15,0,2,137,139,1,3,92,93,108,109,98,99,80,81,100,101,70,71,116,117,96,97,74,75,64,65,112,113,82,83,234,235,212,213,0,0,0,0,0,0,0,0,0,0,0,0,0,0,0,0,0,0,0,0,0,0,0,0,0,0,0,0,0,0,0,0,0,0,0,0,0,0,0,0,0,0,0,0},
  {0,1,2,3,0,1,2,3,0,1,2,3,4,5,6,7,8,9,10,11,12,13,14,15,0,1,2,3,4,5,6,7,8,9,10,11,12,13,14,15,70,64,76,66,0,2,8,10,1,3,9,11,12,14,4,6,13,15,5,7,4,6,0,2,5,7,1,3,12,14,8,10,13,15,9,11,0,2,8,10,4,6,12,14,1,3,9,11,5,7,13,15,93,78,79,84,85,100,101,66,67,74,75,88,89,76,77,96,97,86,87,72,73,116,117,110,111,84,85,88,89,114,115,110,66,71,70,77,69,73,72,64,65,78,67,75,79,74,76,68,12,14,4,6,0,2,13,15,5,7,8,10,1,3,9,11,132,134,128,130,133,135,129,131,136,138,140,142,137,139,141,143,8,10,9,11,4,6,0,2,12,14,5,7,1,3,13,15,4,6,12,14,8,10,5,7,13,15,9,11,0,2,1,3,140,142,136,138,141,143,132,134,137,139,133,135,128,130,129,131,72,73,86,87,102,103,90,91,118,119,68,69,206,207,114,115,66,67,110,111,94,95,88,217,204,205,0,0,0,0,0,0,0,0,0,0,0,0,0,0,0,0,0,0,0,0,0,0,0,0,0,0,0,0,0,0,0,0,0,0,0,0,0,0,0,0,0,0,0,0,0,0,0,0,0,0},
  {0,1,2,3,0,1,2,3,0,1,2,3,4,5,6,7,8,9,10,11,12,13,14,15,0,1,2,3,0,1,2,3,4,5,6,7,8,9,10,11,12,13,14,15,0,2,8,10,1,3,9,11,12,14,4,6,13,15,5,7,4,6,0,2,5,7,1,3,12,14,8,10,13,15,9,11,0,2,8,10,4,6,12,14,1,3,9,11,5,7,13,15,4,6,12,14,8,10,0,2,5,7,13,15,9,11,1,3,8,10,0,2,9,11,1,3,12,14,13,15,4,6,5,7,204,205,236,237,240,241,210,211,226,227,228,229,192,193,200,201,208,209,202,203,212,213,214,215,8,10,12,14,0,2,9,11,13,15,1,3,4,6,5,7,78,74,77,71,70,64,66,69,79,200,75,68,204,73,195,65,4,6,5,7,8,10,12,14,9,11,13,15,0,2,1,3,132,134,140,142,136,138,133,135,141,143,128,130,137,139,129,131,99,102,103,86,87,104,105,78,79,118,119,114,115,88,89,112,113,100,101,64,65,84,85,94,95,224,225,82,83,196,197,0,0,0,0,0,0,0,0,0,0,0,0,0,0,0,0,0,0,0,0,0,0,0,0,0,0,0,0,0,0,0,0,0,0,0,0,0,0,0,0,0,0,0,0,0,0,0,0,0,0,0,0,0},
  {0,1,2,3,0,1,2,3,4,5,6,7,8,9,10,11,12,13,14,15,66,74,68,64,64,74,76,66,68,70,65,72,79,67,69,71,78,75,77,73,0,2,8,10,1,3,9,11,12,14,4,6,13,15,5,7,12,14,8,10,13,15,9,11,0,2,4,6,1,3,5,7,4,6,12,14,8,10,0,2,5,7,13,15,9,11,1,3,0,2,8,10,4,6,12,14,1,3,9,11,5,7,13,15,99,100,101,90,91,70,71,76,77,68,69,110,111,82,83,74,75,96,97,118,119,104,105,238,239,242,243,232,233,218,219,220,221,230,231,196,197,8,10,12,14,0,2,9,11,13,15,1,3,4,6,5,7,8,10,0,2,9,11,12,14,1,3,4,6,13,15,5,7,4,6,5,7,8,10,12,14,9,11,13,15,0,2,1,3,4,6,140,142,136,138,133,135,141,143,128,130,137,139,129,131,80,81,96,97,92,93,108,109,70,71,82,83,100,101,78,79,74,75,114,115,94,95,118,119,200,201,192,193,240,241,226,0,0,0,0,0,0,0,0,0,0,0,0,0,0,0,0,0,0,0,0,0,0,0,0,0,0,0,0,0,0,0,0,0,0,0,0,0,0,0,0,0,0,0,0,0,0,0,0,0,0,0,0,0,0,0,0,0,0,0,0},
  {0,1,2,3,0,1,2,3,4,5,6,7,8,9,10,11,12,13,14,15,69,76,67,65,128,129,130,131,132,133,134,135,136,137,138,139,140,141,142,143,0,2,8,10,1,3,9,11,12,14,4,6,13,15,5,7,4,6,8,10,0,2,5,7,9,11,12,14,1,3,13,15,88,89,94,95,116,117,118,119,106,107,78,79,82,83,112,113,84,85,102,103,98,99,72,73,92,93,64,65,100,101,0,2,4,6,8,10,1,3,5,7,12,14,9,11,13,15,12,14,4,6,13,15,0,2,8,10,5,7,1,3,9,11,222,223,244,245,12,14,4,6,0,2,13,15,5,7,8,10,1,3,9,11,132,134,128,130,133,135,129,131,136,138,140,142,137,139,141,143,8,10,9,11,4,6,0,2,12,14,5,7,1,3,13,15,4,6,5,7,8,10,12,14,9,11,13,15,0,2,1,3,12,14,8,10,13,15,4,6,9,11,5,7,0,2,1,3,65,112,113,98,99,88,89,86,87,84,85,90,91,106,235,68,69,104,105,76,77,116,117,110,111,102,103,194,195,0,0,0,0,0,0,0,0,0,0,0,0,0,0,0,0,0,0,0,0,0,0,0,0,0,0,0,0,0,0,0,0,0,0,0,0,0,0,0,0,0,0,0,0,0,0,0,0,0},
  {0,1,2,3,0,1,2,3,4,5,6,7,8,9,10,11,12,13,14,15,0,1,2,3,64,74,76,66,68,70,65,72,79,67,69,71,78,75,77,73,0,2,8,10,1,3,9,11,12,14,4,6,13,15,5,7,12,14,8,10,13,15,9,11,0,2,4,6,1,3,5,7,96,97,82,83,74,75,110,111,76,77,88,89,118,119,68,69,100,101,104,105,102,103,90,91,8,10,0,2,9,11,1,3,12,14,13,15,4,6,5,7,12,14,4,6,13,15,0,2,8,10,5,7,1,3,9,11,4,6,5,7,0,2,8,10,12,14,1,3,9,11,13,15,4,6,8,10,5,7,0,2,12,14,9,11,1,3,13,15,77,69,78,72,76,68,66,73,79,67,75,65,8,10,9,11,4,6,0,2,12,14,5,7,1,3,13,15,4,6,12,14,8,10,5,7,13,15,9,11,0,2,1,3,12,14,8,10,132,134,0,2,141,143,9,11,133,135,129,131,64,65,80,81,92,93,108,109,106,107,70,71,66,67,90,91,88,89,82,83,96,97,232,233,230,231,0,0,0,0,0,0,0,0,0,0,0,0,0,0,0,0,0,0,0,0,0,0,0,0,0,0,0,0,0,0,0,0,0,0,0,0,0,0,0,0,0,0,0,0,0,0,0,0,0,0},
  {64,65,66,67,68,69,70,71,72,73,74,75,76,77,78,79,0,1,2,3,4,5,6,7,8,9,10,11,12,13,14,15,64,74,76,66,68,70,65,72,79,67,69,71,78,75,77,73,0,2,8,10,1,3,9,11,12,14,4,6,13,15,5,7,4,6,0,2,5,7,1,3,12,14,8,10,13,15,9,11,114,115,76,77,70,71,86,87,90,91,74,75,66,67,68,69,80,81,108,109,110,111,104,105,84,85,88,89,114,115,110,111,98,99,66,67,94,85,68,69,90,91,104,105,70,71,210,211,100,101,234,235,4,6,5,7,0,2,8,10,12,14,1,3,9,11,13,15,8,10,12,14,0,2,9,11,13,15,1,3,4,6,5,7,8,10,0,2,9,11,12,14,1,3,4,6,13,15,5,7,4,6,5,7,8,10,12,14,9,11,13,15,0,2,1,3,4,6,12,14,8,10,133,135,13,15,0,2,137,139,1,3,99,102,103,86,87,104,105,78,79,118,119,114,115,88,89,112,113,100,101,64,65,84,85,94,95,224,225,210,211,196,197,0,0,0,0,0,0,0,0,0,0,0,0,0,0,0,0,0,0,0,0,0,0,0,0,0,0,0,0,0,0,0,0,0,0,0,0,0,0,0,0,0,0,0,0,0,0,0,0,0,0,0,0,0},
  {0,1,2,3,4,5,6,7,8,9,10,11,12,13,14,15,0,1,2,3,4,5,6,7,8,9,10,11,12,13,14,15,0,1,2,3,0,1,2,3,0,1,2,3,0,2,8,10,1,3,9,11,12,14,4,6,13,15,5,7,4,6,8,10,0,2,5,7,9,11,12,14,1,3,13,15,0,2,8,10,4,6,12,14,1,3,9,11,5,7,13,15,72,73,92,93,64,65,100,101,96,97,114,115,76,77,0,2,4,6,8,10,1,3,5,7,12,14,9,11,13,15,204,205,108,109,112,113,210,211,226,227,228,229,192,193,200,201,208,209,202,203,212,213,214,71,69,72,78,64,77,75,74,79,73,67,76,70,68,66,65,68,66,73,79,67,75,65,78,74,77,71,70,64,194,69,207,200,75,196,204,73,195,65,4,6,5,7,8,10,12,14,9,11,13,15,0,2,1,3,12,14,8,10,13,15,4,6,9,11,5,7,0,2,1,3,65,112,113,98,99,88,89,86,87,84,85,90,91,106,107,68,69,104,105,76,77,116,117,238,239,102,103,194,195,0,0,0,0,0,0,0,0,0,0,0,0,0,0,0,0,0,0,0,0,0,0,0,0,0,0,0,0,0,0,0,0,0,0,0,0,0,0,0,0,0,0,0,0,0,0,0,0,0,0,0},
  {0,1,2,3,4,5,6,7,8,9,10,11,12,13,14,15,0,1,2,3,4,5,6,7,8,9,10,11,12,13,14,15,128,129,130,131,132,133,134,135,136,137,138,139,140,141,142,143,192,193,194,195,196,197,198,199,200,201,202,203,204,205,206,207,4,6,8,10,0,2,5,7,9,11,12,14,1,3,13,15,0,2,8,10,4,6,12,14,1,3,9,11,5,7,13,15,64,65,70,71,80,81,112,113,90,91,102,103,118,119,104,105,114,115,106,107,94,95,68,69,82,12,14,4,6,13,15,0,2,8,10,5,7,1,3,9,11,0,2,1,3,4,6,8,10,12,14,5,7,9,11,13,15,68,70,72,74,69,71,64,66,76,78,73,75,65,67,77,79,64,71,78,74,77,70,73,69,66,72,76,79,68,65,67,75,4,6,5,7,8,10,12,14,9,11,13,15,0,2,1,3,4,6,12,14,8,10,5,7,13,15,9,11,0,2,1,3,204,206,200,202,196,198,192,194,205,207,201,203,197,199,193,195,78,79,106,107,86,87,94,95,76,77,220,221,72,73,98,227,212,213,0,0,0,0,0,0,0,0,0,0,0,0,0,0,0,0,0,0,0,0,0,0,0,0,0,0,0,0,0,0,0,0,0,0,0,0,0,0,0,0,0,0,0,0,0},
  {0,1,2,3,0,1,2,3,0,1,2,3,4,5,6,7,8,9,10,11,12,13,14,15,64,67,72,77,69,73,78,76,70,66,74,79,65,68,75,71,0,2,8,10,1,3,9,11,12,14,4,6,13,15,5,7,12,14,8,10,13,15,9,11,0,2,4,6,1,3,5,7,4,6,8,10,0,2,5,7,9,11,12,14,1,3,13,15,8,10,0,2,9,11,1,3,12,14,13,15,4,6,5,7,78,79,64,65,66,67,84,85,68,69,90,91,104,105,70,71,210,211,100,101,106,107,222,223,66,71,70,77,69,73,72,64,65,78,67,75,79,74,76,68,8,10,12,14,0,2,9,11,13,15,1,3,4,6,5,7,8,10,0,2,9,11,12,14,1,3,4,6,13,15,5,7,12,14,8,10,4,6,0,2,13,15,9,11,5,7,1,3,4,6,12,14,8,10,5,7,141,143,0,2,137,139,1,3,92,93,108,109,98,99,80,81,100,101,70,71,116,117,96,97,74,75,64,65,112,113,82,83,106,107,212,213,232,233,0,0,0,0,0,0,0,0,0,0,0,0,0,0,0,0,0,0,0,0,0,0,0,0,0,0,0,0,0,0,0,0,0,0,0,0,0,0,0,0,0,0,0,0,0,0,0,0,0,0,0,0,0,0,0,0,0,0},
  {0,1,2,3,0,1,2,3,0,1,2,3,4,5,6,7,8,9,10,11,12,13,14,15,64,67,72,77,69,73,78,76,70,64,66,76,78,65,67,77,79,68,70,69,71,72,74,73,75,12,14,8,10,13,15,9,11,0,2,4,6,1,3,5,7,76,78,72,74,77,79,73,75,64,66,68,70,65,67,69,71,0,2,8,10,4,6,12,14,1,3,9,11,5,7,13,15,84,85,88,89,114,115,110,111,98,99,66,67,94,95,70,71,76,77,106,107,96,97,64,65,78,79,90,91,4,6,5,7,0,2,8,10,12,14,1,3,9,11,13,15,4,6,8,10,5,7,0,2,12,14,9,11,1,3,13,15,132,134,128,130,133,135,129,131,136,138,140,142,137,139,141,143,12,14,8,10,4,6,0,2,13,15,9,11,5,7,1,3,12,14,8,10,4,6,0,2,13,15,9,11,5,7,1,3,12,14,8,10,13,15,132,134,9,11,133,135,128,130,129,131,99,88,89,86,87,84,85,90,91,234,235,68,69,104,105,76,77,116,117,110,111,102,103,194,195,0,0,0,0,0,0,0,0,0,0,0,0,0,0,0,0,0,0,0,0,0,0,0,0,0,0,0,0,0,0,0,0,0,0,0,0,0,0,0,0,0,0,0,0,0,0,0,0,0,0},
  {0,1,2,3,0,1,2,3,0,1,2,3,4,5,6,7,8,9,10,11,12,13,14,15,79,75,77,73,128,129,130,131,132,133,134,135,136,137,138,139,140,141,142,143,0,2,8,10,1,3,9,11,12,14,4,6,13,15,5,7,4,6,8,10,0,2,5,7,9,11,12,14,1,3,13,15,4,6,12,14,8,10,0,2,5,7,13,15,9,11,1,3,8,10,0,2,9,11,1,3,12,14,13,15,4,6,5,7,8,10,0,2,9,11,1,3,12,14,13,15,4,6,5,7,4,6,5,7,12,14,8,10,0,2,13,15,9,11,1,3,12,14,4,6,0,2,13,15,5,7,8,10,1,3,9,11,8,10,12,14,0,2,9,11,13,15,1,3,4,6,5,7,8,10,9,11,4,6,0,2,12,14,5,7,1,3,13,15,4,6,5,7,8,10,12,14,9,11,13,15,0,2,1,3,4,6,12,14,8,10,5,7,13,15,0,2,9,11,1,3,109,86,87,114,115,98,99,66,67,84,85,96,97,74,75,102,103,80,81,96,97,76,77,218,219,236,237,0,0,0,0,0,0,0,0,0,0,0,0,0,0,0,0,0,0,0,0,0,0,0,0,0,0,0,0,0,0,0,0,0,0,0,0,0,0,0,0,0,0,0,0,0,0,0,0,0},
  {0,1,2,3,0,1,2,3,0,1,2,3,4,5,6,7,8,9,10,11,12,13,14,15,72,78,70,71,66,74,68,70,66,74,79,65,68,75,71,74,72,79,71,78,67,69,65,75,77,68,73,12,14,8,10,13,15,9,11,0,2,4,6,1,3,5,7,4,6,12,14,8,10,0,2,5,7,13,15,9,11,1,3,4,6,8,10,0,2,5,7,9,11,12,14,1,3,13,15,68,69,82,83,98,99,108,109,92,93,78,79,84,85,100,101,66,67,74,75,86,87,92,93,118,119,68,69,216,217,198,199,206,207,246,247,194,195,238,239,242,243,232,233,8,10,12,14,0,2,9,11,13,15,1,3,4,6,5,7,8,10,0,2,9,11,12,14,1,3,4,6,13,15,5,7,4,6,5,7,8,10,12,14,9,11,13,15,0,2,1,3,132,134,140,142,136,138,133,135,141,143,128,130,137,139,129,131,106,107,104,105,92,93,88,89,72,73,90,91,100,101,78,79,116,117,64,65,118,119,208,209,94,95,76,77,240,241,238,239,0,0,0,0,0,0,0,0,0,0,0,0,0,0,0,0,0,0,0,0,0,0,0,0,0,0,0,0,0,0,0,0,0,0,0,0,0,0,0,0,0,0,0,0,0,0,0,0,0,0,0,0,0,0,0,0,0},
  {0,1,2,3,0,1,2,3,0,1,2,3,4,5,6,7,8,9,10,11,12,13,14,15,0,1,2,3,0,1,2,3,4,5,6,7,8,9,10,11,12,13,14,15,76,69,70,72,74,66,71,75,67,77,68,73,79,206,64,65,12,14,8,10,13,15,9,11,0,2,4,6,1,3,5,7,0,2,8,10,4,6,12,14,1,3,9,11,5,7,13,15,0,2,8,10,4,6,12,14,1,3,9,11,5,7,13,15,8,10,0,2,9,11,1,3,12,14,13,15,4,6,5,7,12,14,4,6,13,15,0,2,8,10,5,7,1,3,9,11,0,2,1,3,4,6,8,10,12,14,5,7,9,11,13,15,8,10,12,14,0,2,9,11,13,15,1,3,4,6,5,7,8,10,0,2,9,11,12,14,1,3,4,6,13,15,5,7,4,6,5,7,8,10,12,14,9,11,13,15,0,2,1,3,4,6,140,142,136,138,5,7,141,143,0,2,137,139,129,131,75,98,99,66,67,80,81,92,93,114,115,112,113,88,89,110,111,82,83,68,69,104,105,108,109,102,103,244,245,0,0,0,0,0,0,0,0,0,0,0,0,0,0,0,0,0,0,0,0,0,0,0,0,0,0,0,0,0,0,0,0,0,0,0,0,0,0,0,0,0,0,0,0,0,0,0},
  {0,1,2,3,0,1,2,3,4,5,6,7,8,9,10,11,12,13,14,15,69,76,67,65,0,2,12,14,1,3,13,15,4,6,5,7,8,10,9,11,12,14,8,10,13,15,9,11,0,2,4,6,1,3,5,7,67,108,109,86,87,96,97,82,83,74,75,110,111,76,77,88,89,118,119,68,69,100,101,104,105,102,103,90,91,8,10,0,2,9,11,1,3,12,14,13,15,4,6,5,7,0,2,4,6,8,10,1,3,5,7,12,14,9,11,13,15,4,6,5,7,12,14,8,10,0,2,13,15,9,11,1,3,12,14,4,6,0,2,13,15,5,7,8,10,1,3,9,11,132,134,128,130,133,135,129,131,136,138,140,142,137,139,141,143,8,10,9,11,4,6,0,2,12,14,5,7,1,3,13,15,4,6,12,14,8,10,5,7,13,15,9,11,0,2,1,3,12,14,8,10,4,6,0,2,13,15,9,11,5,7,1,3,80,81,96,97,92,93,108,109,70,71,82,83,100,101,206,207,74,75,114,115,94,95,118,119,200,201,192,0,0,0,0,0,0,0,0,0,0,0,0,0,0,0,0,0,0,0,0,0,0,0,0,0,0,0,0,0,0,0,0,0,0,0,0,0,0,0,0,0,0,0,0,0,0,0,0,0,0,0,0,0,0,0,0},
  {0,1,2,3,0,1,2,3,4,5,6,7,8,9,10,11,12,13,14,15,64,79,75,77,73,69,76,67,65,64,74,76,66,68,70,65,72,79,67,69,71,78,75,77,73,12,14,8,10,13,15,9,11,0,2,4,6,1,3,5,7,4,6,12,14,8,10,0,2,5,7,13,15,9,11,1,3,76,77,88,89,106,107,78,79,96,97,108,109,114,115,100,101,74,75,116,117,118,119,82,83,112,113,98,72,73,80,81,98,99,74,75,110,111,112,113,86,87,92,93,4,6,5,7,0,2,8,10,12,14,1,3,9,11,13,15,12,14,4,6,0,2,13,15,5,7,8,10,1,3,9,11,8,10,12,14,0,2,9,11,13,15,1,3,4,6,5,7,8,10,9,11,4,6,0,2,12,14,5,7,1,3,13,15,4,6,5,7,8,10,12,14,9,11,13,15,0,2,1,3,132,134,133,135,136,138,140,142,137,139,141,143,128,130,129,131,90,91,106,107,92,93,116,117,72,73,76,77,108,109,110,111,208,209,70,71,66,67,202,203,226,0,0,0,0,0,0,0,0,0,0,0,0,0,0,0,0,0,0,0,0,0,0,0,0,0,0,0,0,0,0,0,0,0,0,0,0,0,0,0,0,0,0,0,0,0,0,0,0,0,0,0,0,0,0,0},
  {64,65,66,67,68,69,70,71,72,73,74,75,76,77,78,79,0,1,2,3,0,1,2,3,64,65,66,67,68,69,70,71,72,73,74,75,76,77,78,79,72,76,64,70,66,74,71,78,67,79,65,197,75,68,73,77,4,6,0,2,5,7,1,3,12,14,8,10,13,15,9,11,4,6,12,14,8,10,0,2,5,7,13,15,9,11,1,3,68,70,72,74,64,66,69,71,73,75,76,78,65,67,77,79,8,10,0,2,9,11,1,3,12,14,13,15,4,6,5,7,76,77,108,109,112,113,82,83,226,227,100,101,64,65,200,201,208,209,202,203,212,213,214,215,71,69,72,78,64,77,75,74,79,73,67,8,10,12,14,0,2,9,11,13,15,1,3,4,6,5,7,8,10,9,11,4,6,0,2,12,14,5,7,1,3,13,15,4,6,12,14,8,10,5,7,13,15,9,11,0,2,1,3,132,134,140,142,136,138,133,135,141,143,128,130,137,139,129,131,64,65,84,85,92,93,104,105,74,75,78,79,100,101,82,83,72,73,116,117,222,223,234,235,198,0,0,0,0,0,0,0,0,0,0,0,0,0,0,0,0,0,0,0,0,0,0,0,0,0,0,0,0,0,0,0,0,0,0,0,0,0,0,0,0,0,0,0,0,0,0,0,0,0,0,0,0},
  {0,1,2,3,4,5,6,7,8,9,10,11,12,13,14,15,0,1,2,3,192,193,194,195,196,197,198,199,200,201,202,203,204,205,206,207,64,66,76,78,65,67,77,79,68,70,69,71,72,74,73,75,4,6,0,2,5,7,1,3,12,14,8,10,13,15,9,11,4,6,8,10,0,2,5,7,9,11,12,14,1,3,13,15,0,2,8,10,4,6,12,14,1,3,9,11,5,7,13,15,8,10,0,2,9,11,1,3,12,14,13,15,4,6,5,7,64,66,68,70,72,74,65,67,69,71,76,78,73,75,77,79,68,70,69,71,76,78,72,74,64,66,77,79,73,75,65,67,64,71,78,77,69,72,75,70,74,79,76,73,68,67,66,65,8,10,0,2,9,11,12,14,1,3,4,6,13,15,5,7,4,6,5,7,8,10,12,14,9,11,13,15,0,2,1,3,132,134,140,142,136,138,133,135,141,143,128,130,137,139,129,131,106,107,104,105,92,93,88,89,72,73,90,91,100,101,78,79,84,85,80,81,66,67,90,91,96,97,242,243,202,203,198,199,0,0,0,0,0,0,0,0,0,0,0,0,0,0,0,0,0,0,0,0,0,0,0,0,0,0,0,0,0,0,0,0,0,0,0,0,0,0,0,0,0,0,0,0,0,0,0,0,0,0,0,0},
  {64,65,66,67,68,69,70,71,72,73,74,75,76,77,78,79,0,1,2,3,64,65,66,67,68,69,70,71,72,73,74,75,76,77,78,79,64,66,76,78,65,67,77,79,68,70,69,71,72,74,73,75,64,66,72,74,65,67,73,75,76,78,68,70,77,79,69,71,4,6,8,10,0,2,5,7,9,11,12,14,1,3,13,15,80,81,108,109,110,111,104,105,0,2,8,10,4,6,12,14,1,3,9,11,5,7,13,15,0,2,4,6,8,10,1,3,5,7,12,14,9,11,13,15,4,6,5,7,12,14,8,10,0,2,13,15,9,11,1,3,71,72,69,66,64,78,74,77,76,75,73,8,10,12,14,0,2,9,11,13,15,1,3,4,6,5,7,8,10,0,2,9,11,12,14,1,3,4,6,13,15,5,7,4,6,5,7,8,10,12,14,9,11,13,15,0,2,1,3,132,134,140,142,136,138,133,135,141,143,128,130,137,139,129,131,64,65,78,79,90,91,106,107,94,95,68,69,96,97,74,75,98,99,66,67,80,81,220,221,242,243,112,113,216,217,236,0,0,0,0,0,0,0,0,0,0,0,0,0,0,0,0,0,0,0,0,0,0,0,0,0,0,0,0,0,0,0,0,0,0,0,0,0,0,0,0,0,0,0,0,0,0,0,0,0,0},
  {64,65,66,67,68,69,70,71,72,73,74,75,76,77,78,79,0,1,2,3,0,1,2,3,4,5,6,7,8,9,10,11,12,13,14,15,0,1,2,3,76,69,70,72,74,66,71,75,67,77,68,73,79,78,64,65,4,6,0,2,5,7,1,3,12,14,8,10,13,15,9,11,0,2,8,10,4,6,12,14,1,3,9,11,5,7,13,15,108,109,114,115,100,101,74,75,116,117,118,119,82,83,112,113,98,99,102,103,68,69,110,111,104,105,0,2,4,6,8,10,1,3,5,7,12,14,9,11,13,15,4,6,5,7,12,14,8,10,0,2,13,15,9,11,1,3,64,66,65,67,68,70,72,74,76,78,69,71,73,75,77,79,132,134,128,130,133,135,129,131,136,138,140,142,137,139,141,143,8,10,9,11,4,6,0,2,12,14,5,7,1,3,13,15,4,6,5,7,8,10,12,14,9,11,13,15,0,2,1,3,4,6,12,14,8,10,5,7,13,15,0,2,9,11,1,3,105,72,73,86,87,102,103,90,91,118,119,68,69,78,79,114,115,66,67,110,111,94,95,216,217,204,205,0,0,0,0,0,0,0,0,0,0,0,0,0,0,0,0,0,0,0,0,0,0,0,0,0,0,0,0,0,0,0,0,0,0,0,0,0,0,0,0,0,0,0},
  {64,65,66,67,68,69,70,71,72,73,74,75,76,77,78,79,64,65,66,67,68,69,70,71,72,73,74,75,76,77,78,79,0,1,2,3,128,129,130,131,132,133,134,135,136,137,138,139,140,141,142,143,198,197,194,199,204,203,206,4,6,0,2,5,7,1,3,12,14,8,10,13,15,9,11,0,2,8,10,4,6,12,14,1,3,9,11,5,7,13,15,8,10,0,2,9,11,1,3,12,14,13,15,4,6,5,7,8,10,0,2,9,11,1,3,12,14,13,15,4,6,5,7,12,14,4,6,13,15,0,2,8,10,5,7,1,3,9,11,0,2,1,3,4,6,8,10,12,14,5,7,9,11,13,15,8,10,12,14,0,2,9,11,13,15,1,3,4,6,5,7,8,10,9,11,4,6,0,2,12,14,5,7,1,3,13,15,12,14,8,10,4,6,0,2,13,15,9,11,5,7,1,3,12,14,8,10,13,15,4,6,9,11,5,7,0,2,1,3,118,119,76,77,74,75,68,69,72,73,100,101,110,111,84,85,206,207,116,117,94,95,242,243,86,87,240,241,226,227,0,0,0,0,0,0,0,0,0,0,0,0,0,0,0,0,0,0,0,0,0,0,0,0,0,0,0,0,0,0,0,0,0,0,0,0,0,0,0,0,0,0,0,0,0,0,0},
  {64,65,66,67,68,69,70,71,72,73,74,75,76,77,78,79,0,1,2,3,4,5,6,7,8,9,10,11,12,13,14,15,0,1,2,3,64,66,76,78,65,67,77,79,68,70,69,71,72,74,73,75,4,6,0,2,5,7,1,3,12,14,8,10,13,15,9,11,4,6,12,14,8,10,0,2,5,7,13,15,9,11,1,3,97,108,109,114,115,100,101,74,75,116,117,118,119,82,83,112,113,98,99,102,103,68,69,110,111,104,105,114,115,102,103,98,99,100,101,90,91,70,71,76,77,68,69,110,193,200,201,208,209,202,203,212,213,214,215,222,223,244,245,234,235,224,225,8,10,12,14,0,2,9,11,13,15,1,3,4,6,5,7,8,10,0,2,9,11,12,14,1,3,4,6,13,15,5,7,4,6,12,14,8,10,5,7,13,15,9,11,0,2,1,3,4,6,5,7,8,10,140,142,9,11,13,15,0,2,1,3,90,91,106,107,92,93,116,117,72,73,76,77,108,109,110,111,80,81,70,71,66,67,74,75,98,99,102,103,214,215,0,0,0,0,0,0,0,0,0,0,0,0,0,0,0,0,0,0,0,0,0,0,0,0,0,0,0,0,0,0,0,0,0,0,0,0,0,0,0,0,0,0,0,0,0,0,0,0,0,0,0,0,0,0,0},
  {0,1,2,3,0,1,2,3,0,1,2,3,4,5,6,7,8,9,10,11,12,13,14,15,0,1,2,3,74,66,76,79,70,72,64,67,71,69,78,68,75,65,77,73,0,2,8,10,1,3,9,11,12,14,4,6,13,15,5,7,203,206,200,202,196,201,207,205,195,192,193,0,2,8,10,4,6,12,14,1,3,9,11,5,7,13,15,4,6,12,14,8,10,0,2,5,7,13,15,9,11,1,3,112,113,84,85,88,89,66,67,78,79,92,93,72,73,80,81,106,107,116,117,236,237,64,65,94,95,4,6,5,7,0,2,8,10,12,14,1,3,9,11,13,15,4,6,8,10,5,7,0,2,12,14,9,11,1,3,13,15,72,74,76,78,64,66,73,75,77,79,65,67,68,70,69,71,72,79,194,76,192,67,202,196,199,206,198,197,205,201,193,203,12,14,8,10,13,15,4,6,9,11,5,7,0,2,1,3,90,91,106,107,92,93,116,117,72,73,76,77,108,109,110,111,80,81,70,71,66,67,74,75,98,82,83,68,69,104,105,108,109,102,103,244,245,0,0,0,0,0,0,0,0,0,0,0,0,0,0,0,0,0,0,0,0,0,0,0,0,0,0,0,0,0,0,0,0,0,0,0,0,0,0,0,0,0,0,0,0,0,0,0,0,0,0},
  {0,1,2,3,0,1,2,3,4,5,6,7,8,9,10,11,12,13,14,15,0,1,2,3,74,66,76,79,70,72,64,67,71,69,78,68,75,65,77,73,0,2,8,10,1,3,9,11,12,14,4,6,13,15,5,7,4,6,0,2,5,7,1,3,12,14,8,10,13,15,9,11,202,196,201,207,205,195,192,193,90,91,70,71,72,73,66,67,64,65,84,85,92,93,80,81,86,87,94,95,84,85,88,89,114,115,110,111,98,99,66,67,94,95,70,71,76,77,106,107,96,97,64,65,215,222,223,244,245,234,235,224,225,216,217,198,199,206,4,6,8,10,5,7,0,2,12,14,9,11,1,3,13,15,132,134,128,130,133,135,129,131,136,138,140,142,137,139,141,143,72,79,194,76,192,67,202,196,199,206,198,197,205,201,193,203,12,14,8,10,13,15,4,6,9,11,5,7,0,2,1,3,4,6,12,14,136,138,5,7,13,15,128,130,137,139,129,131,80,81,92,93,108,109,106,107,70,71,66,67,90,91,88,89,82,83,224,225,232,233,230,231,0,0,0,0,0,0,0,0,0,0,0,0,0,0,0,0,0,0,0,0,0,0,0,0,0,0,0,0,0,0,0,0,0,0,0,0,0,0,0,0,0,0,0,0,0,0,0,0,0,0,0,0,0,0},
  {64,65,66,67,68,69,70,71,72,73,74,75,76,77,78,79,0,1,2,3,4,5,6,7,8,9,10,11,12,13,14,15,192,193,194,195,196,197,198,199,200,201,202,203,204,205,206,207,0,2,8,10,1,3,9,11,12,14,4,6,13,15,5,7,4,6,0,2,5,7,1,3,12,14,8,10,13,15,9,11,0,2,8,10,4,6,12,14,1,3,9,11,5,7,13,15,119,82,83,112,113,98,99,102,103,68,69,110,111,104,105,72,74,64,66,73,75,65,67,76,78,77,79,68,70,69,71,66,71,70,77,69,73,72,64,65,78,67,75,79,74,76,68,76,78,68,70,64,66,77,79,69,71,72,74,65,67,73,75,132,134,128,130,133,135,129,131,136,138,140,142,137,139,141,143,78,74,77,71,70,64,194,69,207,200,75,196,204,73,195,65,12,14,8,10,13,15,4,6,9,11,5,7,0,2,1,3,72,74,64,66,73,75,76,78,65,67,196,198,77,79,197,199,68,69,96,97,74,75,98,99,66,67,80,81,92,93,114,115,112,113,88,89,108,109,246,247,0,0,0,0,0,0,0,0,0,0,0,0,0,0,0,0,0,0,0,0,0,0,0,0,0,0,0,0,0,0,0,0,0,0,0,0,0,0,0,0,0,0,0,0,0,0,0,0,0},
  {0,1,2,3,4,5,6,7,8,9,10,11,12,13,14,15,64,65,66,67,68,69,70,71,72,73,74,75,76,77,78,79,0,1,2,3,72,76,64,70,66,74,71,78,67,79,65,197,75,68,73,77,12,14,8,10,13,15,9,11,0,2,4,6,1,3,5,7,108,109,86,87,96,97,82,83,74,75,110,111,76,77,88,89,118,119,68,69,100,101,104,105,102,103,90,91,8,10,0,2,9,11,1,3,12,14,13,15,4,6,5,7,76,77,68,69,110,111,82,83,74,75,96,97,118,119,104,105,4,6,5,7,0,2,8,10,12,14,1,3,9,11,13,15,4,6,8,10,5,7,0,2,12,14,9,11,1,3,13,15,8,10,0,2,9,11,12,14,1,3,4,6,13,15,5,7,12,14,8,10,4,6,0,2,13,15,9,11,5,7,1,3,12,14,8,10,13,15,132,134,9,11,5,7,0,2,1,3,136,138,9,11,132,134,0,2,140,142,133,135,129,131,141,143,79,74,75,114,115,94,95,118,119,72,73,64,208,209,96,97,76,77,218,219,236,237,0,0,0,0,0,0,0,0,0,0,0,0,0,0,0,0,0,0,0,0,0,0,0,0,0,0,0,0,0,0,0,0,0,0,0,0,0,0,0,0,0,0,0,0,0,0,0,0,0,0},
  {64,65,66,67,68,69,70,71,72,73,74,75,76,77,78,79,0,1,2,3,0,1,2,3,66,74,68,64,66,74,79,65,68,75,71,72,76,64,70,66,74,71,78,67,79,65,69,75,68,73,77,4,6,0,2,5,7,1,3,12,14,8,10,13,15,9,11,70,71,64,65,98,99,92,93,78,79,112,113,94,95,72,73,80,81,84,85,114,115,116,117,106,107,66,67,108,8,10,0,2,9,11,1,3,12,14,13,15,4,6,5,7,12,14,4,6,13,15,0,2,8,10,5,7,1,3,9,11,4,6,5,7,12,14,8,10,0,2,13,15,9,11,1,3,76,78,4,6,0,2,13,15,5,7,8,10,1,3,9,11,8,10,0,2,9,11,12,14,1,3,4,6,13,15,5,7,12,14,8,10,4,6,0,2,13,15,9,11,5,7,1,3,12,14,8,10,13,15,4,6,9,11,5,7,0,2,1,3,92,93,108,109,98,99,80,81,100,101,70,71,116,117,96,97,74,75,64,65,112,113,82,83,234,235,84,85,104,112,113,228,229,192,193,216,217,246,247,0,0,0,0,0,0,0,0,0,0,0,0,0,0,0,0,0,0,0,0,0,0,0,0,0,0,0,0,0,0,0,0,0,0,0,0,0,0,0,0,0,0,0,0,0,0,0,0,0},
  {0,1,2,3,4,5,6,7,8,9,10,11,12,13,14,15,0,1,2,3,0,1,2,3,4,5,6,7,8,9,10,11,12,13,14,15,74,66,76,79,70,72,64,67,71,69,78,68,75,65,77,73,198,194,204,206,200,202,196,192,4,6,0,2,5,7,1,3,12,14,8,10,13,15,9,11,4,6,8,10,0,2,5,7,9,11,12,14,1,3,13,15,8,10,0,2,9,11,1,3,12,14,13,15,4,6,5,7,88,89,76,77,96,97,86,87,72,73,116,117,110,111,12,14,4,6,13,15,0,2,8,10,5,7,1,3,9,11,219,220,221,230,231,196,197,4,6,8,10,5,7,0,2,12,14,9,11,1,3,13,15,8,10,0,2,9,11,12,14,1,3,4,6,13,15,5,7,12,14,8,10,4,6,0,2,13,15,9,11,5,7,1,3,12,14,8,10,13,15,4,6,9,11,5,7,0,2,1,3,12,14,8,10,132,134,0,2,13,15,9,11,133,135,1,3,64,65,84,85,92,93,104,105,74,75,206,207,100,101,82,83,200,201,116,117,222,223,0,0,0,0,0,0,0,0,0,0,0,0,0,0,0,0,0,0,0,0,0,0,0,0,0,0,0,0,0,0,0,0,0,0,0,0,0,0,0,0,0,0,0,0,0,0,0,0,0},
  {0,1,2,3,4,5,6,7,8,9,10,11,12,13,14,15,64,65,66,67,68,69,70,71,72,73,74,75,76,77,78,79,0,1,2,3,64,66,76,78,65,67,77,79,68,70,69,71,72,74,73,75,12,14,8,10,13,15,9,11,0,2,4,6,1,3,5,7,4,6,12,14,8,10,0,2,5,7,13,15,9,11,1,3,0,2,8,10,4,6,12,14,1,3,9,11,5,7,13,15,112,113,84,85,88,89,66,67,78,79,92,93,72,73,80,81,106,107,116,117,108,109,64,65,94,95,86,87,4,6,5,7,12,14,8,10,0,2,13,15,9,11,1,3,4,6,8,10,5,7,0,2,12,14,9,11,1,3,13,15,132,134,128,130,133,135,129,131,136,138,140,142,137,139,141,143,200,207,194,204,192,195,202,196,199,206,198,197,205,201,193,203,4,6,12,14,8,10,5,7,13,15,9,11,0,2,1,3,4,6,5,7,136,138,140,142,9,11,141,143,128,130,129,131,82,83,70,71,68,69,102,103,108,109,86,87,114,115,98,99,66,67,84,85,224,225,202,203,0,0,0,0,0,0,0,0,0,0,0,0,0,0,0,0,0,0,0,0,0,0,0,0,0,0,0,0,0,0,0,0,0,0,0,0,0,0,0,0,0,0,0,0,0,0,0,0},
  {64,65,66,67,68,69,70,71,72,73,74,75,76,77,78,79,0,1,2,3,0,1,2,3,4,5,6,7,8,9,10,11,12,13,14,15,64,66,76,78,65,67,77,79,68,70,69,71,72,74,73,75,4,6,0,2,5,7,1,3,12,14,8,10,13,15,9,11,200,202,196,201,207,205,195,192,193,96,97,114,115,76,77,70,71,86,87,90,91,74,75,66,67,68,69,80,81,108,109,110,111,104,105,78,79,90,91,80,81,102,103,104,105,108,109,112,113,72,73,116,117,82,83,100,101,74,204,205,236,237,240,241,210,211,226,227,228,229,192,12,14,4,6,0,2,13,15,5,7,8,10,1,3,9,11,64,71,70,74,8,10,0,2,9,11,12,14,1,3,4,6,13,15,5,7,12,14,8,10,4,6,0,2,13,15,9,11,5,7,1,3,12,14,8,10,13,15,4,6,9,11,5,7,0,2,1,3,80,81,96,97,92,93,108,109,70,71,82,83,100,101,78,79,74,75,114,115,94,95,118,119,72,73,64,112,113,228,229,192,193,216,217,246,247,0,0,0,0,0,0,0,0,0,0,0,0,0,0,0,0,0,0,0,0,0,0,0,0,0,0,0,0,0,0,0,0,0,0,0,0,0,0,0,0,0,0,0,0,0,0,0,0,0,0,0,0},
  {64,65,66,67,68,69,70,71,72,73,74,75,76,77,78,79,0,1,2,3,128,129,130,131,132,133,134,135,136,137,138,139,140,141,142,143,64,66,76,78,65,67,77,79,68,70,69,71,72,74,73,75,4,6,0,2,5,7,1,3,12,14,8,10,13,15,9,11,4,6,12,14,8,10,0,2,5,7,13,15,9,11,1,3,0,2,8,10,4,6,12,14,1,3,9,11,5,7,13,15,8,10,0,2,9,11,1,3,12,14,13,15,4,6,5,7,12,14,4,6,13,15,0,2,8,10,5,7,1,3,9,11,68,70,69,71,76,78,72,74,64,66,77,79,73,75,65,67,79,68,65,67,70,8,10,12,14,0,2,9,11,13,15,1,3,4,6,5,7,8,10,9,11,4,6,0,2,12,14,5,7,1,3,13,15,4,6,12,14,8,10,5,7,13,15,9,11,0,2,1,3,132,134,140,142,136,138,133,135,141,143,128,130,137,139,129,131,118,119,76,77,74,75,68,69,72,73,100,101,110,111,84,85,206,207,116,117,94,95,242,243,214,215,240,241,226,0,0,0,0,0,0,0,0,0,0,0,0,0,0,0,0,0,0,0,0,0,0,0,0,0,0,0,0,0,0,0,0,0,0,0,0,0,0,0,0,0,0,0,0,0,0,0,0,0,0},
  {0,1,2,3,4,5,6,7,8,9,10,11,12,13,14,15,0,1,2,3,4,5,6,7,8,9,10,11,12,13,14,15,70,64,76,66,74,72,79,71,78,67,69,65,75,77,68,73,0,2,8,10,1,3,9,11,12,14,4,6,13,15,5,7,4,6,0,2,5,7,1,3,12,14,8,10,13,15,9,11,0,2,8,10,4,6,12,14,1,3,9,11,5,7,13,15,8,10,0,2,9,11,1,3,12,14,13,15,4,6,5,7,112,113,84,85,88,89,66,67,78,79,76,78,68,70,77,79,64,66,72,74,69,71,65,67,73,75,12,14,4,6,0,2,13,15,5,7,8,10,1,3,9,11,8,10,12,14,0,2,9,11,13,15,1,3,4,6,5,7,8,10,9,11,4,6,0,2,12,14,5,7,1,3,13,15,4,6,12,14,8,10,5,7,13,15,9,11,0,2,1,3,4,6,12,14,8,10,5,7,13,15,9,11,128,130,1,3,89,108,109,118,119,82,83,70,71,100,101,102,103,84,85,116,117,72,73,214,215,238,239,232,233,204,205,0,0,0,0,0,0,0,0,0,0,0,0,0,0,0,0,0,0,0,0,0,0,0,0,0,0,0,0,0,0,0,0,0,0,0,0,0,0,0,0,0,0,0,0,0,0,0,0,0,0,0},
  {64,65,66,67,68,69,70,71,72,73,74,75,76,77,78,79,0,1,2,3,4,5,6,7,8,9,10,11,12,13,14,15,128,129,130,131,132,133,134,135,136,137,138,139,140,141,142,143,198,197,194,199,204,203,206,200,4,6,0,2,5,7,1,3,12,14,8,10,13,15,9,11,0,2,8,10,4,6,12,14,1,3,9,11,5,7,13,15,70,71,86,87,90,91,74,75,66,67,68,69,80,81,108,109,110,111,104,105,0,2,4,6,8,10,1,3,5,7,12,14,9,11,13,15,4,6,5,7,12,14,8,10,0,2,13,15,9,11,1,3,0,2,1,3,4,6,8,10,12,14,5,7,9,11,13,15,8,10,12,14,0,2,9,11,13,15,1,3,4,6,5,7,8,10,0,2,9,11,12,14,1,3,4,6,13,15,5,7,4,6,5,7,8,10,12,14,9,11,13,15,0,2,1,3,4,6,12,14,8,10,5,7,13,15,0,2,9,11,1,3,64,65,78,79,90,91,106,107,94,95,68,69,96,97,74,75,98,99,66,67,208,209,92,93,242,243,240,241,216,0,0,0,0,0,0,0,0,0,0,0,0,0,0,0,0,0,0,0,0,0,0,0,0,0,0,0,0,0,0,0,0,0,0,0,0,0,0,0,0,0,0,0,0,0,0,0},
  {0,1,2,3,4,5,6,7,8,9,10,11,12,13,14,15,64,65,66,67,68,69,70,71,72,73,74,75,76,77,78,79,128,129,130,131,132,133,134,135,136,137,138,139,140,141,142,143,0,2,8,10,1,3,9,11,12,14,4,6,13,15,5,7,197,199,203,201,207,205,195,193,4,6,12,14,8,10,0,2,5,7,13,15,9,11,1,3,88,89,94,95,116,117,118,119,106,107,78,79,82,83,112,113,84,85,102,8,10,0,2,9,11,1,3,12,14,13,15,4,6,5,7,66,71,70,77,69,73,72,64,65,78,67,75,79,74,76,68,12,14,4,6,0,2,13,15,5,7,8,10,1,3,9,11,8,10,12,14,0,2,9,11,13,15,1,3,4,6,5,7,8,10,9,11,4,6,0,2,12,14,5,7,1,3,13,15,4,6,12,14,8,10,5,7,13,15,9,11,0,2,1,3,4,6,12,14,136,138,5,7,13,15,137,139,128,130,129,131,90,91,106,107,92,93,116,117,72,73,76,77,108,109,110,111,80,81,198,199,66,67,202,203,226,0,0,0,0,0,0,0,0,0,0,0,0,0,0,0,0,0,0,0,0,0,0,0,0,0,0,0,0,0,0,0,0,0,0,0,0,0,0,0,0,0,0,0,0,0,0,0,0,0,0,0,0},
  {64,65,66,67,68,69,70,71,72,73,74,75,76,77,78,79,0,1,2,3,4,5,6,7,8,9,10,11,12,13,14,15,72,78,70,71,64,66,76,78,65,67,77,79,68,70,69,71,72,74,73,75,12,14,8,10,13,15,9,11,0,2,4,6,1,3,5,7,109,86,87,96,97,82,83,74,75,110,111,76,77,88,89,118,119,68,69,100,101,104,105,102,103,90,91,64,65,70,71,80,81,112,113,90,91,102,103,118,119,104,105,114,115,106,107,94,95,68,69,12,14,4,6,13,15,0,2,8,10,5,7,1,3,9,11,0,2,1,3,4,6,8,10,12,14,5,7,9,11,13,15,76,70,68,66,65,8,10,12,14,0,2,9,11,13,15,1,3,4,6,5,7,8,10,9,11,4,6,0,2,12,14,5,7,1,3,13,15,4,6,12,14,8,10,5,7,13,15,9,11,0,2,1,3,132,134,140,142,136,138,133,135,141,143,128,130,137,139,129,131,109,118,119,82,83,70,71,100,101,102,103,84,85,116,117,72,73,86,87,110,111,232,233,204,205,0,0,0,0,0,0,0,0,0,0,0,0,0,0,0,0,0,0,0,0,0,0,0,0,0,0,0,0,0,0,0,0,0,0,0,0,0,0,0,0,0,0,0,0,0,0,0,0,0,0,0},
  {64,65,66,67,68,69,70,71,72,73,74,75,76,77,78,79,0,1,2,3,0,1,2,3,4,5,6,7,8,9,10,11,12,13,14,15,64,66,76,78,65,67,77,79,68,70,69,71,72,74,73,75,64,66,72,74,65,67,73,75,76,78,68,70,77,79,69,71,70,71,64,65,98,99,92,93,78,79,112,113,94,95,72,73,80,81,84,85,114,115,116,117,106,107,66,67,108,109,86,87,64,65,70,71,80,81,112,113,90,91,102,103,118,119,104,105,114,115,106,107,94,95,4,6,5,7,12,14,8,10,0,2,13,15,9,11,1,3,0,2,1,3,4,6,8,10,12,14,5,7,9,11,13,15,8,10,12,14,0,2,9,11,13,15,1,3,4,6,5,7,8,10,9,11,4,6,0,2,12,14,5,7,1,3,13,15,4,6,5,7,8,10,12,14,9,11,13,15,0,2,1,3,4,6,12,14,8,10,5,7,13,15,0,2,9,11,1,3,85,104,105,72,73,86,87,102,103,90,91,118,119,68,69,206,207,114,115,66,67,110,111,94,95,216,217,204,205,0,0,0,0,0,0,0,0,0,0,0,0,0,0,0,0,0,0,0,0,0,0,0,0,0,0,0,0,0,0,0,0,0,0,0,0,0,0,0,0,0,0,0,0,0,0,0,0,0},
  {0,1,2,3,4,5,6,7,8,9,10,11,12,13,14,15,0,1,2,3,4,5,6,7,8,9,10,11,12,13,14,15,128,129,130,131,132,133,134,135,136,137,138,139,140,141,142,143,0,2,8,10,1,3,9,11,12,14,4,6,13,15,5,7,4,6,12,14,8,10,0,2,5,7,13,15,9,11,1,3,4,6,0,2,5,7,1,3,12,14,8,10,13,15,9,11,0,2,8,10,4,6,12,14,1,3,9,11,5,7,13,15,0,2,4,6,8,10,1,3,5,7,12,14,9,11,13,15,4,6,5,7,12,14,8,10,0,2,13,15,9,11,1,3,0,2,1,3,4,6,8,10,12,14,5,7,9,11,13,15,8,10,12,14,0,2,9,11,13,15,1,3,4,6,5,7,8,10,9,11,4,6,0,2,12,14,5,7,1,3,13,15,4,6,12,14,8,10,5,7,13,15,9,11,0,2,1,3,4,6,140,142,136,138,5,7,141,143,128,130,137,139,129,131,108,109,118,119,82,83,70,71,100,101,102,103,84,85,116,117,72,73,86,87,110,111,232,233,204,205,0,0,0,0,0,0,0,0,0,0,0,0,0,0,0,0,0,0,0,0,0,0,0,0,0,0,0,0,0,0,0,0,0,0,0,0,0,0,0,0,0,0,0,0,0,0},
  {0,1,2,3,4,5,6,7,8,9,10,11,12,13,14,15,0,1,2,3,4,5,6,7,8,9,10,11,12,13,14,15,74,66,76,79,70,72,64,67,71,69,78,68,75,65,77,73,0,2,8,10,1,3,9,11,12,14,4,6,13,15,5,7,0,2,8,10,4,6,12,14,1,3,9,11,5,7,13,15,4,6,8,10,0,2,5,7,9,11,12,14,1,3,13,15,8,10,0,2,9,11,1,3,12,14,13,15,4,6,5,7,86,87,114,115,102,103,98,99,100,101,90,91,70,71,204,205,68,206,207,246,247,194,195,238,239,242,243,232,233,218,76,78,68,70,64,66,77,79,69,71,72,74,65,67,73,75,8,10,0,2,9,11,12,14,1,3,4,6,13,15,5,7,12,14,8,10,4,6,0,2,13,15,9,11,5,7,1,3,12,14,8,10,13,15,4,6,9,11,5,7,0,2,1,3,110,111,82,83,70,71,68,69,102,103,108,109,86,87,114,115,98,99,66,67,84,85,96,97,74,75,103,208,209,96,97,76,77,218,219,236,237,0,0,0,0,0,0,0,0,0,0,0,0,0,0,0,0,0,0,0,0,0,0,0,0,0,0,0,0,0,0,0,0,0,0,0,0,0,0,0,0,0,0,0,0,0,0,0,0,0,0,0,0,0},
  {0,1,2,3,4,5,6,7,8,9,10,11,12,13,14,15,0,1,2,3,128,129,130,131,132,133,134,135,136,137,138,139,140,141,142,143,64,66,76,78,65,67,77,79,68,70,69,71,72,74,73,75,12,14,8,10,13,15,9,11,0,2,4,6,1,3,5,7,4,6,0,2,5,7,1,3,12,14,8,10,13,15,9,11,4,6,8,10,0,2,5,7,9,11,12,14,1,3,13,15,8,10,0,2,9,11,1,3,12,14,13,15,4,6,5,7,108,109,204,205,88,89,114,115,96,97,102,103,116,117,246,247,0,2,1,3,4,6,8,10,12,14,5,7,9,11,13,15,8,10,12,14,0,2,9,11,13,15,1,3,4,6,5,7,8,10,9,11,4,6,0,2,12,14,5,7,1,3,13,15,12,14,8,10,4,6,0,2,13,15,9,11,5,7,1,3,132,134,140,142,136,138,133,135,141,143,128,130,137,139,129,131,99,102,103,86,87,104,105,78,79,118,119,114,115,88,89,112,113,100,101,64,65,84,85,94,95,224,225,210,211,196,197,0,0,0,0,0,0,0,0,0,0,0,0,0,0,0,0,0,0,0,0,0,0,0,0,0,0,0,0,0,0,0,0,0,0,0,0,0,0,0,0,0,0,0,0,0,0,0,0,0,0,0,0,0},
  {64,65,66,67,68,69,70,71,72,73,74,75,76,77,78,79,0,1,2,3,0,1,2,3,4,5,6,7,8,9,10,11,12,13,14,15,64,66,76,78,65,67,77,79,68,70,69,71,72,74,73,75,64,66,72,74,65,67,73,75,76,78,68,70,77,79,69,71,4,6,12,14,8,10,0,2,5,7,13,15,9,11,1,3,88,89,94,95,116,117,118,119,106,107,78,79,82,83,112,113,84,85,102,103,98,99,8,10,0,2,9,11,1,3,12,14,13,15,4,6,5,7,12,14,4,6,13,15,0,2,8,10,5,7,1,3,9,11,0,2,1,3,4,6,8,10,12,14,5,7,9,11,13,15,8,10,12,14,0,2,9,11,13,15,1,3,4,6,5,7,8,10,9,11,4,6,0,2,12,14,5,7,1,3,13,15,4,6,5,7,8,10,12,14,9,11,13,15,0,2,1,3,4,6,12,14,8,10,5,7,13,15,0,2,9,11,1,3,69,102,103,108,109,86,87,114,115,98,99,66,67,84,85,96,97,74,75,68,69,104,105,108,109,102,103,244,245,0,0,0,0,0,0,0,0,0,0,0,0,0,0,0,0,0,0,0,0,0,0,0,0,0,0,0,0,0,0,0,0,0,0,0,0,0,0,0,0,0,0,0,0,0,0,0,0,0},
  {64,65,66,67,68,69,70,71,72,73,74,75,76,77,78,79,0,1,2,3,0,1,2,3,4,5,6,7,8,9,10,11,12,13,14,15,64,66,76,78,65,67,77,79,68,70,69,71,72,74,73,75,12,14,8,10,13,15,9,11,0,2,4,6,1,3,5,7,4,6,12,14,8,10,0,2,5,7,13,15,9,11,1,3,0,2,8,10,4,6,12,14,1,3,9,11,5,7,13,15,8,10,0,2,9,11,1,3,12,14,13,15,4,6,5,7,94,95,108,109,76,77,88,89,114,115,96,97,102,103,116,117,118,119,0,2,1,3,4,6,8,10,12,14,5,7,9,11,13,15,8,10,12,14,0,2,9,11,13,15,1,3,4,6,5,7,8,10,9,11,4,6,0,2,12,14,5,7,1,3,13,15,4,6,5,7,8,10,12,14,9,11,13,15,0,2,1,3,4,6,12,14,8,10,5,7,13,15,0,2,9,11,1,3,118,119,76,77,74,75,68,69,72,73,100,101,110,111,84,85,78,79,116,117,94,95,242,243,214,215,240,241,226,227,0,0,0,0,0,0,0,0,0,0,0,0,0,0,0,0,0,0,0,0,0,0,0,0,0,0,0,0,0,0,0,0,0,0,0,0,0,0,0,0,0,0,0,0,0,0,0,0,0,0,0,0},
  {64,65,66,67,68,69,70,71,72,73,74,75,76,77,78,79,64,65,66,67,68,69,70,71,72,73,74,75,76,77,78,79,128,129,130,131,132,133,134,135,136,137,138,139,140,141,142,143,0,2,8,10,1,3,9,11,12,14,4,6,13,15,5,7,12,14,8,10,13,15,9,11,0,2,4,6,1,3,5,7,4,6,12,14,8,10,0,2,5,7,13,15,9,11,1,3,68,70,76,78,72,74,64,66,69,71,77,79,73,75,65,67,72,73,80,81,106,107,116,117,108,109,64,65,94,95,86,87,114,115,102,103,226,234,235,224,225,216,217,198,199,206,207,246,247,194,195,64,71,78,77,69,72,75,70,74,79,76,73,68,67,66,65,196,198,192,194,197,199,193,195,200,202,204,206,201,203,205,207,12,14,8,10,4,6,0,2,13,15,9,11,5,7,1,3,12,14,8,10,13,15,132,134,9,11,133,135,128,130,1,3,196,198,204,206,200,202,69,71,205,207,201,203,192,194,193,195,81,66,67,90,91,96,97,114,115,74,75,198,199,238,239,210,211,0,0,0,0,0,0,0,0,0,0,0,0,0,0,0,0,0,0,0,0,0,0,0,0,0,0,0,0,0,0,0,0,0,0,0,0,0,0,0,0,0,0,0,0,0,0,0,0,0,0,0,0},
  {64,65,66,67,68,69,70,71,72,73,74,75,76,77,78,79,0,1,2,3,0,1,2,3,4,5,6,7,8,9,10,11,12,13,14,15,64,66,76,78,65,67,77,79,68,70,69,71,72,74,73,75,4,6,0,2,5,7,1,3,12,14,8,10,13,15,9,11,76,78,72,74,77,79,73,75,64,66,68,70,65,67,69,71,4,6,12,14,8,10,0,2,5,7,13,15,9,11,1,3,8,10,0,2,9,11,1,3,12,14,13,15,4,6,5,7,107,94,95,108,109,76,77,88,89,114,115,96,97,102,103,116,117,118,119,71,72,69,66,64,78,74,77,76,75,73,79,68,65,67,70,8,10,12,14,0,2,9,11,13,15,1,3,4,6,5,7,8,10,0,2,9,11,12,14,1,3,4,6,13,15,5,7,4,6,12,14,8,10,5,7,13,15,9,11,0,2,1,3,4,6,12,14,8,10,5,7,13,15,0,2,9,11,1,3,64,65,78,79,90,91,106,107,94,95,68,69,96,97,74,102,103,208,209,96,97,76,77,218,219,236,237,0,0,0,0,0,0,0,0,0,0,0,0,0,0,0,0,0,0,0,0,0,0,0,0,0,0,0,0,0,0,0,0,0,0,0,0,0,0,0,0,0,0,0,0,0,0,0,0,0,0,0,0,0,0},
  {0,1,2,3,4,5,6,7,8,9,10,11,12,13,14,15,0,1,2,3,79,75,77,73,128,129,130,131,132,133,134,135,136,137,138,139,140,141,142,143,0,2,8,10,1,3,9,11,12,14,4,6,13,15,5,7,4,6,8,10,0,2,5,7,9,11,12,14,1,3,13,15,4,6,8,10,0,2,5,7,9,11,12,14,1,3,13,15,4,6,12,14,8,10,0,2,5,7,13,15,9,11,1,3,72,73,80,81,98,99,74,75,110,111,112,113,86,87,92,93,78,79,64,65,66,67,84,85,68,69,90,91,104,218,219,220,221,230,231,196,197,71,69,72,78,64,77,75,74,79,73,67,76,70,68,66,65,8,10,0,2,9,11,12,14,1,3,4,6,13,15,5,7,12,14,8,10,4,6,0,2,13,15,9,11,5,7,1,3,12,14,8,10,13,15,4,6,9,11,5,7,0,2,1,3,196,198,204,206,200,202,197,199,205,207,192,194,201,203,193,195,78,79,106,235,86,87,94,95,76,77,220,221,200,201,98,99,212,213,0,0,0,0,0,0,0,0,0,0,0,0,0,0,0,0,0,0,0,0,0,0,0,0,0,0,0,0,0,0,0,0,0,0,0,0,0,0,0,0,0,0,0,0,0,0,0,0,0,0,0,0,0,0,0,0,0},
  {64,65,66,67,68,69,70,71,72,73,74,75,76,77,78,79,0,1,2,3,72,78,70,71,0,2,12,14,1,3,13,15,4,6,5,7,8,10,9,11,12,14,8,10,13,15,9,11,0,2,4,6,1,3,5,7,4,6,8,10,0,2,5,7,9,11,12,14,1,3,13,15,8,10,0,2,9,11,1,3,12,14,13,15,4,6,5,7,95,70,71,76,77,106,107,96,97,64,65,78,79,90,91,80,81,102,69,110,111,82,83,74,75,96,97,118,119,104,105,94,223,244,245,234,235,224,225,216,217,198,199,71,69,72,78,64,77,75,74,79,73,67,76,70,68,66,65,8,10,0,2,9,11,12,14,1,3,4,6,13,15,5,7,12,14,8,10,4,6,0,2,13,15,9,11,5,7,1,3,4,6,12,14,8,10,5,7,13,15,9,11,0,2,1,3,68,70,69,71,200,202,204,206,201,203,205,207,192,194,193,195,64,65,78,79,90,91,106,107,94,95,112,113,228,229,64,193,216,217,246,247,0,0,0,0,0,0,0,0,0,0,0,0,0,0,0,0,0,0,0,0,0,0,0,0,0,0,0,0,0,0,0,0,0,0,0,0,0,0,0,0,0,0,0,0,0,0,0,0,0,0,0,0,0,0,0,0,0,0,0,0,0,0,0,0,0},
  {64,65,66,67,68,69,70,71,72,73,74,75,76,77,78,79,0,1,2,3,128,129,130,131,132,133,134,135,136,137,138,139,140,141,142,143,64,66,76,78,65,67,77,79,68,70,69,71,72,74,73,75,12,14,8,10,13,15,9,11,0,2,4,6,1,3,5,7,70,71,64,65,98,99,92,93,78,79,112,113,94,95,72,73,80,81,84,85,114,115,116,117,106,107,66,67,111,98,99,66,67,94,95,70,71,76,77,106,107,96,97,64,65,78,79,90,91,80,81,102,103,104,105,236,237,240,241,72,105,70,71,210,211,100,101,106,71,72,69,66,64,78,74,77,76,75,73,79,68,65,67,70,64,71,70,74,77,69,78,72,76,78,74,77,71,70,64,66,69,207,200,75,68,204,73,195,65,4,6,5,7,8,10,12,14,9,11,13,15,0,2,1,3,12,14,8,10,13,15,132,134,9,11,133,135,0,2,1,3,118,119,76,77,74,75,68,69,72,73,100,101,110,111,84,85,206,207,116,117,94,95,114,115,214,215,112,113,98,99,192,193,0,0,0,0,0,0,0,0,0,0,0,0,0,0,0,0,0,0,0,0,0,0,0,0,0,0,0,0,0,0,0,0,0,0,0,0,0,0,0,0,0,0,0,0,0,0,0,0,0,0,0,0,0,0,0},
  {64,65,66,67,68,69,70,71,72,73,74,75,76,77,78,79,0,1,2,3,64,65,66,67,68,69,70,71,72,73,74,75,76,77,78,79,64,66,76,78,65,67,77,79,68,70,69,71,72,74,73,75,4,6,0,2,5,7,1,3,12,14,8,10,13,15,9,11,4,6,12,14,8,10,0,2,5,7,13,15,9,11,1,3,4,6,12,14,8,10,0,2,5,7,13,15,9,11,1,3,92,93,72,73,80,81,106,107,116,117,108,109,64,65,94,95,86,87,114,115,102,103,98,99,100,101,90,91,70,71,207,246,247,194,195,238,239,242,243,232,233,218,4,6,8,10,5,7,0,2,12,14,9,11,1,3,13,15,64,71,78,74,77,70,73,69,66,72,76,79,68,65,67,75,12,14,8,10,4,6,0,2,13,15,9,11,5,7,1,3,12,14,8,10,13,15,4,6,9,11,5,7,0,2,1,3,204,206,200,202,205,207,196,198,201,203,197,199,192,194,193,195,71,66,67,112,113,98,99,86,87,110,111,114,115,88,89,118,119,68,69,230,231,0,0,0,0,0,0,0,0,0,0,0,0,0,0,0,0,0,0,0,0,0,0,0,0,0,0,0,0,0,0,0,0,0,0,0,0,0,0,0,0,0,0,0,0,0,0,0,0,0,0,0,0,0},
  {64,65,66,67,68,69,70,71,72,73,74,75,76,77,78,79,0,1,2,3,0,1,2,3,4,5,6,7,8,9,10,11,12,13,14,15,64,66,76,78,65,67,77,79,68,70,69,71,72,74,73,75,12,14,8,10,13,15,9,11,0,2,4,6,1,3,5,7,4,6,0,2,5,7,1,3,12,14,8,10,13,15,9,11,4,6,8,10,0,2,5,7,9,11,12,14,1,3,13,15,82,83,98,99,108,109,92,93,78,79,84,85,100,101,66,67,74,75,112,113,84,85,88,89,66,67,78,79,92,93,4,6,5,7,0,2,8,10,12,14,1,3,9,11,13,15,4,6,8,10,5,7,0,2,12,14,9,11,1,3,13,15,8,10,0,2,9,11,12,14,1,3,4,6,13,15,5,7,12,14,8,10,4,6,0,2,13,15,9,11,5,7,1,3,12,14,8,10,13,15,132,134,9,11,5,7,0,2,1,3,196,198,69,71,200,202,204,206,201,203,205,207,192,194,193,195,78,79,106,107,86,87,94,95,76,77,220,221,200,201,98,99,212,213,208,0,0,0,0,0,0,0,0,0,0,0,0,0,0,0,0,0,0,0,0,0,0,0,0,0,0,0,0,0,0,0,0,0,0,0,0,0,0,0,0,0,0,0,0,0,0,0,0,0,0,0},
  {0,1,2,3,4,5,6,7,8,9,10,11,12,13,14,15,0,1,2,3,0,1,2,3,4,5,6,7,8,9,10,11,12,13,14,15,64,66,76,78,65,67,77,79,68,70,69,71,72,74,73,75,4,6,0,2,5,7,1,3,12,14,8,10,13,15,9,11,4,6,8,10,0,2,5,7,9,11,12,14,1,3,13,15,0,2,8,10,4,6,12,14,1,3,9,11,5,7,13,15,80,81,102,103,104,105,108,109,112,113,72,73,116,117,82,83,100,101,74,75,86,87,92,93,118,119,68,69,4,6,5,7,0,2,8,10,12,14,1,3,9,11,13,15,4,6,8,10,5,7,0,2,12,14,9,11,1,3,13,15,8,10,0,2,9,11,12,14,1,3,4,6,13,15,5,7,200,207,194,204,192,195,202,196,199,206,198,197,205,201,193,203,12,14,8,10,13,15,4,6,9,11,5,7,0,2,1,3,132,134,12,14,136,138,133,135,13,15,137,139,128,130,129,131,106,107,70,71,66,67,112,113,98,99,86,87,110,111,242,243,88,89,118,119,196,197,0,0,0,0,0,0,0,0,0,0,0,0,0,0,0,0,0,0,0,0,0,0,0,0,0,0,0,0,0,0,0,0,0,0,0,0,0,0,0,0,0,0,0,0,0,0,0,0,0,0},
  {64,65,66,67,68,69,70,71,72,73,74,75,76,77,78,79,0,1,2,3,4,5,6,7,8,9,10,11,12,13,14,15,0,1,2,3,72,76,64,70,66,74,71,78,67,79,65,69,75,68,73,77,4,6,0,2,5,7,1,3,12,14,8,10,13,15,9,11,4,6,8,10,0,2,5,7,9,11,12,14,1,3,13,15,0,2,8,10,4,6,12,14,1,3,9,11,5,7,13,15,64,66,72,74,68,70,76,78,65,67,73,75,69,71,77,79,111,82,83,74,75,96,97,118,119,104,105,4,6,5,7,0,2,8,10,12,14,1,3,9,11,13,15,76,78,68,70,0,2,13,15,5,7,8,10,1,3,9,11,8,10,0,2,9,11,12,14,1,3,4,6,13,15,5,7,12,14,8,10,4,6,0,2,13,15,9,11,5,7,1,3,4,6,12,14,8,10,5,7,13,15,9,11,0,2,1,3,12,14,136,138,132,134,0,2,141,143,137,139,133,135,129,131,64,65,84,85,92,93,104,105,74,75,206,207,100,101,82,83,200,201,116,117,222,223,234,0,0,0,0,0,0,0,0,0,0,0,0,0,0,0,0,0,0,0,0,0,0,0,0,0,0,0,0,0,0,0,0,0,0,0,0,0,0,0,0,0,0,0,0,0,0,0,0,0,0},
  {64,65,66,67,68,69,70,71,72,73,74,75,76,77,78,79,0,1,2,3,4,5,6,7,8,9,10,11,12,13,14,15,69,76,67,65,64,66,76,78,65,67,77,79,68,70,69,71,72,74,73,75,12,14,8,10,13,15,9,11,0,2,4,6,1,3,5,7,4,6,8,10,0,2,5,7,9,11,12,14,1,3,13,15,90,91,70,71,72,73,66,67,64,65,84,85,92,93,80,81,86,87,94,95,76,77,88,89,106,107,78,79,96,0,2,4,6,8,10,1,3,5,7,12,14,9,11,13,15,4,6,5,7,0,2,8,10,12,14,1,3,9,11,13,15,4,6,8,10,5,7,0,2,12,14,9,11,1,3,13,15,132,134,128,130,133,135,129,131,136,138,140,142,137,139,141,143,8,10,9,11,4,6,0,2,12,14,5,7,1,3,13,15,4,6,12,14,8,10,5,7,13,15,9,11,0,2,1,3,132,134,140,142,136,138,133,135,141,143,128,130,137,139,129,131,104,105,78,79,118,119,114,115,88,89,112,113,100,101,64,65,84,85,94,95,96,97,210,211,196,197,0,0,0,0,0,0,0,0,0,0,0,0,0,0,0,0,0,0,0,0,0,0,0,0,0,0,0,0,0,0,0,0,0,0,0,0,0,0,0,0,0,0,0,0,0},
  {64,65,66,67,68,69,70,71,72,73,74,75,76,77,78,79,0,1,2,3,128,129,130,131,132,133,134,135,136,137,138,139,140,141,142,143,128,129,130,131,132,133,134,135,136,137,138,139,140,141,142,143,0,2,8,10,1,3,9,11,12,14,4,6,13,15,5,7,4,6,8,10,0,2,5,7,9,11,12,14,1,3,13,15,4,6,12,14,8,10,0,2,5,7,13,15,9,11,1,3,103,104,105,108,109,112,113,72,73,116,117,82,83,100,101,74,75,86,87,92,93,118,119,68,69,76,78,68,70,77,79,64,66,72,74,69,71,65,67,73,75,0,2,1,3,4,6,8,10,12,14,5,7,9,11,13,15,132,134,128,130,133,135,129,131,136,138,140,142,137,139,141,143,8,10,9,11,4,6,0,2,12,14,5,7,1,3,13,15,4,6,12,14,8,10,5,7,13,15,9,11,0,2,1,3,132,134,140,142,136,138,133,135,141,143,128,130,137,139,129,131,65,112,113,98,99,88,89,86,87,84,85,90,91,106,107,68,69,104,105,76,77,116,117,110,111,102,103,194,195,0,0,0,0,0,0,0,0,0,0,0,0,0,0,0,0,0,0,0,0,0,0,0,0,0,0,0,0,0,0,0,0,0,0,0,0,0,0,0,0,0,0,0,0,0,0},
  {64,65,66,67,68,69,70,71,72,73,74,75,76,77,78,79,0,1,2,3,4,5,6,7,8,9,10,11,12,13,14,15,64,67,72,77,69,73,78,76,76,69,70,72,74,66,71,75,67,77,68,73,79,206,64,65,4,6,8,10,0,2,5,7,9,11,12,14,1,3,13,15,4,6,12,14,8,10,0,2,5,7,13,15,9,11,1,3,0,2,8,10,4,6,12,14,1,3,9,11,5,7,13,15,0,2,4,6,8,10,1,3,5,7,12,14,9,11,13,15,4,6,5,7,12,14,8,10,0,2,13,15,9,11,1,3,0,2,1,3,4,6,8,10,12,14,5,7,9,11,13,15,8,10,12,14,0,2,9,11,13,15,1,3,4,6,5,7,8,10,0,2,9,11,12,14,1,3,4,6,13,15,5,7,12,14,8,10,4,6,0,2,13,15,9,11,5,7,1,3,4,6,12,14,8,10,5,7,13,15,9,11,0,2,1,3,116,117,64,65,118,119,80,81,94,95,76,77,112,113,110,111,82,83,70,71,68,112,113,228,229,64,65,88,217,246,247,0,0,0,0,0,0,0,0,0,0,0,0,0,0,0,0,0,0,0,0,0,0,0,0,0,0,0,0,0,0,0,0,0,0,0,0,0,0,0,0,0,0,0,0,0,0,0,0,0},
  {64,65,66,67,68,69,70,71,72,73,74,75,76,77,78,79,0,1,2,3,128,129,130,131,132,133,134,135,136,137,138,139,140,141,142,143,64,66,76,78,65,67,77,79,68,70,69,71,72,74,73,75,12,14,8,10,13,15,9,11,0,2,4,6,1,3,5,7,4,6,8,10,0,2,5,7,9,11,12,14,1,3,13,15,64,65,70,71,80,81,112,113,90,91,102,103,118,119,104,105,114,115,106,107,94,95,68,69,82,83,98,99,108,109,92,12,14,4,6,13,15,0,2,8,10,5,7,1,3,9,11,4,6,5,7,0,2,8,10,12,14,1,3,9,11,13,15,76,78,68,70,64,66,77,79,69,71,72,74,65,67,73,75,132,134,128,130,133,135,129,131,136,138,140,142,137,139,141,143,12,14,8,10,4,6,0,2,13,15,9,11,5,7,1,3,4,6,12,14,8,10,5,7,13,15,9,11,0,2,1,3,4,6,12,14,136,138,5,7,13,15,137,139,128,130,129,131,64,65,84,85,92,93,104,105,74,75,206,207,100,101,82,83,72,73,116,117,222,223,234,235,198,0,0,0,0,0,0,0,0,0,0,0,0,0,0,0,0,0,0,0,0,0,0,0,0,0,0,0,0,0,0,0,0,0,0,0,0,0,0,0,0,0,0,0,0},
  {0,1,2,3,4,5,6,7,8,9,10,11,12,13,14,15,64,65,66,67,68,69,70,71,72,73,74,75,76,77,78,79,128,129,130,131,132,133,134,135,136,137,138,139,140,141,142,143,0,2,8,10,1,3,9,11,12,14,4,6,13,15,5,7,4,6,8,10,0,2,5,7,9,11,12,14,1,3,13,15,103,98,99,72,73,92,93,64,65,100,101,96,97,114,115,76,77,70,71,86,87,90,91,74,75,66,67,68,69,0,2,4,6,8,10,1,3,5,7,12,14,9,11,13,15,12,14,4,6,13,15,0,2,8,10,5,7,1,3,9,11,0,2,1,3,4,6,8,10,12,14,5,7,9,11,13,15,132,134,128,130,133,135,129,131,136,138,140,142,137,139,141,143,79,67,75,65,8,10,0,2,9,11,12,14,1,3,4,6,13,15,5,7,4,6,12,14,8,10,5,7,13,15,9,11,0,2,1,3,8,10,9,11,4,6,0,2,140,142,133,135,1,3,141,143,64,65,80,81,92,93,108,109,106,107,70,71,66,67,90,91,88,89,82,83,224,225,232,233,230,231,0,0,0,0,0,0,0,0,0,0,0,0,0,0,0,0,0,0,0,0,0,0,0,0,0,0,0,0,0,0,0,0,0,0,0,0,0,0,0,0,0,0,0,0,0},
  {64,65,66,67,68,69,70,71,72,73,74,75,76,77,78,79,0,1,2,3,64,65,66,67,68,69,70,71,72,73,74,75,76,77,78,79,64,66,76,78,65,67,77,79,68,70,69,71,72,74,73,75,4,6,0,2,5,7,1,3,12,14,8,10,13,15,9,11,4,6,8,10,0,2,5,7,9,11,12,14,1,3,13,15,90,91,70,71,72,73,66,67,64,65,84,85,92,93,80,81,86,87,94,95,76,77,88,89,106,107,78,79,96,97,0,2,4,6,8,10,1,3,5,7,12,14,9,11,13,15,4,6,5,7,0,2,8,10,12,14,1,3,9,11,13,15,12,14,4,6,0,2,13,15,5,7,8,10,1,3,9,11,64,71,70,74,77,69,78,72,76,68,66,73,8,10,9,11,4,6,0,2,12,14,5,7,1,3,13,15,4,6,12,14,8,10,5,7,13,15,9,11,0,2,1,3,12,14,8,10,13,15,4,6,9,11,5,7,0,2,1,3,106,107,104,105,92,93,88,89,72,73,90,91,100,101,206,207,116,117,64,65,118,119,80,209,222,223,204,0,0,0,0,0,0,0,0,0,0,0,0,0,0,0,0,0,0,0,0,0,0,0,0,0,0,0,0,0,0,0,0,0,0,0,0,0,0,0,0,0,0,0,0,0,0,0},
  {0,1,2,3,4,5,6,7,8,9,10,11,12,13,14,15,0,1,2,3,64,65,66,67,68,69,70,71,72,73,74,75,76,77,78,79,64,66,76,78,65,67,77,79,68,70,69,71,72,74,73,75,64,66,72,74,65,67,73,75,76,78,68,70,77,79,69,71,4,6,8,10,0,2,5,7,9,11,12,14,1,3,13,15,68,70,64,66,69,71,65,67,76,78,72,74,77,79,73,75,8,10,0,2,9,11,1,3,12,14,13,15,4,6,5,7,64,66,68,70,72,74,65,67,69,71,76,78,73,75,77,79,4,6,5,7,0,2,8,10,12,14,1,3,9,11,13,15,4,6,8,10,5,7,0,2,12,14,9,11,1,3,13,15,64,71,78,74,77,70,73,69,66,72,76,79,68,65,67,75,12,14,8,10,4,6,0,2,13,15,9,11,5,7,1,3,12,14,8,10,13,15,132,134,9,11,133,135,0,2,1,3,204,206,200,202,205,207,196,198,201,203,197,199,192,194,193,195,107,70,71,66,67,112,113,98,99,86,87,110,111,242,243,88,89,118,119,196,197,0,0,0,0,0,0,0,0,0,0,0,0,0,0,0,0,0,0,0,0,0,0,0,0,0,0,0,0,0,0,0,0,0,0,0,0,0,0,0,0,0,0,0,0,0,0,0},
  {64,65,66,67,68,69,70,71,72,73,74,75,76,77,78,79,0,1,2,3,72,78,70,71,128,129,130,131,132,133,134,135,136,137,138,139,140,141,142,143,0,2,8,10,1,3,9,11,12,14,4,6,13,15,5,7,12,14,8,10,13,15,9,11,0,2,4,6,1,3,5,7,4,6,12,14,8,10,0,2,5,7,13,15,9,11,1,3,8,10,0,2,9,11,1,3,12,14,13,15,4,6,5,7,75,88,89,76,77,96,97,86,87,72,73,116,117,110,111,4,6,5,7,12,14,8,10,0,2,13,15,9,11,1,3,12,14,4,6,0,2,13,15,5,7,8,10,1,3,9,11,132,134,128,130,133,135,129,131,136,138,140,142,137,139,141,143,8,10,9,11,4,6,0,2,12,14,5,7,1,3,13,15,4,6,5,7,8,10,12,14,9,11,13,15,0,2,1,3,12,14,8,10,13,15,132,134,9,11,133,135,128,130,129,131,116,117,96,97,74,75,64,65,112,113,82,83,106,107,84,80,81,66,67,90,91,96,97,242,243,74,75,198,199,0,0,0,0,0,0,0,0,0,0,0,0,0,0,0,0,0,0,0,0,0,0,0,0,0,0,0,0,0,0,0,0,0,0,0,0,0,0,0,0,0,0,0,0,0,0,0,0,0,0,0,0},
  {0,1,2,3,4,5,6,7,8,9,10,11,12,13,14,15,0,1,2,3,0,1,2,3,4,5,6,7,8,9,10,11,12,13,14,15,0,1,2,3,76,69,70,72,74,66,71,75,67,77,68,73,79,78,64,65,12,14,8,10,13,15,9,11,0,2,4,6,1,3,5,7,4,6,8,10,0,2,5,7,9,11,12,14,1,3,13,15,0,2,8,10,4,6,12,14,1,3,9,11,5,7,13,15,0,2,4,6,8,10,1,3,5,7,12,14,9,11,13,15,95,108,109,76,77,88,89,114,115,96,97,102,103,244,245,246,247,219,220,221,230,231,196,197,4,6,8,10,5,7,0,2,12,14,9,11,1,3,13,15,64,71,70,74,77,69,78,72,76,68,66,73,79,67,75,65,12,14,8,10,4,6,0,2,13,15,9,11,5,7,1,3,12,14,8,10,13,15,4,6,9,11,5,7,0,2,1,3,76,78,72,74,77,79,68,70,73,75,69,71,64,66,65,67,82,83,70,71,100,101,102,103,84,85,116,117,72,73,86,87,110,111,232,233,204,205,0,0,0,0,0,0,0,0,0,0,0,0,0,0,0,0,0,0,0,0,0,0,0,0,0,0,0,0,0,0,0,0,0,0,0,0,0,0,0,0,0,0,0,0,0,0,0,0,0,0},
  {64,65,66,67,68,69,70,71,72,73,74,75,76,77,78,79,0,1,2,3,4,5,6,7,8,9,10,11,12,13,14,15,70,64,76,66,74,72,79,71,78,67,69,65,75,77,68,73,0,2,8,10,1,3,9,11,12,14,4,6,13,15,5,7,4,6,12,14,8,10,0,2,5,7,13,15,9,11,1,3,4,6,12,14,8,10,0,2,5,7,13,15,9,11,1,3,8,10,0,2,9,11,1,3,12,14,13,15,4,6,5,7,12,14,4,6,13,15,0,2,8,10,5,7,1,3,9,11,4,6,5,7,0,2,8,10,12,14,1,3,9,11,13,15,4,6,8,10,5,7,0,2,12,14,9,11,1,3,13,15,132,134,128,130,133,135,129,131,136,138,140,142,137,139,141,143,8,10,9,11,4,6,0,2,12,14,5,7,1,3,13,15,4,6,12,14,8,10,5,7,13,15,9,11,0,2,1,3,8,10,0,2,9,11,140,142,1,3,132,134,141,143,133,135,92,93,108,109,98,99,80,81,100,101,70,71,110,111,82,83,68,69,104,105,108,109,102,103,244,245,0,0,0,0,0,0,0,0,0,0,0,0,0,0,0,0,0,0,0,0,0,0,0,0,0,0,0,0,0,0,0,0,0,0,0,0,0,0,0,0,0,0,0,0,0,0},
  {0,1,2,3,4,5,6,7,8,9,10,11,12,13,14,15,0,1,2,3,0,1,2,3,4,5,6,7,8,9,10,11,12,13,14,15,64,66,76,78,65,67,77,79,68,70,69,71,72,74,73,75,12,14,8,10,13,15,9,11,0,2,4,6,1,3,5,7,4,6,0,2,5,7,1,3,12,14,8,10,13,15,9,11,90,91,70,71,72,73,66,67,64,65,84,85,92,93,80,81,86,87,94,95,76,77,88,89,106,107,78,79,96,97,108,109,72,73,80,81,98,99,74,75,110,111,240,241,86,87,92,93,206,207,192,193,0,2,1,3,4,6,8,10,12,14,5,7,9,11,13,15,8,10,12,14,0,2,9,11,13,15,1,3,4,6,5,7,8,10,9,11,4,6,0,2,12,14,5,7,1,3,13,15,4,6,5,7,8,10,12,14,9,11,13,15,0,2,1,3,132,134,5,7,136,138,140,142,9,11,141,143,128,130,129,131,104,105,72,73,86,87,102,103,90,91,118,119,68,69,206,207,114,115,66,67,110,111,222,223,216,217,204,205,0,0,0,0,0,0,0,0,0,0,0,0,0,0,0,0,0,0,0,0,0,0,0,0,0,0,0,0,0,0,0,0,0,0,0,0,0,0,0,0,0,0,0,0,0,0,0,0,0,0,0,0},
  {64,65,66,67,68,69,70,71,72,73,74,75,76,77,78,79,0,1,2,3,128,129,130,131,132,133,134,135,136,137,138,139,140,141,142,143,64,66,76,78,65,67,77,79,68,70,69,71,72,74,73,75,12,14,8,10,13,15,9,11,0,2,4,6,1,3,5,7,4,6,8,10,0,2,5,7,9,11,12,14,1,3,13,15,0,2,8,10,4,6,12,14,1,3,9,11,5,7,13,15,99,102,103,68,69,110,111,104,105,73,116,117,82,83,100,101,74,75,86,87,92,93,118,119,68,69,4,6,5,7,12,14,8,10,0,2,13,15,9,11,1,3,79,68,65,67,70,64,71,78,77,69,72,75,70,74,79,76,73,68,67,66,65,8,10,0,2,9,11,12,14,1,3,4,6,13,15,5,7,12,14,8,10,4,6,0,2,13,15,9,11,5,7,1,3,4,6,12,14,8,10,5,7,13,15,0,2,9,11,1,3,80,81,96,97,92,93,108,109,70,71,82,83,100,101,78,206,207,106,107,86,87,94,95,76,77,220,221,200,201,226,227,0,0,0,0,0,0,0,0,0,0,0,0,0,0,0,0,0,0,0,0,0,0,0,0,0,0,0,0,0,0,0,0,0,0,0,0,0,0,0,0,0,0,0,0,0,0,0,0,0,0,0,0,0,0},
};

struct alignas(64) Params {
  CUtensorMap a[6];
  CUtensorMap w[4];
  CUtensorMap ow;
  CUtensorMap xr;
  const bf16 *x0, *wqkv;
  bf16* out;
  uint32_t swap;
  uint32_t jobs[NPAIR][JMAX];
  uint8_t kseq[NPAIR][KMAX];
};

template <class T> __device__ __forceinline__ T* at(T* base, uint32_t bytes) {
  T* r;
  asm("{\n.reg .u32 lo, hi;\nmov.b64 {lo, hi}, %1;\nadd.cc.u32 lo, lo, %2;\naddc.u32 hi, hi, 0;\nmov.b64 %0, {lo, hi};\n}" : "=l"(r) : "l"(base), "r"(bytes));
  return r;
}
#define SCR(sm, member, bytes) reinterpret_cast<decltype(&scratch_base()->member[0])>(at((sm).scratch, offsetof(Scratch, member) + (bytes)))
#define counter(line, word) SCR(sm, cnt, (line) * 128 + (word) * 4)
#define TRS(st, slot) do {} while (0)
#define TRX(cond, job, bit, slot, reg) do {} while (0)
#define TR(job, slot) do {} while (0)
#define TRI(cond, job, slot) do {} while (0)
#define TRK(cond, job, slot) do {} while (0)
#define TRC(job, slot) do {} while (0)

__device__ __forceinline__ uint32_t smem_u32(const void* p) { return (uint32_t)__cvta_generic_to_shared(p); }
__device__ __forceinline__ void mbar_init(uint32_t bar, uint32_t cnt) { asm volatile("mbarrier.init.shared::cta.b64 [%0], %1;" ::"r"(bar), "r"(cnt) : "memory"); }
__device__ __forceinline__ void mbar_expect_tx(uint32_t bar, uint32_t bytes) { asm volatile("mbarrier.arrive.expect_tx.shared::cta.b64 _, [%0], %1;" ::"r"(bar), "r"(bytes) : "memory"); }
__device__ __forceinline__ void mbar_arrive_n(uint32_t bar, uint32_t cnt) { asm volatile("mbarrier.arrive.shared::cta.b64 _, [%0], %1;" ::"r"(bar), "r"(cnt) : "memory"); }
__device__ __forceinline__ void mbar_arrive_cl_if(uint32_t cond, uint32_t bar) {
  asm volatile("{\n.reg .pred p;\nsetp.ne.u32 p, %1, 0;\n@p mbarrier.arrive.shared::cluster.b64 _, [%0];\n}" ::"r"(bar), "r"(cond) : "memory");
}
__device__ __forceinline__ void mbar_arrive_warp(uint32_t bar) {
  asm volatile("{\n.reg .pred p;\nbar.warp.sync -1;\nelect.sync _|p, -1;\n@p mbarrier.arrive.shared::cta.b64 _, [%0];\n}" ::"r"(bar) : "memory");
}
__device__ __forceinline__ uint32_t mapa(uint32_t addr, uint32_t cta) { uint32_t r; asm("mapa.shared::cluster.u32 %0, %1, %2;" : "=r"(r) : "r"(addr), "r"(cta)); return r; }
__device__ __forceinline__ bool mbar_test(uint32_t bar, uint32_t parity) {
  uint32_t ok;
  asm volatile("{\n.reg .pred p;\nmbarrier.test_wait.parity.shared::cta.b64 p, [%1], %2;\nselp.u32 %0, 1, 0, p;\n}\n" : "=r"(ok) : "r"(bar), "r"(parity) : "memory");
  return ok;
}
__device__ __forceinline__ void mbar_wait(uint32_t bar, uint32_t parity) {
  asm volatile(
      "{\n.reg .pred p;\n.reg .u32 n;\nmov.u32 n, 0;\n"
      "WAIT:\nmbarrier.try_wait.parity.shared::cta.b64 p, [%0], %1;\n@p bra DONE;\n"
      "add.u32 n, n, 1;\nsetp.lt.u32 p, n, %2;\n@p bra WAIT;\ntrap;\nDONE:\n}\n" ::"r"(bar), "r"(parity), "n"(SPIN_LIMIT) : "memory");
}
template <int ID, int N> __device__ __forceinline__ void bar_sync() { asm volatile("bar.sync %0, %1;" ::"n"(ID), "n"(N) : "memory"); }
template <int ID, int N> __device__ __forceinline__ void bar_arrive() { asm volatile("bar.arrive %0, %1;" ::"n"(ID), "n"(N) : "memory"); }
__device__ __forceinline__ uint32_t ld_relaxed(const uint32_t* p) { uint32_t v; asm volatile("ld.relaxed.gpu.global.u32 %0, [%1];" : "=r"(v) : "l"(p) : "memory"); return v; }
__device__ __forceinline__ void red_relaxed(uint32_t* p, uint32_t v) { asm volatile("red.relaxed.gpu.global.add.u32 [%0], %1;" ::"l"(p), "r"(v) : "memory"); }
__device__ __forceinline__ void red_release(uint32_t* p, uint32_t v) {
  asm volatile("fence.release.gpu;\nred.relaxed.gpu.global.add.u32 [%0], %1;" ::"l"(p), "r"(v) : "memory");
}
__device__ __forceinline__ bool elect() {
  uint32_t p;
  asm volatile("{\n.reg .pred P;\nelect.sync _|P, 0xffffffff;\nselp.u32 %0, 1, 0, P;\n}\n" : "=r"(p));
  return p;
}
__device__ __forceinline__ void fence_acquire() { asm volatile("fence.acquire.gpu;" ::: "memory"); }
__device__ __forceinline__ void wait_count(const uint32_t* p, uint32_t target) {
  for (uint32_t n = 0; !__all_sync(~0u, (int)(ld_relaxed(p) - target) >= 0); n++) {
    __nanosleep(200);
    if (n > SPIN_LIMIT) __trap();
  }
  fence_acquire();
}
__device__ __forceinline__ void fence_proxy_async() { asm volatile("fence.proxy.async.global;" ::: "memory"); }
__device__ __forceinline__ void fence_proxy_async_smem() { asm volatile("fence.proxy.async.shared::cta;" ::: "memory"); }
__device__ __forceinline__ void tma4d_mc(uint32_t dst, const CUtensorMap* tm, int c1, int c2, uint32_t bar, uint64_t pol) {
  asm volatile("cp.async.bulk.tensor.4d.shared::cluster.global.mbarrier::complete_tx::bytes.multicast::cluster.L2::cache_hint [%0], [%1, {%3, %4, %5, %3}], [%2], %6, %7;"
               ::"r"(dst), "l"(tm), "r"(bar), "r"(0), "r"(c1), "r"(c2), "h"((uint16_t)3), "l"(pol) : "memory");
}
__device__ __forceinline__ void tma3d(uint32_t dst, const CUtensorMap* tm, int c0, int c1, int c2, uint32_t bar, uint64_t pol) {
  asm volatile("cp.async.bulk.tensor.3d.shared::cluster.global.mbarrier::complete_tx::bytes.L2::cache_hint [%0], [%1, {%3, %4, %5}], [%2], %6;"
               ::"r"(dst), "l"(tm), "r"(bar), "r"(c0), "r"(c1), "r"(c2), "l"(pol) : "memory");
}
__device__ __forceinline__ void tma3d_reduce_add(const CUtensorMap* tm, int c0, int c1, int c2, uint32_t src) {
  asm volatile("cp.reduce.async.bulk.tensor.3d.global.shared::cta.add.tile.bulk_group [%0, {%2, %3, %4}], [%1];"
               ::"l"(tm), "r"(src), "r"(c0), "r"(c1), "r"(c2) : "memory");
}
__device__ __forceinline__ void tma3d_store(const CUtensorMap* tm, int c0, int c1, int c2, uint32_t src) {
  asm volatile("cp.async.bulk.tensor.3d.global.shared::cta.tile.bulk_group [%0, {%2, %3, %4}], [%1];"
               ::"l"(tm), "r"(src), "r"(c0), "r"(c1), "r"(c2) : "memory");
}
__device__ __forceinline__ void bulk_commit() { asm volatile("cp.async.bulk.commit_group;" ::: "memory"); }
template <int N> __device__ __forceinline__ void bulk_wait_read() { asm volatile("cp.async.bulk.wait_group.read %0;" ::"n"(N) : "memory"); }
__device__ __forceinline__ void bulk_wait() { asm volatile("cp.async.bulk.wait_group 0;" ::: "memory"); }
__device__ __forceinline__ uint2 lds64(uint32_t a) { uint2 v; asm volatile("ld.shared.v2.u32 {%0,%1}, [%2];" : "=r"(v.x), "=r"(v.y) : "r"(a) : "memory"); return v; }
__device__ __forceinline__ float lds32f(uint32_t a) { float v; asm volatile("ld.shared.f32 %0, [%1];" : "=f"(v) : "r"(a) : "memory"); return v; }
__device__ __forceinline__ uint4 lds128(uint32_t a) { uint4 v; asm volatile("ld.shared.v4.u32 {%0,%1,%2,%3}, [%4];" : "=r"(v.x), "=r"(v.y), "=r"(v.z), "=r"(v.w) : "r"(a) : "memory"); return v; }
__device__ __forceinline__ uint2 lds64v(uint32_t a) { uint2 v; asm volatile("ld.volatile.shared.v2.u32 {%0,%1}, [%2];" : "=r"(v.x), "=r"(v.y) : "r"(a) : "memory"); return v; }
__device__ __forceinline__ uint4 lds128v(uint32_t a) { uint4 v; asm volatile("ld.volatile.shared.v4.u32 {%0,%1,%2,%3}, [%4];" : "=r"(v.x), "=r"(v.y), "=r"(v.z), "=r"(v.w) : "r"(a) : "memory"); return v; }
__device__ __forceinline__ void sts32(uint32_t a, uint32_t v) { asm volatile("st.shared.u32 [%0], %1;" ::"r"(a), "r"(v) : "memory"); }
__device__ __forceinline__ void sts64(uint32_t a, uint2 v) { asm volatile("st.shared.v2.u32 [%0], {%1,%2};" ::"r"(a), "r"(v.x), "r"(v.y) : "memory"); }
__device__ __forceinline__ void stg128(void* p, uint4 v) { asm volatile("st.global.L1::no_allocate.v4.u32 [%0], {%1,%2,%3,%4};" ::"l"(p), "r"(v.x), "r"(v.y), "r"(v.z), "r"(v.w) : "memory"); }
__device__ __forceinline__ uint4 ldg128(const void* p) { uint4 v; asm volatile("ld.relaxed.gpu.global.v4.u32 {%0,%1,%2,%3}, [%4];" : "=r"(v.x), "=r"(v.y), "=r"(v.z), "=r"(v.w) : "l"(p) : "memory"); return v; }
__device__ __forceinline__ void prefetch_tm(const CUtensorMap* tm) { asm volatile("prefetch.tensormap [%0];" ::"l"(tm) : "memory"); }
template <int N> __device__ __forceinline__ void wg_wait() { asm volatile("wgmma.wait_group.sync.aligned %0;" ::"n"(N) : "memory"); }
__device__ __forceinline__ void cluster_arrive() { asm volatile("barrier.cluster.arrive.relaxed.aligned;" ::: "memory"); }
__device__ __forceinline__ void cluster_wait() { asm volatile("barrier.cluster.wait.acquire.aligned;" ::: "memory"); }
__device__ __forceinline__ uint32_t pack_bf16(float lo, float hi) { uint32_t r; asm("cvt.rn.bf16x2.f32 %0, %1, %2;" : "=r"(r) : "f"(hi), "f"(lo)); return r; }
__device__ __forceinline__ float bf_lo(uint32_t v) { return __uint_as_float(v << 16); }
__device__ __forceinline__ float bf_hi(uint32_t v) { return __uint_as_float(v & 0xffff0000u); }
__device__ __forceinline__ uint32_t dup_hi(uint32_t v) { return __byte_perm(v, 0, 0x3232); }
__device__ __forceinline__ float bf_round(float x) { return __bfloat162float(__float2bfloat16_rn(x)); }
__device__ __forceinline__ uint32_t bf2_add(uint32_t a, uint32_t b) { uint32_t r; asm("add.rn.bf16x2 %0, %1, %2;" : "=r"(r) : "r"(a), "r"(b)); return r; }
__device__ __forceinline__ uint32_t bf2_mul(uint32_t a, uint32_t b) { uint32_t r; asm("mul.rn.bf16x2 %0, %1, %2;" : "=r"(r) : "r"(a), "r"(b)); return r; }
__device__ __forceinline__ uint32_t bf2_fma(uint32_t a, uint32_t b, uint32_t c) { uint32_t r; asm("fma.rn.bf16x2 %0, %1, %2, %3;" : "=r"(r) : "r"(a), "r"(b), "r"(c)); return r; }
__device__ __forceinline__ uint4 add8(uint4 a, uint4 b) { return make_uint4(bf2_add(a.x, b.x), bf2_add(a.y, b.y), bf2_add(a.z, b.z), bf2_add(a.w, b.w)); }
__device__ __forceinline__ uint4 fma8(uint32_t a, uint4 b, uint4 c) { return make_uint4(bf2_fma(a, b.x, c.x), bf2_fma(a, b.y, c.y), bf2_fma(a, b.z, c.z), bf2_fma(a, b.w, c.w)); }
__device__ __forceinline__ void stsm4(uint32_t a, uint32_t r0, uint32_t r1, uint32_t r2, uint32_t r3) {
  asm volatile("stmatrix.sync.aligned.m8n8.x4.shared.b16 [%0], {%1,%2,%3,%4};" ::"r"(a), "r"(r0), "r"(r1), "r"(r2), "r"(r3) : "memory");
}
__device__ __forceinline__ void ldsm4(uint32_t a, uint32_t (&r)[4]) {
  asm volatile("ldmatrix.sync.aligned.m8n8.x4.shared.b16 {%0,%1,%2,%3}, [%4];" : "=r"(r[0]), "=r"(r[1]), "=r"(r[2]), "=r"(r[3]) : "r"(a) : "memory");
}
__device__ __forceinline__ void ldsm4t(uint32_t a, uint32_t (&r)[4]) {
  asm volatile("ldmatrix.sync.aligned.m8n8.x4.trans.shared.b16 {%0,%1,%2,%3}, [%4];" : "=r"(r[0]), "=r"(r[1]), "=r"(r[2]), "=r"(r[3]) : "r"(a) : "memory");
}
__device__ __forceinline__ void mma16816(float (&c)[4], uint32_t a0, uint32_t a1, uint32_t a2, uint32_t a3, uint32_t b0, uint32_t b1) {
  asm volatile("mma.sync.aligned.m16n8k16.row.col.f32.bf16.bf16.f32 {%0,%1,%2,%3}, {%4,%5,%6,%7}, {%8,%9}, {%0,%1,%2,%3};"
               : "+f"(c[0]), "+f"(c[1]), "+f"(c[2]), "+f"(c[3]) : "r"(a0), "r"(a1), "r"(a2), "r"(a3), "r"(b0), "r"(b1));
}
__device__ __forceinline__ void mma1688(float (&c)[4], uint32_t a0, uint32_t a1, uint32_t b0) {
  asm volatile("mma.sync.aligned.m16n8k8.row.col.f32.bf16.bf16.f32 {%0,%1,%2,%3}, {%4,%5}, {%6}, {%0,%1,%2,%3};"
               : "+f"(c[0]), "+f"(c[1]), "+f"(c[2]), "+f"(c[3]) : "r"(a0), "r"(a1), "r"(b0));
}
__device__ __forceinline__ float ex2(float x) { float y; asm("ex2.approx.ftz.f32 %0, %1;" : "=f"(y) : "f"(x)); return y; }
__device__ __forceinline__ float sqrt_fast(float x) { float y; asm("sqrt.approx.f32 %0, %1;" : "=f"(y) : "f"(x)); return y; }
__device__ __forceinline__ float tanh_fast(float x) { float y; asm("tanh.approx.f32 %0, %1;" : "=f"(y) : "f"(x)); return y; }
__device__ __forceinline__ float rcp(float x) { float y; asm("rcp.approx.ftz.f32 %0, %1;" : "=f"(y) : "f"(x)); return y; }
__device__ __forceinline__ uint32_t opaque_zero() { uint32_t z; asm volatile("mov.u32 %0, %%ctaid.y;" : "=r"(z)); return z; }
__device__ __forceinline__ int fresh_tid() { int t; asm volatile("mov.u32 %0, %%tid.x;" : "=r"(t)); return t; }

__device__ __forceinline__ void first_kstep(float (&d)[128], uint32_t a, uint32_t b) {
  asm volatile("{\n.reg .u32 t;\n.reg .u64 da, db;\nwgmma.fence.sync.aligned;\n"
    "add.u32 t, %128, 0;\nmov.b64 da, {t, %130};\nadd.u32 t, %129, 0;\nmov.b64 db, {t, %130};\n"
    "wgmma.mma_async.sync.aligned.m64n256k16.f32.bf16.bf16 {%0, %1, %2, %3, %4, %5, %6, %7, %8, %9, %10, %11, %12, %13, %14, %15, %16, %17, %18, %19, %20, %21, %22, %23, %24, %25, %26, %27, %28, %29, %30, %31, %32, %33, %34, %35, %36, %37, %38, %39, %40, %41, %42, %43, %44, %45, %46, %47, %48, %49, %50, %51, %52, %53, %54, %55, %56, %57, %58, %59, %60, %61, %62, %63, %64, %65, %66, %67, %68, %69, %70, %71, %72, %73, %74, %75, %76, %77, %78, %79, %80, %81, %82, %83, %84, %85, %86, %87, %88, %89, %90, %91, %92, %93, %94, %95, %96, %97, %98, %99, %100, %101, %102, %103, %104, %105, %106, %107, %108, %109, %110, %111, %112, %113, %114, %115, %116, %117, %118, %119, %120, %121, %122, %123, %124, %125, %126, %127}, da, db, 0, 1, 1, 0, 1;\nwgmma.commit_group.sync.aligned;\n"
    "add.u32 t, %128, 2;\nmov.b64 da, {t, %130};\nadd.u32 t, %129, 128;\nmov.b64 db, {t, %130};\n"
    "wgmma.mma_async.sync.aligned.m64n256k16.f32.bf16.bf16 {%0, %1, %2, %3, %4, %5, %6, %7, %8, %9, %10, %11, %12, %13, %14, %15, %16, %17, %18, %19, %20, %21, %22, %23, %24, %25, %26, %27, %28, %29, %30, %31, %32, %33, %34, %35, %36, %37, %38, %39, %40, %41, %42, %43, %44, %45, %46, %47, %48, %49, %50, %51, %52, %53, %54, %55, %56, %57, %58, %59, %60, %61, %62, %63, %64, %65, %66, %67, %68, %69, %70, %71, %72, %73, %74, %75, %76, %77, %78, %79, %80, %81, %82, %83, %84, %85, %86, %87, %88, %89, %90, %91, %92, %93, %94, %95, %96, %97, %98, %99, %100, %101, %102, %103, %104, %105, %106, %107, %108, %109, %110, %111, %112, %113, %114, %115, %116, %117, %118, %119, %120, %121, %122, %123, %124, %125, %126, %127}, da, db, 1, 1, 1, 0, 1;\n"
    "add.u32 t, %128, 4;\nmov.b64 da, {t, %130};\nadd.u32 t, %129, 1024;\nmov.b64 db, {t, %130};\n"
    "wgmma.mma_async.sync.aligned.m64n256k16.f32.bf16.bf16 {%0, %1, %2, %3, %4, %5, %6, %7, %8, %9, %10, %11, %12, %13, %14, %15, %16, %17, %18, %19, %20, %21, %22, %23, %24, %25, %26, %27, %28, %29, %30, %31, %32, %33, %34, %35, %36, %37, %38, %39, %40, %41, %42, %43, %44, %45, %46, %47, %48, %49, %50, %51, %52, %53, %54, %55, %56, %57, %58, %59, %60, %61, %62, %63, %64, %65, %66, %67, %68, %69, %70, %71, %72, %73, %74, %75, %76, %77, %78, %79, %80, %81, %82, %83, %84, %85, %86, %87, %88, %89, %90, %91, %92, %93, %94, %95, %96, %97, %98, %99, %100, %101, %102, %103, %104, %105, %106, %107, %108, %109, %110, %111, %112, %113, %114, %115, %116, %117, %118, %119, %120, %121, %122, %123, %124, %125, %126, %127}, da, db, 1, 1, 1, 0, 1;\n"
    "add.u32 t, %128, 6;\nmov.b64 da, {t, %130};\nadd.u32 t, %129, 1152;\nmov.b64 db, {t, %130};\n"
    "wgmma.mma_async.sync.aligned.m64n256k16.f32.bf16.bf16 {%0, %1, %2, %3, %4, %5, %6, %7, %8, %9, %10, %11, %12, %13, %14, %15, %16, %17, %18, %19, %20, %21, %22, %23, %24, %25, %26, %27, %28, %29, %30, %31, %32, %33, %34, %35, %36, %37, %38, %39, %40, %41, %42, %43, %44, %45, %46, %47, %48, %49, %50, %51, %52, %53, %54, %55, %56, %57, %58, %59, %60, %61, %62, %63, %64, %65, %66, %67, %68, %69, %70, %71, %72, %73, %74, %75, %76, %77, %78, %79, %80, %81, %82, %83, %84, %85, %86, %87, %88, %89, %90, %91, %92, %93, %94, %95, %96, %97, %98, %99, %100, %101, %102, %103, %104, %105, %106, %107, %108, %109, %110, %111, %112, %113, %114, %115, %116, %117, %118, %119, %120, %121, %122, %123, %124, %125, %126, %127}, da, db, 1, 1, 1, 0, 1;\nwgmma.commit_group.sync.aligned;\n"
    "}\n"
    : "=f"(d[0]), "=f"(d[1]), "=f"(d[2]), "=f"(d[3]), "=f"(d[4]), "=f"(d[5]), "=f"(d[6]), "=f"(d[7]), "=f"(d[8]), "=f"(d[9]), "=f"(d[10]), "=f"(d[11]), "=f"(d[12]), "=f"(d[13]), "=f"(d[14]), "=f"(d[15]), "=f"(d[16]), "=f"(d[17]), "=f"(d[18]), "=f"(d[19]), "=f"(d[20]), "=f"(d[21]), "=f"(d[22]), "=f"(d[23]), "=f"(d[24]), "=f"(d[25]), "=f"(d[26]), "=f"(d[27]), "=f"(d[28]), "=f"(d[29]), "=f"(d[30]), "=f"(d[31]), "=f"(d[32]), "=f"(d[33]), "=f"(d[34]), "=f"(d[35]), "=f"(d[36]), "=f"(d[37]), "=f"(d[38]), "=f"(d[39]), "=f"(d[40]), "=f"(d[41]), "=f"(d[42]), "=f"(d[43]), "=f"(d[44]), "=f"(d[45]), "=f"(d[46]), "=f"(d[47]), "=f"(d[48]), "=f"(d[49]), "=f"(d[50]), "=f"(d[51]), "=f"(d[52]), "=f"(d[53]), "=f"(d[54]), "=f"(d[55]), "=f"(d[56]), "=f"(d[57]), "=f"(d[58]), "=f"(d[59]), "=f"(d[60]), "=f"(d[61]), "=f"(d[62]), "=f"(d[63]), "=f"(d[64]), "=f"(d[65]), "=f"(d[66]), "=f"(d[67]), "=f"(d[68]), "=f"(d[69]), "=f"(d[70]), "=f"(d[71]), "=f"(d[72]), "=f"(d[73]), "=f"(d[74]), "=f"(d[75]), "=f"(d[76]), "=f"(d[77]), "=f"(d[78]), "=f"(d[79]), "=f"(d[80]), "=f"(d[81]), "=f"(d[82]), "=f"(d[83]), "=f"(d[84]), "=f"(d[85]), "=f"(d[86]), "=f"(d[87]), "=f"(d[88]), "=f"(d[89]), "=f"(d[90]), "=f"(d[91]), "=f"(d[92]), "=f"(d[93]), "=f"(d[94]), "=f"(d[95]), "=f"(d[96]), "=f"(d[97]), "=f"(d[98]), "=f"(d[99]), "=f"(d[100]), "=f"(d[101]), "=f"(d[102]), "=f"(d[103]), "=f"(d[104]), "=f"(d[105]), "=f"(d[106]), "=f"(d[107]), "=f"(d[108]), "=f"(d[109]), "=f"(d[110]), "=f"(d[111]), "=f"(d[112]), "=f"(d[113]), "=f"(d[114]), "=f"(d[115]), "=f"(d[116]), "=f"(d[117]), "=f"(d[118]), "=f"(d[119]), "=f"(d[120]), "=f"(d[121]), "=f"(d[122]), "=f"(d[123]), "=f"(d[124]), "=f"(d[125]), "=f"(d[126]), "=f"(d[127])
    : "r"(a), "r"(b), "n"(0x40000040) : "memory");
}
__device__ __forceinline__ void kstep(float (&d)[128], uint32_t a, uint32_t b) {
  asm volatile("{\n.reg .u32 t;\n.reg .u64 da, db;\nwgmma.fence.sync.aligned;\n"
    "add.u32 t, %128, 0;\nmov.b64 da, {t, %130};\nadd.u32 t, %129, 0;\nmov.b64 db, {t, %130};\n"
    "wgmma.mma_async.sync.aligned.m64n256k16.f32.bf16.bf16 {%0, %1, %2, %3, %4, %5, %6, %7, %8, %9, %10, %11, %12, %13, %14, %15, %16, %17, %18, %19, %20, %21, %22, %23, %24, %25, %26, %27, %28, %29, %30, %31, %32, %33, %34, %35, %36, %37, %38, %39, %40, %41, %42, %43, %44, %45, %46, %47, %48, %49, %50, %51, %52, %53, %54, %55, %56, %57, %58, %59, %60, %61, %62, %63, %64, %65, %66, %67, %68, %69, %70, %71, %72, %73, %74, %75, %76, %77, %78, %79, %80, %81, %82, %83, %84, %85, %86, %87, %88, %89, %90, %91, %92, %93, %94, %95, %96, %97, %98, %99, %100, %101, %102, %103, %104, %105, %106, %107, %108, %109, %110, %111, %112, %113, %114, %115, %116, %117, %118, %119, %120, %121, %122, %123, %124, %125, %126, %127}, da, db, 1, 1, 1, 0, 1;\nwgmma.commit_group.sync.aligned;\n"
    "add.u32 t, %128, 2;\nmov.b64 da, {t, %130};\nadd.u32 t, %129, 128;\nmov.b64 db, {t, %130};\n"
    "wgmma.mma_async.sync.aligned.m64n256k16.f32.bf16.bf16 {%0, %1, %2, %3, %4, %5, %6, %7, %8, %9, %10, %11, %12, %13, %14, %15, %16, %17, %18, %19, %20, %21, %22, %23, %24, %25, %26, %27, %28, %29, %30, %31, %32, %33, %34, %35, %36, %37, %38, %39, %40, %41, %42, %43, %44, %45, %46, %47, %48, %49, %50, %51, %52, %53, %54, %55, %56, %57, %58, %59, %60, %61, %62, %63, %64, %65, %66, %67, %68, %69, %70, %71, %72, %73, %74, %75, %76, %77, %78, %79, %80, %81, %82, %83, %84, %85, %86, %87, %88, %89, %90, %91, %92, %93, %94, %95, %96, %97, %98, %99, %100, %101, %102, %103, %104, %105, %106, %107, %108, %109, %110, %111, %112, %113, %114, %115, %116, %117, %118, %119, %120, %121, %122, %123, %124, %125, %126, %127}, da, db, 1, 1, 1, 0, 1;\n"
    "add.u32 t, %128, 4;\nmov.b64 da, {t, %130};\nadd.u32 t, %129, 1024;\nmov.b64 db, {t, %130};\n"
    "wgmma.mma_async.sync.aligned.m64n256k16.f32.bf16.bf16 {%0, %1, %2, %3, %4, %5, %6, %7, %8, %9, %10, %11, %12, %13, %14, %15, %16, %17, %18, %19, %20, %21, %22, %23, %24, %25, %26, %27, %28, %29, %30, %31, %32, %33, %34, %35, %36, %37, %38, %39, %40, %41, %42, %43, %44, %45, %46, %47, %48, %49, %50, %51, %52, %53, %54, %55, %56, %57, %58, %59, %60, %61, %62, %63, %64, %65, %66, %67, %68, %69, %70, %71, %72, %73, %74, %75, %76, %77, %78, %79, %80, %81, %82, %83, %84, %85, %86, %87, %88, %89, %90, %91, %92, %93, %94, %95, %96, %97, %98, %99, %100, %101, %102, %103, %104, %105, %106, %107, %108, %109, %110, %111, %112, %113, %114, %115, %116, %117, %118, %119, %120, %121, %122, %123, %124, %125, %126, %127}, da, db, 1, 1, 1, 0, 1;\n"
    "add.u32 t, %128, 6;\nmov.b64 da, {t, %130};\nadd.u32 t, %129, 1152;\nmov.b64 db, {t, %130};\n"
    "wgmma.mma_async.sync.aligned.m64n256k16.f32.bf16.bf16 {%0, %1, %2, %3, %4, %5, %6, %7, %8, %9, %10, %11, %12, %13, %14, %15, %16, %17, %18, %19, %20, %21, %22, %23, %24, %25, %26, %27, %28, %29, %30, %31, %32, %33, %34, %35, %36, %37, %38, %39, %40, %41, %42, %43, %44, %45, %46, %47, %48, %49, %50, %51, %52, %53, %54, %55, %56, %57, %58, %59, %60, %61, %62, %63, %64, %65, %66, %67, %68, %69, %70, %71, %72, %73, %74, %75, %76, %77, %78, %79, %80, %81, %82, %83, %84, %85, %86, %87, %88, %89, %90, %91, %92, %93, %94, %95, %96, %97, %98, %99, %100, %101, %102, %103, %104, %105, %106, %107, %108, %109, %110, %111, %112, %113, %114, %115, %116, %117, %118, %119, %120, %121, %122, %123, %124, %125, %126, %127}, da, db, 1, 1, 1, 0, 1;\nwgmma.commit_group.sync.aligned;\n"
    "}\n"
    : "+f"(d[0]), "+f"(d[1]), "+f"(d[2]), "+f"(d[3]), "+f"(d[4]), "+f"(d[5]), "+f"(d[6]), "+f"(d[7]), "+f"(d[8]), "+f"(d[9]), "+f"(d[10]), "+f"(d[11]), "+f"(d[12]), "+f"(d[13]), "+f"(d[14]), "+f"(d[15]), "+f"(d[16]), "+f"(d[17]), "+f"(d[18]), "+f"(d[19]), "+f"(d[20]), "+f"(d[21]), "+f"(d[22]), "+f"(d[23]), "+f"(d[24]), "+f"(d[25]), "+f"(d[26]), "+f"(d[27]), "+f"(d[28]), "+f"(d[29]), "+f"(d[30]), "+f"(d[31]), "+f"(d[32]), "+f"(d[33]), "+f"(d[34]), "+f"(d[35]), "+f"(d[36]), "+f"(d[37]), "+f"(d[38]), "+f"(d[39]), "+f"(d[40]), "+f"(d[41]), "+f"(d[42]), "+f"(d[43]), "+f"(d[44]), "+f"(d[45]), "+f"(d[46]), "+f"(d[47]), "+f"(d[48]), "+f"(d[49]), "+f"(d[50]), "+f"(d[51]), "+f"(d[52]), "+f"(d[53]), "+f"(d[54]), "+f"(d[55]), "+f"(d[56]), "+f"(d[57]), "+f"(d[58]), "+f"(d[59]), "+f"(d[60]), "+f"(d[61]), "+f"(d[62]), "+f"(d[63]), "+f"(d[64]), "+f"(d[65]), "+f"(d[66]), "+f"(d[67]), "+f"(d[68]), "+f"(d[69]), "+f"(d[70]), "+f"(d[71]), "+f"(d[72]), "+f"(d[73]), "+f"(d[74]), "+f"(d[75]), "+f"(d[76]), "+f"(d[77]), "+f"(d[78]), "+f"(d[79]), "+f"(d[80]), "+f"(d[81]), "+f"(d[82]), "+f"(d[83]), "+f"(d[84]), "+f"(d[85]), "+f"(d[86]), "+f"(d[87]), "+f"(d[88]), "+f"(d[89]), "+f"(d[90]), "+f"(d[91]), "+f"(d[92]), "+f"(d[93]), "+f"(d[94]), "+f"(d[95]), "+f"(d[96]), "+f"(d[97]), "+f"(d[98]), "+f"(d[99]), "+f"(d[100]), "+f"(d[101]), "+f"(d[102]), "+f"(d[103]), "+f"(d[104]), "+f"(d[105]), "+f"(d[106]), "+f"(d[107]), "+f"(d[108]), "+f"(d[109]), "+f"(d[110]), "+f"(d[111]), "+f"(d[112]), "+f"(d[113]), "+f"(d[114]), "+f"(d[115]), "+f"(d[116]), "+f"(d[117]), "+f"(d[118]), "+f"(d[119]), "+f"(d[120]), "+f"(d[121]), "+f"(d[122]), "+f"(d[123]), "+f"(d[124]), "+f"(d[125]), "+f"(d[126]), "+f"(d[127])
    : "r"(a), "r"(b), "n"(0x40000040) : "memory");
}
__device__ __forceinline__ void first_kstep(float (&d)[96], uint32_t a, uint32_t b) {
  asm volatile("{\n.reg .u32 t;\n.reg .u64 da, db;\nwgmma.fence.sync.aligned;\n"
    "add.u32 t, %96, 0;\nmov.b64 da, {t, %98};\nadd.u32 t, %97, 0;\nmov.b64 db, {t, %98};\n"
    "wgmma.mma_async.sync.aligned.m64n192k16.f32.bf16.bf16 {%0, %1, %2, %3, %4, %5, %6, %7, %8, %9, %10, %11, %12, %13, %14, %15, %16, %17, %18, %19, %20, %21, %22, %23, %24, %25, %26, %27, %28, %29, %30, %31, %32, %33, %34, %35, %36, %37, %38, %39, %40, %41, %42, %43, %44, %45, %46, %47, %48, %49, %50, %51, %52, %53, %54, %55, %56, %57, %58, %59, %60, %61, %62, %63, %64, %65, %66, %67, %68, %69, %70, %71, %72, %73, %74, %75, %76, %77, %78, %79, %80, %81, %82, %83, %84, %85, %86, %87, %88, %89, %90, %91, %92, %93, %94, %95}, da, db, 0, 1, 1, 0, 1;\nwgmma.commit_group.sync.aligned;\n"
    "add.u32 t, %96, 2;\nmov.b64 da, {t, %98};\nadd.u32 t, %97, 128;\nmov.b64 db, {t, %98};\n"
    "wgmma.mma_async.sync.aligned.m64n192k16.f32.bf16.bf16 {%0, %1, %2, %3, %4, %5, %6, %7, %8, %9, %10, %11, %12, %13, %14, %15, %16, %17, %18, %19, %20, %21, %22, %23, %24, %25, %26, %27, %28, %29, %30, %31, %32, %33, %34, %35, %36, %37, %38, %39, %40, %41, %42, %43, %44, %45, %46, %47, %48, %49, %50, %51, %52, %53, %54, %55, %56, %57, %58, %59, %60, %61, %62, %63, %64, %65, %66, %67, %68, %69, %70, %71, %72, %73, %74, %75, %76, %77, %78, %79, %80, %81, %82, %83, %84, %85, %86, %87, %88, %89, %90, %91, %92, %93, %94, %95}, da, db, 1, 1, 1, 0, 1;\n"
    "add.u32 t, %96, 4;\nmov.b64 da, {t, %98};\nadd.u32 t, %97, 1024;\nmov.b64 db, {t, %98};\n"
    "wgmma.mma_async.sync.aligned.m64n192k16.f32.bf16.bf16 {%0, %1, %2, %3, %4, %5, %6, %7, %8, %9, %10, %11, %12, %13, %14, %15, %16, %17, %18, %19, %20, %21, %22, %23, %24, %25, %26, %27, %28, %29, %30, %31, %32, %33, %34, %35, %36, %37, %38, %39, %40, %41, %42, %43, %44, %45, %46, %47, %48, %49, %50, %51, %52, %53, %54, %55, %56, %57, %58, %59, %60, %61, %62, %63, %64, %65, %66, %67, %68, %69, %70, %71, %72, %73, %74, %75, %76, %77, %78, %79, %80, %81, %82, %83, %84, %85, %86, %87, %88, %89, %90, %91, %92, %93, %94, %95}, da, db, 1, 1, 1, 0, 1;\n"
    "add.u32 t, %96, 6;\nmov.b64 da, {t, %98};\nadd.u32 t, %97, 1152;\nmov.b64 db, {t, %98};\n"
    "wgmma.mma_async.sync.aligned.m64n192k16.f32.bf16.bf16 {%0, %1, %2, %3, %4, %5, %6, %7, %8, %9, %10, %11, %12, %13, %14, %15, %16, %17, %18, %19, %20, %21, %22, %23, %24, %25, %26, %27, %28, %29, %30, %31, %32, %33, %34, %35, %36, %37, %38, %39, %40, %41, %42, %43, %44, %45, %46, %47, %48, %49, %50, %51, %52, %53, %54, %55, %56, %57, %58, %59, %60, %61, %62, %63, %64, %65, %66, %67, %68, %69, %70, %71, %72, %73, %74, %75, %76, %77, %78, %79, %80, %81, %82, %83, %84, %85, %86, %87, %88, %89, %90, %91, %92, %93, %94, %95}, da, db, 1, 1, 1, 0, 1;\nwgmma.commit_group.sync.aligned;\n"
    "}\n"
    : "=f"(d[0]), "=f"(d[1]), "=f"(d[2]), "=f"(d[3]), "=f"(d[4]), "=f"(d[5]), "=f"(d[6]), "=f"(d[7]), "=f"(d[8]), "=f"(d[9]), "=f"(d[10]), "=f"(d[11]), "=f"(d[12]), "=f"(d[13]), "=f"(d[14]), "=f"(d[15]), "=f"(d[16]), "=f"(d[17]), "=f"(d[18]), "=f"(d[19]), "=f"(d[20]), "=f"(d[21]), "=f"(d[22]), "=f"(d[23]), "=f"(d[24]), "=f"(d[25]), "=f"(d[26]), "=f"(d[27]), "=f"(d[28]), "=f"(d[29]), "=f"(d[30]), "=f"(d[31]), "=f"(d[32]), "=f"(d[33]), "=f"(d[34]), "=f"(d[35]), "=f"(d[36]), "=f"(d[37]), "=f"(d[38]), "=f"(d[39]), "=f"(d[40]), "=f"(d[41]), "=f"(d[42]), "=f"(d[43]), "=f"(d[44]), "=f"(d[45]), "=f"(d[46]), "=f"(d[47]), "=f"(d[48]), "=f"(d[49]), "=f"(d[50]), "=f"(d[51]), "=f"(d[52]), "=f"(d[53]), "=f"(d[54]), "=f"(d[55]), "=f"(d[56]), "=f"(d[57]), "=f"(d[58]), "=f"(d[59]), "=f"(d[60]), "=f"(d[61]), "=f"(d[62]), "=f"(d[63]), "=f"(d[64]), "=f"(d[65]), "=f"(d[66]), "=f"(d[67]), "=f"(d[68]), "=f"(d[69]), "=f"(d[70]), "=f"(d[71]), "=f"(d[72]), "=f"(d[73]), "=f"(d[74]), "=f"(d[75]), "=f"(d[76]), "=f"(d[77]), "=f"(d[78]), "=f"(d[79]), "=f"(d[80]), "=f"(d[81]), "=f"(d[82]), "=f"(d[83]), "=f"(d[84]), "=f"(d[85]), "=f"(d[86]), "=f"(d[87]), "=f"(d[88]), "=f"(d[89]), "=f"(d[90]), "=f"(d[91]), "=f"(d[92]), "=f"(d[93]), "=f"(d[94]), "=f"(d[95])
    : "r"(a), "r"(b), "n"(0x40000040) : "memory");
}
__device__ __forceinline__ void kstep(float (&d)[96], uint32_t a, uint32_t b) {
  asm volatile("{\n.reg .u32 t;\n.reg .u64 da, db;\nwgmma.fence.sync.aligned;\n"
    "add.u32 t, %96, 0;\nmov.b64 da, {t, %98};\nadd.u32 t, %97, 0;\nmov.b64 db, {t, %98};\n"
    "wgmma.mma_async.sync.aligned.m64n192k16.f32.bf16.bf16 {%0, %1, %2, %3, %4, %5, %6, %7, %8, %9, %10, %11, %12, %13, %14, %15, %16, %17, %18, %19, %20, %21, %22, %23, %24, %25, %26, %27, %28, %29, %30, %31, %32, %33, %34, %35, %36, %37, %38, %39, %40, %41, %42, %43, %44, %45, %46, %47, %48, %49, %50, %51, %52, %53, %54, %55, %56, %57, %58, %59, %60, %61, %62, %63, %64, %65, %66, %67, %68, %69, %70, %71, %72, %73, %74, %75, %76, %77, %78, %79, %80, %81, %82, %83, %84, %85, %86, %87, %88, %89, %90, %91, %92, %93, %94, %95}, da, db, 1, 1, 1, 0, 1;\nwgmma.commit_group.sync.aligned;\n"
    "add.u32 t, %96, 2;\nmov.b64 da, {t, %98};\nadd.u32 t, %97, 128;\nmov.b64 db, {t, %98};\n"
    "wgmma.mma_async.sync.aligned.m64n192k16.f32.bf16.bf16 {%0, %1, %2, %3, %4, %5, %6, %7, %8, %9, %10, %11, %12, %13, %14, %15, %16, %17, %18, %19, %20, %21, %22, %23, %24, %25, %26, %27, %28, %29, %30, %31, %32, %33, %34, %35, %36, %37, %38, %39, %40, %41, %42, %43, %44, %45, %46, %47, %48, %49, %50, %51, %52, %53, %54, %55, %56, %57, %58, %59, %60, %61, %62, %63, %64, %65, %66, %67, %68, %69, %70, %71, %72, %73, %74, %75, %76, %77, %78, %79, %80, %81, %82, %83, %84, %85, %86, %87, %88, %89, %90, %91, %92, %93, %94, %95}, da, db, 1, 1, 1, 0, 1;\n"
    "add.u32 t, %96, 4;\nmov.b64 da, {t, %98};\nadd.u32 t, %97, 1024;\nmov.b64 db, {t, %98};\n"
    "wgmma.mma_async.sync.aligned.m64n192k16.f32.bf16.bf16 {%0, %1, %2, %3, %4, %5, %6, %7, %8, %9, %10, %11, %12, %13, %14, %15, %16, %17, %18, %19, %20, %21, %22, %23, %24, %25, %26, %27, %28, %29, %30, %31, %32, %33, %34, %35, %36, %37, %38, %39, %40, %41, %42, %43, %44, %45, %46, %47, %48, %49, %50, %51, %52, %53, %54, %55, %56, %57, %58, %59, %60, %61, %62, %63, %64, %65, %66, %67, %68, %69, %70, %71, %72, %73, %74, %75, %76, %77, %78, %79, %80, %81, %82, %83, %84, %85, %86, %87, %88, %89, %90, %91, %92, %93, %94, %95}, da, db, 1, 1, 1, 0, 1;\n"
    "add.u32 t, %96, 6;\nmov.b64 da, {t, %98};\nadd.u32 t, %97, 1152;\nmov.b64 db, {t, %98};\n"
    "wgmma.mma_async.sync.aligned.m64n192k16.f32.bf16.bf16 {%0, %1, %2, %3, %4, %5, %6, %7, %8, %9, %10, %11, %12, %13, %14, %15, %16, %17, %18, %19, %20, %21, %22, %23, %24, %25, %26, %27, %28, %29, %30, %31, %32, %33, %34, %35, %36, %37, %38, %39, %40, %41, %42, %43, %44, %45, %46, %47, %48, %49, %50, %51, %52, %53, %54, %55, %56, %57, %58, %59, %60, %61, %62, %63, %64, %65, %66, %67, %68, %69, %70, %71, %72, %73, %74, %75, %76, %77, %78, %79, %80, %81, %82, %83, %84, %85, %86, %87, %88, %89, %90, %91, %92, %93, %94, %95}, da, db, 1, 1, 1, 0, 1;\nwgmma.commit_group.sync.aligned;\n"
    "}\n"
    : "+f"(d[0]), "+f"(d[1]), "+f"(d[2]), "+f"(d[3]), "+f"(d[4]), "+f"(d[5]), "+f"(d[6]), "+f"(d[7]), "+f"(d[8]), "+f"(d[9]), "+f"(d[10]), "+f"(d[11]), "+f"(d[12]), "+f"(d[13]), "+f"(d[14]), "+f"(d[15]), "+f"(d[16]), "+f"(d[17]), "+f"(d[18]), "+f"(d[19]), "+f"(d[20]), "+f"(d[21]), "+f"(d[22]), "+f"(d[23]), "+f"(d[24]), "+f"(d[25]), "+f"(d[26]), "+f"(d[27]), "+f"(d[28]), "+f"(d[29]), "+f"(d[30]), "+f"(d[31]), "+f"(d[32]), "+f"(d[33]), "+f"(d[34]), "+f"(d[35]), "+f"(d[36]), "+f"(d[37]), "+f"(d[38]), "+f"(d[39]), "+f"(d[40]), "+f"(d[41]), "+f"(d[42]), "+f"(d[43]), "+f"(d[44]), "+f"(d[45]), "+f"(d[46]), "+f"(d[47]), "+f"(d[48]), "+f"(d[49]), "+f"(d[50]), "+f"(d[51]), "+f"(d[52]), "+f"(d[53]), "+f"(d[54]), "+f"(d[55]), "+f"(d[56]), "+f"(d[57]), "+f"(d[58]), "+f"(d[59]), "+f"(d[60]), "+f"(d[61]), "+f"(d[62]), "+f"(d[63]), "+f"(d[64]), "+f"(d[65]), "+f"(d[66]), "+f"(d[67]), "+f"(d[68]), "+f"(d[69]), "+f"(d[70]), "+f"(d[71]), "+f"(d[72]), "+f"(d[73]), "+f"(d[74]), "+f"(d[75]), "+f"(d[76]), "+f"(d[77]), "+f"(d[78]), "+f"(d[79]), "+f"(d[80]), "+f"(d[81]), "+f"(d[82]), "+f"(d[83]), "+f"(d[84]), "+f"(d[85]), "+f"(d[86]), "+f"(d[87]), "+f"(d[88]), "+f"(d[89]), "+f"(d[90]), "+f"(d[91]), "+f"(d[92]), "+f"(d[93]), "+f"(d[94]), "+f"(d[95])
    : "r"(a), "r"(b), "n"(0x40000040) : "memory");
}
__device__ __forceinline__ void half_kstep0(float (&d)[64], uint32_t a, uint32_t b) {
  asm volatile("{\n.reg .u32 t;\n.reg .u64 da, db;\nwgmma.fence.sync.aligned;\n"
    "add.u32 t, %64, 0;\nmov.b64 da, {t, %66};\nadd.u32 t, %65, 0;\nmov.b64 db, {t, %66};\n"
    "wgmma.mma_async.sync.aligned.m64n128k16.f32.bf16.bf16 {%0, %1, %2, %3, %4, %5, %6, %7, %8, %9, %10, %11, %12, %13, %14, %15, %16, %17, %18, %19, %20, %21, %22, %23, %24, %25, %26, %27, %28, %29, %30, %31, %32, %33, %34, %35, %36, %37, %38, %39, %40, %41, %42, %43, %44, %45, %46, %47, %48, %49, %50, %51, %52, %53, %54, %55, %56, %57, %58, %59, %60, %61, %62, %63}, da, db, 1, 1, 1, 0, 1;\n"
    "add.u32 t, %64, 2;\nmov.b64 da, {t, %66};\nadd.u32 t, %65, 128;\nmov.b64 db, {t, %66};\n"
    "wgmma.mma_async.sync.aligned.m64n128k16.f32.bf16.bf16 {%0, %1, %2, %3, %4, %5, %6, %7, %8, %9, %10, %11, %12, %13, %14, %15, %16, %17, %18, %19, %20, %21, %22, %23, %24, %25, %26, %27, %28, %29, %30, %31, %32, %33, %34, %35, %36, %37, %38, %39, %40, %41, %42, %43, %44, %45, %46, %47, %48, %49, %50, %51, %52, %53, %54, %55, %56, %57, %58, %59, %60, %61, %62, %63}, da, db, 1, 1, 1, 0, 1;\n"
    "add.u32 t, %64, 4;\nmov.b64 da, {t, %66};\nadd.u32 t, %65, 1024;\nmov.b64 db, {t, %66};\n"
    "wgmma.mma_async.sync.aligned.m64n128k16.f32.bf16.bf16 {%0, %1, %2, %3, %4, %5, %6, %7, %8, %9, %10, %11, %12, %13, %14, %15, %16, %17, %18, %19, %20, %21, %22, %23, %24, %25, %26, %27, %28, %29, %30, %31, %32, %33, %34, %35, %36, %37, %38, %39, %40, %41, %42, %43, %44, %45, %46, %47, %48, %49, %50, %51, %52, %53, %54, %55, %56, %57, %58, %59, %60, %61, %62, %63}, da, db, 1, 1, 1, 0, 1;\n"
    "add.u32 t, %64, 6;\nmov.b64 da, {t, %66};\nadd.u32 t, %65, 1152;\nmov.b64 db, {t, %66};\n"
    "wgmma.mma_async.sync.aligned.m64n128k16.f32.bf16.bf16 {%0, %1, %2, %3, %4, %5, %6, %7, %8, %9, %10, %11, %12, %13, %14, %15, %16, %17, %18, %19, %20, %21, %22, %23, %24, %25, %26, %27, %28, %29, %30, %31, %32, %33, %34, %35, %36, %37, %38, %39, %40, %41, %42, %43, %44, %45, %46, %47, %48, %49, %50, %51, %52, %53, %54, %55, %56, %57, %58, %59, %60, %61, %62, %63}, da, db, 1, 1, 1, 0, 1;\n"
    "wgmma.commit_group.sync.aligned;\n}\n"
    : "+f"(d[0]), "+f"(d[1]), "+f"(d[2]), "+f"(d[3]), "+f"(d[4]), "+f"(d[5]), "+f"(d[6]), "+f"(d[7]), "+f"(d[8]), "+f"(d[9]), "+f"(d[10]), "+f"(d[11]), "+f"(d[12]), "+f"(d[13]), "+f"(d[14]), "+f"(d[15]), "+f"(d[16]), "+f"(d[17]), "+f"(d[18]), "+f"(d[19]), "+f"(d[20]), "+f"(d[21]), "+f"(d[22]), "+f"(d[23]), "+f"(d[24]), "+f"(d[25]), "+f"(d[26]), "+f"(d[27]), "+f"(d[28]), "+f"(d[29]), "+f"(d[30]), "+f"(d[31]), "+f"(d[32]), "+f"(d[33]), "+f"(d[34]), "+f"(d[35]), "+f"(d[36]), "+f"(d[37]), "+f"(d[38]), "+f"(d[39]), "+f"(d[40]), "+f"(d[41]), "+f"(d[42]), "+f"(d[43]), "+f"(d[44]), "+f"(d[45]), "+f"(d[46]), "+f"(d[47]), "+f"(d[48]), "+f"(d[49]), "+f"(d[50]), "+f"(d[51]), "+f"(d[52]), "+f"(d[53]), "+f"(d[54]), "+f"(d[55]), "+f"(d[56]), "+f"(d[57]), "+f"(d[58]), "+f"(d[59]), "+f"(d[60]), "+f"(d[61]), "+f"(d[62]), "+f"(d[63])
    : "r"(a), "r"(b), "n"(0x40000040) : "memory");
}
__device__ __forceinline__ void half_kstep1(float (&d)[64], uint32_t a, uint32_t b) {
  asm volatile("{\n.reg .u32 t;\n.reg .u64 da, db;\nwgmma.fence.sync.aligned;\n"
    "add.u32 t, %64, 0;\nmov.b64 da, {t, %66};\nadd.u32 t, %65, 512;\nmov.b64 db, {t, %66};\n"
    "wgmma.mma_async.sync.aligned.m64n128k16.f32.bf16.bf16 {%0, %1, %2, %3, %4, %5, %6, %7, %8, %9, %10, %11, %12, %13, %14, %15, %16, %17, %18, %19, %20, %21, %22, %23, %24, %25, %26, %27, %28, %29, %30, %31, %32, %33, %34, %35, %36, %37, %38, %39, %40, %41, %42, %43, %44, %45, %46, %47, %48, %49, %50, %51, %52, %53, %54, %55, %56, %57, %58, %59, %60, %61, %62, %63}, da, db, 1, 1, 1, 0, 1;\n"
    "add.u32 t, %64, 2;\nmov.b64 da, {t, %66};\nadd.u32 t, %65, 640;\nmov.b64 db, {t, %66};\n"
    "wgmma.mma_async.sync.aligned.m64n128k16.f32.bf16.bf16 {%0, %1, %2, %3, %4, %5, %6, %7, %8, %9, %10, %11, %12, %13, %14, %15, %16, %17, %18, %19, %20, %21, %22, %23, %24, %25, %26, %27, %28, %29, %30, %31, %32, %33, %34, %35, %36, %37, %38, %39, %40, %41, %42, %43, %44, %45, %46, %47, %48, %49, %50, %51, %52, %53, %54, %55, %56, %57, %58, %59, %60, %61, %62, %63}, da, db, 1, 1, 1, 0, 1;\n"
    "add.u32 t, %64, 4;\nmov.b64 da, {t, %66};\nadd.u32 t, %65, 1536;\nmov.b64 db, {t, %66};\n"
    "wgmma.mma_async.sync.aligned.m64n128k16.f32.bf16.bf16 {%0, %1, %2, %3, %4, %5, %6, %7, %8, %9, %10, %11, %12, %13, %14, %15, %16, %17, %18, %19, %20, %21, %22, %23, %24, %25, %26, %27, %28, %29, %30, %31, %32, %33, %34, %35, %36, %37, %38, %39, %40, %41, %42, %43, %44, %45, %46, %47, %48, %49, %50, %51, %52, %53, %54, %55, %56, %57, %58, %59, %60, %61, %62, %63}, da, db, 1, 1, 1, 0, 1;\n"
    "add.u32 t, %64, 6;\nmov.b64 da, {t, %66};\nadd.u32 t, %65, 1664;\nmov.b64 db, {t, %66};\n"
    "wgmma.mma_async.sync.aligned.m64n128k16.f32.bf16.bf16 {%0, %1, %2, %3, %4, %5, %6, %7, %8, %9, %10, %11, %12, %13, %14, %15, %16, %17, %18, %19, %20, %21, %22, %23, %24, %25, %26, %27, %28, %29, %30, %31, %32, %33, %34, %35, %36, %37, %38, %39, %40, %41, %42, %43, %44, %45, %46, %47, %48, %49, %50, %51, %52, %53, %54, %55, %56, %57, %58, %59, %60, %61, %62, %63}, da, db, 1, 1, 1, 0, 1;\n"
    "wgmma.commit_group.sync.aligned;\n}\n"
    : "+f"(d[0]), "+f"(d[1]), "+f"(d[2]), "+f"(d[3]), "+f"(d[4]), "+f"(d[5]), "+f"(d[6]), "+f"(d[7]), "+f"(d[8]), "+f"(d[9]), "+f"(d[10]), "+f"(d[11]), "+f"(d[12]), "+f"(d[13]), "+f"(d[14]), "+f"(d[15]), "+f"(d[16]), "+f"(d[17]), "+f"(d[18]), "+f"(d[19]), "+f"(d[20]), "+f"(d[21]), "+f"(d[22]), "+f"(d[23]), "+f"(d[24]), "+f"(d[25]), "+f"(d[26]), "+f"(d[27]), "+f"(d[28]), "+f"(d[29]), "+f"(d[30]), "+f"(d[31]), "+f"(d[32]), "+f"(d[33]), "+f"(d[34]), "+f"(d[35]), "+f"(d[36]), "+f"(d[37]), "+f"(d[38]), "+f"(d[39]), "+f"(d[40]), "+f"(d[41]), "+f"(d[42]), "+f"(d[43]), "+f"(d[44]), "+f"(d[45]), "+f"(d[46]), "+f"(d[47]), "+f"(d[48]), "+f"(d[49]), "+f"(d[50]), "+f"(d[51]), "+f"(d[52]), "+f"(d[53]), "+f"(d[54]), "+f"(d[55]), "+f"(d[56]), "+f"(d[57]), "+f"(d[58]), "+f"(d[59]), "+f"(d[60]), "+f"(d[61]), "+f"(d[62]), "+f"(d[63])
    : "r"(a), "r"(b), "n"(0x40000040) : "memory");
}

__device__ __forceinline__ void sum_columns(float (&d)[4], uint32_t a, uint32_t b) {
  asm volatile("{\n.reg .u32 t;\n.reg .u64 da, db;\nmov.b64 db, {%5, 0};\nwgmma.fence.sync.aligned;\n"
               "add.u32 t, %4, 0;\nmov.b64 da, {t, %6};\nwgmma.mma_async.sync.aligned.m64n8k16.f32.bf16.bf16 {%0, %1, %2, %3}, da, db, 1, 1, 1, 1, 0;\n"
               "add.u32 t, %4, 128;\nmov.b64 da, {t, %6};\nwgmma.mma_async.sync.aligned.m64n8k16.f32.bf16.bf16 {%0, %1, %2, %3}, da, db, 1, 1, 1, 1, 0;\n"
               "add.u32 t, %4, 256;\nmov.b64 da, {t, %6};\nwgmma.mma_async.sync.aligned.m64n8k16.f32.bf16.bf16 {%0, %1, %2, %3}, da, db, 1, 1, 1, 1, 0;\n"
               "add.u32 t, %4, 384;\nmov.b64 da, {t, %6};\nwgmma.mma_async.sync.aligned.m64n8k16.f32.bf16.bf16 {%0, %1, %2, %3}, da, db, 1, 1, 1, 1, 0;\n"
               "add.u32 t, %4, 512;\nmov.b64 da, {t, %6};\nwgmma.mma_async.sync.aligned.m64n8k16.f32.bf16.bf16 {%0, %1, %2, %3}, da, db, 1, 1, 1, 1, 0;\n"
               "add.u32 t, %4, 640;\nmov.b64 da, {t, %6};\nwgmma.mma_async.sync.aligned.m64n8k16.f32.bf16.bf16 {%0, %1, %2, %3}, da, db, 1, 1, 1, 1, 0;\n"
               "add.u32 t, %4, 768;\nmov.b64 da, {t, %6};\nwgmma.mma_async.sync.aligned.m64n8k16.f32.bf16.bf16 {%0, %1, %2, %3}, da, db, 1, 1, 1, 1, 0;\n"
               "add.u32 t, %4, 896;\nmov.b64 da, {t, %6};\nwgmma.mma_async.sync.aligned.m64n8k16.f32.bf16.bf16 {%0, %1, %2, %3}, da, db, 1, 1, 1, 1, 0;\n"
               "add.u32 t, %4, 1024;\nmov.b64 da, {t, %6};\nwgmma.mma_async.sync.aligned.m64n8k16.f32.bf16.bf16 {%0, %1, %2, %3}, da, db, 1, 1, 1, 1, 0;\n"
               "add.u32 t, %4, 1152;\nmov.b64 da, {t, %6};\nwgmma.mma_async.sync.aligned.m64n8k16.f32.bf16.bf16 {%0, %1, %2, %3}, da, db, 1, 1, 1, 1, 0;\n"
               "add.u32 t, %4, 1280;\nmov.b64 da, {t, %6};\nwgmma.mma_async.sync.aligned.m64n8k16.f32.bf16.bf16 {%0, %1, %2, %3}, da, db, 1, 1, 1, 1, 0;\n"
               "add.u32 t, %4, 1408;\nmov.b64 da, {t, %6};\nwgmma.mma_async.sync.aligned.m64n8k16.f32.bf16.bf16 {%0, %1, %2, %3}, da, db, 1, 1, 1, 1, 0;\n"
               "add.u32 t, %4, 1536;\nmov.b64 da, {t, %6};\nwgmma.mma_async.sync.aligned.m64n8k16.f32.bf16.bf16 {%0, %1, %2, %3}, da, db, 1, 1, 1, 1, 0;\n"
               "add.u32 t, %4, 1664;\nmov.b64 da, {t, %6};\nwgmma.mma_async.sync.aligned.m64n8k16.f32.bf16.bf16 {%0, %1, %2, %3}, da, db, 1, 1, 1, 1, 0;\n"
               "add.u32 t, %4, 1792;\nmov.b64 da, {t, %6};\nwgmma.mma_async.sync.aligned.m64n8k16.f32.bf16.bf16 {%0, %1, %2, %3}, da, db, 1, 1, 1, 1, 0;\n"
               "add.u32 t, %4, 1920;\nmov.b64 da, {t, %6};\nwgmma.mma_async.sync.aligned.m64n8k16.f32.bf16.bf16 {%0, %1, %2, %3}, da, db, 1, 1, 1, 1, 0;\n"
               "wgmma.commit_group.sync.aligned;\nwgmma.wait_group.sync.aligned 0;\n}"
               : "+f"(d[0]), "+f"(d[1]), "+f"(d[2]), "+f"(d[3]) : "r"(a), "r"(b), "n"(0x40000040) : "memory");
}
struct Job {
  uint32_t type, layer, R, col, nk;
  __device__ __forceinline__ explicit Job(uint32_t j) : type(j & 3), layer((j >> 2) & 1), R((j >> 3) & 7), col((j >> 6) & 63), nk((j >> 12) & 63) {}
  __device__ __forceinline__ uint32_t inst() const { return layer * 2 + (type >> 1); }
};
struct Smem {
  char* scratch;
  uint32_t base;
  __device__ __forceinline__ uint32_t stage(uint32_t s) const { return base + (s & (NSTAGE - 1)) * STAGE; }
  __device__ __forceinline__ uint32_t slot(uint32_t c) const { return base + STG_OFF + c * SLOT; }
  __device__ __forceinline__ uint32_t full(uint32_t s) const { return base + BAR_OFF + (s & (NSTAGE - 1)) * 8; }
  __device__ __forceinline__ uint32_t empty(uint32_t s) const { return base + BAR_OFF + 32 + (s & (NSTAGE - 1)) * 8; }
  __device__ __forceinline__ uint32_t filled(uint32_t u) const { return base + BAR_OFF + 64 + u * 8; }
  __device__ __forceinline__ uint32_t vacant(uint32_t u) const { return base + BAR_OFF + 96 + u * 8; }
  __device__ __forceinline__ uint32_t summed(uint32_t s) const { return base + BAR_OFF + 128 + (s & (NSTAGE - 1)) * 8; }
  __device__ __forceinline__ uint32_t aux_full() const { return base + BAR_OFF + 160; }
  __device__ __forceinline__ uint32_t boot() const { return base + BAR_OFF + 168; }
  __device__ __forceinline__ uint32_t xchg_full() const { return base + BAR_OFF + 176; }
  __device__ __forceinline__ uint32_t wgmma_done() const { return base + BAR_OFF + 184; }
  __device__ __forceinline__ uint32_t mma_done() const { return base + BAR_OFF + 192; }
  __device__ __forceinline__ uint32_t kv_ready(int w) const { return base + BAR_OFF + 208 + w * 8; }
  __device__ __forceinline__ uint32_t pair_id() const { return base + BAR_OFF + 280; }
  __device__ __forceinline__ uint32_t stats() const { return base + AUX_OFF; }
  __device__ __forceinline__ uint32_t sums() const { return base + AUX_OFF + 1088; }
  __device__ __forceinline__ uint32_t xchg() const { return base + AUX_OFF + 1600; }
};
__device__ __forceinline__ uint32_t par(uint32_t s) { return (s / NSTAGE) & 1; }

__device__ __forceinline__ void st_word(u64* p, uint32_t lo, uint32_t hi) {
  asm volatile("st.relaxed.gpu.global.u64 [%0], %1;" ::"l"(p), "l"(((u64)hi << 32) | lo) : "memory");
}
__device__ __forceinline__ uint2 ld_word(const u64* p) {
  u64 v;
  asm volatile("ld.relaxed.gpu.global.u64 %0, [%1];" : "=l"(v) : "l"(p) : "memory");
  return make_uint2((uint32_t)v, (uint32_t)(v >> 32));
}
__device__ __forceinline__ void add_moments(uint4 v, float (&m)[4]) {
  const uint32_t w[4] = {v.x, v.y, v.z, v.w};
#pragma unroll
  for (int c = 0; c < 4; c++) {
    const float lo = bf_lo(w[c]), hi = bf_hi(w[c]);
    m[0] += lo; m[1] += hi; m[2] = fmaf(lo, lo, m[2]); m[3] = fmaf(hi, hi, m[3]);
  }
}
__device__ __forceinline__ void publish_stats(const Smem& sm, float s, float q, uint32_t idx, bool valid, uint32_t e1) {
  const float mean = s * (1.f / D), var = fmaxf(q * (1.f / D) - mean * mean, 0.f);
  const u64 word = ((u64)((__float_as_uint(-bf_round(mean)) & 0xffff0000u) | (e1 & 0xffff)) << 32) | __float_as_uint(rcp(bf_round(sqrt_fast(bf_round(bf_round(var) + 1e-5f)))));
  asm volatile("{\n.reg .pred p;\nsetp.ne.u32 p, %2, 0;\n@p st.relaxed.gpu.global.u64 [%0], %1;\n}" ::"l"(SCR(sm, stats, idx * 8)), "l"(word), "r"((uint32_t)valid) : "memory");
}
__device__ __forceinline__ void stats_task(const Smem& sm, uint32_t jw, int rank, int w, uint32_t e1, const bf16* x) {
  const uint32_t inst = (jw >> 22) & 3, lane = fresh_tid() & 31, steps = (jw >> 31) * 2 + 2;
  uint32_t row = ((jw >> 24) & 127) * 8 + (w - 1) * 4 + (lane >> 3);
  wait_count(counter(C_X + inst * 16 + (row >> 7) * 2 + rank, lane & 7), e1 * (inst & 1 ? 56 : 16));
  const uint4* p = at(reinterpret_cast<const uint4*>(x), (row * 2 + rank) * (D * 2) + (lane & 7) * 16);
  uint4 v[8];
  float m[4] = {0.f, 0.f, 0.f, 0.f};
#pragma unroll
  for (int i = 0; i < 8; i++) v[i] = ldg128(p + i * 8);
#pragma unroll 1
  for (uint32_t it = 1; it <= steps; it++) {
    p = at(p, it & 1 ? 1024 : 8 * D * 4 - 1024);
#pragma unroll
    for (int i = 0; i < 8; i++) {
      add_moments(v[i], m);
      if (it < steps) v[i] = ldg128(p + i * 8);
    }
    if (!(it & 1)) {
      m[0] += m[1]; m[2] += m[3];
#pragma unroll
      for (int o = 1; o <= 4; o <<= 1) { m[0] += __shfl_xor_sync(~0u, m[0], o); m[2] += __shfl_xor_sync(~0u, m[2], o); }
      publish_stats(sm, m[0], m[2], (inst + 1) * S + rank * (S / 2) + row, (lane & 7) == 0, e1);
      m[0] = m[1] = m[2] = m[3] = 0.f;
      row += 8;
    }
  }
}
struct Stager {
  uint2 st[5], cs[4];
  __device__ __forceinline__ void load(const Smem& sm, const Job& J, int rank, int lane, bool sums) {
#pragma unroll
    for (int i = 0; i < 5; i++) st[i] = ld_word(SCR(sm, stats, (J.inst() * S + rank * (S / 2) + J.R * 128 + min(max(lane - 8 + 32 * i, J.R && J.type == T_Q ? -8 : 0), 127)) * 8));
#pragma unroll
    for (int i = 0; i < 4; i++)
      if (sums && (i < 3 || J.type == T_G)) cs[i] = ld_word(SCR(sm, cs, ((J.col + J.type * 8) * 128 + lane) * 8) + i * 32);
  }
  __device__ __forceinline__ void store(const Smem& sm, const Job& J, int rank, int lane, bool sums, uint32_t e1) {
    for (uint32_t n = 0;; n++) {
      uint32_t bad = (st[1].y ^ e1) | (st[2].y ^ e1) | (st[3].y ^ e1);
      bad |= (st[0].y ^ e1) | (st[4].y ^ e1);
      if (sums) bad |= (cs[0].y ^ e1) | (cs[1].y ^ e1) | (cs[2].y ^ e1);
      if (J.type == T_G) bad |= cs[3].y ^ e1;
      if (__all_sync(~0u, (bad & 0xffff) == 0)) break;
      __nanosleep(300);
      if (n > SPIN_LIMIT) __trap();
      load(sm, J, rank, lane, sums);
    }
#pragma unroll
    for (int i = 0; i < 5; i++) {
      if (i < 4 || lane < 8) sts64(sm.stats() + (lane + 32 * i) * 8, st[i]);
      if (i < 4 && sums && (i < 3 || J.type == T_G)) sts32(sm.sums() + (lane + 32 * i) * 4, cs[i].x);
    }
  }
};
__device__ __forceinline__ void add_cols(float (&a)[8], uint4 x, uint4 y) {
  const uint4 t = add8(x, y);
  a[0] += bf_lo(t.x); a[1] += bf_hi(t.x); a[2] += bf_lo(t.y); a[3] += bf_hi(t.y);
  a[4] += bf_lo(t.z); a[5] += bf_hi(t.z); a[6] += bf_lo(t.w); a[7] += bf_hi(t.w);
}
__device__ __forceinline__ void reduce_cols(float (&a)[8], int lane) {
#pragma unroll
  for (int i = 0; i < 4; i++) { const bool up = lane & 16; const float o = __shfl_xor_sync(~0u, up ? a[i] : a[i + 4], 16); a[i] = (up ? a[i + 4] : a[i]) + o; }
#pragma unroll
  for (int i = 0; i < 2; i++) { const bool up = lane & 8; const float o = __shfl_xor_sync(~0u, up ? a[i] : a[i + 2], 8); a[i] = (up ? a[i + 2] : a[i]) + o; }
}
template <class Fn>
__device__ __forceinline__ uint32_t qkv_col_sums(const Smem& sm, int rank, int w, int lane, const uint32_t& rest, Fn between) {
  float a[8] = {0.f, 0.f, 0.f, 0.f, 0.f, 0.f, 0.f, 0.f};
#pragma unroll 1
  for (int s = 0; s < RING_SUMS; s++) {
    between(s);
    const uint32_t p = sm.stage(s) + SLOT + rank * SLOT + w * 4096 + (lane >> 3) * 128 + (((lane & 7) ^ (lane >> 3)) << 4);
    uint4 v[8];
    mbar_wait(sm.full(s), par(s));
#pragma unroll
    for (int j = 0; j < 8; j++) v[j] = lds128((p ^ ((j & 1) * 64)) + j * 512);
    __syncwarp();
    mbar_arrive_cl_if(lane < 2, mapa(sm.summed(s), lane & 1));
    add_cols(a, add8(v[0], v[1]), add8(v[2], v[3]));
    add_cols(a, add8(v[4], v[5]), add8(v[6], v[7]));
  }
  reduce_cols(a, lane);
  const uint32_t slot = sm.xchg() + (w * 32 + lane) * 8;
  asm volatile("st.async.weak.shared::cluster.mbarrier::complete_tx::bytes.v2.b32 [%0], {%1, %2}, [%3];"
               ::"r"(mapa(slot, rank ^ 1)), "r"(__float_as_uint(a[0])), "r"(__float_as_uint(a[1])), "r"(mapa(sm.xchg_full(), rank ^ 1)) : "memory");
  mbar_wait(sm.xchg_full(), 0);
  const uint2 o = lds64(slot);
  return pack_bf16(a[0] + __uint_as_float(o.x) + bf_lo(rest), a[1] + __uint_as_float(o.y) + bf_hi(rest));
}

constexpr float LOGIT_SCALE = 0.17677669529663687f * 1.4426950408889634f;
constexpr float MASKED = -1e30f;
enum { A_CS = 16, A_NM = 40, A_KT = 42, A_KU = 44, A_CT = 46, A_CU = 48, A_BIAS = 50, A_MASK = 52, A_ZERO = 53 };
__device__ __forceinline__ void attention_prepare(uint32_t (&r)[64], const Smem& sm, int W, int lane, bool first) {
  const int i = lane >> 2, c = (lane & 3) * 2;
  r[A_ZERO] = opaque_zero();
  r[A_MASK] = (c > i ? 0xffffu : 0u) | (c + 1 > i ? 0xffff0000u : 0u);
  const uint32_t a = sm.stats() + W * 128;
  const uint2 r0 = lds64(a + 64 + i * 8), r1 = lds64(a + 128 + i * 8);
#pragma unroll
  for (int y = 0; y < 2; y++) {
    const uint32_t k = a + (c + y + (c + y > i ? 0 : 8)) * 8;
    const float kt = lds32f(k), ku = lds32f(k + 64);
    r[A_KT + y] = __float_as_uint(kt); r[A_CT + y] = __float_as_uint(__uint_as_float(r0.x) * LOGIT_SCALE * kt);
    r[A_KU + y] = __float_as_uint(ku); r[A_CU + y] = __float_as_uint(__uint_as_float(r1.x) * LOGIT_SCALE * ku);
    r[A_BIAS + y] = __float_as_uint(first && W == 0 && c + y > i ? MASKED : 0.f);
  }
#pragma unroll
  for (int j = 0; j < 6; j++) {
    const uint4 v = lds128(sm.sums() + c * 48 + j * 16);
    r[A_CS + 4 * j] = v.x; r[A_CS + 4 * j + 1] = v.y; r[A_CS + 4 * j + 2] = v.z; r[A_CS + 4 * j + 3] = v.w;
  }
  r[A_NM] = dup_hi(r0.y); r[A_NM + 1] = dup_hi(r1.y);
}
__device__ __forceinline__ bool attention(const float (&acc)[96], uint32_t (&r)[64], const Smem& sm, int W, int lane, uint32_t t8, uint32_t t16,
                                          bool halo, uint32_t block, uint32_t tag, uint32_t parity, uint32_t next_bar, uint32_t next_parity, int ji) {
#define TRW W
  const uint32_t own = (W >> 2) * SLOT;
  const uint32_t pk = W == 0 ? (halo ? 4096 : 1024) : W == 4 ? 7168 : own - 1024;
  const uint32_t pv = W == 0 && halo ? 6144 : pk + 8192;
  uint32_t x[48];
  auto pack = [&](int j0, int step, int count) {
#pragma unroll
    for (int j = j0; j < j0 + step * count; j += step) x[j] = bf2_fma(r[A_NM + j % 2], r[A_CS + j / 2], pack_bf16(acc[2 * j], acc[2 * j + 1]));
  };
  auto put8 = [&](uint32_t a, int j) {
    stsm4(t8 + a, x[j], x[j + 2], x[j + 4], x[j + 6]);
    stsm4((t8 ^ 64) + a, x[j + 8], x[j + 10], x[j + 12], x[j + 14]);
  };
  uint32_t k0[2][4], v0[2][4], v12[4][4];
  pack(17, 2, 8);
  put8(own + 1024, 17);
  pack(32, 1, 16);
#pragma unroll
  for (int j = 0; j < 4; j++) stsm4((t16 ^ (j << 5)) + (own + 8192), x[32 + 4 * j], x[33 + 4 * j], x[34 + 4 * j], x[35 + 4 * j]);
  mbar_arrive_warp(sm.kv_ready(W));
  pack(16, 2, 8);
  pack(0, 1, 16);
  if (W == 0) {
    put8(0, 16);
#pragma unroll
    for (int j = 0; j < 4; j++) stsm4(lane & 8 ? sm.xchg() : (t16 ^ (j << 5)) + 2048, x[4 * j], x[4 * j + 1], x[4 * j + 2], x[4 * j + 3]);
  }
  mbar_wait(sm.kv_ready(W - 1), parity);
#pragma unroll
  for (int h = 0; h < 2; h++) ldsm4((t8 ^ (h * 64)) + pk, k0[h]);
#pragma unroll
  for (int j = 0; j < 4; j++) ldsm4t((t16 ^ (j << 5)) + (own + 8192), v12[j]);
#pragma unroll
  for (int h = 0; h < 2; h++) ldsm4t((t8 ^ (h * 64)) + pv, v0[h]);
  if (W < 4) mbar_wait(sm.wgmma_done(), parity);
  const bool next_full = mbar_test(next_bar, next_parity);
  TRC(ji, 20);
  float s0[2][4], s1[2][4], s2[2][4];
#pragma unroll
  for (int h = 0; h < 2; h++) {
#pragma unroll
    for (int y = 0; y < 4; y++) s0[h][y] = s1[h][y] = s2[h][y] = 0.f;
  }
#pragma unroll
  for (int ks = 0; ks < 2; ks++)
#pragma unroll
    for (int h = 0; h < 2; h++) {
      const int n = 8 * h + 4 * ks;
      mma16816(s1[h], x[n], x[n + 1], x[n + 2], x[n + 3], x[16 + n], x[18 + n]);
      mma16816(s2[h], x[n], x[n + 1], x[n + 2], x[n + 3], x[17 + n], x[19 + n]);
      mma16816(s0[h], x[n], x[n + 1], x[n + 2], x[n + 3], k0[h][2 * ks], k0[h][2 * ks + 1]);
    }
  const uint32_t mask = r[A_MASK];
  const bool after[2] = {(mask & 1) != 0, (int)mask < 0};
  float lt[2][2], lu[2][2], mt[2], mu[2];
#pragma unroll
  for (int h = 0; h < 2; h++) {
#pragma unroll
    for (int y = 0; y < 2; y++) {
      lt[h][y] = fmaf(after[y] ? s0[h][y] : s1[h][y], __uint_as_float(r[A_CT + y]), __uint_as_float(r[A_BIAS + y]));
      lu[h][y] = (after[y] ? s1[h][2 + y] : s2[h][2 + y]) * __uint_as_float(r[A_CU + y]);
    }
    mt[h] = fmaxf(lt[h][0], lt[h][1]);
    mu[h] = fmaxf(lu[h][0], lu[h][1]);
  }
#pragma unroll
  for (int d = 1; d <= 2; d++)
#pragma unroll
    for (int h = 0; h < 2; h++) {
      mt[h] = fmaxf(mt[h], __shfl_xor_sync(~0u, mt[h], d));
      mu[h] = fmaxf(mu[h], __shfl_xor_sync(~0u, mu[h], d));
    }
  float o[2][4][4];
#pragma unroll
  for (int h = 0; h < 2; h++) {
#pragma unroll
    for (int y = 0; y < 2; y++) { lt[h][y] = ex2(lt[h][y] - mt[h]); lu[h][y] = ex2(lu[h][y] - mu[h]); }
    const uint32_t pt = pack_bf16(lt[h][0] * __uint_as_float(r[A_KT]), lt[h][1] * __uint_as_float(r[A_KT + 1]));
    const uint32_t pu = pack_bf16(lu[h][0] * __uint_as_float(r[A_KU]), lu[h][1] * __uint_as_float(r[A_KU + 1]));
#pragma unroll
    for (int n = 0; n < 4; n++) {
      o[h][n][0] = o[h][n][1] = o[h][n][2] = o[h][n][3] = 0.f;
      mma16816(o[h][n], pt & ~mask, pu & mask, 0u, pu & ~mask, v12[2 * h + n / 2][n % 2 * 2], v12[2 * h + n / 2][n % 2 * 2 + 1]);
    }
#pragma unroll
    for (int n = 0; n < 4; n++) mma1688(o[h][n], pt & mask, 0u, v0[h][n]);
    mt[h] = lt[h][0] + lt[h][1];
    mu[h] = lu[h][0] + lu[h][1];
  }
#pragma unroll
  for (int d = 1; d <= 2; d++)
#pragma unroll
    for (int h = 0; h < 2; h++) {
      mt[h] += __shfl_xor_sync(~0u, mt[h], d);
      mu[h] += __shfl_xor_sync(~0u, mu[h], d);
    }
  uint32_t dep = 0;
#pragma unroll
  for (int n = 0; n < 3; n++) dep |= __float_as_uint(o[n % 2][n / 2][0]);
  mbar_arrive_warp(sm.mma_done() + (dep & r[A_ZERO]));
  TRC(ji, 22);
  if (W == 7) {
    ulonglong2* exp = SCR(sm, halo, (block * 256 + lane) * 16);
#pragma unroll
    for (int m = 0; m < 8; m++)
      asm volatile("st.relaxed.gpu.global.v2.u64 [%0], {%1,%2};" ::"l"(exp + m * 32), "l"(((u64)tag << 32) | x[17 + 4 * m]), "l"(((u64)tag << 32) | x[19 + 4 * m]) : "memory");
  }
#pragma unroll
  for (int h = 0; h < 2; h++) {
    const float rt = rcp(mt[h]), ru = rcp(mu[h]);
#pragma unroll
    for (int n = 0; n < 4; n++) {
      r[8 * h + 2 * n] = pack_bf16(o[h][n][0] * rt, o[h][n][1] * rt);
      r[8 * h + 2 * n + 1] = pack_bf16(o[h][n][2] * ru, o[h][n][3] * ru);
    }
  }
  return next_full;
}
__device__ __forceinline__ void import_halo(const Smem& sm, const ulonglong2* halo, uint32_t tag, int lane) {
  u64 x[16];
  for (uint32_t n = 0;; n++) {
#pragma unroll
    for (int m = 0; m < 8; m++)
      asm volatile("ld.relaxed.gpu.global.v2.u64 {%0,%1}, [%2];" : "=l"(x[2 * m]), "=l"(x[2 * m + 1]) : "l"(halo + m * 32) : "memory");
    uint32_t bad = 0;
#pragma unroll
    for (int m = 0; m < 16; m++) bad |= (uint32_t)(x[m] >> 32) ^ tag;
    if (__all_sync(~0u, bad == 0)) break;
    __nanosleep(300);
    if (n > SPIN_LIMIT) __trap();
  }
  const uint32_t a = sm.slot(0) + 4096 + (lane & 7) * 128 + (((lane >> 3) ^ (lane & 7)) << 4);
#pragma unroll
  for (int m = 0; m < 4; m++) stsm4((a ^ ((m & 1) * 64)) + (m >> 1) * 2048, (uint32_t)x[4 * m], (uint32_t)x[4 * m + 1], (uint32_t)x[4 * m + 2], (uint32_t)x[4 * m + 3]);
}
__device__ __forceinline__ void unpack8(uint4 v, float* f) {
  f[0] = bf_lo(v.x); f[1] = bf_hi(v.x); f[2] = bf_lo(v.y); f[3] = bf_hi(v.y);
  f[4] = bf_lo(v.z); f[5] = bf_hi(v.z); f[6] = bf_lo(v.w); f[7] = bf_hi(v.w);
}
__device__ __forceinline__ void boundary_rows(const Smem& sm, int h, int lane, uint32_t out) {
  const int i = lane >> 2, u = h * 4 + (lane & 3);
  uint4 r[8];
  float x[8], l[8], ik[8];
  unpack8(lds128(sm.slot(0) + 2048 + i * 128 + ((u ^ i) << 4)), x);
#pragma unroll
  for (int j = 0; j < 8; j++) {
    r[j] = lds128(sm.slot(0) + j * 128 + (j > i ? 4096 : 0) + ((u ^ j) << 4));
    ik[j] = lds32f(sm.stats() + j * 8 + (j > i ? 0 : 64));
  }
  const float cq = lds32f(sm.stats() + 64 + i * 8) * LOGIT_SCALE;
#pragma unroll
  for (int j = 0; j < 8; j++) {
    float kf[8];
    unpack8(r[j], kf);
    r[j] = lds128(sm.slot(0) + j * 128 + (j > i ? 6144 : 8192) + ((u ^ j) << 4));
    l[j] = 0.f;
#pragma unroll
    for (int d = 0; d < 8; d++) l[j] = fmaf(x[d], kf[d], l[j]);
  }
#pragma unroll
  for (int d = 1; d <= 2; d++)
#pragma unroll
    for (int j = 0; j < 8; j++) l[j] += __shfl_xor_sync(~0u, l[j], d);
  float m = MASKED, sum = 0.f;
#pragma unroll
  for (int j = 0; j < 8; j++) { l[j] *= cq * ik[j]; m = fmaxf(m, l[j]); }
#pragma unroll
  for (int j = 0; j < 8; j++) { l[j] = ex2(l[j] - m); sum += l[j]; }
  const float rs = rcp(sum);
#pragma unroll
  for (int d = 0; d < 8; d++) x[d] = 0.f;
#pragma unroll
  for (int j = 0; j < 8; j++) {
    const float pw = l[j] * ik[j] * rs;
    float vf[8];
    unpack8(r[j], vf);
#pragma unroll
    for (int d = 0; d < 8; d++) x[d] = fmaf(pw, vf[d], x[d]);
  }
  stg128(SCR(sm, o, out + i * (2 * D) + u * 16), make_uint4(pack_bf16(x[0], x[1]), pack_bf16(x[2], x[3]), pack_bf16(x[4], x[5]), pack_bf16(x[6], x[7])));
}
__device__ __forceinline__ uint32_t swiglu2(uint32_t g, uint32_t u, float hinv, float hinv2) {
  const float a = bf_lo(g) * hinv, b = bf_hi(g) * hinv, a2 = bf_lo(g) * hinv2, b2 = bf_hi(g) * hinv2;
  return bf2_mul(pack_bf16(fmaf(a2, tanh_fast(a), a2), fmaf(b2, tanh_fast(b), b2)), u);
}

__device__ __forceinline__ const uint32_t* dep_counter(const Smem& sm, uint32_t jw, int rank, uint32_t k) {
  const Job J(jw);
  const uint32_t b = J.R * 2 + rank;
  const uint32_t line = J.type == T_O ? C_O + J.layer * 16 + b : J.type == T_D ? C_H + J.layer * 16 + b : C_X + max((int)J.inst() - 1, 0) * 16 + b;
  return counter(line, J.type & 1 ? k >> (J.type >> 1) : (k >> 2) * 2 + (k & 1));
}
__device__ __forceinline__ void producer(const Params& P, const Smem& sm, const uint32_t* jobs, const uint8_t* kseq, int rank, int lane, uint32_t e1) {
  uint32_t s = (jobs[0] & JOB_C) ? 0 : NSTAGE;
  uint32_t end = 0, poll = 0;
  uint64_t keep, stream;
  asm("createpolicy.fractional.L2::evict_unchanged.b64 %0, 1.0;" : "=l"(keep));
  asm("createpolicy.fractional.L2::evict_first.b64 %0, 1.0;" : "=l"(stream));
  const uint32_t* dep = counter(0, 0);
  const uint32_t summed_end = (jobs[0] & JOB_C) ? 0 : RING_SUMS + NSTAGE;
  for (int ji = 0;; ji++) {
    const uint32_t jw = jobs[ji];
    const Job J(jw);
    if (J.nk == 0) break;
    const bool isC = jw & JOB_C, isX = isC && (jw & JOB_X);
    const uint32_t target = (jw & 7) == 0 ? 0 : e1 * (J.type == T_Q ? 56 : J.type == T_G ? 16 : 1);
    const uint32_t g = J.col * 2 + rank;
    const CUtensorMap* tmA = &P.a[isC ? 4 + isX : (jw & 7) == 4 ? 2 : J.type];
    const CUtensorMap* tmB = &P.w[J.type];
    const uint32_t bytes = isC ? 32768 : J.type == T_Q ? 40960 : STAGE, bcol = J.col << (J.type == T_Q ? 0 : J.type == T_G ? 1 : 2);
    const uint32_t a0 = isX ? 0 : (g >> 2) * 128 + (g & 1) * 64, a1 = isX ? g * 64 : J.R * 128, ak = isX ? 0 : 256, a2 = isC ? (g >> 1) & 1 : rank;
    end += J.nk;
    uint32_t sa = s, spins = 0;
    auto issue_a = [&](uint32_t k) { TRS(sa, 1); tma3d(sm.stage(sa), tmA, isC ? a0 : (k & 63) * 64, isC ? a1 + k * ak : a1, isX ? k * 4 : a2, sm.full(sa), (k & K_LAST_A) ? stream : keep); };
    auto issue_b = [&](uint32_t k) {
      mbar_expect_tx(sm.full(s), bytes);
      TRS(s, 0);
      if (!isC) tma4d_mc(sm.stage(s) + SLOT + rank * SLOT, tmB, (k & 63) * 64 + rank * 32, bcol, sm.full(s), (k & K_LAST_B) ? stream : keep);
    };
    TRI(lane == 0, ji, 6);
    TRK(lane == 0, ji, 24);
    while (true) {
      const uint32_t missing = __ballot_sync(~0u, (int)(poll - target) < 0 && lane < J.nk);
      uint32_t lim = end;
      if (missing) lim += __ffs(missing) - 1 - J.nk;
      if (lim > sa) {
        fence_acquire();
        fence_proxy_async();
        TRI(sa == end - J.nk && lane == 0, ji, 7);
#pragma unroll 1
        for (; sa < min(lim, s); sa++) {
          const uint32_t k = kseq[sa];
          if (elect()) issue_a(k);
        }
#pragma unroll 1
        for (int phase = 0;; phase++) {
          const uint32_t upto = phase == 2 ? lim : phase == 1 ? lim - LOOK : min((int)lim - LOOK, (int)sa + MID);
#pragma unroll 1
          for (; (int)sa < (int)upto; sa++, s++) {
            const uint32_t k = kseq[s];
            uint32_t stage = sm.stage(s), bar = sm.full(s), c0 = isC ? a0 : (k & 63) * 64, c1 = isC ? a1 + k * ak : a1, kb = (k & 63) * 64 + rank * 32, c2 = isX ? k * 4 : a2;
            uint64_t pa = (k & K_LAST_A) ? stream : keep, pb = (k & K_LAST_B) ? stream : keep;
            asm volatile("" : "+r"(stage), "+r"(bar), "+r"(c0), "+r"(c1), "+r"(kb), "+r"(c2), "+l"(pa), "+l"(pb));
            if (s < summed_end) mbar_wait(sm.summed(s), par(s) ^ 1);
            mbar_wait(bar + 32, par(s) ^ 1);
            TRS(s, 0);
            asm volatile("{\n.reg .pred p, q;\nelect.sync _|p, -1;\nsetp.eq.and.u32 q, %14, 0, p;\n"
                         "@q cp.async.bulk.tensor.4d.shared::cluster.global.mbarrier::complete_tx::bytes.multicast::cluster.L2::cache_hint [%3], [%4, {%5, %6, %7, %5}], [%0], %8, %9;\n"
                         "@p cp.async.bulk.tensor.3d.shared::cluster.global.mbarrier::complete_tx::bytes.L2::cache_hint [%2], [%10, {%11, %12, %13}], [%0], %15;\n"
                         "@p mbarrier.arrive.expect_tx.shared::cta.b64 _, [%0], %1;\n}"
                         ::"r"(bar), "r"(bytes), "r"(stage), "r"(stage + SLOT + rank * SLOT), "l"(tmB), "r"(0), "r"(kb), "r"(bcol), "h"((uint16_t)3), "l"(pb),
                           "l"(tmA), "r"(c0), "r"(c1), "r"(c2), "r"((uint32_t)isC), "l"(pa) : "memory");
            TRS(s, 1);
          }
          if (phase == 2) break;
          if (phase == 1) poll = ld_relaxed(dep);
          else if (lim == end) dep = dep_counter(sm, jobs[ji + 1], rank, (reinterpret_cast<const uint32_t*>(kseq)[(end + lane) >> 2] >> ((end + lane) % 4 * 8)) & 63);
        }
        if (lim == end) break;
      } else {
        if (s < min(end, sa + NSTAGE) && __all_sync(~0u, mbar_test(sm.empty(s), par(s) ^ 1))) {
          const uint32_t k = kseq[s];
          if (s < summed_end) mbar_wait(sm.summed(s), par(s) ^ 1);
          if (elect()) issue_b(k);
          s++;
        }
        poll = ld_relaxed(dep);
        if (++spins > SPIN_LIMIT) __trap();
      }
    }
    TRI(lane == 0, ji, 8);
  }
}

__global__ void __cluster_dims__(2, 1, 1) __launch_bounds__(384, 1) mega_kernel(char* scratch, uint32_t by_place, const __grid_constant__ Params P) {
#undef TRW
#define TRW warp
  extern __shared__ __align__(1024) uint8_t smem_raw[];
  TRX(threadIdx.x == 320, JMAX - 1, 0, 1, "%%globaltimer_lo");
  TRX(threadIdx.x == 320, JMAX - 1, 0, 25, "%%clock");
  TRX(threadIdx.x == 320, JMAX - 1, 0, 28, "%%smid");
  Smem sm;
  sm.scratch = scratch;
  sm.base = smem_u32(smem_raw);
  if ((sm.base & 0x3FFFF) != SMEM_BASE) __trap();
  const int warp = __shfl_sync(~0u, threadIdx.x >> 5, 0);
  const int rank = blockIdx.x & 1;
  uint32_t smid;
  asm("mov.u32 %0, %%smid;" : "=r"(smid));
  const uint32_t pair = !by_place ? blockIdx.x >> 1 : smid < 2 * NPAIR - 8 ? (smid >> 1) + 4 : (smid >> 1) + 4 - NPAIR;
  const uint32_t* jobs = P.jobs[pair];
  const uint32_t launches = ld_relaxed(counter(C_EP, blockIdx.x + threadIdx.y));
  if (warp == 10) {
    if (elect()) {
      for (int i = 0; i < NSTAGE; i++) mbar_init(sm.full(i), 1);
      mbar_init(sm.boot(), 1);
      asm volatile("fence.mbarrier_init.release.cluster;" ::: "memory");
    }
    cluster_arrive();
    const uint32_t first = jobs[0];
    const bool isC = first & JOB_C;
    if (elect()) {
      prefetch_tm(&P.a[0]);
      prefetch_tm(&P.w[0]);
    }
    uint64_t keep;
    asm("createpolicy.fractional.L2::evict_unchanged.b64 %0, 1.0;" : "=l"(keep));
    const Job J(first);
    if (!isC) {
      if (elect()) {
        mbar_expect_tx(sm.full(0), 40960);
        tma3d(sm.stage(0), &P.a[0], 0, J.R * 128, rank, sm.full(0), keep);
        TRS(0, 1);
      }
      TRX(threadIdx.x == 320, JMAX - 1, 0, 26, "%%clock");
      cluster_wait();
      TRX(threadIdx.x == 320, JMAX - 1, 0, 27, "%%clock");
      if (elect()) {
        tma4d_mc(sm.stage(0) + SLOT + rank * SLOT, &P.w[0], rank * 32, J.col, sm.full(0), keep);
        TRS(0, 0);
      }
#pragma unroll 1
      for (int k = 1; k < NSTAGE; k++) {
        if (elect()) {
          tma4d_mc(sm.stage(k) + SLOT + rank * SLOT, &P.w[0], k * 64 + rank * 32, J.col, sm.full(k), keep);
          TRS(k, 0);
          mbar_expect_tx(sm.full(k), 40960);
          tma3d(sm.stage(k), &P.a[0], k * 64, J.R * 128, rank, sm.full(k), keep);
          TRS(k, 1);
        }
      }
    } else {
      cluster_wait();
      if (!(first & JOB_X)) mbar_wait(sm.boot(), 0);
    }
  } else {
    if (warp < 8 && elect()) {
      mbar_init(sm.kv_ready(warp), 1);
      if (warp == 3) {
        mbar_init(sm.aux_full(), 3); mbar_init(sm.wgmma_done(), 4); mbar_init(sm.mma_done(), 8); mbar_init(sm.xchg_full(), 1); mbar_init(sm.kv_ready(-1), 1);
        mbar_expect_tx(sm.xchg_full(), 768);
      } else if (warp > 3) {
        mbar_init(sm.empty(warp), 4); mbar_init(sm.summed(warp), 6); mbar_init(sm.filled(warp - 4), 4); mbar_init(sm.vacant(warp - 4), 3);
      }
      asm volatile("fence.mbarrier_init.release.cluster;" ::: "memory");
    }
    cluster_arrive();
  }
  TRI(threadIdx.x == 0, JMAX - 1, 0);

  if (warp < 8) {
    asm volatile("setmaxnreg.inc.sync.aligned.u32 208;");
    const uint32_t e1 = launches + 1;
    cluster_wait();
    const uint32_t wg = warp >> 2;
    uint32_t rel = (threadIdx.x & 95) == 0 ? mapa(sm.empty(0), (threadIdx.x & 32) ? rank ^ 1 : rank) : 0;
    uint32_t dst = sm.slot(0) + (warp & 3) * 2048 + (threadIdx.x & 15) * 128 + ((((threadIdx.x >> 4) & 1) ^ (threadIdx.x & 7)) << 4);
    uint32_t t8 = sm.slot(0) + (warp & 3) * 2048 + (threadIdx.x & 7) * 128 + ((((threadIdx.x >> 3) & 3) ^ (threadIdx.x & 7)) << 4);
    rel = __shfl_sync(~0u, rel, threadIdx.x);
    dst = __shfl_sync(~0u, dst, threadIdx.x);
    t8 = __shfl_sync(~0u, t8, threadIdx.x);
    const uint32_t da0 = ((SMEM_BASE >> 4) | (1 << 16)) + wg * 512, dba = (255 << 16) + 1024 - wg * 512;
    uint32_t pend[64], todo = 0, pbar = 0, vbar = sm.vacant(0), ppar = 0, poff = 0, direct = 0;
    uint32_t s = 0, na = 0, nb = 0, ready = 0;
    auto release = [&](uint32_t st) { mbar_arrive_cl_if(rel, rel + (st & (NSTAGE - 1)) * 8); };
    auto flush = [&](bool vacant) {
      if (__all_sync(~0u, vacant)) {
        const uint32_t a = dst + poff;
        if (todo & 2) {
#pragma unroll
          for (int j = 0; j < 4; j++) stsm4(a ^ (j << 5), pend[4 * j], pend[4 * j + 1], pend[4 * j + 2], pend[4 * j + 3]);
          if (todo == 2) {
#pragma unroll
            for (int j = 0; j < 4; j++) stsm4((a ^ (j << 5)) + 8192, pend[16 + 4 * j], pend[17 + 4 * j], pend[18 + 4 * j], pend[19 + 4 * j]);
          }
        } else {
#pragma unroll
          for (int j = 0; j < 8; j++) stsm4((a ^ ((j & 3) << 5)) + (j >> 2) * 8192, pend[32 + 4 * j], pend[33 + 4 * j], pend[34 + 4 * j], pend[35 + 4 * j]);
        }
        mbar_arrive_warp(pbar);
        pbar += 16; vbar += 16; ppar = ~nb & 1;
        todo = todo == 2;
      }
    };
    uint32_t jw = jobs[0];
#pragma unroll
    for (int i = 0; i < 64; i++) pend[i] = 0;
    for (int ji = 0;; ji++) {
      const uint32_t cur = jw, nk = (jw >> 12) & 63, isQ = (jw & 3) == T_Q;
      jw = jobs[ji + 1];
      if (__builtin_expect((cur & JOB_C) || !ready, 0)) {
        for (uint32_t spins = 0; todo && ((cur & JOB_C) || !ready);) {
          if (direct && todo == 1) {
            vbar = sm.empty(s); ppar = par(s) ^ 1; poff = sm.stage(s) - sm.slot(0) + wg * SLOT;
          }
          flush(mbar_test(vbar, ppar));
          ready = __all_sync(~0u, mbar_test(sm.full(s), par(s)));
          if (++spins > SPIN_LIMIT) __trap();
        }
        if (cur & JOB_C) {
          if (nk == 0) break;
          TRC(ji, 16);
          constexpr uint32_t ONES = 0x3f803f80;
          const uint32_t lane = fresh_tid() & 31, g = ((cur >> 6) & 63) * 2 + rank;
          if (!(cur & JOB_X)) {
            float d[4] = {0.f, 0.f, 0.f, 0.f};
            sts32(sm.xchg() + 128 + lane * 4, ONES);
            fence_proxy_async_smem();
            bar_sync<9, 256>();
#pragma unroll 1
            for (int i = 0; i < 4; i++, s++) {
              mbar_wait(sm.full(s), par(s));
              if (!wg) sum_columns(d, da0 + (s & (NSTAGE - 1)) * (STAGE / 16), (SMEM_BASE + AUX_OFF + 1600 + 128) >> 4);
              release(s);
            }
            const float c = lane & 1 ? d[2] : d[0], c1 = __shfl_down_sync(~0u, c, 4);
            asm volatile("{\n.reg .pred p;\nsetp.eq.u32 p, %2, 0;\n@p st.relaxed.gpu.global.u64 [%0], %1;\n}"
                         ::"l"(SCR(sm, cs, (16 * 128 + g * 32 + (warp & 3) * 8 + (lane & 1) * 4 + (lane >> 3)) * 8)), "l"(((u64)e1 << 32) | pack_bf16(c, c1)), "r"((lane & 6) | wg) : "memory");
          } else {
            float a[6][4];
#pragma unroll
            for (int n = 0; n < 24; n++) pend[n] = 0;
#pragma unroll 1
            for (int i = 0;; i++) {
              const uint32_t p = dst - sm.slot(0) + sm.stage(s) + wg * SLOT;
              mbar_wait(sm.full(s), par(s));
              uint32_t v[8][4];
#pragma unroll
              for (int n = 0; n < 24; n++) a[n / 4][n % 4] = __uint_as_float(pend[n]);
#pragma unroll
              for (int j = 0; j < 8; j++) ldsm4((p ^ ((j & 3) << 5)) + (j >> 2) * 8192, v[j]);
#pragma unroll
              for (int j = 0; j < 8; j++) {
                mma16816(a[4 + (j & 1)], v[j][0], v[j][1], v[j][2], v[j][3], ONES, ONES);
#pragma unroll
                for (int n = 0; n < 4; n++) mma1688(a[n], v[j][n & 2], v[j][(n & 2) + 1], v[j][n]);
              }
#pragma unroll
              for (int n = 0; n < 24; n++) pend[n] = __float_as_uint(a[n / 4][n % 4]);
              if (i == 3) break;
              bar_sync<9, 256>();
              release(s++);
            }
            const uint32_t part = sm.stage(s) + 2 * SLOT + lane * 8, row = g * 64 + (warp & 3) * 16 + wg * 8 + (lane >> 2);
            const bool odd = lane & 4;
            const float s0 = a[4][0] + a[5][0], q0 = odd ? a[0][1] + a[2][1] : a[0][0] + a[2][0];
            const float s1 = a[4][2] + a[5][2], q1 = odd ? a[1][3] + a[3][3] : a[1][2] + a[3][2];
            sts64(part + warp * 256, make_uint2(__float_as_uint(wg ? s0 : s1), __float_as_uint(wg ? q0 : q1)));
            bar_sync<9, 256>();
            const uint2 o = lds64(part + (warp ^ 4) * 256);
            fence_proxy_async_smem();
            bar_sync<9, 256>();
            release(s++);
            publish_stats(sm, (wg ? s1 : s0) + __uint_as_float(o.x), (wg ? q1 : q0) + __uint_as_float(o.y), (row & 1) * (S / 2) + (row >> 1), (lane & 3) == lane >> 3, e1);
          }
          ready = 0;
          TRC(ji, 18);
          continue;
        }
        if (!ready) mbar_wait(sm.full(s), par(s));
      }
      auto mainloop = [&](auto& acc, uint32_t nk, uint32_t last_lead, auto near_end) {
        const uint32_t lead = (jw >> 12) % 64 == 0 ? min(last_lead, nk - 2) : 2, turn = wg ? lead : nk - 2, hurry = nk - lead - wg;
        uint32_t owed = 0;
        uint32_t da = da0 + (s & (NSTAGE - 1)) * (STAGE / 16);
        if (todo == 3) mbar_wait(vbar, ppar);
        if (wg) bar_sync<13, 256>();
        TRC(ji, 16);
        first_kstep(acc, da, da + dba);
        if (!wg) bar_arrive<13, 256>();
        constexpr uint32_t CLEAR = sizeof(acc) == 96 * 4 ? PREP + 2 : 3;
        for (uint32_t left = nk - 1;; left--) {
          for (uint32_t spins = 0;; spins++) {
            const bool vacant = mbar_test(vbar, ppar), next_full = mbar_test(sm.full(s + 1), par(s + 1));
            wg_wait<2>();
            mbar_arrive_cl_if(owed, owed + ((s - 1) & (NSTAGE - 1)) * 8);
            owed = 0;
            ready = __all_sync(~0u, next_full);
            if (!todo) {
              near_end(left, vacant);
              break;
            }
            const bool go = ready && left >= max(CLEAR, lead + 1);
            if (!(go && spins)) flush(vacant);
            if (go) break;
            if (spins > SPIN_LIMIT) __trap();
          }
          if (left == 0) break;
          if (!ready) mbar_wait(sm.full(s + 1), par(s + 1));
          owed = rel;
          if (left == turn) {
            wg_wait<0>();
            release(s);
            owed = 0;
            if (wg) bar_sync<1, 256>();
          }
          if (left - lead < hurry) wg_wait<1>();
          s++;
          da = da0 + (s & (NSTAGE - 1)) * (STAGE / 16);
          kstep(acc, da, da + dba);
          if (left == 1 + wg * 64) bar_arrive<1, 256>();
        }
      };
      if (isQ) {
        float acc[96];
        const uint32_t lane = (((dst - SMEM_BASE) >> 7) & 15) | ((dst ^ (dst >> 3)) & 16), qpar = (na ^ nb) & 1;
        uint32_t prepare_at = PREP;
        mainloop(acc, nk, LAST_LEAD, [&](uint32_t left, bool aux_full) {
          if (left == PREP + 1) {
            vbar = sm.aux_full(); ppar = qpar;
          } else if (left == prepare_at) {
            if (left == 0) mbar_wait(vbar, ppar);
            if (left == 0 || __all_sync(~0u, aux_full)) attention_prepare(pend, sm, warp, lane, !(cur & 0x38));
            else prepare_at--;
          }
        });
        wg_wait<0>();
        release(s);
        u64 token = 0;
        asm volatile("{\n.reg .pred p;\nsetp.eq.u32 p, %2, 0;\n@p mbarrier.arrive.shared::cta.b64 %0, [%1];\n}" : "+l"(token) : "r"(sm.wgmma_done()), "r"(lane + 1 - wg) : "memory");
        pend[A_NM + 1] |= (uint32_t)token & pend[A_ZERO];
        TRC(ji, 18);
        ready = __all_sync(~0u, attention(acc, pend, sm, warp, lane, t8, dst, cur & JOB_EARLY, (((cur >> 2) & 1) * 16 + ((cur >> 3) & 7) * 2 + rank) * 16 + ((cur >> 6) & 15), e1, qpar,
                                          sm.full(s + 1), par(s + 1), ji));
        todo = 3; pbar = sm.filled(wg); vbar = sm.mma_done(); ppar = qpar; poff = SLOT + wg * 8192;
      } else {
        float acc[128];
        direct = (cur & 1) && (jw >> 12) % 64 == 0;
        const bool split = direct && nk >= SPLIT_MIN;
        mainloop(acc, split ? nk - 3 : nk, split ? 0 : LAST_LEAD, [](uint32_t, bool) {});
        pbar = sm.filled(wg); vbar = pbar + 32; ppar = na & 1; poff = wg * SLOT;
        nb++;
        todo = 2;
        if (__builtin_expect(split, 0)) {
          const uint32_t s0 = s;
          uint32_t d[3];
#pragma unroll
          for (int i = 0; i < 3; i++) d[i] = da0 + ((s0 + 1 + i) & (NSTAGE - 1)) * (STAGE / 16);
          wg_wait<0>();
          release(s0);
          float lo[64], hi[64];
#pragma unroll
          for (int i = 0; i < 64; i++) {
            asm volatile("mov.b32 %0, %1;" : "=f"(lo[i]) : "f"(acc[i]));
            asm volatile("mov.b32 %0, %1;" : "=f"(hi[i]) : "f"(acc[64 + i]));
          }
          if (wg) {
            bar_sync<1, 256>();
            bar_sync<3, 256>();
          }
          mbar_wait(sm.full(s0 + 1), par(s0 + 1));
          half_kstep0(lo, d[0], d[0] + dba);
          mbar_wait(sm.full(s0 + 2), par(s0 + 2));
          half_kstep0(lo, d[1], d[1] + dba);
          half_kstep1(hi, d[0], d[0] + dba);
          mbar_wait(sm.full(s0 + 3), par(s0 + 3));
          half_kstep0(lo, d[2], d[2] + dba);
          half_kstep1(hi, d[1], d[1] + dba);
          half_kstep1(hi, d[2], d[2] + dba);
          if (!wg) bar_arrive<3, 256>();
          s += 3;
          wg_wait<2>();
#pragma unroll
          for (int i = 0; i < 32; i++) pend[i] = pack_bf16(lo[2 * i], lo[2 * i + 1]);
          mbar_wait(vbar, ppar);
          flush(true);
          wg_wait<0>();
          TRC(ji, 18);
#pragma unroll
          for (int i = 0; i < 32; i++) pend[32 + i] = pack_bf16(hi[2 * i], hi[2 * i + 1]);
        } else {
          wg_wait<0>();
          release(s);
          const bool next_full = mbar_test(sm.full(s + 1), par(s + 1));
          TRC(ji, 18);
#pragma unroll
          for (int i = 0; i < 64; i++) {
            const int j = (i & 15) + (i & 16) * 2 + (i >> 5) * 16;
            pend[i] = pack_bf16(acc[2 * j], acc[2 * j + 1]);
          }
          ready = __all_sync(~0u, next_full);
        }
      }
      na++;
      s++;
    }
  } else {
    asm volatile("setmaxnreg.dec.sync.aligned.u32 88;");
    if (warp == 10) {
      producer(P, sm, jobs, P.kseq[pair], rank, threadIdx.x & 31, __shfl_sync(~0u, launches, 0) + 1);
    } else {
      const uint32_t e1 = __shfl_sync(~0u, launches, 0) + 1;
      const int w = min(warp - 8, 2);
      cluster_wait();
      if (w == 1) asm volatile("st.shared::cluster.u32 [%0], %1;" ::"r"(mapa(sm.pair_id(), rank ^ 1)), "r"(pair) : "memory");
      auto copy_rows = [&](uint32_t step) {
        constexpr int IN = 2 * SLOT / BOOT_PIECES;
        if (step == BOOT_STEP) mbar_wait(sm.boot(), 0);
        if (elect()) {
          if (step == 0) mbar_expect_tx(sm.boot(), blockIdx.x < S / 16 ? 2 * SLOT : 0);
          if (step < BOOT_PIECES && blockIdx.x < S / 16)
            asm volatile("cp.async.bulk.shared::cluster.global.mbarrier::complete_tx::bytes [%0], [%1], %2, [%3];"
                         ::"r"(sm.slot(0) + step * IN), "l"(at(P.x0, blockIdx.x * 32768 + step * IN)), "n"(IN), "r"(sm.boot()) : "memory");
          if (step - BOOT_STEP < 8 && blockIdx.x < S / 16) {
            asm volatile("cp.async.bulk.global.shared::cta.bulk_group [%0], [%1], %2;"
                         ::"l"(at(P.out, blockIdx.x * 32768 + (step - BOOT_STEP) * 4096)), "r"(sm.slot(0) + (step - BOOT_STEP) * 4096), "n"(4096) : "memory");
            bulk_commit();
          }
        }
        if (step == BOOT_STEP + 8) {
          bulk_wait();
          if (elect()) {
            mbar_arrive_n(sm.vacant(0), 3);
            mbar_arrive_n(sm.vacant(1), 3);
          }
        }
      };
      if (jobs[0] & JOB_C) {
        const uint32_t u = (((jobs[0] >> 6) & 63) * 2 + rank) * 2 + w, lane = threadIdx.x & 31;
        if (RING_SUMS < 16 && (jobs[0] & JOB_X) && w < 2 && u < 48) {
          const uint32_t part = u & 3 ? (u & 3) - 1 : u >> 4, c = u & 3 ? u >> 2 : 12 + ((u >> 2) & 3);
          const uint4* p = at(reinterpret_cast<const uint4*>(P.wqkv), (RING_SUMS * 64 + (lane >> 3)) * (6 * D) + part * (2 * D) + c * 128 + (lane & 7) * 16);
          float a[8] = {0.f, 0.f, 0.f, 0.f, 0.f, 0.f, 0.f, 0.f};
          mbar_wait(sm.full(REST_AT), 0);
#pragma unroll 1
          for (int i = RING_SUMS * 2; i < 32; i++, p = at(p, 32 * 6 * D)) {
            uint4 v[8];
#pragma unroll
            for (int j = 0; j < 8; j++) v[j] = __ldg(p + j * (4 * 6 * D / 16));
            add_cols(a, add8(v[0], v[1]), add8(v[2], v[3]));
            add_cols(a, add8(v[4], v[5]), add8(v[6], v[7]));
          }
          reduce_cols(a, lane);
          st_word(SCR(sm, cs, ((44 + c) * 128 + (lane >> 3) * 24 + part * 8 + (lane & 7)) * 8), pack_bf16(a[0], a[1]), e1);
        }
        if (w == 2) {
          if (jobs[0] & JOB_X) mbar_wait(sm.full(3), 0);
#pragma unroll 1
          for (int i = 0; i <= BOOT_STEP + 8; i++) {
            copy_rows(i);
            bulk_wait_read<0>();
          }
        }
      } else {
        const int lane = threadIdx.x & 31, word = (lane >> 3) * 24 + w * 8 + (lane & 7);
        Stager st;
        uint2 rest = make_uint2(0, 0);
        const u64* rp = SCR(sm, cs, ((44 + ((jobs[0] >> 6) & 15)) * 128 + word) * 8);
        const uint32_t cs = qkv_col_sums(sm, rank, w, lane, rest.x, [&](int s) {
          if (RING_SUMS < 16 && s == RING_SUMS - 3) rest = ld_word(rp);
          if (RING_SUMS < 16 && s == RING_SUMS - 1) {
            for (uint32_t n = 0; !__all_sync(~0u, rest.y == e1); n++) {
              rest = ld_word(rp);
              if (n > SPIN_LIMIT) __trap();
            }
          }
          if (w == 2) copy_rows(s - (RING_SUMS > 13));
          if (w == 0 && s == ST_STEP) st.load(sm, Job(jobs[0]), rank, lane, false);
          if (w == 0 && s == ST_STEP + 2) st.store(sm, Job(jobs[0]), rank, lane, false, e1);
        });
        sts32(sm.sums() + word * 4, cs);
        mbar_arrive_warp(sm.aux_full());
        if ((jobs[0] & 0x38) == 0 && rank == 0) st_word(SCR(sm, cs, (((jobs[0] >> 6) & 15) * 128 + word) * 8), cs, e1);
      }
      bar_sync<2, 96>();
      if (w == 2 && blockIdx.x < S / 16 && elect()) {
        red_release(counter(C_RD + (blockIdx.x >> 4) * 2, 0), 1);
        red_relaxed(counter(C_RD + (blockIdx.x >> 4) * 2 + 1, 0), 1);
      }
      uint32_t na = 0, nb = 0, stages = 0;
      for (int ji = 0;; ji++) {
        const uint32_t jw = jobs[ji];
        const Job J(jw);
        if (J.nk == 0) break;
        stages += J.nk;
        if (w != 0 && ((jw >> 22) & 3) != 3) {
          stats_task(sm, jw, rank, w, e1, P.out);
          TRI(threadIdx.x == 11 * 32, ji, 10);
        }
        if (jw & JOB_C) continue;
        const int lane = fresh_tid() & 31;
        const uint32_t b = J.R * 2 + rank;
        if (w == 0 && !(J.type & 1) && ji != 0) {
          Stager st;
          st.load(sm, J, rank, lane, true);
          st.store(sm, J, rank, lane, true, e1);
          TRI(lane == 0, ji, 9);
        }
        if (J.type == T_G) {
          bar_sync<2, 96>();
          constexpr int PER = 16 / NG;
          const uint32_t swap = P.swap, never = jw, ac = sm.sums() + (lane & 7) * 16;
          uint32_t ag[NG], au[NG], as = sm.stats() + 64 + w * NG * 32 + (lane >> 3) * 8;
          uint32_t ho = (rank * (S / 2) + J.R * 128 + w * NG * 4 + (lane >> 3)) * (F * 2) + J.col * 256 + (lane & 7) * 16;
          uint4 cg = lds128(ac + (swap >> 5)), cu = lds128(ac + 256 - (swap >> 5)), g4[NG], u4[NG];
          uint2 st[NG];
          auto load = [&] {
#pragma unroll
            for (int i = 0; i < NG; i++) { st[i] = lds64v(as + i * 32); g4[i] = lds128v(ag[i]); u4[i] = lds128v(au[i]); }
          };
#pragma unroll
          for (int i = 0; i < NG; i++) {
            const uint32_t a = (sm.slot(0) + (w * NG + i) * 512 + (lane >> 3) * 128 + (((lane & 7) ^ (lane >> 3)) << 4)) ^ (((w * NG + i) & 1) << 6);
            ag[i] = a + swap; au[i] = a + (swap ^ 8192);
          }
          mbar_wait(sm.filled(0), na & 1);
          mbar_wait(sm.filled(1), na & 1);
          load();
          if (w == 2 && elect()) red_relaxed(counter(C_RD + J.inst() * 16 + b, 0), 1);
          TRI(threadIdx.x == 11 * 32, ji, 3);
#pragma unroll 1
          for (uint32_t g = w; g < 4 * PER; g += 3) {
            float hinv[NG], hinv2[NG];
            uint4 gc[NG], uc[NG];
            const bool turn = ((g + 3) ^ g) & PER, half = ((g + 3) ^ g) & (2 * PER);
#pragma unroll
            for (int i = 0; i < NG; i++) {
              hinv[i] = 0.5f * __uint_as_float(st[i].x);
              hinv2[i] = hinv[i] * __uint_as_float(st[i].x);
              asm volatile("" : "+f"(hinv[i]), "+f"(hinv2[i]));
              gc[i] = fma8(dup_hi(st[i].y), cg, g4[i]);
              uc[i] = fma8(dup_hi(st[i].y), cu, u4[i]);
              ag[i] = (ag[i] + NG * 1536) ^ ((NG & 1) << 6);
              au[i] = (au[i] + NG * 1536) ^ ((NG & 1) << 6);
            }
            as += NG * 96;
            if (turn) {
              mbar_arrive_warp(sm.vacant((g / PER) ^ 2));
              if (half) {
                cg = lds128(ac + (swap >> 5) + 128); cu = lds128(ac + 384 - (swap >> 5));
                as -= 1024;
              }
#pragma unroll
              for (int i = 0; i < NG; i++) { ag[i] += half ? -3 * 8192 : 8192; au[i] += half ? -3 * 8192 : 8192; }
              TRX(threadIdx.x == 11 * 32 && g < 3 * PER, ji, 25, 25 + g / PER * 2, "%%clock");
              if (g < 3 * PER) mbar_wait(sm.filled(g / PER + 1), (g < PER ? na : nb) & 1);
              TRX(threadIdx.x == 11 * 32 && g < 3 * PER, ji, 25, 26 + g / PER * 2, "%%clock");
            }
            load();
            if (g == never) mbar_wait(sm.boot(), 0);
            bf16* out = SCR(sm, h, ho);
#pragma unroll
            for (int i = 0; i < NG; i++)
              stg128(out + i * 4 * F, make_uint4(swiglu2(gc[i].x, uc[i].x, hinv[i], hinv2[i]), swiglu2(gc[i].y, uc[i].y, hinv[i], hinv2[i]),
                                                 swiglu2(gc[i].z, uc[i].z, hinv[i], hinv2[i]), swiglu2(gc[i].w, uc[i].w, hinv[i], hinv2[i])));
            ho += NG * 12 * F * 2 - (half ? 128 * F * 2 - 128 : 0);
          }
          bar_sync<2, 96>();
          TRI(threadIdx.x == 11 * 32, ji, 4);
          if (w == 2 && elect()) red_release(counter(C_H + J.layer * 16 + b, J.col), 1);
          TRI(threadIdx.x == 11 * 32, ji, 5);
        } else if (J.type == T_Q) {
          const bool late = J.R > 0 && !(jw & JOB_EARLY);
          if (w == 0) {
            __syncwarp();
            if (ji != 0 && elect()) mbar_arrive_n(sm.aux_full(), 3);
#pragma unroll 1
            for (int phase = 0; phase < 2; phase++) {
              if (J.R > 0 && phase == late) import_halo(sm, SCR(sm, halo, (((J.layer * 16 + b - 2) * 16 + J.col) * 256 + lane) * 16), e1, lane);
              if (phase == 0) {
                mbar_arrive_warp(sm.kv_ready(-1));
                TRI(lane == 0, ji, 11);
#pragma unroll 1
                for (int h = 0; h < 2; h++) {
                  mbar_wait(sm.filled(h), na & 1);
                  TRI(lane == 0, ji, 3);
                  fence_proxy_async_smem();
                  bulk_wait_read<0>();
                  if (elect()) {
                    tma3d_store(&P.ow, J.col * 64, J.R * 128 + h * 64, rank, sm.slot(1) + h * 8192);
                    bulk_commit();
                  }
                }
                if (J.layer && elect()) red_relaxed(counter(C_RD + 32 + b, 0), 1);
              }
            }
            bulk_wait();
          }
          if (late && w < 2) {
            bar_sync<7, 64>();
            boundary_rows(sm, w, lane, rank * O_PLANE + J.R * 128 * (D * 2) + J.col * 128);
            bar_sync<7, 64>();
          }
          TRI(threadIdx.x == 256, ji, 4);
          if (w == 0 && elect()) {
            mbar_arrive_n(sm.vacant(0), 3);
            mbar_arrive_n(sm.vacant(1), 3);
            red_release(counter(C_O + J.layer * 16 + b, J.col), 1);
          }
          TRI(threadIdx.x == 256, ji, 5);
        } else if (w == 0) {
          wait_count(counter(C_RD + J.inst() * 16 + b, 0), e1 * (J.type == T_D ? 28 : 16));
          fence_proxy_async();
          const bool last = Job(jobs[ji + 1]).nk == 0, split = last && J.nk >= SPLIT_MIN;
#pragma unroll 1
          for (uint32_t v = 0; v < 4; v++) {
            const uint32_t u = last ? (v >> 1) + (v & 1) * 2 : v;
            mbar_wait(sm.filled(u), (u & 2 ? nb : na) & 1);
            TRI(u == 0 && lane == 0, ji, 3);
            fence_proxy_async_smem();
            const uint32_t src = (last && (u & 2) ? sm.stage(stages) : sm.slot(0)) + (u & 1) * SLOT;
#pragma unroll 1
            for (uint32_t p = 0; p < 16384 / PIECE; p++) {
              if (elect()) {
                tma3d_reduce_add(&P.xr, J.col * 256 + (split ? (u & 2) * 64 + p * PIECE / 8192 * 64 : (u & 2) * 32 + p * PIECE / 8192 * 128), J.R * 128 + (u & 1) * 64 + p * PIECE % 8192 / 128, rank, src + p * PIECE);
                bulk_commit();
              }
              if (!last) bulk_wait_read<DEPTH - 1>();
            }
            if (!last) {
              bulk_wait();
              if (elect()) mbar_arrive_n(sm.vacant(u ^ 2), 3);
            }
            if (u == 1 && J.inst() != 3) bar_arrive<8, 64>();
          }
          bulk_wait();
        }
        if ((J.type & 1) && J.inst() != 3 && w < 2) {
          if (w == 1) bar_sync<8, 64>();
          TRX(lane == 0, ji, 4, w ? 12 : 4, "%%globaltimer_lo");
          if (elect()) red_release(counter(C_X + J.inst() * 16 + b, J.col * 2 + 1 - w), J.nk);
          TRX(lane == 0, ji, 5, w ? 13 : 5, "%%globaltimer_lo");
          if (w == 1) bar_arrive<10, 64>(); else bar_sync<10, 64>();
        }
        na++;
        nb += J.type != T_Q;
      }
      TRI(threadIdx.x == 8 * 32, JMAX - 1, 6);
      TRK(threadIdx.x == 8 * 32, JMAX - 1, 24);
      if (w == 0 && elect()) red_relaxed(counter(C_EP, blockIdx.x), 1);
      if (w == 2 && __float_as_uint(lds32f(sm.pair_id())) != pair) __trap();
    }
  }
  cluster_arrive();
  cluster_wait();
}

typedef CUresult (*EncodeFn)(CUtensorMap*, CUtensorMapDataType, cuuint32_t, void*, const cuuint64_t*, const cuuint64_t*, const cuuint32_t*,
                             const cuuint32_t*, CUtensorMapInterleave, CUtensorMapSwizzle, CUtensorMapL2promotion, CUtensorMapFloatOOBfill);
struct Dim { cuuint64_t size, stride; cuuint32_t box; };
template <int N> void encode(EncodeFn fn, CUtensorMap* m, const void* ptr, const Dim (&d)[N]) {
  cuuint64_t dims[N], strides[N];
  cuuint32_t box[N], es[N];
  for (int i = 0; i < N; i++) { dims[i] = d[i].size; strides[i] = d[i].stride; box[i] = d[i].box; es[i] = 1; }
  fn(m, CU_TENSOR_MAP_DATA_TYPE_BFLOAT16, N, const_cast<void*>(ptr), dims, strides + 1, box, es, CU_TENSOR_MAP_INTERLEAVE_NONE,
     CU_TENSOR_MAP_SWIZZLE_128B, CU_TENSOR_MAP_L2_PROMOTION_L2_128B, CU_TENSOR_MAP_FLOAT_OOB_FILL_NONE);
}

}

extern "C" void kernel_launch(void* const* d_in, const int* in_sizes, int n_in, void* d_out, int out_size) {
  (void)in_sizes; (void)n_in; (void)out_size;
  static EncodeFn fn = nullptr;
  static Scratch* scr;
  static int sms;
  if (!fn) {
    void* p = nullptr;
    cudaDriverEntryPointQueryResult q;
    cudaGetDriverEntryPoint("cuTensorMapEncodeTiled", &p, cudaEnableDefault, &q);
    fn = (EncodeFn)p;
    scr = scratch_base();
    int device = 0;
    cudaGetDevice(&device);
    cudaDeviceGetAttribute(&sms, cudaDevAttrMultiProcessorCount, device);
    cudaFuncSetAttribute(mega_kernel, cudaFuncAttributeMaxDynamicSharedMemorySize, SMEM_BYTES);
  }
  static Params P;
  const char *wg = (const char*)d_in[4], *wu = (const char*)d_in[5], *w0 = wg < wu ? wg : wu;
  const cuuint64_t plane = wg < wu ? wu - wg : wg - wu;
  P.swap = wg < wu ? 0 : 8192;
  encode(fn, &P.a[0], d_in[0], {{D, 2, 64}, {S / 2, D * 4, 128}, {2, D * 2, 1}});
  encode(fn, &P.a[1], scr->o, {{D, 2, 64}, {S / 2, D * 2, 128}, {2, O_PLANE, 1}});
  encode(fn, &P.ow, scr->o, {{D, 2, 64}, {S / 2, D * 2, 64}, {2, O_PLANE, 1}});
  encode(fn, &P.a[2], d_out, {{D, 2, 64}, {S / 2, D * 4, 128}, {2, D * 2, 1}});
  encode(fn, &P.a[3], scr->h, {{F, 2, 64}, {S / 2, F * 2, 128}, {2, (cuuint64_t)F * S, 1}});
  encode(fn, &P.a[4], w0, {{F, 2, 64}, {D, F * 2, 256}, {2, plane, 1}});
  encode(fn, &P.a[5], d_in[0], {{64, 2, 64}, {S, D * 2, 64}, {16, 128, 4}});
  encode(fn, &P.w[T_Q], d_in[1], {{64, 2, 64}, {D, 3 * D * 2, 32}, {16, 128, 1}, {3, D * 2, 3}});
  encode(fn, &P.w[T_O], d_in[2], {{64, 2, 64}, {D, D * 2, 32}, {16, 128, 4}, {1, (cuuint64_t)D * D * 2, 1}});
  encode(fn, &P.w[T_G], w0, {{64, 2, 64}, {D, F * 2, 32}, {F / 64, 128, 2}, {2, plane, 2}});
  encode(fn, &P.w[T_D], d_in[6], {{64, 2, 64}, {F, D * 2, 32}, {16, 128, 4}, {1, (cuuint64_t)F * D * 2, 1}});
  encode(fn, &P.xr, d_out, {{D, 2, 64}, {S / 2, D * 4, PIECE / 128}, {2, D * 2, 1}});
  memcpy(P.jobs, kJobs, sizeof(kJobs));
  memcpy(P.kseq, kSeq, sizeof(kSeq));
  P.x0 = (const bf16*)d_in[0];
  P.wqkv = (const bf16*)d_in[1];
  P.out = (bf16*)d_out;
  mega_kernel<<<2 * NPAIR, 384, SMEM_BYTES>>>((char*)scr, sms == 2 * NPAIR, P);
}
```

```cpp
#include <cuda_runtime.h>
#include <cuda_bf16.h>
#include <cuda.h>
#include <stddef.h>
#include <stdint.h>
#include <string.h>

namespace {

typedef __nv_bfloat16 bf16;
typedef unsigned long long u64;
constexpr int S = 2048, D = 1024, F = 3584;
constexpr int STAGE = 49152, NSTAGE = 4, SLOT = 16384;
constexpr int STG_OFF = NSTAGE * STAGE, BAR_OFF = STG_OFF + 2 * SLOT, AUX_OFF = BAR_OFF + 336;
constexpr int SMEM_BYTES = AUX_OFF + 2736;
constexpr int SMEM_BASE = 1024;
constexpr int NPAIR = 66, JMAX = 24, KMAX = 296;
constexpr int T_Q = 0, T_O = 1, T_G = 2, T_D = 3;
constexpr uint32_t JOB_C = 1u << 18;
constexpr uint32_t K_LAST_A = 64, K_LAST_B = 128;
constexpr uint32_t JOB_EARLY = 1u << 21;
constexpr uint32_t JOB_X = JOB_EARLY;
#define V_BOOTP 4
#define V_BOOTS 5
#define V_BOOTO 8
#define V_STS 9
constexpr int BOOT_PIECES = V_BOOTP, BOOT_OUT = V_BOOTO, BOOT_STEP = V_BOOTS, ST_STEP = V_STS;
constexpr int SPLIT_MIN = 6;
#define V_PREP 3
constexpr int PREP = V_PREP, LAST_LEAD = 3;
#define V_LOOK 2
#define V_MID 7
constexpr int LOOK = V_LOOK, MID = V_MID;
#define V_PIECE 8192
#define V_DEPTH 2
constexpr int NG = 2, PIECE = V_PIECE, DEPTH = V_DEPTH;
#define V_SL1 200
#define V_SL2 300
#define V_SL3 300
constexpr uint32_t SPIN_LIMIT = 1u << 21;

constexpr int C_X = 0;
constexpr int C_O = C_X + 48;
constexpr int C_H = C_O + 32;
constexpr int C_RD = C_H + 32;
constexpr int C_EP = C_RD + 64;
constexpr int C_LINES = C_EP + 5;

struct Scratch {
  bf16 h[S * F];
  uint32_t cnt[256 * 32];
  bf16 o[S / 2 * D];
  u64 stats[4 * S];
  bf16 o1[S / 2 * D];
  u64 cs[44 * 128];
  ulonglong2 halo[2 * 16 * 16 * 8 * 32];
};
constexpr uint32_t O_PLANE = offsetof(Scratch, o1) - offsetof(Scratch, o);
static_assert(C_LINES <= 256, "");
constexpr size_t PAGE = 2 << 20;
__device__ __align__(1024) char g_scratch[sizeof(Scratch) + PAGE];
Scratch* scratch_base() {
  char* p;
  cudaGetSymbolAddress((void**)&p, g_scratch);
  return (Scratch*)(p + (-(size_t)p & (PAGE - 1)));
}

uint32_t kJobs[NPAIR][JMAX] = {
  {0xe44200,0xc10020,0xc44040,0xc08009,0xc10082,0x4101001a,0xc10022,0xc1800b,0x184170b3,0x46610054,0x5b610034,0x7d41000e,0xc1001e,0xc10076,0xc10096,0xc14037,0xc40000,0xc40000,0xc40000,0xc40000,0xc40000,0xc40000,0xc40000,0xc40000},
  {0xe44000,0xc10018,0xc44080,0xc08009,0xc10021,0x22010052,0xc10092,0xc100aa,0xc09013,0x16410004,0x2d61004c,0x3461002c,0x4e410086,0xc10056,0x618100ae,0xc100b6,0xc1b02f,0xc40000,0xc40000,0xc40000,0xc40000,0xc40000,0xc40000,0xc40000},
  {0xc10000,0xc44140,0xc04001,0xc10042,0x3a01004a,0xc1006a,0xc100b2,0xc1201b,0x26413033,0x6440b00d,0x681001d,0x3281002d,0xd48100a6,0xc101be,0xc1e007,0xc40000,0xc40000,0xc40000,0xc40000,0xc40000,0xc40000,0xc40000,0xc40000,0xc40000},
  {0xc10010,0xc440c0,0xc04001,0xc10002,0x3b01008a,0xc1019a,0xc101aa,0xc0800b,0x1a40d01b,0xc10014,0x66410064,0x2810006,0xc1008e,0xc10066,0xc1007e,0xc0e087,0xc1003f,0xc40000,0xc40000,0xc40000,0xc40000,0xc40000,0xc40000,0xc40000},
  {0xc10048,0xe10058,0xe10070,0xc05039,0x21010012,0x7a01b003,0xc1003a,0x29410044,0x3561001c,0x4f61005c,0x5761003c,0x7e41004e,0x6081009e,0xc100be,0xc1c00f,0xc40000,0xc40000,0xc40000,0xc40000,0xc40000,0xc40000,0xc40000,0xc40000,0xc40000},
  {0xe44240,0xc443c0,0xe10158,0xc10130,0xc040e1,0x170101ca,0x620101da,0xc101f2,0x641905b,0xc07063,0x324100c5,0x7a61016c,0x12a1013c,0x288101d6,0xc101ee,0xc10236,0xc1a04f,0xc40000,0xc40000,0xc40000,0xc40000,0xc40000,0xc40000,0xc40000},
  {0xe44280,0xc44780,0xc10228,0x1f044840,0xe10270,0xc103ca,0x5e01039a,0xc103b2,0xc1042a,0xc103ba,0x6d4180bb,0x8810506,0xc100b5,0xd2810426,0xc103be,0xc1f097,0xc40000,0xc40000,0xc40000,0xc40000,0xc40000,0xc40000,0xc40000,0xc40000},
  {0xe44380,0xc102d0,0xc040c1,0xc10091,0x1101044a,0x67010452,0xc1046a,0xc104f2,0x2c4170ab,0x5240e0bb,0x5810486,0xc104ce,0xc10466,0xc1047e,0xc1f09f,0xc40000,0xc40000,0xc40000,0xc40000,0xc40000,0xc40000,0xc40000,0xc40000,0xc40000},
  {0xe442c0,0xc10320,0xc040c1,0x1d210338,0xc1054a,0x610105e2,0x7301e0cb,0xc10344,0xc1030c,0xc040bb,0x6041036c,0x1ca1033c,0x29810596,0x6c8105a6,0xc106f6,0xc1d0df,0xc40000,0xc40000,0xc40000,0xc40000,0xc40000,0xc40000,0xc40000,0xc40000},
  {0xe443c0,0xc10390,0xc44d80,0xc100d1,0x1501060a,0x64010612,0x720180c3,0x24106ba,0xc1038c,0x404103dc,0xc103f4,0x2c80c0e5,0x4d810656,0xc1066e,0xc1069e,0xc1a0ef,0xc40000,0xc40000,0xc40000,0xc40000,0xc40000,0xc40000,0xc40000,0xc40000},
  {0xc10088,0xe100e0,0xc10011,0x270100ca,0x6c01015a,0x7c01800b,0xc0d023,0x2140f0b3,0x516100dc,0xc10106,0xc1010e,0xc10166,0xc1013e,0xc1f017,0xc40000,0xc40000,0xc40000,0xc40000,0xc40000,0xc40000,0xc40000,0xc40000,0xc40000,0xc40000},
  {0xc10198,0xc101b0,0x1b0445c0,0xc44600,0xc446c0,0xc1030a,0x5d010322,0xc102f2,0xc0e04b,0xc101c4,0xc1707b,0x79410055,0xc07065,0xb0810075,0xd0810326,0xc10336,0xc1d05f,0xc40000,0xc40000,0xc40000,0xc40000,0xc40000,0xc40000,0xc40000},
  {0xc10050,0xc10060,0xc10038,0x29210078,0x3e010062,0xc10032,0x441901b,0x2461000c,0x36610024,0x5d410074,0x228100ad,0x5b810026,0xc1006e,0xc1005e,0xc1203f,0xc40000,0xc40000,0xc40000,0xc40000,0xc40000,0xc40000,0xc40000,0xc40000,0xc40000},
  {0xe44040,0xc444c0,0xc10168,0xc10049,0x1601024a,0x63010252,0xc10262,0xc1027a,0xc18073,0x55410045,0x48101c6,0xc1034e,0xc1035e,0xc1023e,0xc1e04f,0xc40000,0xc40000,0xc40000,0xc40000,0xc40000,0xc40000,0xc40000,0xc40000,0xc40000},
  {0xe44080,0xc44700,0xe10220,0xc09089,0xc103c2,0x5a010412,0xc10512,0xc103f2,0x1e41c0a3,0x4961021c,0x58410234,0x36a1027c,0x4881041e,0x7281051e,0xc10436,0xc1909f,0xc40000,0xc40000,0xc40000,0xc40000,0xc40000,0xc40000,0xc40000,0xc40000},
  {0xe44180,0xc44880,0xe102a0,0xc04081,0x1c2102f8,0xc104ca,0x66010462,0xc104ea,0xc104ba,0xc104fa,0xc102d4,0xc102ac,0x1d8104c6,0xc104d6,0x6d8104a6,0xc1053e,0xc0f087,0xc0c0b7,0xc40000,0xc40000,0xc40000,0xc40000,0xc40000,0xc40000},
  {0xe440c0,0xc44ac0,0xc10328,0xc07041,0xc080c9,0xc0c0e1,0xb2010592,0xc105aa,0xc106e2,0x1d4130db,0xc090e3,0x484100fb,0xc810546,0x3f81054e,0x5d810566,0xc1057e,0xc200c7,0xc40000,0xc40000,0xc40000,0xc40000,0xc40000,0xc40000,0xc40000},
  {0xe441c0,0xc44c40,0xc10398,0xc44d40,0xe103f0,0xc100f1,0xd0010692,0xc10632,0xc10672,0xc1067a,0x6f6103cc,0x736103a4,0x13810606,0xc1064e,0xc10626,0xc1067e,0xc0f0e7,0xc0e0ff,0xc40000,0xc40000,0xc40000,0xc40000,0xc40000,0xc40000},
  {0xe44300,0xc100a0,0xc04001,0xc100c2,0x3c010112,0x7b01d003,0x741013a,0x234100c4,0x374100d4,0xc100ac,0x39a100fc,0xc10156,0x6981012e,0xc1019e,0xc1b01f,0xc40000,0xc40000,0xc40000,0xc40000,0xc40000,0xc40000,0xc40000,0xc40000,0xc40000},
  {0xe44340,0xc101d8,0xc09041,0xc10051,0x24010352,0xc1032a,0xc1b053,0x12410073,0xe101dc,0xe101ac,0xc10286,0x40810296,0x758102a6,0xc102e6,0xc19057,0xc40000,0xc40000,0xc40000,0xc40000,0xc40000,0xc40000,0xc40000,0xc40000,0xc40000},
  {0xc10008,0xc44000,0xc44100,0xe10068,0xc10029,0x3601009a,0xc1002a,0xc100a2,0xc1007a,0x3041803b,0xc0b095,0x10810046,0x41810016,0x7881002e,0xc1003e,0xc19037,0xc40000,0xc40000,0xc40000,0xc40000,0xc40000,0xc40000,0xc40000,0xc40000},
  {0xc10110,0xc44440,0xe10160,0xc101c2,0x4201021a,0xc10222,0xc10272,0xc101fa,0x3f410104,0x5e610114,0xc100dd,0x2081024e,0x5c8101e6,0xc101fe,0xc10047,0xc1007f,0xc40000,0xc40000,0xc40000,0xc40000,0xc40000,0xc40000,0xc40000,0xc40000},
  {0xc10200,0xc44a00,0xc10260,0x3010402,0x4301050a,0xc10422,0xc0808b,0xc10432,0xc10244,0xe10214,0xc0b08d,0x7810386,0xc1050e,0x5f8103e6,0xc103fe,0xc1f0a7,0xc40000,0xc40000,0xc40000,0xc40000,0xc40000,0xc40000,0xc40000,0xc40000},
  {0xc102c0,0xc44900,0xc102b0,0x40449c0,0x120100b1,0x3801045a,0xc10472,0xa41a093,0x3d8102c4,0x4fa10294,0xe102e4,0xe102bc,0xc10516,0xc104e6,0xc104fe,0xc1b08f,0xc40000,0xc40000,0xc40000,0xc40000,0xc40000,0xc40000,0xc40000,0xc40000},
  {0xc10308,0xe10350,0xc44b00,0xe10378,0xc070f9,0x3f01059a,0xc105f2,0xc105ba,0x134105fa,0xe1034c,0xe10364,0xc106c6,0xc10556,0xc1055e,0xc105f6,0xc1e0ef,0xc40000,0xc40000,0xc40000,0xc40000,0xc40000,0xc40000,0xc40000,0xc40000},
  {0xc10388,0xe103e0,0xc44d00,0xc10682,0x5801065a,0xc106aa,0xc41b0d3,0xc110eb,0x4a4130fb,0x3810686,0xc106ce,0xc106ee,0xc106a6,0xc1e0d7,0xc40000,0xc40000,0xc40000,0xc40000,0xc40000,0xc40000,0xc40000,0xc40000,0xc40000,0xc40000},
  {0xe44100,0xc44180,0xe100d8,0xc44280,0xc10019,0x1001010a,0xc0b039,0xc10172,0xc1016a,0x1441a02b,0x4241009c,0xb8100f4,0x24810146,0x5981003d,0xf08100f6,0xc19017,0xc0c03f,0xc40000,0xc40000,0xc40000,0xc40000,0xc40000,0xc40000,0xc40000},
  {0xe44140,0xc101a0,0xc44640,0xc10059,0x1301028a,0x6501029a,0xc08079,0x71014053,0xc180e3,0xc0e07b,0xc101b4,0x37a101bc,0x4981007d,0x668102b6,0xc1033e,0xc1806f,0xc40000,0xc40000,0xc40000,0xc40000,0xc40000,0xc40000,0xc40000,0xc40000},
  {0x2e010040,0xe10028,0xe10030,0xc1000a,0x6801005a,0xc10072,0x40f013,0x104100ba,0x56410005,0x7161006c,0x14a1007c,0x2a810035,0x68810036,0xc1018e,0xc18027,0xc40000,0xc40000,0xc40000,0xc40000,0xc40000,0xc40000,0xc40000,0xc40000,0xc40000},
  {0xc10150,0xe10118,0xc44680,0xc10069,0x2f0101d2,0x7701c043,0x541023a,0x2241006b,0x4741011c,0xc10174,0x2f81020e,0xc1025e,0x7a8101f6,0xc10256,0xc0c05f,0xc0a077,0xc40000,0xc40000,0xc40000,0xc40000,0xc40000,0xc40000,0xc40000,0xc40000},
  {0xc10208,0xc44740,0xc447c0,0xc04081,0xc07089,0x100a9,0xb00103da,0x7501d083,0x34103fa,0xe1020c,0xe10254,0xe1022c,0xc1038e,0xc1039e,0x768103b6,0xc1d08f,0xc0a0bf,0xc40000,0xc40000,0xc40000,0xc40000,0xc40000,0xc40000,0xc40000},
  {0xc10290,0xc44940,0xc102f0,0x5010099,0x200080b9,0xd201049a,0xc104a2,0xc1047a,0xc0e09b,0x3e6102cc,0x5f40707b,0xc102f4,0x2b81048e,0xc1049e,0x7b8104b6,0xc104de,0xc160b7,0xc40000,0xc40000,0xc40000,0xc40000,0xc40000,0xc40000,0xc40000},
  {0xc10318,0xc10358,0xc44b80,0xc10542,0x59010552,0xc1056a,0xc10572,0xc1c0eb,0x4b610314,0x59610374,0x7f61037c,0x158100fd,0x648105ae,0xc105e6,0xc180c7,0xc40000,0xc40000,0xc40000,0xc40000,0xc40000,0xc40000,0xc40000,0xc40000,0xc40000},
  {0xc103c0,0xc44c00,0xc103e8,0x6010602,0x4401061a,0xc090f9,0x7401a0cb,0xc170e3,0xc0d0fb,0xc103ec,0xc040e5,0x2e81068e,0xc1065e,0x7e8106b6,0xc1b0df,0xc0a0ff,0xc40000,0xc40000,0xc40000,0xc40000,0xc40000,0xc40000,0xc40000,0xc40000},
  {0xc100c8,0xc44240,0xc100b0,0x7010102,0x450100da,0xc1012a,0xc100f2,0xc100fa,0xe1008c,0xe10094,0xc0500d,0x1810186,0xc10196,0x6781016e,0xc100fe,0xc1d02f,0xc40000,0xc40000,0xc40000,0xc40000,0xc40000,0xc40000,0xc40000,0xc40000},
  {0xc101d0,0xe101e0,0xc100a1,0x250102ca,0x6e01031a,0x7e0102b2,0xc102ba,0xc0a06b,0x3161018c,0x676101ec,0x744102c6,0xc102d6,0x6f8102ae,0xc1032e,0xc1b067,0xc40000,0xc40000,0xc40000,0xc40000,0xc40000,0xc40000,0xc40000,0xc40000,0xc40000},
  {0xc10108,0xe10170,0xe10138,0xc08079,0x3701025a,0xc10232,0xc1404b,0x1b410144,0x2e610154,0x38610164,0x68410206,0xc101ce,0xc10226,0xc1037e,0xc1d067,0xc40000,0xc40000,0xc40000,0xc40000,0xc40000,0xc40000,0xc40000,0xc40000,0xc40000},
  {0xc10218,0xc10258,0xc10278,0x2a01040a,0xc080b9,0xc103ea,0xc1308b,0x1f41053a,0xc10085,0x7c61026c,0x16810406,0x478103d6,0x738103ae,0xc1042e,0xc19097,0xc40000,0xc40000,0xc40000,0xc40000,0xc40000,0xc40000,0xc40000,0xc40000,0xc40000},
  {0xc102c8,0xe102a8,0xc04081,0x1010482,0x5b010492,0x7601b083,0x941809b,0xe1028c,0xe102a4,0xc05095,0x11810446,0x42810496,0xc1046e,0xc104be,0xc190a7,0xc40000,0xc40000,0xc40000,0xc40000,0xc40000,0xc40000,0xc40000,0xc40000,0xc40000},
  {0xc10348,0xc44bc0,0xc10370,0x80105c2,0x4601058a,0x790200c3,0x14160db,0x3c410354,0x61610324,0x754105c6,0xc105d6,0x658106e6,0xc105fe,0xc1d0cf,0xc40000,0xc40000,0xc40000,0xc40000,0xc40000,0xc40000,0xc40000,0xc40000,0xc40000,0xc40000},
  {0xc103d0,0xc103a8,0xc103f8,0x2b01064a,0x6901062a,0xc1069a,0xc106b2,0x27410384,0x394103d4,0x7b6103e4,0x17810646,0x448106d6,0xc106ae,0xc106be,0xc1a0e7,0xc40000,0xc40000,0xc40000,0xc40000,0xc40000,0xc40000,0xc40000,0xc40000,0xc40000},
  {0xc100d0,0xe100a8,0xc100d9,0x2801018a,0x6d010132,0x7d010162,0xc1017a,0xc1102b,0x4140d03b,0xfa100ec,0x1b8100ce,0xc1015e,0x7d810136,0xc1a007,0xc0b037,0xc40000,0xc40000,0xc40000,0xc40000,0xc40000,0xc40000,0xc40000,0xc40000,0xc40000},
  {0xc10190,0xc44580,0xc101f0,0x9010282,0x47010292,0xc102da,0xc102e2,0xc1033a,0xc10073,0x536101e4,0xc10306,0xc10356,0xc1029e,0xc102be,0xc1f057,0xc40000,0xc40000,0xc40000,0xc40000,0xc40000,0xc40000,0xc40000,0xc40000,0xc40000},
  {0xc10148,0xc44400,0xc10128,0xa010202,0x4801020a,0xc101ea,0xc1604b,0x1c41037a,0x6e61010c,0x76610124,0x18810246,0xc10216,0x63810266,0xc1027e,0xc13047,0xc0a0bf,0xc40000,0xc40000,0xc40000,0xc40000,0xc40000,0xc40000,0xc40000,0xc40000},
  {0xc10248,0xc44a40,0xc10268,0xb010382,0x490103d2,0xc103aa,0xc10532,0xc1043a,0xc120b3,0x50410264,0x8103c6,0xc10396,0xc103a6,0xc1043e,0xc1e0af,0xc40000,0xc40000,0xc40000,0xc40000,0xc40000,0xc40000,0xc40000,0xc40000,0xc40000},
  {0xc10288,0x2c2102d8,0xe102b8,0xc1048a,0x6a0104d2,0xc104aa,0xc1052a,0x284150ab,0x5440e0bb,0xa81009d,0x34a102fc,0x4a81045e,0xc10476,0xc104ee,0xc110bf,0xc40000,0xc40000,0xc40000,0xc40000,0xc40000,0xc40000,0xc40000,0xc40000,0xc40000},
  {0xc10340,0xc44a80,0xc10368,0xc010582,0x4a0106da,0xc105d2,0xc105ea,0xc106fa,0xc130f3,0x654100cd,0x1f810586,0xc105ce,0x6e8105ee,0xc105be,0xc0f0e7,0xc0c0f7,0xc40000,0xc40000,0xc40000,0xc40000,0xc40000,0xc40000,0xc40000,0xc40000},
  {0xc103d8,0xc44cc0,0xc040c1,0xc103b8,0x140106ca,0x5f010662,0xc106a2,0xc106ea,0xc1d0f3,0xc080fb,0xe8100d5,0x2381060e,0x5881061e,0xc10636,0xc106fe,0xc120ff,0xc40000,0xc40000,0xc40000,0xc40000,0xc40000,0xc40000,0xc40000,0xc40000},
  {0xc10080,0xc441c0,0xc04001,0xc10142,0x3d0100d2,0xc101a2,0xc101ba,0xc12023,0x2540d02b,0x4340c03b,0x72410015,0x2681014e,0xc1011e,0xc100ee,0xc101a6,0xc0a027,0xc0a03f,0xc40000,0xc40000,0xc40000,0xc40000,0xc40000,0xc40000,0xc40000},
  {0xc10180,0xc44500,0xc101f8,0xd010302,0x4b0102d2,0x7801c043,0x8420063,0xc080f3,0x6241004d,0x1e809065,0x218100f5,0xd6810366,0xc102f6,0xc2006f,0xc40000,0xc40000,0xc40000,0xc40000,0xc40000,0xc40000,0xc40000,0xc40000,0xc40000,0xc40000},
  {0xc10140,0xc44380,0xc10120,0xe010342,0x4c01035a,0xc1022a,0xc1026a,0xc1e06b,0x4540c07b,0xc10134,0x3581006d,0x458101de,0x7c810276,0xc10376,0xc15077,0xc40000,0xc40000,0xc40000,0xc40000,0xc40000,0xc40000,0xc40000,0xc40000,0xc40000},
  {0xc10240,0xc44800,0xe10230,0xc10502,0x4d010392,0xc1041a,0xc103a2,0xc1209b,0x2040c0ab,0x4441025c,0xd810274,0x2581040e,0xc103de,0x7f8103f6,0xc10526,0xc130bf,0xc40000,0xc40000,0xc40000,0xc40000,0xc40000,0xc40000,0xc40000,0xc40000},
  {0xc10298,0xc448c0,0xc102e8,0xf010442,0x4e0104da,0xc10522,0xc104b2,0xc1c0a3,0x4c41029c,0x706102b4,0x1981044e,0x5a8100bd,0x6a810536,0xc1052e,0xc160b7,0xc40000,0xc40000,0xc40000,0xc40000,0xc40000,0xc40000,0xc40000,0xc40000,0xc40000},
  {0xc10300,0xe10330,0xc44dc0,0xc100e9,0xb401055a,0xc105a2,0xc105b2,0xc106f2,0xc0b0eb,0x4d61035c,0x5a61032c,0xc1058e,0xc1059e,0x7781056e,0xc105de,0xc170f7,0xc40000,0xc40000,0xc40000,0xc40000,0xc40000,0xc40000,0xc40000,0xc40000},
  {0xc103c8,0xe103a0,0xc04081,0x2010642,0x5c010652,0xc10622,0xb41d0d3,0x3c8103c4,0x4ba1039c,0xe103b4,0xe103bc,0xc10616,0xc1062e,0xc1063e,0xc1a0d7,0xc40000,0xc40000,0xc40000,0xc40000,0xc40000,0xc40000,0xc40000,0xc40000,0xc40000},
  {0xc100c0,0xc442c0,0xc100b8,0x192100f8,0x2301014a,0xc100e2,0xc100ea,0xc19023,0x336100cc,0x694100e4,0x3aa100bc,0xc10116,0xc101ae,0xc1017e,0xc1d01f,0xc40000,0xc40000,0xc40000,0xc40000,0xc40000,0xc40000,0xc40000,0xc40000,0xc40000},
  {0xc10188,0xe101a8,0xc080c9,0x18010071,0x400102a2,0xc102ea,0xc10332,0x11410184,0x2f6101d4,0x3a6101a4,0x6a410346,0xc102ce,0xc102de,0xc1036e,0xc15047,0xc0a07f,0xc40000,0xc40000,0xc40000,0xc40000,0xc40000,0xc40000,0xc40000,0xc40000},
  {0xc10100,0xc44480,0xc10178,0xc10242,0x4f010212,0xc101e2,0xe41f05b,0x2b61014c,0x3b61015c,0x6b61012c,0x7761017c,0x1a81021e,0x7481022e,0xc1026e,0xc19077,0xc40000,0xc40000,0xc40000,0xc40000,0xc40000,0xc40000,0xc40000,0xc40000,0xc40000},
  {0xc10210,0x2d210250,0xe10238,0xc1038a,0x6b0103e2,0x7001d08b,0x19410204,0xe1024c,0xe10224,0xe1023c,0xc040a5,0x4e8103ce,0xc103ee,0xc10416,0xc1a0af,0xc40000,0xc40000,0xc40000,0xc40000,0xc40000,0xc40000,0xc40000,0xc40000,0xc40000},
  {0xc10280,0xc44980,0xc102e0,0xc104c2,0x5401051a,0xc104e2,0xd41e093,0xc10284,0xc102dc,0xc102ec,0xc0c0a5,0x3e810456,0x6b8104ae,0xc104f6,0xc1b087,0xc40000,0xc40000,0xc40000,0xc40000,0xc40000,0xc40000,0xc40000,0xc40000,0xc40000},
  {0xc10310,0xc44b40,0xc10360,0xc106c2,0x550105ca,0xc10562,0xc105da,0xc1057a,0xc10304,0xc1031c,0xc10334,0x278100ed,0x438106de,0xc10576,0xc105b6,0xc150f7,0xc40000,0xc40000,0xc40000,0xc40000,0xc40000,0xc40000,0xc40000,0xc40000},
  {0xc10380,0xc44c80,0xc040c1,0x1e2103b0,0xc1068a,0x600106d2,0xc1066a,0xc1063a,0xc0f0db,0x3d610394,0x6c4103ac,0x3ba103fc,0xc10696,0xc10666,0xc10676,0xc0f0cf,0xc0e0ff,0xc40000,0xc40000,0xc40000,0xc40000,0xc40000,0xc40000,0xc40000},
  {0xc10090,0xc44200,0xc100e8,0x1a044340,0xc10031,0x39010152,0xc10122,0xc101b2,0x17410084,0xc11033,0x5c40703b,0xc100b4,0x2d810025,0x468100de,0x79810176,0xc101b6,0xc16027,0xc40000,0xc40000,0xc40000,0xc40000,0xc40000,0xc40000,0xc40000},
  {0xc101c8,0xc101e8,0xc10061,0x2601034a,0x6f0102aa,0x7f01036a,0xc102fa,0xe101cc,0xc1019c,0xc101f4,0x38a101fc,0x4c810316,0xc102ee,0xc1030e,0xc0c0cf,0xc0e07f,0xc40000,0xc40000,0xc40000,0xc40000,0xc40000,0xc40000,0xc40000,0xc40000},
  {0xc10098,0xc44300,0xc100f0,0xc10182,0x56010192,0xc1011a,0xf420013,0x2a414033,0x636100a4,0x784100c6,0xc100d6,0x628100e6,0xc10126,0xc1c00f,0xc40000,0xc40000,0xc40000,0xc40000,0xc40000,0xc40000,0xc40000,0xc40000,0xc40000,0xc40000},
  {0xc101c0,0xc44540,0xc101b8,0xc102c2,0x57010312,0xc10362,0xc10372,0xc09053,0x15411063,0xc10194,0xc0508d,0x981005d,0x3381028e,0x5e81031e,0xc102fe,0xc0f05f,0xc1007f,0xc40000,0xc40000,0xc40000,0xc40000,0xc40000,0xc40000,0xc40000},
};
uint8_t kSeq[NPAIR][KMAX] = {
  {0,1,2,3,0,1,2,3,4,5,6,7,8,9,10,11,12,13,14,15,0,1,2,3,64,67,72,78,76,70,66,74,64,66,76,78,65,67,77,79,68,70,69,71,72,74,73,75,4,6,0,2,5,7,1,3,12,14,8,10,13,15,9,11,4,6,8,10,0,2,5,7,9,11,12,14,1,3,13,15,88,89,94,95,116,117,118,119,106,107,78,79,82,83,112,113,84,85,102,103,98,99,72,73,72,73,80,81,98,99,74,75,110,111,112,113,86,87,92,93,78,79,64,65,66,67,84,68,70,69,71,76,78,72,74,64,66,77,79,73,75,65,67,68,70,72,74,69,71,64,66,76,78,73,75,65,67,77,79,8,10,0,2,9,11,12,14,1,3,4,6,13,15,5,7,12,14,8,10,4,6,0,2,13,15,9,11,5,7,1,3,12,14,8,10,13,15,4,6,9,11,5,7,0,2,1,3,200,202,73,75,196,198,192,194,204,206,197,199,193,195,205,207,71,66,67,112,113,98,99,86,87,110,111,114,115,88,89,118,119,196,197,230,0,0,0,0,0,0,0,0,0,0,0,0,0,0,0,0,0,0,0,0,0,0,0,0,0,0,0,0,0,0,0,0,0,0,0,0,0,0,0,0,0,0,0,0,0,0,0,0,0,0,0,0,0},
  {0,1,2,3,0,1,2,3,4,5,6,7,8,9,10,11,12,13,14,15,0,1,2,3,77,69,73,79,65,68,75,71,70,64,76,66,74,72,79,71,78,67,69,65,75,77,68,73,12,14,8,10,13,15,9,11,0,2,4,6,1,3,5,7,76,78,72,74,77,79,73,75,64,66,68,70,65,67,69,71,4,6,12,14,8,10,0,2,5,7,13,15,9,11,1,3,114,115,100,101,74,75,116,117,118,0,2,4,6,8,10,1,3,5,7,12,14,9,11,13,15,76,78,68,70,77,79,64,66,72,74,69,71,65,67,73,75,12,14,4,6,0,2,13,15,5,7,8,10,1,3,9,11,8,10,12,14,0,2,9,11,13,15,1,3,4,6,5,7,8,10,9,11,4,6,0,2,12,14,5,7,1,3,13,15,4,6,12,14,8,10,5,7,13,15,9,11,0,2,1,3,12,14,8,10,13,15,4,6,9,11,5,7,128,130,1,3,99,64,65,80,81,92,93,108,109,106,107,70,71,66,67,90,91,88,89,82,83,224,225,232,233,230,231,0,0,0,0,0,0,0,0,0,0,0,0,0,0,0,0,0,0,0,0,0,0,0,0,0,0,0,0,0,0,0,0,0,0,0,0,0,0,0,0,0,0,0,0,0,0,0,0,0,0,0,0},
  {64,65,66,67,68,69,70,71,72,73,74,75,76,77,78,79,0,1,2,3,79,75,77,73,0,2,12,14,1,3,13,15,4,6,5,7,8,10,9,11,64,66,72,74,65,67,73,75,76,78,68,70,77,79,69,71,4,6,12,14,8,10,0,2,5,7,13,15,9,11,1,3,0,2,8,10,4,6,12,14,1,3,9,11,5,7,13,15,83,98,99,108,109,92,93,78,79,84,85,100,101,66,67,74,75,88,66,67,84,85,68,69,90,91,104,105,70,71,210,211,228,229,106,107,222,71,72,69,66,64,78,74,77,76,75,73,64,71,78,77,69,72,75,70,74,79,76,73,68,67,66,65,64,71,78,74,77,70,73,69,66,72,76,79,68,65,67,75,4,6,5,7,8,10,12,14,9,11,13,15,0,2,1,3,4,6,12,14,8,10,5,7,13,15,0,2,9,11,1,3,106,107,104,105,92,93,88,89,72,73,90,91,100,101,78,79,116,117,64,65,118,119,208,209,94,95,76,77,240,241,0,0,0,0,0,0,0,0,0,0,0,0,0,0,0,0,0,0,0,0,0,0,0,0,0,0,0,0,0,0,0,0,0,0,0,0,0,0,0,0,0,0,0,0,0,0,0,0,0,0,0,0,0,0,0,0,0,0,0,0,0,0,0,0,0,0},
  {0,1,2,3,4,5,6,7,8,9,10,11,12,13,14,15,0,1,2,3,66,74,68,64,0,2,12,14,1,3,13,15,4,6,5,7,8,10,9,11,64,66,72,74,65,67,73,75,76,78,68,70,77,79,69,71,4,6,0,2,5,7,1,3,12,14,8,10,13,15,9,11,4,6,12,14,8,10,0,2,5,7,13,15,9,11,1,3,92,93,64,65,100,101,96,97,89,76,77,96,97,86,87,72,73,116,117,110,111,4,6,5,7,12,14,8,10,0,2,13,15,9,11,1,3,0,2,1,3,4,6,8,10,12,14,5,7,9,11,13,15,8,10,12,14,0,2,9,11,13,15,1,3,4,6,5,7,8,10,0,2,9,11,12,14,1,3,4,6,13,15,5,7,4,6,5,7,8,10,12,14,9,11,13,15,0,2,1,3,4,6,12,14,8,10,5,7,13,15,0,2,9,11,1,3,77,112,113,110,111,82,83,70,71,68,69,102,103,108,80,81,66,67,90,91,96,97,242,243,202,203,70,199,238,239,0,0,0,0,0,0,0,0,0,0,0,0,0,0,0,0,0,0,0,0,0,0,0,0,0,0,0,0,0,0,0,0,0,0,0,0,0,0,0,0,0,0,0,0,0,0,0,0,0,0,0,0,0,0,0,0,0,0,0,0,0},
  {64,65,66,67,68,69,70,71,72,73,74,75,76,77,78,79,64,65,66,67,68,69,70,71,72,73,74,75,76,77,78,79,64,65,66,67,68,69,70,71,72,73,74,75,76,77,78,79,198,69,194,199,204,12,14,8,10,13,15,9,11,0,2,4,6,1,3,5,7,70,71,64,65,98,99,92,93,78,79,112,113,94,95,72,73,80,81,84,85,114,115,116,117,106,107,66,8,10,0,2,9,11,1,3,12,14,13,15,4,6,5,7,0,2,4,6,8,10,1,3,5,7,12,14,9,11,13,15,4,6,5,7,0,2,8,10,12,14,1,3,9,11,13,15,68,70,69,71,64,66,72,74,76,78,65,67,73,75,77,79,132,134,128,130,133,135,129,131,136,138,140,142,137,139,141,143,8,10,0,2,9,11,12,14,1,3,4,6,13,15,5,7,12,14,8,10,4,6,0,2,13,15,9,11,5,7,1,3,4,6,12,14,8,10,5,7,13,15,0,2,137,139,1,3,92,93,108,109,98,99,80,81,100,101,70,71,116,117,96,97,74,75,64,65,112,113,82,83,234,235,212,213,0,0,0,0,0,0,0,0,0,0,0,0,0,0,0,0,0,0,0,0,0,0,0,0,0,0,0,0,0,0,0,0,0,0,0,0,0,0,0,0,0,0,0,0},
  {0,1,2,3,0,1,2,3,0,1,2,3,4,5,6,7,8,9,10,11,12,13,14,15,0,1,2,3,4,5,6,7,8,9,10,11,12,13,14,15,70,64,76,66,0,2,8,10,1,3,9,11,12,14,4,6,13,15,5,7,4,6,0,2,5,7,1,3,12,14,8,10,13,15,9,11,0,2,8,10,4,6,12,14,1,3,9,11,5,7,13,15,93,78,79,84,85,100,101,66,67,74,75,88,89,76,77,96,97,86,87,72,73,116,117,110,111,84,85,88,89,114,115,110,66,71,70,77,69,73,72,64,65,78,67,75,79,74,76,68,12,14,4,6,0,2,13,15,5,7,8,10,1,3,9,11,132,134,128,130,133,135,129,131,136,138,140,142,137,139,141,143,8,10,9,11,4,6,0,2,12,14,5,7,1,3,13,15,4,6,12,14,8,10,5,7,13,15,9,11,0,2,1,3,140,142,136,138,141,143,132,134,137,139,133,135,128,130,129,131,72,73,86,87,102,103,90,91,118,119,68,69,206,207,114,115,66,67,110,111,94,95,88,217,204,205,0,0,0,0,0,0,0,0,0,0,0,0,0,0,0,0,0,0,0,0,0,0,0,0,0,0,0,0,0,0,0,0,0,0,0,0,0,0,0,0,0,0,0,0,0,0,0,0,0,0},
  {0,1,2,3,0,1,2,3,0,1,2,3,4,5,6,7,8,9,10,11,12,13,14,15,0,1,2,3,0,1,2,3,4,5,6,7,8,9,10,11,12,13,14,15,0,2,8,10,1,3,9,11,12,14,4,6,13,15,5,7,4,6,0,2,5,7,1,3,12,14,8,10,13,15,9,11,0,2,8,10,4,6,12,14,1,3,9,11,5,7,13,15,4,6,12,14,8,10,0,2,5,7,13,15,9,11,1,3,8,10,0,2,9,11,1,3,12,14,13,15,4,6,5,7,204,205,236,237,240,241,210,211,226,227,228,229,192,193,200,201,208,209,202,203,212,213,214,215,8,10,12,14,0,2,9,11,13,15,1,3,4,6,5,7,78,74,77,71,70,64,66,69,79,200,75,68,204,73,195,65,4,6,5,7,8,10,12,14,9,11,13,15,0,2,1,3,132,134,140,142,136,138,133,135,141,143,128,130,137,139,129,131,99,102,103,86,87,104,105,78,79,118,119,114,115,88,89,112,113,100,101,64,65,84,85,94,95,224,225,82,83,196,197,0,0,0,0,0,0,0,0,0,0,0,0,0,0,0,0,0,0,0,0,0,0,0,0,0,0,0,0,0,0,0,0,0,0,0,0,0,0,0,0,0,0,0,0,0,0,0,0,0,0,0,0,0},
  {0,1,2,3,0,1,2,3,4,5,6,7,8,9,10,11,12,13,14,15,66,74,68,64,64,74,76,66,68,70,65,72,79,67,69,71,78,75,77,73,0,2,8,10,1,3,9,11,12,14,4,6,13,15,5,7,12,14,8,10,13,15,9,11,0,2,4,6,1,3,5,7,4,6,12,14,8,10,0,2,5,7,13,15,9,11,1,3,0,2,8,10,4,6,12,14,1,3,9,11,5,7,13,15,99,100,101,90,91,70,71,76,77,68,69,110,111,82,83,74,75,96,97,118,119,104,105,238,239,242,243,232,233,218,219,220,221,230,231,196,197,8,10,12,14,0,2,9,11,13,15,1,3,4,6,5,7,8,10,0,2,9,11,12,14,1,3,4,6,13,15,5,7,4,6,5,7,8,10,12,14,9,11,13,15,0,2,1,3,4,6,140,142,136,138,133,135,141,143,128,130,137,139,129,131,80,81,96,97,92,93,108,109,70,71,82,83,100,101,78,79,74,75,114,115,94,95,118,119,200,201,192,193,240,241,226,0,0,0,0,0,0,0,0,0,0,0,0,0,0,0,0,0,0,0,0,0,0,0,0,0,0,0,0,0,0,0,0,0,0,0,0,0,0,0,0,0,0,0,0,0,0,0,0,0,0,0,0,0,0,0,0,0,0,0,0},
  {0,1,2,3,0,1,2,3,4,5,6,7,8,9,10,11,12,13,14,15,69,76,67,65,128,129,130,131,132,133,134,135,136,137,138,139,140,141,142,143,0,2,8,10,1,3,9,11,12,14,4,6,13,15,5,7,4,6,8,10,0,2,5,7,9,11,12,14,1,3,13,15,88,89,94,95,116,117,118,119,106,107,78,79,82,83,112,113,84,85,102,103,98,99,72,73,92,93,64,65,100,101,0,2,4,6,8,10,1,3,5,7,12,14,9,11,13,15,12,14,4,6,13,15,0,2,8,10,5,7,1,3,9,11,222,223,244,245,12,14,4,6,0,2,13,15,5,7,8,10,1,3,9,11,132,134,128,130,133,135,129,131,136,138,140,142,137,139,141,143,8,10,9,11,4,6,0,2,12,14,5,7,1,3,13,15,4,6,5,7,8,10,12,14,9,11,13,15,0,2,1,3,12,14,8,10,13,15,4,6,9,11,5,7,0,2,1,3,65,112,113,98,99,88,89,86,87,84,85,90,91,106,235,68,69,104,105,76,77,116,117,110,111,102,103,194,195,0,0,0,0,0,0,0,0,0,0,0,0,0,0,0,0,0,0,0,0,0,0,0,0,0,0,0,0,0,0,0,0,0,0,0,0,0,0,0,0,0,0,0,0,0,0,0,0,0},
  {0,1,2,3,0,1,2,3,4,5,6,7,8,9,10,11,12,13,14,15,0,1,2,3,64,74,76,66,68,70,65,72,79,67,69,71,78,75,77,73,0,2,8,10,1,3,9,11,12,14,4,6,13,15,5,7,12,14,8,10,13,15,9,11,0,2,4,6,1,3,5,7,96,97,82,83,74,75,110,111,76,77,88,89,118,119,68,69,100,101,104,105,102,103,90,91,8,10,0,2,9,11,1,3,12,14,13,15,4,6,5,7,12,14,4,6,13,15,0,2,8,10,5,7,1,3,9,11,4,6,5,7,0,2,8,10,12,14,1,3,9,11,13,15,4,6,8,10,5,7,0,2,12,14,9,11,1,3,13,15,77,69,78,72,76,68,66,73,79,67,75,65,8,10,9,11,4,6,0,2,12,14,5,7,1,3,13,15,4,6,12,14,8,10,5,7,13,15,9,11,0,2,1,3,12,14,8,10,132,134,0,2,141,143,9,11,133,135,129,131,64,65,80,81,92,93,108,109,106,107,70,71,66,67,90,91,88,89,82,83,96,97,232,233,230,231,0,0,0,0,0,0,0,0,0,0,0,0,0,0,0,0,0,0,0,0,0,0,0,0,0,0,0,0,0,0,0,0,0,0,0,0,0,0,0,0,0,0,0,0,0,0,0,0,0,0},
  {64,65,66,67,68,69,70,71,72,73,74,75,76,77,78,79,0,1,2,3,4,5,6,7,8,9,10,11,12,13,14,15,64,74,76,66,68,70,65,72,79,67,69,71,78,75,77,73,0,2,8,10,1,3,9,11,12,14,4,6,13,15,5,7,4,6,0,2,5,7,1,3,12,14,8,10,13,15,9,11,114,115,76,77,70,71,86,87,90,91,74,75,66,67,68,69,80,81,108,109,110,111,104,105,84,85,88,89,114,115,110,111,98,99,66,67,94,85,68,69,90,91,104,105,70,71,210,211,100,101,234,235,4,6,5,7,0,2,8,10,12,14,1,3,9,11,13,15,8,10,12,14,0,2,9,11,13,15,1,3,4,6,5,7,8,10,0,2,9,11,12,14,1,3,4,6,13,15,5,7,4,6,5,7,8,10,12,14,9,11,13,15,0,2,1,3,4,6,12,14,8,10,133,135,13,15,0,2,137,139,1,3,99,102,103,86,87,104,105,78,79,118,119,114,115,88,89,112,113,100,101,64,65,84,85,94,95,224,225,210,211,196,197,0,0,0,0,0,0,0,0,0,0,0,0,0,0,0,0,0,0,0,0,0,0,0,0,0,0,0,0,0,0,0,0,0,0,0,0,0,0,0,0,0,0,0,0,0,0,0,0,0,0,0,0,0},
  {0,1,2,3,4,5,6,7,8,9,10,11,12,13,14,15,0,1,2,3,4,5,6,7,8,9,10,11,12,13,14,15,0,1,2,3,0,1,2,3,0,1,2,3,0,2,8,10,1,3,9,11,12,14,4,6,13,15,5,7,4,6,8,10,0,2,5,7,9,11,12,14,1,3,13,15,0,2,8,10,4,6,12,14,1,3,9,11,5,7,13,15,72,73,92,93,64,65,100,101,96,97,114,115,76,77,0,2,4,6,8,10,1,3,5,7,12,14,9,11,13,15,204,205,108,109,112,113,210,211,226,227,228,229,192,193,200,201,208,209,202,203,212,213,214,71,69,72,78,64,77,75,74,79,73,67,76,70,68,66,65,68,66,73,79,67,75,65,78,74,77,71,70,64,194,69,207,200,75,196,204,73,195,65,4,6,5,7,8,10,12,14,9,11,13,15,0,2,1,3,12,14,8,10,13,15,4,6,9,11,5,7,0,2,1,3,65,112,113,98,99,88,89,86,87,84,85,90,91,106,107,68,69,104,105,76,77,116,117,238,239,102,103,194,195,0,0,0,0,0,0,0,0,0,0,0,0,0,0,0,0,0,0,0,0,0,0,0,0,0,0,0,0,0,0,0,0,0,0,0,0,0,0,0,0,0,0,0,0,0,0,0,0,0,0,0},
  {0,1,2,3,4,5,6,7,8,9,10,11,12,13,14,15,0,1,2,3,4,5,6,7,8,9,10,11,12,13,14,15,128,129,130,131,132,133,134,135,136,137,138,139,140,141,142,143,192,193,194,195,196,197,198,199,200,201,202,203,204,205,206,207,4,6,8,10,0,2,5,7,9,11,12,14,1,3,13,15,0,2,8,10,4,6,12,14,1,3,9,11,5,7,13,15,64,65,70,71,80,81,112,113,90,91,102,103,118,119,104,105,114,115,106,107,94,95,68,69,82,12,14,4,6,13,15,0,2,8,10,5,7,1,3,9,11,0,2,1,3,4,6,8,10,12,14,5,7,9,11,13,15,68,70,72,74,69,71,64,66,76,78,73,75,65,67,77,79,64,71,78,74,77,70,73,69,66,72,76,79,68,65,67,75,4,6,5,7,8,10,12,14,9,11,13,15,0,2,1,3,4,6,12,14,8,10,5,7,13,15,9,11,0,2,1,3,204,206,200,202,196,198,192,194,205,207,201,203,197,199,193,195,78,79,106,107,86,87,94,95,76,77,220,221,72,73,98,227,212,213,0,0,0,0,0,0,0,0,0,0,0,0,0,0,0,0,0,0,0,0,0,0,0,0,0,0,0,0,0,0,0,0,0,0,0,0,0,0,0,0,0,0,0,0,0},
  {0,1,2,3,0,1,2,3,0,1,2,3,4,5,6,7,8,9,10,11,12,13,14,15,64,67,72,77,69,73,78,76,70,66,74,79,65,68,75,71,0,2,8,10,1,3,9,11,12,14,4,6,13,15,5,7,12,14,8,10,13,15,9,11,0,2,4,6,1,3,5,7,4,6,8,10,0,2,5,7,9,11,12,14,1,3,13,15,8,10,0,2,9,11,1,3,12,14,13,15,4,6,5,7,78,79,64,65,66,67,84,85,68,69,90,91,104,105,70,71,210,211,100,101,106,107,222,223,66,71,70,77,69,73,72,64,65,78,67,75,79,74,76,68,8,10,12,14,0,2,9,11,13,15,1,3,4,6,5,7,8,10,0,2,9,11,12,14,1,3,4,6,13,15,5,7,12,14,8,10,4,6,0,2,13,15,9,11,5,7,1,3,4,6,12,14,8,10,5,7,141,143,0,2,137,139,1,3,92,93,108,109,98,99,80,81,100,101,70,71,116,117,96,97,74,75,64,65,112,113,82,83,106,107,212,213,232,233,0,0,0,0,0,0,0,0,0,0,0,0,0,0,0,0,0,0,0,0,0,0,0,0,0,0,0,0,0,0,0,0,0,0,0,0,0,0,0,0,0,0,0,0,0,0,0,0,0,0,0,0,0,0,0,0,0,0},
  {0,1,2,3,0,1,2,3,0,1,2,3,4,5,6,7,8,9,10,11,12,13,14,15,64,67,72,77,69,73,78,76,70,64,66,76,78,65,67,77,79,68,70,69,71,72,74,73,75,12,14,8,10,13,15,9,11,0,2,4,6,1,3,5,7,76,78,72,74,77,79,73,75,64,66,68,70,65,67,69,71,0,2,8,10,4,6,12,14,1,3,9,11,5,7,13,15,84,85,88,89,114,115,110,111,98,99,66,67,94,95,70,71,76,77,106,107,96,97,64,65,78,79,90,91,4,6,5,7,0,2,8,10,12,14,1,3,9,11,13,15,4,6,8,10,5,7,0,2,12,14,9,11,1,3,13,15,132,134,128,130,133,135,129,131,136,138,140,142,137,139,141,143,12,14,8,10,4,6,0,2,13,15,9,11,5,7,1,3,12,14,8,10,4,6,0,2,13,15,9,11,5,7,1,3,12,14,8,10,13,15,132,134,9,11,133,135,128,130,129,131,99,88,89,86,87,84,85,90,91,234,235,68,69,104,105,76,77,116,117,110,111,102,103,194,195,0,0,0,0,0,0,0,0,0,0,0,0,0,0,0,0,0,0,0,0,0,0,0,0,0,0,0,0,0,0,0,0,0,0,0,0,0,0,0,0,0,0,0,0,0,0,0,0,0,0},
  {0,1,2,3,0,1,2,3,0,1,2,3,4,5,6,7,8,9,10,11,12,13,14,15,79,75,77,73,128,129,130,131,132,133,134,135,136,137,138,139,140,141,142,143,0,2,8,10,1,3,9,11,12,14,4,6,13,15,5,7,4,6,8,10,0,2,5,7,9,11,12,14,1,3,13,15,4,6,12,14,8,10,0,2,5,7,13,15,9,11,1,3,8,10,0,2,9,11,1,3,12,14,13,15,4,6,5,7,8,10,0,2,9,11,1,3,12,14,13,15,4,6,5,7,4,6,5,7,12,14,8,10,0,2,13,15,9,11,1,3,12,14,4,6,0,2,13,15,5,7,8,10,1,3,9,11,8,10,12,14,0,2,9,11,13,15,1,3,4,6,5,7,8,10,9,11,4,6,0,2,12,14,5,7,1,3,13,15,4,6,5,7,8,10,12,14,9,11,13,15,0,2,1,3,4,6,12,14,8,10,5,7,13,15,0,2,9,11,1,3,109,86,87,114,115,98,99,66,67,84,85,96,97,74,75,102,103,80,81,96,97,76,77,218,219,236,237,0,0,0,0,0,0,0,0,0,0,0,0,0,0,0,0,0,0,0,0,0,0,0,0,0,0,0,0,0,0,0,0,0,0,0,0,0,0,0,0,0,0,0,0,0,0,0,0,0},
  {0,1,2,3,0,1,2,3,0,1,2,3,4,5,6,7,8,9,10,11,12,13,14,15,72,78,70,71,66,74,68,70,66,74,79,65,68,75,71,74,72,79,71,78,67,69,65,75,77,68,73,12,14,8,10,13,15,9,11,0,2,4,6,1,3,5,7,4,6,12,14,8,10,0,2,5,7,13,15,9,11,1,3,4,6,8,10,0,2,5,7,9,11,12,14,1,3,13,15,68,69,82,83,98,99,108,109,92,93,78,79,84,85,100,101,66,67,74,75,86,87,92,93,118,119,68,69,216,217,198,199,206,207,246,247,194,195,238,239,242,243,232,233,8,10,12,14,0,2,9,11,13,15,1,3,4,6,5,7,8,10,0,2,9,11,12,14,1,3,4,6,13,15,5,7,4,6,5,7,8,10,12,14,9,11,13,15,0,2,1,3,132,134,140,142,136,138,133,135,141,143,128,130,137,139,129,131,106,107,104,105,92,93,88,89,72,73,90,91,100,101,78,79,116,117,64,65,118,119,208,209,94,95,76,77,240,241,238,239,0,0,0,0,0,0,0,0,0,0,0,0,0,0,0,0,0,0,0,0,0,0,0,0,0,0,0,0,0,0,0,0,0,0,0,0,0,0,0,0,0,0,0,0,0,0,0,0,0,0,0,0,0,0,0,0,0},
  {0,1,2,3,0,1,2,3,0,1,2,3,4,5,6,7,8,9,10,11,12,13,14,15,0,1,2,3,0,1,2,3,4,5,6,7,8,9,10,11,12,13,14,15,76,69,70,72,74,66,71,75,67,77,68,73,79,206,64,65,12,14,8,10,13,15,9,11,0,2,4,6,1,3,5,7,0,2,8,10,4,6,12,14,1,3,9,11,5,7,13,15,0,2,8,10,4,6,12,14,1,3,9,11,5,7,13,15,8,10,0,2,9,11,1,3,12,14,13,15,4,6,5,7,12,14,4,6,13,15,0,2,8,10,5,7,1,3,9,11,0,2,1,3,4,6,8,10,12,14,5,7,9,11,13,15,8,10,12,14,0,2,9,11,13,15,1,3,4,6,5,7,8,10,0,2,9,11,12,14,1,3,4,6,13,15,5,7,4,6,5,7,8,10,12,14,9,11,13,15,0,2,1,3,4,6,140,142,136,138,5,7,141,143,0,2,137,139,129,131,75,98,99,66,67,80,81,92,93,114,115,112,113,88,89,110,111,82,83,68,69,104,105,108,109,102,103,244,245,0,0,0,0,0,0,0,0,0,0,0,0,0,0,0,0,0,0,0,0,0,0,0,0,0,0,0,0,0,0,0,0,0,0,0,0,0,0,0,0,0,0,0,0,0,0,0},
  {0,1,2,3,0,1,2,3,4,5,6,7,8,9,10,11,12,13,14,15,69,76,67,65,0,2,12,14,1,3,13,15,4,6,5,7,8,10,9,11,12,14,8,10,13,15,9,11,0,2,4,6,1,3,5,7,67,108,109,86,87,96,97,82,83,74,75,110,111,76,77,88,89,118,119,68,69,100,101,104,105,102,103,90,91,8,10,0,2,9,11,1,3,12,14,13,15,4,6,5,7,0,2,4,6,8,10,1,3,5,7,12,14,9,11,13,15,4,6,5,7,12,14,8,10,0,2,13,15,9,11,1,3,12,14,4,6,0,2,13,15,5,7,8,10,1,3,9,11,132,134,128,130,133,135,129,131,136,138,140,142,137,139,141,143,8,10,9,11,4,6,0,2,12,14,5,7,1,3,13,15,4,6,12,14,8,10,5,7,13,15,9,11,0,2,1,3,12,14,8,10,4,6,0,2,13,15,9,11,5,7,1,3,80,81,96,97,92,93,108,109,70,71,82,83,100,101,206,207,74,75,114,115,94,95,118,119,200,201,192,0,0,0,0,0,0,0,0,0,0,0,0,0,0,0,0,0,0,0,0,0,0,0,0,0,0,0,0,0,0,0,0,0,0,0,0,0,0,0,0,0,0,0,0,0,0,0,0,0,0,0,0,0,0,0,0},
  {0,1,2,3,0,1,2,3,4,5,6,7,8,9,10,11,12,13,14,15,64,79,75,77,73,69,76,67,65,64,74,76,66,68,70,65,72,79,67,69,71,78,75,77,73,12,14,8,10,13,15,9,11,0,2,4,6,1,3,5,7,4,6,12,14,8,10,0,2,5,7,13,15,9,11,1,3,76,77,88,89,106,107,78,79,96,97,108,109,114,115,100,101,74,75,116,117,118,119,82,83,112,113,98,72,73,80,81,98,99,74,75,110,111,112,113,86,87,92,93,4,6,5,7,0,2,8,10,12,14,1,3,9,11,13,15,12,14,4,6,0,2,13,15,5,7,8,10,1,3,9,11,8,10,12,14,0,2,9,11,13,15,1,3,4,6,5,7,8,10,9,11,4,6,0,2,12,14,5,7,1,3,13,15,4,6,5,7,8,10,12,14,9,11,13,15,0,2,1,3,132,134,133,135,136,138,140,142,137,139,141,143,128,130,129,131,90,91,106,107,92,93,116,117,72,73,76,77,108,109,110,111,208,209,70,71,66,67,202,203,226,0,0,0,0,0,0,0,0,0,0,0,0,0,0,0,0,0,0,0,0,0,0,0,0,0,0,0,0,0,0,0,0,0,0,0,0,0,0,0,0,0,0,0,0,0,0,0,0,0,0,0,0,0,0,0},
  {64,65,66,67,68,69,70,71,72,73,74,75,76,77,78,79,0,1,2,3,0,1,2,3,64,65,66,67,68,69,70,71,72,73,74,75,76,77,78,79,72,76,64,70,66,74,71,78,67,79,65,197,75,68,73,77,4,6,0,2,5,7,1,3,12,14,8,10,13,15,9,11,4,6,12,14,8,10,0,2,5,7,13,15,9,11,1,3,68,70,72,74,64,66,69,71,73,75,76,78,65,67,77,79,8,10,0,2,9,11,1,3,12,14,13,15,4,6,5,7,76,77,108,109,112,113,82,83,226,227,100,101,64,65,200,201,208,209,202,203,212,213,214,215,71,69,72,78,64,77,75,74,79,73,67,8,10,12,14,0,2,9,11,13,15,1,3,4,6,5,7,8,10,9,11,4,6,0,2,12,14,5,7,1,3,13,15,4,6,12,14,8,10,5,7,13,15,9,11,0,2,1,3,132,134,140,142,136,138,133,135,141,143,128,130,137,139,129,131,64,65,84,85,92,93,104,105,74,75,78,79,100,101,82,83,72,73,116,117,222,223,234,235,198,0,0,0,0,0,0,0,0,0,0,0,0,0,0,0,0,0,0,0,0,0,0,0,0,0,0,0,0,0,0,0,0,0,0,0,0,0,0,0,0,0,0,0,0,0,0,0,0,0,0,0,0},
  {0,1,2,3,4,5,6,7,8,9,10,11,12,13,14,15,0,1,2,3,192,193,194,195,196,197,198,199,200,201,202,203,204,205,206,207,64,66,76,78,65,67,77,79,68,70,69,71,72,74,73,75,4,6,0,2,5,7,1,3,12,14,8,10,13,15,9,11,4,6,8,10,0,2,5,7,9,11,12,14,1,3,13,15,0,2,8,10,4,6,12,14,1,3,9,11,5,7,13,15,8,10,0,2,9,11,1,3,12,14,13,15,4,6,5,7,64,66,68,70,72,74,65,67,69,71,76,78,73,75,77,79,68,70,69,71,76,78,72,74,64,66,77,79,73,75,65,67,64,71,78,77,69,72,75,70,74,79,76,73,68,67,66,65,8,10,0,2,9,11,12,14,1,3,4,6,13,15,5,7,4,6,5,7,8,10,12,14,9,11,13,15,0,2,1,3,132,134,140,142,136,138,133,135,141,143,128,130,137,139,129,131,106,107,104,105,92,93,88,89,72,73,90,91,100,101,78,79,84,85,80,81,66,67,90,91,96,97,242,243,202,203,198,199,0,0,0,0,0,0,0,0,0,0,0,0,0,0,0,0,0,0,0,0,0,0,0,0,0,0,0,0,0,0,0,0,0,0,0,0,0,0,0,0,0,0,0,0,0,0,0,0,0,0,0,0},
  {64,65,66,67,68,69,70,71,72,73,74,75,76,77,78,79,0,1,2,3,64,65,66,67,68,69,70,71,72,73,74,75,76,77,78,79,64,66,76,78,65,67,77,79,68,70,69,71,72,74,73,75,64,66,72,74,65,67,73,75,76,78,68,70,77,79,69,71,4,6,8,10,0,2,5,7,9,11,12,14,1,3,13,15,80,81,108,109,110,111,104,105,0,2,8,10,4,6,12,14,1,3,9,11,5,7,13,15,0,2,4,6,8,10,1,3,5,7,12,14,9,11,13,15,4,6,5,7,12,14,8,10,0,2,13,15,9,11,1,3,71,72,69,66,64,78,74,77,76,75,73,8,10,12,14,0,2,9,11,13,15,1,3,4,6,5,7,8,10,0,2,9,11,12,14,1,3,4,6,13,15,5,7,4,6,5,7,8,10,12,14,9,11,13,15,0,2,1,3,132,134,140,142,136,138,133,135,141,143,128,130,137,139,129,131,64,65,78,79,90,91,106,107,94,95,68,69,96,97,74,75,98,99,66,67,80,81,220,221,242,243,112,113,216,217,236,0,0,0,0,0,0,0,0,0,0,0,0,0,0,0,0,0,0,0,0,0,0,0,0,0,0,0,0,0,0,0,0,0,0,0,0,0,0,0,0,0,0,0,0,0,0,0,0,0,0},
  {64,65,66,67,68,69,70,71,72,73,74,75,76,77,78,79,0,1,2,3,0,1,2,3,4,5,6,7,8,9,10,11,12,13,14,15,0,1,2,3,76,69,70,72,74,66,71,75,67,77,68,73,79,78,64,65,4,6,0,2,5,7,1,3,12,14,8,10,13,15,9,11,0,2,8,10,4,6,12,14,1,3,9,11,5,7,13,15,108,109,114,115,100,101,74,75,116,117,118,119,82,83,112,113,98,99,102,103,68,69,110,111,104,105,0,2,4,6,8,10,1,3,5,7,12,14,9,11,13,15,4,6,5,7,12,14,8,10,0,2,13,15,9,11,1,3,64,66,65,67,68,70,72,74,76,78,69,71,73,75,77,79,132,134,128,130,133,135,129,131,136,138,140,142,137,139,141,143,8,10,9,11,4,6,0,2,12,14,5,7,1,3,13,15,4,6,5,7,8,10,12,14,9,11,13,15,0,2,1,3,4,6,12,14,8,10,5,7,13,15,0,2,9,11,1,3,105,72,73,86,87,102,103,90,91,118,119,68,69,78,79,114,115,66,67,110,111,94,95,216,217,204,205,0,0,0,0,0,0,0,0,0,0,0,0,0,0,0,0,0,0,0,0,0,0,0,0,0,0,0,0,0,0,0,0,0,0,0,0,0,0,0,0,0,0,0},
  {64,65,66,67,68,69,70,71,72,73,74,75,76,77,78,79,64,65,66,67,68,69,70,71,72,73,74,75,76,77,78,79,0,1,2,3,128,129,130,131,132,133,134,135,136,137,138,139,140,141,142,143,198,197,194,199,204,203,206,4,6,0,2,5,7,1,3,12,14,8,10,13,15,9,11,0,2,8,10,4,6,12,14,1,3,9,11,5,7,13,15,8,10,0,2,9,11,1,3,12,14,13,15,4,6,5,7,8,10,0,2,9,11,1,3,12,14,13,15,4,6,5,7,12,14,4,6,13,15,0,2,8,10,5,7,1,3,9,11,0,2,1,3,4,6,8,10,12,14,5,7,9,11,13,15,8,10,12,14,0,2,9,11,13,15,1,3,4,6,5,7,8,10,9,11,4,6,0,2,12,14,5,7,1,3,13,15,12,14,8,10,4,6,0,2,13,15,9,11,5,7,1,3,12,14,8,10,13,15,4,6,9,11,5,7,0,2,1,3,118,119,76,77,74,75,68,69,72,73,100,101,110,111,84,85,206,207,116,117,94,95,242,243,86,87,240,241,226,227,0,0,0,0,0,0,0,0,0,0,0,0,0,0,0,0,0,0,0,0,0,0,0,0,0,0,0,0,0,0,0,0,0,0,0,0,0,0,0,0,0,0,0,0,0,0,0},
  {64,65,66,67,68,69,70,71,72,73,74,75,76,77,78,79,0,1,2,3,4,5,6,7,8,9,10,11,12,13,14,15,0,1,2,3,64,66,76,78,65,67,77,79,68,70,69,71,72,74,73,75,4,6,0,2,5,7,1,3,12,14,8,10,13,15,9,11,4,6,12,14,8,10,0,2,5,7,13,15,9,11,1,3,97,108,109,114,115,100,101,74,75,116,117,118,119,82,83,112,113,98,99,102,103,68,69,110,111,104,105,114,115,102,103,98,99,100,101,90,91,70,71,76,77,68,69,110,193,200,201,208,209,202,203,212,213,214,215,222,223,244,245,234,235,224,225,8,10,12,14,0,2,9,11,13,15,1,3,4,6,5,7,8,10,0,2,9,11,12,14,1,3,4,6,13,15,5,7,4,6,12,14,8,10,5,7,13,15,9,11,0,2,1,3,4,6,5,7,8,10,140,142,9,11,13,15,0,2,1,3,90,91,106,107,92,93,116,117,72,73,76,77,108,109,110,111,80,81,70,71,66,67,74,75,98,99,102,103,214,215,0,0,0,0,0,0,0,0,0,0,0,0,0,0,0,0,0,0,0,0,0,0,0,0,0,0,0,0,0,0,0,0,0,0,0,0,0,0,0,0,0,0,0,0,0,0,0,0,0,0,0,0,0,0,0},
  {0,1,2,3,0,1,2,3,0,1,2,3,4,5,6,7,8,9,10,11,12,13,14,15,0,1,2,3,74,66,76,79,70,72,64,67,71,69,78,68,75,65,77,73,0,2,8,10,1,3,9,11,12,14,4,6,13,15,5,7,203,206,200,202,196,201,207,205,195,192,193,0,2,8,10,4,6,12,14,1,3,9,11,5,7,13,15,4,6,12,14,8,10,0,2,5,7,13,15,9,11,1,3,112,113,84,85,88,89,66,67,78,79,92,93,72,73,80,81,106,107,116,117,236,237,64,65,94,95,4,6,5,7,0,2,8,10,12,14,1,3,9,11,13,15,4,6,8,10,5,7,0,2,12,14,9,11,1,3,13,15,72,74,76,78,64,66,73,75,77,79,65,67,68,70,69,71,72,79,194,76,192,67,202,196,199,206,198,197,205,201,193,203,12,14,8,10,13,15,4,6,9,11,5,7,0,2,1,3,90,91,106,107,92,93,116,117,72,73,76,77,108,109,110,111,80,81,70,71,66,67,74,75,98,82,83,68,69,104,105,108,109,102,103,244,245,0,0,0,0,0,0,0,0,0,0,0,0,0,0,0,0,0,0,0,0,0,0,0,0,0,0,0,0,0,0,0,0,0,0,0,0,0,0,0,0,0,0,0,0,0,0,0,0,0,0},
  {0,1,2,3,0,1,2,3,4,5,6,7,8,9,10,11,12,13,14,15,0,1,2,3,74,66,76,79,70,72,64,67,71,69,78,68,75,65,77,73,0,2,8,10,1,3,9,11,12,14,4,6,13,15,5,7,4,6,0,2,5,7,1,3,12,14,8,10,13,15,9,11,202,196,201,207,205,195,192,193,90,91,70,71,72,73,66,67,64,65,84,85,92,93,80,81,86,87,94,95,84,85,88,89,114,115,110,111,98,99,66,67,94,95,70,71,76,77,106,107,96,97,64,65,215,222,223,244,245,234,235,224,225,216,217,198,199,206,4,6,8,10,5,7,0,2,12,14,9,11,1,3,13,15,132,134,128,130,133,135,129,131,136,138,140,142,137,139,141,143,72,79,194,76,192,67,202,196,199,206,198,197,205,201,193,203,12,14,8,10,13,15,4,6,9,11,5,7,0,2,1,3,4,6,12,14,136,138,5,7,13,15,128,130,137,139,129,131,80,81,92,93,108,109,106,107,70,71,66,67,90,91,88,89,82,83,224,225,232,233,230,231,0,0,0,0,0,0,0,0,0,0,0,0,0,0,0,0,0,0,0,0,0,0,0,0,0,0,0,0,0,0,0,0,0,0,0,0,0,0,0,0,0,0,0,0,0,0,0,0,0,0,0,0,0,0},
  {64,65,66,67,68,69,70,71,72,73,74,75,76,77,78,79,0,1,2,3,4,5,6,7,8,9,10,11,12,13,14,15,192,193,194,195,196,197,198,199,200,201,202,203,204,205,206,207,0,2,8,10,1,3,9,11,12,14,4,6,13,15,5,7,4,6,0,2,5,7,1,3,12,14,8,10,13,15,9,11,0,2,8,10,4,6,12,14,1,3,9,11,5,7,13,15,119,82,83,112,113,98,99,102,103,68,69,110,111,104,105,72,74,64,66,73,75,65,67,76,78,77,79,68,70,69,71,66,71,70,77,69,73,72,64,65,78,67,75,79,74,76,68,76,78,68,70,64,66,77,79,69,71,72,74,65,67,73,75,132,134,128,130,133,135,129,131,136,138,140,142,137,139,141,143,78,74,77,71,70,64,194,69,207,200,75,196,204,73,195,65,12,14,8,10,13,15,4,6,9,11,5,7,0,2,1,3,72,74,64,66,73,75,76,78,65,67,196,198,77,79,197,199,68,69,96,97,74,75,98,99,66,67,80,81,92,93,114,115,112,113,88,89,108,109,246,247,0,0,0,0,0,0,0,0,0,0,0,0,0,0,0,0,0,0,0,0,0,0,0,0,0,0,0,0,0,0,0,0,0,0,0,0,0,0,0,0,0,0,0,0,0,0,0,0,0},
  {0,1,2,3,4,5,6,7,8,9,10,11,12,13,14,15,64,65,66,67,68,69,70,71,72,73,74,75,76,77,78,79,0,1,2,3,72,76,64,70,66,74,71,78,67,79,65,197,75,68,73,77,12,14,8,10,13,15,9,11,0,2,4,6,1,3,5,7,108,109,86,87,96,97,82,83,74,75,110,111,76,77,88,89,118,119,68,69,100,101,104,105,102,103,90,91,8,10,0,2,9,11,1,3,12,14,13,15,4,6,5,7,76,77,68,69,110,111,82,83,74,75,96,97,118,119,104,105,4,6,5,7,0,2,8,10,12,14,1,3,9,11,13,15,4,6,8,10,5,7,0,2,12,14,9,11,1,3,13,15,8,10,0,2,9,11,12,14,1,3,4,6,13,15,5,7,12,14,8,10,4,6,0,2,13,15,9,11,5,7,1,3,12,14,8,10,13,15,132,134,9,11,5,7,0,2,1,3,136,138,9,11,132,134,0,2,140,142,133,135,129,131,141,143,79,74,75,114,115,94,95,118,119,72,73,64,208,209,96,97,76,77,218,219,236,237,0,0,0,0,0,0,0,0,0,0,0,0,0,0,0,0,0,0,0,0,0,0,0,0,0,0,0,0,0,0,0,0,0,0,0,0,0,0,0,0,0,0,0,0,0,0,0,0,0,0},
  {64,65,66,67,68,69,70,71,72,73,74,75,76,77,78,79,0,1,2,3,0,1,2,3,66,74,68,64,66,74,79,65,68,75,71,72,76,64,70,66,74,71,78,67,79,65,69,75,68,73,77,4,6,0,2,5,7,1,3,12,14,8,10,13,15,9,11,70,71,64,65,98,99,92,93,78,79,112,113,94,95,72,73,80,81,84,85,114,115,116,117,106,107,66,67,108,8,10,0,2,9,11,1,3,12,14,13,15,4,6,5,7,12,14,4,6,13,15,0,2,8,10,5,7,1,3,9,11,4,6,5,7,12,14,8,10,0,2,13,15,9,11,1,3,76,78,4,6,0,2,13,15,5,7,8,10,1,3,9,11,8,10,0,2,9,11,12,14,1,3,4,6,13,15,5,7,12,14,8,10,4,6,0,2,13,15,9,11,5,7,1,3,12,14,8,10,13,15,4,6,9,11,5,7,0,2,1,3,92,93,108,109,98,99,80,81,100,101,70,71,116,117,96,97,74,75,64,65,112,113,82,83,234,235,84,85,104,112,113,228,229,192,193,216,217,246,247,0,0,0,0,0,0,0,0,0,0,0,0,0,0,0,0,0,0,0,0,0,0,0,0,0,0,0,0,0,0,0,0,0,0,0,0,0,0,0,0,0,0,0,0,0,0,0,0,0},
  {0,1,2,3,4,5,6,7,8,9,10,11,12,13,14,15,0,1,2,3,0,1,2,3,4,5,6,7,8,9,10,11,12,13,14,15,74,66,76,79,70,72,64,67,71,69,78,68,75,65,77,73,198,194,204,206,200,202,196,192,4,6,0,2,5,7,1,3,12,14,8,10,13,15,9,11,4,6,8,10,0,2,5,7,9,11,12,14,1,3,13,15,8,10,0,2,9,11,1,3,12,14,13,15,4,6,5,7,88,89,76,77,96,97,86,87,72,73,116,117,110,111,12,14,4,6,13,15,0,2,8,10,5,7,1,3,9,11,219,220,221,230,231,196,197,4,6,8,10,5,7,0,2,12,14,9,11,1,3,13,15,8,10,0,2,9,11,12,14,1,3,4,6,13,15,5,7,12,14,8,10,4,6,0,2,13,15,9,11,5,7,1,3,12,14,8,10,13,15,4,6,9,11,5,7,0,2,1,3,12,14,8,10,132,134,0,2,13,15,9,11,133,135,1,3,64,65,84,85,92,93,104,105,74,75,206,207,100,101,82,83,200,201,116,117,222,223,0,0,0,0,0,0,0,0,0,0,0,0,0,0,0,0,0,0,0,0,0,0,0,0,0,0,0,0,0,0,0,0,0,0,0,0,0,0,0,0,0,0,0,0,0,0,0,0,0},
  {0,1,2,3,4,5,6,7,8,9,10,11,12,13,14,15,64,65,66,67,68,69,70,71,72,73,74,75,76,77,78,79,0,1,2,3,64,66,76,78,65,67,77,79,68,70,69,71,72,74,73,75,12,14,8,10,13,15,9,11,0,2,4,6,1,3,5,7,4,6,12,14,8,10,0,2,5,7,13,15,9,11,1,3,0,2,8,10,4,6,12,14,1,3,9,11,5,7,13,15,112,113,84,85,88,89,66,67,78,79,92,93,72,73,80,81,106,107,116,117,108,109,64,65,94,95,86,87,4,6,5,7,12,14,8,10,0,2,13,15,9,11,1,3,4,6,8,10,5,7,0,2,12,14,9,11,1,3,13,15,132,134,128,130,133,135,129,131,136,138,140,142,137,139,141,143,200,207,194,204,192,195,202,196,199,206,198,197,205,201,193,203,4,6,12,14,8,10,5,7,13,15,9,11,0,2,1,3,4,6,5,7,136,138,140,142,9,11,141,143,128,130,129,131,82,83,70,71,68,69,102,103,108,109,86,87,114,115,98,99,66,67,84,85,224,225,202,203,0,0,0,0,0,0,0,0,0,0,0,0,0,0,0,0,0,0,0,0,0,0,0,0,0,0,0,0,0,0,0,0,0,0,0,0,0,0,0,0,0,0,0,0,0,0,0,0},
  {64,65,66,67,68,69,70,71,72,73,74,75,76,77,78,79,0,1,2,3,0,1,2,3,4,5,6,7,8,9,10,11,12,13,14,15,64,66,76,78,65,67,77,79,68,70,69,71,72,74,73,75,4,6,0,2,5,7,1,3,12,14,8,10,13,15,9,11,200,202,196,201,207,205,195,192,193,96,97,114,115,76,77,70,71,86,87,90,91,74,75,66,67,68,69,80,81,108,109,110,111,104,105,78,79,90,91,80,81,102,103,104,105,108,109,112,113,72,73,116,117,82,83,100,101,74,204,205,236,237,240,241,210,211,226,227,228,229,192,12,14,4,6,0,2,13,15,5,7,8,10,1,3,9,11,64,71,70,74,8,10,0,2,9,11,12,14,1,3,4,6,13,15,5,7,12,14,8,10,4,6,0,2,13,15,9,11,5,7,1,3,12,14,8,10,13,15,4,6,9,11,5,7,0,2,1,3,80,81,96,97,92,93,108,109,70,71,82,83,100,101,78,79,74,75,114,115,94,95,118,119,72,73,64,112,113,228,229,192,193,216,217,246,247,0,0,0,0,0,0,0,0,0,0,0,0,0,0,0,0,0,0,0,0,0,0,0,0,0,0,0,0,0,0,0,0,0,0,0,0,0,0,0,0,0,0,0,0,0,0,0,0,0,0,0,0},
  {64,65,66,67,68,69,70,71,72,73,74,75,76,77,78,79,0,1,2,3,128,129,130,131,132,133,134,135,136,137,138,139,140,141,142,143,64,66,76,78,65,67,77,79,68,70,69,71,72,74,73,75,4,6,0,2,5,7,1,3,12,14,8,10,13,15,9,11,4,6,12,14,8,10,0,2,5,7,13,15,9,11,1,3,0,2,8,10,4,6,12,14,1,3,9,11,5,7,13,15,8,10,0,2,9,11,1,3,12,14,13,15,4,6,5,7,12,14,4,6,13,15,0,2,8,10,5,7,1,3,9,11,68,70,69,71,76,78,72,74,64,66,77,79,73,75,65,67,79,68,65,67,70,8,10,12,14,0,2,9,11,13,15,1,3,4,6,5,7,8,10,9,11,4,6,0,2,12,14,5,7,1,3,13,15,4,6,12,14,8,10,5,7,13,15,9,11,0,2,1,3,132,134,140,142,136,138,133,135,141,143,128,130,137,139,129,131,118,119,76,77,74,75,68,69,72,73,100,101,110,111,84,85,206,207,116,117,94,95,242,243,214,215,240,241,226,0,0,0,0,0,0,0,0,0,0,0,0,0,0,0,0,0,0,0,0,0,0,0,0,0,0,0,0,0,0,0,0,0,0,0,0,0,0,0,0,0,0,0,0,0,0,0,0,0,0},
  {0,1,2,3,4,5,6,7,8,9,10,11,12,13,14,15,0,1,2,3,4,5,6,7,8,9,10,11,12,13,14,15,70,64,76,66,74,72,79,71,78,67,69,65,75,77,68,73,0,2,8,10,1,3,9,11,12,14,4,6,13,15,5,7,4,6,0,2,5,7,1,3,12,14,8,10,13,15,9,11,0,2,8,10,4,6,12,14,1,3,9,11,5,7,13,15,8,10,0,2,9,11,1,3,12,14,13,15,4,6,5,7,112,113,84,85,88,89,66,67,78,79,76,78,68,70,77,79,64,66,72,74,69,71,65,67,73,75,12,14,4,6,0,2,13,15,5,7,8,10,1,3,9,11,8,10,12,14,0,2,9,11,13,15,1,3,4,6,5,7,8,10,9,11,4,6,0,2,12,14,5,7,1,3,13,15,4,6,12,14,8,10,5,7,13,15,9,11,0,2,1,3,4,6,12,14,8,10,5,7,13,15,9,11,128,130,1,3,89,108,109,118,119,82,83,70,71,100,101,102,103,84,85,116,117,72,73,214,215,238,239,232,233,204,205,0,0,0,0,0,0,0,0,0,0,0,0,0,0,0,0,0,0,0,0,0,0,0,0,0,0,0,0,0,0,0,0,0,0,0,0,0,0,0,0,0,0,0,0,0,0,0,0,0,0,0},
  {64,65,66,67,68,69,70,71,72,73,74,75,76,77,78,79,0,1,2,3,4,5,6,7,8,9,10,11,12,13,14,15,128,129,130,131,132,133,134,135,136,137,138,139,140,141,142,143,198,197,194,199,204,203,206,200,4,6,0,2,5,7,1,3,12,14,8,10,13,15,9,11,0,2,8,10,4,6,12,14,1,3,9,11,5,7,13,15,70,71,86,87,90,91,74,75,66,67,68,69,80,81,108,109,110,111,104,105,0,2,4,6,8,10,1,3,5,7,12,14,9,11,13,15,4,6,5,7,12,14,8,10,0,2,13,15,9,11,1,3,0,2,1,3,4,6,8,10,12,14,5,7,9,11,13,15,8,10,12,14,0,2,9,11,13,15,1,3,4,6,5,7,8,10,0,2,9,11,12,14,1,3,4,6,13,15,5,7,4,6,5,7,8,10,12,14,9,11,13,15,0,2,1,3,4,6,12,14,8,10,5,7,13,15,0,2,9,11,1,3,64,65,78,79,90,91,106,107,94,95,68,69,96,97,74,75,98,99,66,67,208,209,92,93,242,243,240,241,216,0,0,0,0,0,0,0,0,0,0,0,0,0,0,0,0,0,0,0,0,0,0,0,0,0,0,0,0,0,0,0,0,0,0,0,0,0,0,0,0,0,0,0,0,0,0,0},
  {0,1,2,3,4,5,6,7,8,9,10,11,12,13,14,15,64,65,66,67,68,69,70,71,72,73,74,75,76,77,78,79,128,129,130,131,132,133,134,135,136,137,138,139,140,141,142,143,0,2,8,10,1,3,9,11,12,14,4,6,13,15,5,7,197,199,203,201,207,205,195,193,4,6,12,14,8,10,0,2,5,7,13,15,9,11,1,3,88,89,94,95,116,117,118,119,106,107,78,79,82,83,112,113,84,85,102,8,10,0,2,9,11,1,3,12,14,13,15,4,6,5,7,66,71,70,77,69,73,72,64,65,78,67,75,79,74,76,68,12,14,4,6,0,2,13,15,5,7,8,10,1,3,9,11,8,10,12,14,0,2,9,11,13,15,1,3,4,6,5,7,8,10,9,11,4,6,0,2,12,14,5,7,1,3,13,15,4,6,12,14,8,10,5,7,13,15,9,11,0,2,1,3,4,6,12,14,136,138,5,7,13,15,137,139,128,130,129,131,90,91,106,107,92,93,116,117,72,73,76,77,108,109,110,111,80,81,198,199,66,67,202,203,226,0,0,0,0,0,0,0,0,0,0,0,0,0,0,0,0,0,0,0,0,0,0,0,0,0,0,0,0,0,0,0,0,0,0,0,0,0,0,0,0,0,0,0,0,0,0,0,0,0,0,0,0},
  {64,65,66,67,68,69,70,71,72,73,74,75,76,77,78,79,0,1,2,3,4,5,6,7,8,9,10,11,12,13,14,15,72,78,70,71,64,66,76,78,65,67,77,79,68,70,69,71,72,74,73,75,12,14,8,10,13,15,9,11,0,2,4,6,1,3,5,7,109,86,87,96,97,82,83,74,75,110,111,76,77,88,89,118,119,68,69,100,101,104,105,102,103,90,91,64,65,70,71,80,81,112,113,90,91,102,103,118,119,104,105,114,115,106,107,94,95,68,69,12,14,4,6,13,15,0,2,8,10,5,7,1,3,9,11,0,2,1,3,4,6,8,10,12,14,5,7,9,11,13,15,76,70,68,66,65,8,10,12,14,0,2,9,11,13,15,1,3,4,6,5,7,8,10,9,11,4,6,0,2,12,14,5,7,1,3,13,15,4,6,12,14,8,10,5,7,13,15,9,11,0,2,1,3,132,134,140,142,136,138,133,135,141,143,128,130,137,139,129,131,109,118,119,82,83,70,71,100,101,102,103,84,85,116,117,72,73,86,87,110,111,232,233,204,205,0,0,0,0,0,0,0,0,0,0,0,0,0,0,0,0,0,0,0,0,0,0,0,0,0,0,0,0,0,0,0,0,0,0,0,0,0,0,0,0,0,0,0,0,0,0,0,0,0,0,0},
  {64,65,66,67,68,69,70,71,72,73,74,75,76,77,78,79,0,1,2,3,0,1,2,3,4,5,6,7,8,9,10,11,12,13,14,15,64,66,76,78,65,67,77,79,68,70,69,71,72,74,73,75,64,66,72,74,65,67,73,75,76,78,68,70,77,79,69,71,70,71,64,65,98,99,92,93,78,79,112,113,94,95,72,73,80,81,84,85,114,115,116,117,106,107,66,67,108,109,86,87,64,65,70,71,80,81,112,113,90,91,102,103,118,119,104,105,114,115,106,107,94,95,4,6,5,7,12,14,8,10,0,2,13,15,9,11,1,3,0,2,1,3,4,6,8,10,12,14,5,7,9,11,13,15,8,10,12,14,0,2,9,11,13,15,1,3,4,6,5,7,8,10,9,11,4,6,0,2,12,14,5,7,1,3,13,15,4,6,5,7,8,10,12,14,9,11,13,15,0,2,1,3,4,6,12,14,8,10,5,7,13,15,0,2,9,11,1,3,85,104,105,72,73,86,87,102,103,90,91,118,119,68,69,206,207,114,115,66,67,110,111,94,95,216,217,204,205,0,0,0,0,0,0,0,0,0,0,0,0,0,0,0,0,0,0,0,0,0,0,0,0,0,0,0,0,0,0,0,0,0,0,0,0,0,0,0,0,0,0,0,0,0,0,0,0,0},
  {0,1,2,3,4,5,6,7,8,9,10,11,12,13,14,15,0,1,2,3,4,5,6,7,8,9,10,11,12,13,14,15,128,129,130,131,132,133,134,135,136,137,138,139,140,141,142,143,0,2,8,10,1,3,9,11,12,14,4,6,13,15,5,7,4,6,12,14,8,10,0,2,5,7,13,15,9,11,1,3,4,6,0,2,5,7,1,3,12,14,8,10,13,15,9,11,0,2,8,10,4,6,12,14,1,3,9,11,5,7,13,15,0,2,4,6,8,10,1,3,5,7,12,14,9,11,13,15,4,6,5,7,12,14,8,10,0,2,13,15,9,11,1,3,0,2,1,3,4,6,8,10,12,14,5,7,9,11,13,15,8,10,12,14,0,2,9,11,13,15,1,3,4,6,5,7,8,10,9,11,4,6,0,2,12,14,5,7,1,3,13,15,4,6,12,14,8,10,5,7,13,15,9,11,0,2,1,3,4,6,140,142,136,138,5,7,141,143,128,130,137,139,129,131,108,109,118,119,82,83,70,71,100,101,102,103,84,85,116,117,72,73,86,87,110,111,232,233,204,205,0,0,0,0,0,0,0,0,0,0,0,0,0,0,0,0,0,0,0,0,0,0,0,0,0,0,0,0,0,0,0,0,0,0,0,0,0,0,0,0,0,0,0,0,0,0},
  {0,1,2,3,4,5,6,7,8,9,10,11,12,13,14,15,0,1,2,3,4,5,6,7,8,9,10,11,12,13,14,15,74,66,76,79,70,72,64,67,71,69,78,68,75,65,77,73,0,2,8,10,1,3,9,11,12,14,4,6,13,15,5,7,0,2,8,10,4,6,12,14,1,3,9,11,5,7,13,15,4,6,8,10,0,2,5,7,9,11,12,14,1,3,13,15,8,10,0,2,9,11,1,3,12,14,13,15,4,6,5,7,86,87,114,115,102,103,98,99,100,101,90,91,70,71,204,205,68,206,207,246,247,194,195,238,239,242,243,232,233,218,76,78,68,70,64,66,77,79,69,71,72,74,65,67,73,75,8,10,0,2,9,11,12,14,1,3,4,6,13,15,5,7,12,14,8,10,4,6,0,2,13,15,9,11,5,7,1,3,12,14,8,10,13,15,4,6,9,11,5,7,0,2,1,3,110,111,82,83,70,71,68,69,102,103,108,109,86,87,114,115,98,99,66,67,84,85,96,97,74,75,103,208,209,96,97,76,77,218,219,236,237,0,0,0,0,0,0,0,0,0,0,0,0,0,0,0,0,0,0,0,0,0,0,0,0,0,0,0,0,0,0,0,0,0,0,0,0,0,0,0,0,0,0,0,0,0,0,0,0,0,0,0,0,0},
  {0,1,2,3,4,5,6,7,8,9,10,11,12,13,14,15,0,1,2,3,128,129,130,131,132,133,134,135,136,137,138,139,140,141,142,143,64,66,76,78,65,67,77,79,68,70,69,71,72,74,73,75,12,14,8,10,13,15,9,11,0,2,4,6,1,3,5,7,4,6,0,2,5,7,1,3,12,14,8,10,13,15,9,11,4,6,8,10,0,2,5,7,9,11,12,14,1,3,13,15,8,10,0,2,9,11,1,3,12,14,13,15,4,6,5,7,108,109,204,205,88,89,114,115,96,97,102,103,116,117,246,247,0,2,1,3,4,6,8,10,12,14,5,7,9,11,13,15,8,10,12,14,0,2,9,11,13,15,1,3,4,6,5,7,8,10,9,11,4,6,0,2,12,14,5,7,1,3,13,15,12,14,8,10,4,6,0,2,13,15,9,11,5,7,1,3,132,134,140,142,136,138,133,135,141,143,128,130,137,139,129,131,99,102,103,86,87,104,105,78,79,118,119,114,115,88,89,112,113,100,101,64,65,84,85,94,95,224,225,210,211,196,197,0,0,0,0,0,0,0,0,0,0,0,0,0,0,0,0,0,0,0,0,0,0,0,0,0,0,0,0,0,0,0,0,0,0,0,0,0,0,0,0,0,0,0,0,0,0,0,0,0,0,0,0,0},
  {64,65,66,67,68,69,70,71,72,73,74,75,76,77,78,79,0,1,2,3,0,1,2,3,4,5,6,7,8,9,10,11,12,13,14,15,64,66,76,78,65,67,77,79,68,70,69,71,72,74,73,75,64,66,72,74,65,67,73,75,76,78,68,70,77,79,69,71,4,6,12,14,8,10,0,2,5,7,13,15,9,11,1,3,88,89,94,95,116,117,118,119,106,107,78,79,82,83,112,113,84,85,102,103,98,99,8,10,0,2,9,11,1,3,12,14,13,15,4,6,5,7,12,14,4,6,13,15,0,2,8,10,5,7,1,3,9,11,0,2,1,3,4,6,8,10,12,14,5,7,9,11,13,15,8,10,12,14,0,2,9,11,13,15,1,3,4,6,5,7,8,10,9,11,4,6,0,2,12,14,5,7,1,3,13,15,4,6,5,7,8,10,12,14,9,11,13,15,0,2,1,3,4,6,12,14,8,10,5,7,13,15,0,2,9,11,1,3,69,102,103,108,109,86,87,114,115,98,99,66,67,84,85,96,97,74,75,68,69,104,105,108,109,102,103,244,245,0,0,0,0,0,0,0,0,0,0,0,0,0,0,0,0,0,0,0,0,0,0,0,0,0,0,0,0,0,0,0,0,0,0,0,0,0,0,0,0,0,0,0,0,0,0,0,0,0},
  {64,65,66,67,68,69,70,71,72,73,74,75,76,77,78,79,0,1,2,3,0,1,2,3,4,5,6,7,8,9,10,11,12,13,14,15,64,66,76,78,65,67,77,79,68,70,69,71,72,74,73,75,12,14,8,10,13,15,9,11,0,2,4,6,1,3,5,7,4,6,12,14,8,10,0,2,5,7,13,15,9,11,1,3,0,2,8,10,4,6,12,14,1,3,9,11,5,7,13,15,8,10,0,2,9,11,1,3,12,14,13,15,4,6,5,7,94,95,108,109,76,77,88,89,114,115,96,97,102,103,116,117,118,119,0,2,1,3,4,6,8,10,12,14,5,7,9,11,13,15,8,10,12,14,0,2,9,11,13,15,1,3,4,6,5,7,8,10,9,11,4,6,0,2,12,14,5,7,1,3,13,15,4,6,5,7,8,10,12,14,9,11,13,15,0,2,1,3,4,6,12,14,8,10,5,7,13,15,0,2,9,11,1,3,118,119,76,77,74,75,68,69,72,73,100,101,110,111,84,85,78,79,116,117,94,95,242,243,214,215,240,241,226,227,0,0,0,0,0,0,0,0,0,0,0,0,0,0,0,0,0,0,0,0,0,0,0,0,0,0,0,0,0,0,0,0,0,0,0,0,0,0,0,0,0,0,0,0,0,0,0,0,0,0,0,0},
  {64,65,66,67,68,69,70,71,72,73,74,75,76,77,78,79,64,65,66,67,68,69,70,71,72,73,74,75,76,77,78,79,128,129,130,131,132,133,134,135,136,137,138,139,140,141,142,143,0,2,8,10,1,3,9,11,12,14,4,6,13,15,5,7,12,14,8,10,13,15,9,11,0,2,4,6,1,3,5,7,4,6,12,14,8,10,0,2,5,7,13,15,9,11,1,3,68,70,76,78,72,74,64,66,69,71,77,79,73,75,65,67,72,73,80,81,106,107,116,117,108,109,64,65,94,95,86,87,114,115,102,103,226,234,235,224,225,216,217,198,199,206,207,246,247,194,195,64,71,78,77,69,72,75,70,74,79,76,73,68,67,66,65,196,198,192,194,197,199,193,195,200,202,204,206,201,203,205,207,12,14,8,10,4,6,0,2,13,15,9,11,5,7,1,3,12,14,8,10,13,15,132,134,9,11,133,135,128,130,1,3,196,198,204,206,200,202,69,71,205,207,201,203,192,194,193,195,81,66,67,90,91,96,97,114,115,74,75,198,199,238,239,210,211,0,0,0,0,0,0,0,0,0,0,0,0,0,0,0,0,0,0,0,0,0,0,0,0,0,0,0,0,0,0,0,0,0,0,0,0,0,0,0,0,0,0,0,0,0,0,0,0,0,0,0,0},
  {64,65,66,67,68,69,70,71,72,73,74,75,76,77,78,79,0,1,2,3,0,1,2,3,4,5,6,7,8,9,10,11,12,13,14,15,64,66,76,78,65,67,77,79,68,70,69,71,72,74,73,75,4,6,0,2,5,7,1,3,12,14,8,10,13,15,9,11,76,78,72,74,77,79,73,75,64,66,68,70,65,67,69,71,4,6,12,14,8,10,0,2,5,7,13,15,9,11,1,3,8,10,0,2,9,11,1,3,12,14,13,15,4,6,5,7,107,94,95,108,109,76,77,88,89,114,115,96,97,102,103,116,117,118,119,71,72,69,66,64,78,74,77,76,75,73,79,68,65,67,70,8,10,12,14,0,2,9,11,13,15,1,3,4,6,5,7,8,10,0,2,9,11,12,14,1,3,4,6,13,15,5,7,4,6,12,14,8,10,5,7,13,15,9,11,0,2,1,3,4,6,12,14,8,10,5,7,13,15,0,2,9,11,1,3,64,65,78,79,90,91,106,107,94,95,68,69,96,97,74,102,103,208,209,96,97,76,77,218,219,236,237,0,0,0,0,0,0,0,0,0,0,0,0,0,0,0,0,0,0,0,0,0,0,0,0,0,0,0,0,0,0,0,0,0,0,0,0,0,0,0,0,0,0,0,0,0,0,0,0,0,0,0,0,0,0},
  {0,1,2,3,4,5,6,7,8,9,10,11,12,13,14,15,0,1,2,3,79,75,77,73,128,129,130,131,132,133,134,135,136,137,138,139,140,141,142,143,0,2,8,10,1,3,9,11,12,14,4,6,13,15,5,7,4,6,8,10,0,2,5,7,9,11,12,14,1,3,13,15,4,6,8,10,0,2,5,7,9,11,12,14,1,3,13,15,4,6,12,14,8,10,0,2,5,7,13,15,9,11,1,3,72,73,80,81,98,99,74,75,110,111,112,113,86,87,92,93,78,79,64,65,66,67,84,85,68,69,90,91,104,218,219,220,221,230,231,196,197,71,69,72,78,64,77,75,74,79,73,67,76,70,68,66,65,8,10,0,2,9,11,12,14,1,3,4,6,13,15,5,7,12,14,8,10,4,6,0,2,13,15,9,11,5,7,1,3,12,14,8,10,13,15,4,6,9,11,5,7,0,2,1,3,196,198,204,206,200,202,197,199,205,207,192,194,201,203,193,195,78,79,106,235,86,87,94,95,76,77,220,221,200,201,98,99,212,213,0,0,0,0,0,0,0,0,0,0,0,0,0,0,0,0,0,0,0,0,0,0,0,0,0,0,0,0,0,0,0,0,0,0,0,0,0,0,0,0,0,0,0,0,0,0,0,0,0,0,0,0,0,0,0,0,0},
  {64,65,66,67,68,69,70,71,72,73,74,75,76,77,78,79,0,1,2,3,72,78,70,71,0,2,12,14,1,3,13,15,4,6,5,7,8,10,9,11,12,14,8,10,13,15,9,11,0,2,4,6,1,3,5,7,4,6,8,10,0,2,5,7,9,11,12,14,1,3,13,15,8,10,0,2,9,11,1,3,12,14,13,15,4,6,5,7,95,70,71,76,77,106,107,96,97,64,65,78,79,90,91,80,81,102,69,110,111,82,83,74,75,96,97,118,119,104,105,94,223,244,245,234,235,224,225,216,217,198,199,71,69,72,78,64,77,75,74,79,73,67,76,70,68,66,65,8,10,0,2,9,11,12,14,1,3,4,6,13,15,5,7,12,14,8,10,4,6,0,2,13,15,9,11,5,7,1,3,4,6,12,14,8,10,5,7,13,15,9,11,0,2,1,3,68,70,69,71,200,202,204,206,201,203,205,207,192,194,193,195,64,65,78,79,90,91,106,107,94,95,112,113,228,229,64,193,216,217,246,247,0,0,0,0,0,0,0,0,0,0,0,0,0,0,0,0,0,0,0,0,0,0,0,0,0,0,0,0,0,0,0,0,0,0,0,0,0,0,0,0,0,0,0,0,0,0,0,0,0,0,0,0,0,0,0,0,0,0,0,0,0,0,0,0,0},
  {64,65,66,67,68,69,70,71,72,73,74,75,76,77,78,79,0,1,2,3,128,129,130,131,132,133,134,135,136,137,138,139,140,141,142,143,64,66,76,78,65,67,77,79,68,70,69,71,72,74,73,75,12,14,8,10,13,15,9,11,0,2,4,6,1,3,5,7,70,71,64,65,98,99,92,93,78,79,112,113,94,95,72,73,80,81,84,85,114,115,116,117,106,107,66,67,111,98,99,66,67,94,95,70,71,76,77,106,107,96,97,64,65,78,79,90,91,80,81,102,103,104,105,236,237,240,241,72,105,70,71,210,211,100,101,106,71,72,69,66,64,78,74,77,76,75,73,79,68,65,67,70,64,71,70,74,77,69,78,72,76,78,74,77,71,70,64,66,69,207,200,75,68,204,73,195,65,4,6,5,7,8,10,12,14,9,11,13,15,0,2,1,3,12,14,8,10,13,15,132,134,9,11,133,135,0,2,1,3,118,119,76,77,74,75,68,69,72,73,100,101,110,111,84,85,206,207,116,117,94,95,114,115,214,215,112,113,98,99,192,193,0,0,0,0,0,0,0,0,0,0,0,0,0,0,0,0,0,0,0,0,0,0,0,0,0,0,0,0,0,0,0,0,0,0,0,0,0,0,0,0,0,0,0,0,0,0,0,0,0,0,0,0,0,0,0},
  {64,65,66,67,68,69,70,71,72,73,74,75,76,77,78,79,0,1,2,3,64,65,66,67,68,69,70,71,72,73,74,75,76,77,78,79,64,66,76,78,65,67,77,79,68,70,69,71,72,74,73,75,4,6,0,2,5,7,1,3,12,14,8,10,13,15,9,11,4,6,12,14,8,10,0,2,5,7,13,15,9,11,1,3,4,6,12,14,8,10,0,2,5,7,13,15,9,11,1,3,92,93,72,73,80,81,106,107,116,117,108,109,64,65,94,95,86,87,114,115,102,103,98,99,100,101,90,91,70,71,207,246,247,194,195,238,239,242,243,232,233,218,4,6,8,10,5,7,0,2,12,14,9,11,1,3,13,15,64,71,78,74,77,70,73,69,66,72,76,79,68,65,67,75,12,14,8,10,4,6,0,2,13,15,9,11,5,7,1,3,12,14,8,10,13,15,4,6,9,11,5,7,0,2,1,3,204,206,200,202,205,207,196,198,201,203,197,199,192,194,193,195,71,66,67,112,113,98,99,86,87,110,111,114,115,88,89,118,119,68,69,230,231,0,0,0,0,0,0,0,0,0,0,0,0,0,0,0,0,0,0,0,0,0,0,0,0,0,0,0,0,0,0,0,0,0,0,0,0,0,0,0,0,0,0,0,0,0,0,0,0,0,0,0,0,0},
  {64,65,66,67,68,69,70,71,72,73,74,75,76,77,78,79,0,1,2,3,0,1,2,3,4,5,6,7,8,9,10,11,12,13,14,15,64,66,76,78,65,67,77,79,68,70,69,71,72,74,73,75,12,14,8,10,13,15,9,11,0,2,4,6,1,3,5,7,4,6,0,2,5,7,1,3,12,14,8,10,13,15,9,11,4,6,8,10,0,2,5,7,9,11,12,14,1,3,13,15,82,83,98,99,108,109,92,93,78,79,84,85,100,101,66,67,74,75,112,113,84,85,88,89,66,67,78,79,92,93,4,6,5,7,0,2,8,10,12,14,1,3,9,11,13,15,4,6,8,10,5,7,0,2,12,14,9,11,1,3,13,15,8,10,0,2,9,11,12,14,1,3,4,6,13,15,5,7,12,14,8,10,4,6,0,2,13,15,9,11,5,7,1,3,12,14,8,10,13,15,132,134,9,11,5,7,0,2,1,3,196,198,69,71,200,202,204,206,201,203,205,207,192,194,193,195,78,79,106,107,86,87,94,95,76,77,220,221,200,201,98,99,212,213,208,0,0,0,0,0,0,0,0,0,0,0,0,0,0,0,0,0,0,0,0,0,0,0,0,0,0,0,0,0,0,0,0,0,0,0,0,0,0,0,0,0,0,0,0,0,0,0,0,0,0,0},
  {0,1,2,3,4,5,6,7,8,9,10,11,12,13,14,15,0,1,2,3,0,1,2,3,4,5,6,7,8,9,10,11,12,13,14,15,64,66,76,78,65,67,77,79,68,70,69,71,72,74,73,75,4,6,0,2,5,7,1,3,12,14,8,10,13,15,9,11,4,6,8,10,0,2,5,7,9,11,12,14,1,3,13,15,0,2,8,10,4,6,12,14,1,3,9,11,5,7,13,15,80,81,102,103,104,105,108,109,112,113,72,73,116,117,82,83,100,101,74,75,86,87,92,93,118,119,68,69,4,6,5,7,0,2,8,10,12,14,1,3,9,11,13,15,4,6,8,10,5,7,0,2,12,14,9,11,1,3,13,15,8,10,0,2,9,11,12,14,1,3,4,6,13,15,5,7,200,207,194,204,192,195,202,196,199,206,198,197,205,201,193,203,12,14,8,10,13,15,4,6,9,11,5,7,0,2,1,3,132,134,12,14,136,138,133,135,13,15,137,139,128,130,129,131,106,107,70,71,66,67,112,113,98,99,86,87,110,111,242,243,88,89,118,119,196,197,0,0,0,0,0,0,0,0,0,0,0,0,0,0,0,0,0,0,0,0,0,0,0,0,0,0,0,0,0,0,0,0,0,0,0,0,0,0,0,0,0,0,0,0,0,0,0,0,0,0},
  {64,65,66,67,68,69,70,71,72,73,74,75,76,77,78,79,0,1,2,3,4,5,6,7,8,9,10,11,12,13,14,15,0,1,2,3,72,76,64,70,66,74,71,78,67,79,65,69,75,68,73,77,4,6,0,2,5,7,1,3,12,14,8,10,13,15,9,11,4,6,8,10,0,2,5,7,9,11,12,14,1,3,13,15,0,2,8,10,4,6,12,14,1,3,9,11,5,7,13,15,64,66,72,74,68,70,76,78,65,67,73,75,69,71,77,79,111,82,83,74,75,96,97,118,119,104,105,4,6,5,7,0,2,8,10,12,14,1,3,9,11,13,15,76,78,68,70,0,2,13,15,5,7,8,10,1,3,9,11,8,10,0,2,9,11,12,14,1,3,4,6,13,15,5,7,12,14,8,10,4,6,0,2,13,15,9,11,5,7,1,3,4,6,12,14,8,10,5,7,13,15,9,11,0,2,1,3,12,14,136,138,132,134,0,2,141,143,137,139,133,135,129,131,64,65,84,85,92,93,104,105,74,75,206,207,100,101,82,83,200,201,116,117,222,223,234,0,0,0,0,0,0,0,0,0,0,0,0,0,0,0,0,0,0,0,0,0,0,0,0,0,0,0,0,0,0,0,0,0,0,0,0,0,0,0,0,0,0,0,0,0,0,0,0,0,0},
  {64,65,66,67,68,69,70,71,72,73,74,75,76,77,78,79,0,1,2,3,4,5,6,7,8,9,10,11,12,13,14,15,69,76,67,65,64,66,76,78,65,67,77,79,68,70,69,71,72,74,73,75,12,14,8,10,13,15,9,11,0,2,4,6,1,3,5,7,4,6,8,10,0,2,5,7,9,11,12,14,1,3,13,15,90,91,70,71,72,73,66,67,64,65,84,85,92,93,80,81,86,87,94,95,76,77,88,89,106,107,78,79,96,0,2,4,6,8,10,1,3,5,7,12,14,9,11,13,15,4,6,5,7,0,2,8,10,12,14,1,3,9,11,13,15,4,6,8,10,5,7,0,2,12,14,9,11,1,3,13,15,132,134,128,130,133,135,129,131,136,138,140,142,137,139,141,143,8,10,9,11,4,6,0,2,12,14,5,7,1,3,13,15,4,6,12,14,8,10,5,7,13,15,9,11,0,2,1,3,132,134,140,142,136,138,133,135,141,143,128,130,137,139,129,131,104,105,78,79,118,119,114,115,88,89,112,113,100,101,64,65,84,85,94,95,96,97,210,211,196,197,0,0,0,0,0,0,0,0,0,0,0,0,0,0,0,0,0,0,0,0,0,0,0,0,0,0,0,0,0,0,0,0,0,0,0,0,0,0,0,0,0,0,0,0,0},
  {64,65,66,67,68,69,70,71,72,73,74,75,76,77,78,79,0,1,2,3,128,129,130,131,132,133,134,135,136,137,138,139,140,141,142,143,128,129,130,131,132,133,134,135,136,137,138,139,140,141,142,143,0,2,8,10,1,3,9,11,12,14,4,6,13,15,5,7,4,6,8,10,0,2,5,7,9,11,12,14,1,3,13,15,4,6,12,14,8,10,0,2,5,7,13,15,9,11,1,3,103,104,105,108,109,112,113,72,73,116,117,82,83,100,101,74,75,86,87,92,93,118,119,68,69,76,78,68,70,77,79,64,66,72,74,69,71,65,67,73,75,0,2,1,3,4,6,8,10,12,14,5,7,9,11,13,15,132,134,128,130,133,135,129,131,136,138,140,142,137,139,141,143,8,10,9,11,4,6,0,2,12,14,5,7,1,3,13,15,4,6,12,14,8,10,5,7,13,15,9,11,0,2,1,3,132,134,140,142,136,138,133,135,141,143,128,130,137,139,129,131,65,112,113,98,99,88,89,86,87,84,85,90,91,106,107,68,69,104,105,76,77,116,117,110,111,102,103,194,195,0,0,0,0,0,0,0,0,0,0,0,0,0,0,0,0,0,0,0,0,0,0,0,0,0,0,0,0,0,0,0,0,0,0,0,0,0,0,0,0,0,0,0,0,0,0},
  {64,65,66,67,68,69,70,71,72,73,74,75,76,77,78,79,0,1,2,3,4,5,6,7,8,9,10,11,12,13,14,15,64,67,72,77,69,73,78,76,76,69,70,72,74,66,71,75,67,77,68,73,79,206,64,65,4,6,8,10,0,2,5,7,9,11,12,14,1,3,13,15,4,6,12,14,8,10,0,2,5,7,13,15,9,11,1,3,0,2,8,10,4,6,12,14,1,3,9,11,5,7,13,15,0,2,4,6,8,10,1,3,5,7,12,14,9,11,13,15,4,6,5,7,12,14,8,10,0,2,13,15,9,11,1,3,0,2,1,3,4,6,8,10,12,14,5,7,9,11,13,15,8,10,12,14,0,2,9,11,13,15,1,3,4,6,5,7,8,10,0,2,9,11,12,14,1,3,4,6,13,15,5,7,12,14,8,10,4,6,0,2,13,15,9,11,5,7,1,3,4,6,12,14,8,10,5,7,13,15,9,11,0,2,1,3,116,117,64,65,118,119,80,81,94,95,76,77,112,113,110,111,82,83,70,71,68,112,113,228,229,64,65,88,217,246,247,0,0,0,0,0,0,0,0,0,0,0,0,0,0,0,0,0,0,0,0,0,0,0,0,0,0,0,0,0,0,0,0,0,0,0,0,0,0,0,0,0,0,0,0,0,0,0,0,0},
  {64,65,66,67,68,69,70,71,72,73,74,75,76,77,78,79,0,1,2,3,128,129,130,131,132,133,134,135,136,137,138,139,140,141,142,143,64,66,76,78,65,67,77,79,68,70,69,71,72,74,73,75,12,14,8,10,13,15,9,11,0,2,4,6,1,3,5,7,4,6,8,10,0,2,5,7,9,11,12,14,1,3,13,15,64,65,70,71,80,81,112,113,90,91,102,103,118,119,104,105,114,115,106,107,94,95,68,69,82,83,98,99,108,109,92,12,14,4,6,13,15,0,2,8,10,5,7,1,3,9,11,4,6,5,7,0,2,8,10,12,14,1,3,9,11,13,15,76,78,68,70,64,66,77,79,69,71,72,74,65,67,73,75,132,134,128,130,133,135,129,131,136,138,140,142,137,139,141,143,12,14,8,10,4,6,0,2,13,15,9,11,5,7,1,3,4,6,12,14,8,10,5,7,13,15,9,11,0,2,1,3,4,6,12,14,136,138,5,7,13,15,137,139,128,130,129,131,64,65,84,85,92,93,104,105,74,75,206,207,100,101,82,83,72,73,116,117,222,223,234,235,198,0,0,0,0,0,0,0,0,0,0,0,0,0,0,0,0,0,0,0,0,0,0,0,0,0,0,0,0,0,0,0,0,0,0,0,0,0,0,0,0,0,0,0,0},
  {0,1,2,3,4,5,6,7,8,9,10,11,12,13,14,15,64,65,66,67,68,69,70,71,72,73,74,75,76,77,78,79,128,129,130,131,132,133,134,135,136,137,138,139,140,141,142,143,0,2,8,10,1,3,9,11,12,14,4,6,13,15,5,7,4,6,8,10,0,2,5,7,9,11,12,14,1,3,13,15,103,98,99,72,73,92,93,64,65,100,101,96,97,114,115,76,77,70,71,86,87,90,91,74,75,66,67,68,69,0,2,4,6,8,10,1,3,5,7,12,14,9,11,13,15,12,14,4,6,13,15,0,2,8,10,5,7,1,3,9,11,0,2,1,3,4,6,8,10,12,14,5,7,9,11,13,15,132,134,128,130,133,135,129,131,136,138,140,142,137,139,141,143,79,67,75,65,8,10,0,2,9,11,12,14,1,3,4,6,13,15,5,7,4,6,12,14,8,10,5,7,13,15,9,11,0,2,1,3,8,10,9,11,4,6,0,2,140,142,133,135,1,3,141,143,64,65,80,81,92,93,108,109,106,107,70,71,66,67,90,91,88,89,82,83,224,225,232,233,230,231,0,0,0,0,0,0,0,0,0,0,0,0,0,0,0,0,0,0,0,0,0,0,0,0,0,0,0,0,0,0,0,0,0,0,0,0,0,0,0,0,0,0,0,0,0},
  {64,65,66,67,68,69,70,71,72,73,74,75,76,77,78,79,0,1,2,3,64,65,66,67,68,69,70,71,72,73,74,75,76,77,78,79,64,66,76,78,65,67,77,79,68,70,69,71,72,74,73,75,4,6,0,2,5,7,1,3,12,14,8,10,13,15,9,11,4,6,8,10,0,2,5,7,9,11,12,14,1,3,13,15,90,91,70,71,72,73,66,67,64,65,84,85,92,93,80,81,86,87,94,95,76,77,88,89,106,107,78,79,96,97,0,2,4,6,8,10,1,3,5,7,12,14,9,11,13,15,4,6,5,7,0,2,8,10,12,14,1,3,9,11,13,15,12,14,4,6,0,2,13,15,5,7,8,10,1,3,9,11,64,71,70,74,77,69,78,72,76,68,66,73,8,10,9,11,4,6,0,2,12,14,5,7,1,3,13,15,4,6,12,14,8,10,5,7,13,15,9,11,0,2,1,3,12,14,8,10,13,15,4,6,9,11,5,7,0,2,1,3,106,107,104,105,92,93,88,89,72,73,90,91,100,101,206,207,116,117,64,65,118,119,80,209,222,223,204,0,0,0,0,0,0,0,0,0,0,0,0,0,0,0,0,0,0,0,0,0,0,0,0,0,0,0,0,0,0,0,0,0,0,0,0,0,0,0,0,0,0,0,0,0,0,0},
  {0,1,2,3,4,5,6,7,8,9,10,11,12,13,14,15,0,1,2,3,64,65,66,67,68,69,70,71,72,73,74,75,76,77,78,79,64,66,76,78,65,67,77,79,68,70,69,71,72,74,73,75,64,66,72,74,65,67,73,75,76,78,68,70,77,79,69,71,4,6,8,10,0,2,5,7,9,11,12,14,1,3,13,15,68,70,64,66,69,71,65,67,76,78,72,74,77,79,73,75,8,10,0,2,9,11,1,3,12,14,13,15,4,6,5,7,64,66,68,70,72,74,65,67,69,71,76,78,73,75,77,79,4,6,5,7,0,2,8,10,12,14,1,3,9,11,13,15,4,6,8,10,5,7,0,2,12,14,9,11,1,3,13,15,64,71,78,74,77,70,73,69,66,72,76,79,68,65,67,75,12,14,8,10,4,6,0,2,13,15,9,11,5,7,1,3,12,14,8,10,13,15,132,134,9,11,133,135,0,2,1,3,204,206,200,202,205,207,196,198,201,203,197,199,192,194,193,195,107,70,71,66,67,112,113,98,99,86,87,110,111,242,243,88,89,118,119,196,197,0,0,0,0,0,0,0,0,0,0,0,0,0,0,0,0,0,0,0,0,0,0,0,0,0,0,0,0,0,0,0,0,0,0,0,0,0,0,0,0,0,0,0,0,0,0,0},
  {64,65,66,67,68,69,70,71,72,73,74,75,76,77,78,79,0,1,2,3,72,78,70,71,128,129,130,131,132,133,134,135,136,137,138,139,140,141,142,143,0,2,8,10,1,3,9,11,12,14,4,6,13,15,5,7,12,14,8,10,13,15,9,11,0,2,4,6,1,3,5,7,4,6,12,14,8,10,0,2,5,7,13,15,9,11,1,3,8,10,0,2,9,11,1,3,12,14,13,15,4,6,5,7,75,88,89,76,77,96,97,86,87,72,73,116,117,110,111,4,6,5,7,12,14,8,10,0,2,13,15,9,11,1,3,12,14,4,6,0,2,13,15,5,7,8,10,1,3,9,11,132,134,128,130,133,135,129,131,136,138,140,142,137,139,141,143,8,10,9,11,4,6,0,2,12,14,5,7,1,3,13,15,4,6,5,7,8,10,12,14,9,11,13,15,0,2,1,3,12,14,8,10,13,15,132,134,9,11,133,135,128,130,129,131,116,117,96,97,74,75,64,65,112,113,82,83,106,107,84,80,81,66,67,90,91,96,97,242,243,74,75,198,199,0,0,0,0,0,0,0,0,0,0,0,0,0,0,0,0,0,0,0,0,0,0,0,0,0,0,0,0,0,0,0,0,0,0,0,0,0,0,0,0,0,0,0,0,0,0,0,0,0,0,0,0},
  {0,1,2,3,4,5,6,7,8,9,10,11,12,13,14,15,0,1,2,3,0,1,2,3,4,5,6,7,8,9,10,11,12,13,14,15,0,1,2,3,76,69,70,72,74,66,71,75,67,77,68,73,79,78,64,65,12,14,8,10,13,15,9,11,0,2,4,6,1,3,5,7,4,6,8,10,0,2,5,7,9,11,12,14,1,3,13,15,0,2,8,10,4,6,12,14,1,3,9,11,5,7,13,15,0,2,4,6,8,10,1,3,5,7,12,14,9,11,13,15,95,108,109,76,77,88,89,114,115,96,97,102,103,244,245,246,247,219,220,221,230,231,196,197,4,6,8,10,5,7,0,2,12,14,9,11,1,3,13,15,64,71,70,74,77,69,78,72,76,68,66,73,79,67,75,65,12,14,8,10,4,6,0,2,13,15,9,11,5,7,1,3,12,14,8,10,13,15,4,6,9,11,5,7,0,2,1,3,76,78,72,74,77,79,68,70,73,75,69,71,64,66,65,67,82,83,70,71,100,101,102,103,84,85,116,117,72,73,86,87,110,111,232,233,204,205,0,0,0,0,0,0,0,0,0,0,0,0,0,0,0,0,0,0,0,0,0,0,0,0,0,0,0,0,0,0,0,0,0,0,0,0,0,0,0,0,0,0,0,0,0,0,0,0,0,0},
  {64,65,66,67,68,69,70,71,72,73,74,75,76,77,78,79,0,1,2,3,4,5,6,7,8,9,10,11,12,13,14,15,70,64,76,66,74,72,79,71,78,67,69,65,75,77,68,73,0,2,8,10,1,3,9,11,12,14,4,6,13,15,5,7,4,6,12,14,8,10,0,2,5,7,13,15,9,11,1,3,4,6,12,14,8,10,0,2,5,7,13,15,9,11,1,3,8,10,0,2,9,11,1,3,12,14,13,15,4,6,5,7,12,14,4,6,13,15,0,2,8,10,5,7,1,3,9,11,4,6,5,7,0,2,8,10,12,14,1,3,9,11,13,15,4,6,8,10,5,7,0,2,12,14,9,11,1,3,13,15,132,134,128,130,133,135,129,131,136,138,140,142,137,139,141,143,8,10,9,11,4,6,0,2,12,14,5,7,1,3,13,15,4,6,12,14,8,10,5,7,13,15,9,11,0,2,1,3,8,10,0,2,9,11,140,142,1,3,132,134,141,143,133,135,92,93,108,109,98,99,80,81,100,101,70,71,110,111,82,83,68,69,104,105,108,109,102,103,244,245,0,0,0,0,0,0,0,0,0,0,0,0,0,0,0,0,0,0,0,0,0,0,0,0,0,0,0,0,0,0,0,0,0,0,0,0,0,0,0,0,0,0,0,0,0,0},
  {0,1,2,3,4,5,6,7,8,9,10,11,12,13,14,15,0,1,2,3,0,1,2,3,4,5,6,7,8,9,10,11,12,13,14,15,64,66,76,78,65,67,77,79,68,70,69,71,72,74,73,75,12,14,8,10,13,15,9,11,0,2,4,6,1,3,5,7,4,6,0,2,5,7,1,3,12,14,8,10,13,15,9,11,90,91,70,71,72,73,66,67,64,65,84,85,92,93,80,81,86,87,94,95,76,77,88,89,106,107,78,79,96,97,108,109,72,73,80,81,98,99,74,75,110,111,240,241,86,87,92,93,206,207,192,193,0,2,1,3,4,6,8,10,12,14,5,7,9,11,13,15,8,10,12,14,0,2,9,11,13,15,1,3,4,6,5,7,8,10,9,11,4,6,0,2,12,14,5,7,1,3,13,15,4,6,5,7,8,10,12,14,9,11,13,15,0,2,1,3,132,134,5,7,136,138,140,142,9,11,141,143,128,130,129,131,104,105,72,73,86,87,102,103,90,91,118,119,68,69,206,207,114,115,66,67,110,111,222,223,216,217,204,205,0,0,0,0,0,0,0,0,0,0,0,0,0,0,0,0,0,0,0,0,0,0,0,0,0,0,0,0,0,0,0,0,0,0,0,0,0,0,0,0,0,0,0,0,0,0,0,0,0,0,0,0},
  {64,65,66,67,68,69,70,71,72,73,74,75,76,77,78,79,0,1,2,3,128,129,130,131,132,133,134,135,136,137,138,139,140,141,142,143,64,66,76,78,65,67,77,79,68,70,69,71,72,74,73,75,12,14,8,10,13,15,9,11,0,2,4,6,1,3,5,7,4,6,8,10,0,2,5,7,9,11,12,14,1,3,13,15,0,2,8,10,4,6,12,14,1,3,9,11,5,7,13,15,99,102,103,68,69,110,111,104,105,73,116,117,82,83,100,101,74,75,86,87,92,93,118,119,68,69,4,6,5,7,12,14,8,10,0,2,13,15,9,11,1,3,79,68,65,67,70,64,71,78,77,69,72,75,70,74,79,76,73,68,67,66,65,8,10,0,2,9,11,12,14,1,3,4,6,13,15,5,7,12,14,8,10,4,6,0,2,13,15,9,11,5,7,1,3,4,6,12,14,8,10,5,7,13,15,0,2,9,11,1,3,80,81,96,97,92,93,108,109,70,71,82,83,100,101,78,206,207,106,107,86,87,94,95,76,77,220,221,200,201,226,227,0,0,0,0,0,0,0,0,0,0,0,0,0,0,0,0,0,0,0,0,0,0,0,0,0,0,0,0,0,0,0,0,0,0,0,0,0,0,0,0,0,0,0,0,0,0,0,0,0,0,0,0,0,0},
};

struct alignas(64) Params {
  CUtensorMap a[6];
  CUtensorMap w[4];
  CUtensorMap ow;
  CUtensorMap xr;
  const bf16 *x0, *wqkv;
  bf16* out;
  uint32_t swap;
  uint32_t jobs[NPAIR][JMAX];
  uint8_t kseq[NPAIR][KMAX];
};

template <class T> __device__ __forceinline__ T* at(T* base, uint32_t bytes) {
  T* r;
  asm("{\n.reg .u32 lo, hi;\nmov.b64 {lo, hi}, %1;\nadd.cc.u32 lo, lo, %2;\naddc.u32 hi, hi, 0;\nmov.b64 %0, {lo, hi};\n}" : "=l"(r) : "l"(base), "r"(bytes));
  return r;
}
#define SCR(sm, member, bytes) reinterpret_cast<decltype(&scratch_base()->member[0])>(at((sm).scratch, offsetof(Scratch, member) + (bytes)))
#define counter(line, word) SCR(sm, cnt, (line) * 128 + (word) * 4)
#define TRS(st, slot) do {} while (0)
#define TRX(cond, job, bit, slot, reg) do {} while (0)
#define TR(job, slot) do {} while (0)
#define TRI(cond, job, slot) do {} while (0)
#define TRK(cond, job, slot) do {} while (0)
#define TRC(job, slot) do {} while (0)

__device__ __forceinline__ uint32_t smem_u32(const void* p) { return (uint32_t)__cvta_generic_to_shared(p); }
__device__ __forceinline__ void mbar_init(uint32_t bar, uint32_t cnt) { asm volatile("mbarrier.init.shared::cta.b64 [%0], %1;" ::"r"(bar), "r"(cnt) : "memory"); }
__device__ __forceinline__ void mbar_expect_tx(uint32_t bar, uint32_t bytes) { asm volatile("mbarrier.arrive.expect_tx.shared::cta.b64 _, [%0], %1;" ::"r"(bar), "r"(bytes) : "memory"); }
__device__ __forceinline__ void mbar_arrive_n(uint32_t bar, uint32_t cnt) { asm volatile("mbarrier.arrive.shared::cta.b64 _, [%0], %1;" ::"r"(bar), "r"(cnt) : "memory"); }
__device__ __forceinline__ void mbar_arrive_cl_if(uint32_t cond, uint32_t bar) {
  asm volatile("{\n.reg .pred p;\nsetp.ne.u32 p, %1, 0;\n@p mbarrier.arrive.shared::cluster.b64 _, [%0];\n}" ::"r"(bar), "r"(cond) : "memory");
}
__device__ __forceinline__ void mbar_arrive_warp(uint32_t bar) {
  asm volatile("{\n.reg .pred p;\nbar.warp.sync -1;\nelect.sync _|p, -1;\n@p mbarrier.arrive.shared::cta.b64 _, [%0];\n}" ::"r"(bar) : "memory");
}
__device__ __forceinline__ uint32_t mapa(uint32_t addr, uint32_t cta) { uint32_t r; asm("mapa.shared::cluster.u32 %0, %1, %2;" : "=r"(r) : "r"(addr), "r"(cta)); return r; }
__device__ __forceinline__ bool mbar_test(uint32_t bar, uint32_t parity) {
  uint32_t ok;
  asm volatile("{\n.reg .pred p;\nmbarrier.test_wait.parity.shared::cta.b64 p, [%1], %2;\nselp.u32 %0, 1, 0, p;\n}\n" : "=r"(ok) : "r"(bar), "r"(parity) : "memory");
  return ok;
}
__device__ __forceinline__ void mbar_wait(uint32_t bar, uint32_t parity) {
  asm volatile(
      "{\n.reg .pred p;\n.reg .u32 n;\nmov.u32 n, 0;\n"
      "WAIT:\nmbarrier.try_wait.parity.shared::cta.b64 p, [%0], %1;\n@p bra DONE;\n"
      "add.u32 n, n, 1;\nsetp.lt.u32 p, n, %2;\n@p bra WAIT;\ntrap;\nDONE:\n}\n" ::"r"(bar), "r"(parity), "n"(SPIN_LIMIT) : "memory");
}
template <int ID, int N> __device__ __forceinline__ void bar_sync() { asm volatile("bar.sync %0, %1;" ::"n"(ID), "n"(N) : "memory"); }
template <int ID, int N> __device__ __forceinline__ void bar_arrive() { asm volatile("bar.arrive %0, %1;" ::"n"(ID), "n"(N) : "memory"); }
__device__ __forceinline__ uint32_t ld_relaxed(const uint32_t* p) { uint32_t v; asm volatile("ld.relaxed.gpu.global.u32 %0, [%1];" : "=r"(v) : "l"(p) : "memory"); return v; }
__device__ __forceinline__ void red_relaxed(uint32_t* p, uint32_t v) { asm volatile("red.relaxed.gpu.global.add.u32 [%0], %1;" ::"l"(p), "r"(v) : "memory"); }
__device__ __forceinline__ void red_release(uint32_t* p, uint32_t v) {
  asm volatile("fence.release.gpu;\nred.relaxed.gpu.global.add.u32 [%0], %1;" ::"l"(p), "r"(v) : "memory");
}
__device__ __forceinline__ bool elect() {
  uint32_t p;
  asm volatile("{\n.reg .pred P;\nelect.sync _|P, 0xffffffff;\nselp.u32 %0, 1, 0, P;\n}\n" : "=r"(p));
  return p;
}
__device__ __forceinline__ void fence_acquire() { asm volatile("fence.acquire.gpu;" ::: "memory"); }
__device__ __forceinline__ void wait_count(const uint32_t* p, uint32_t target) {
  for (uint32_t n = 0; !__all_sync(~0u, (int)(ld_relaxed(p) - target) >= 0); n++) {
    __nanosleep(V_SL1);
    if (n > SPIN_LIMIT) __trap();
  }
  fence_acquire();
}
__device__ __forceinline__ void fence_proxy_async() { asm volatile("fence.proxy.async.global;" ::: "memory"); }
__device__ __forceinline__ void fence_proxy_async_smem() { asm volatile("fence.proxy.async.shared::cta;" ::: "memory"); }
__device__ __forceinline__ void tma4d_mc(uint32_t dst, const CUtensorMap* tm, int c1, int c2, uint32_t bar, uint64_t pol) {
  asm volatile("cp.async.bulk.tensor.4d.shared::cluster.global.mbarrier::complete_tx::bytes.multicast::cluster.L2::cache_hint [%0], [%1, {%3, %4, %5, %3}], [%2], %6, %7;"
               ::"r"(dst), "l"(tm), "r"(bar), "r"(0), "r"(c1), "r"(c2), "h"((uint16_t)3), "l"(pol) : "memory");
}
__device__ __forceinline__ void tma3d(uint32_t dst, const CUtensorMap* tm, int c0, int c1, int c2, uint32_t bar, uint64_t pol) {
  asm volatile("cp.async.bulk.tensor.3d.shared::cluster.global.mbarrier::complete_tx::bytes.L2::cache_hint [%0], [%1, {%3, %4, %5}], [%2], %6;"
               ::"r"(dst), "l"(tm), "r"(bar), "r"(c0), "r"(c1), "r"(c2), "l"(pol) : "memory");
}
__device__ __forceinline__ void tma3d_reduce_add(const CUtensorMap* tm, int c0, int c1, int c2, uint32_t src) {
  asm volatile("cp.reduce.async.bulk.tensor.3d.global.shared::cta.add.tile.bulk_group [%0, {%2, %3, %4}], [%1];"
               ::"l"(tm), "r"(src), "r"(c0), "r"(c1), "r"(c2) : "memory");
}
__device__ __forceinline__ void tma3d_store(const CUtensorMap* tm, int c0, int c1, int c2, uint32_t src) {
  asm volatile("cp.async.bulk.tensor.3d.global.shared::cta.tile.bulk_group [%0, {%2, %3, %4}], [%1];"
               ::"l"(tm), "r"(src), "r"(c0), "r"(c1), "r"(c2) : "memory");
}
__device__ __forceinline__ void bulk_commit() { asm volatile("cp.async.bulk.commit_group;" ::: "memory"); }
template <int N> __device__ __forceinline__ void bulk_wait_read() { asm volatile("cp.async.bulk.wait_group.read %0;" ::"n"(N) : "memory"); }
__device__ __forceinline__ void bulk_wait() { asm volatile("cp.async.bulk.wait_group 0;" ::: "memory"); }
__device__ __forceinline__ uint2 lds64(uint32_t a) { uint2 v; asm volatile("ld.shared.v2.u32 {%0,%1}, [%2];" : "=r"(v.x), "=r"(v.y) : "r"(a) : "memory"); return v; }
__device__ __forceinline__ float lds32f(uint32_t a) { float v; asm volatile("ld.shared.f32 %0, [%1];" : "=f"(v) : "r"(a) : "memory"); return v; }
__device__ __forceinline__ uint4 lds128(uint32_t a) { uint4 v; asm volatile("ld.shared.v4.u32 {%0,%1,%2,%3}, [%4];" : "=r"(v.x), "=r"(v.y), "=r"(v.z), "=r"(v.w) : "r"(a) : "memory"); return v; }
__device__ __forceinline__ uint2 lds64v(uint32_t a) { uint2 v; asm volatile("ld.volatile.shared.v2.u32 {%0,%1}, [%2];" : "=r"(v.x), "=r"(v.y) : "r"(a) : "memory"); return v; }
__device__ __forceinline__ uint4 lds128v(uint32_t a) { uint4 v; asm volatile("ld.volatile.shared.v4.u32 {%0,%1,%2,%3}, [%4];" : "=r"(v.x), "=r"(v.y), "=r"(v.z), "=r"(v.w) : "r"(a) : "memory"); return v; }
__device__ __forceinline__ void sts32(uint32_t a, uint32_t v) { asm volatile("st.shared.u32 [%0], %1;" ::"r"(a), "r"(v) : "memory"); }
__device__ __forceinline__ void sts64(uint32_t a, uint2 v) { asm volatile("st.shared.v2.u32 [%0], {%1,%2};" ::"r"(a), "r"(v.x), "r"(v.y) : "memory"); }
__device__ __forceinline__ void stg128(void* p, uint4 v) { asm volatile("st.global.L1::no_allocate.v4.u32 [%0], {%1,%2,%3,%4};" ::"l"(p), "r"(v.x), "r"(v.y), "r"(v.z), "r"(v.w) : "memory"); }
__device__ __forceinline__ uint4 ldg128(const void* p) { uint4 v; asm volatile("ld.relaxed.gpu.global.v4.u32 {%0,%1,%2,%3}, [%4];" : "=r"(v.x), "=r"(v.y), "=r"(v.z), "=r"(v.w) : "l"(p) : "memory"); return v; }
__device__ __forceinline__ void prefetch_tm(const CUtensorMap* tm) { asm volatile("prefetch.tensormap [%0];" ::"l"(tm) : "memory"); }
template <int N> __device__ __forceinline__ void wg_wait() { asm volatile("wgmma.wait_group.sync.aligned %0;" ::"n"(N) : "memory"); }
__device__ __forceinline__ void cluster_arrive() { asm volatile("barrier.cluster.arrive.relaxed.aligned;" ::: "memory"); }
__device__ __forceinline__ void cluster_wait() { asm volatile("barrier.cluster.wait.acquire.aligned;" ::: "memory"); }
__device__ __forceinline__ uint32_t pack_bf16(float lo, float hi) { uint32_t r; asm("cvt.rn.bf16x2.f32 %0, %1, %2;" : "=r"(r) : "f"(hi), "f"(lo)); return r; }
__device__ __forceinline__ float bf_lo(uint32_t v) { return __uint_as_float(v << 16); }
__device__ __forceinline__ float bf_hi(uint32_t v) { return __uint_as_float(v & 0xffff0000u); }
__device__ __forceinline__ uint32_t dup_hi(uint32_t v) { return __byte_perm(v, 0, 0x3232); }
__device__ __forceinline__ float bf_round(float x) { return __bfloat162float(__float2bfloat16_rn(x)); }
__device__ __forceinline__ uint32_t bf2_add(uint32_t a, uint32_t b) { uint32_t r; asm("add.rn.bf16x2 %0, %1, %2;" : "=r"(r) : "r"(a), "r"(b)); return r; }
__device__ __forceinline__ uint32_t bf2_mul(uint32_t a, uint32_t b) { uint32_t r; asm("mul.rn.bf16x2 %0, %1, %2;" : "=r"(r) : "r"(a), "r"(b)); return r; }
__device__ __forceinline__ uint32_t bf2_fma(uint32_t a, uint32_t b, uint32_t c) { uint32_t r; asm("fma.rn.bf16x2 %0, %1, %2, %3;" : "=r"(r) : "r"(a), "r"(b), "r"(c)); return r; }
__device__ __forceinline__ uint4 add8(uint4 a, uint4 b) { return make_uint4(bf2_add(a.x, b.x), bf2_add(a.y, b.y), bf2_add(a.z, b.z), bf2_add(a.w, b.w)); }
__device__ __forceinline__ uint4 fma8(uint32_t a, uint4 b, uint4 c) { return make_uint4(bf2_fma(a, b.x, c.x), bf2_fma(a, b.y, c.y), bf2_fma(a, b.z, c.z), bf2_fma(a, b.w, c.w)); }
__device__ __forceinline__ void stsm4(uint32_t a, uint32_t r0, uint32_t r1, uint32_t r2, uint32_t r3) {
  asm volatile("stmatrix.sync.aligned.m8n8.x4.shared.b16 [%0], {%1,%2,%3,%4};" ::"r"(a), "r"(r0), "r"(r1), "r"(r2), "r"(r3) : "memory");
}
__device__ __forceinline__ void ldsm4(uint32_t a, uint32_t (&r)[4]) {
  asm volatile("ldmatrix.sync.aligned.m8n8.x4.shared.b16 {%0,%1,%2,%3}, [%4];" : "=r"(r[0]), "=r"(r[1]), "=r"(r[2]), "=r"(r[3]) : "r"(a) : "memory");
}
__device__ __forceinline__ void ldsm4t(uint32_t a, uint32_t (&r)[4]) {
  asm volatile("ldmatrix.sync.aligned.m8n8.x4.trans.shared.b16 {%0,%1,%2,%3}, [%4];" : "=r"(r[0]), "=r"(r[1]), "=r"(r[2]), "=r"(r[3]) : "r"(a) : "memory");
}
__device__ __forceinline__ void mma16816(float (&c)[4], uint32_t a0, uint32_t a1, uint32_t a2, uint32_t a3, uint32_t b0, uint32_t b1) {
  asm volatile("mma.sync.aligned.m16n8k16.row.col.f32.bf16.bf16.f32 {%0,%1,%2,%3}, {%4,%5,%6,%7}, {%8,%9}, {%0,%1,%2,%3};"
               : "+f"(c[0]), "+f"(c[1]), "+f"(c[2]), "+f"(c[3]) : "r"(a0), "r"(a1), "r"(a2), "r"(a3), "r"(b0), "r"(b1));
}
__device__ __forceinline__ void mma1688(float (&c)[4], uint32_t a0, uint32_t a1, uint32_t b0) {
  asm volatile("mma.sync.aligned.m16n8k8.row.col.f32.bf16.bf16.f32 {%0,%1,%2,%3}, {%4,%5}, {%6}, {%0,%1,%2,%3};"
               : "+f"(c[0]), "+f"(c[1]), "+f"(c[2]), "+f"(c[3]) : "r"(a0), "r"(a1), "r"(b0));
}
__device__ __forceinline__ float ex2(float x) { float y; asm("ex2.approx.ftz.f32 %0, %1;" : "=f"(y) : "f"(x)); return y; }
__device__ __forceinline__ float sqrt_fast(float x) { float y; asm("sqrt.approx.f32 %0, %1;" : "=f"(y) : "f"(x)); return y; }
__device__ __forceinline__ float tanh_fast(float x) { float y; asm("tanh.approx.f32 %0, %1;" : "=f"(y) : "f"(x)); return y; }
__device__ __forceinline__ float rcp(float x) { float y; asm("rcp.approx.ftz.f32 %0, %1;" : "=f"(y) : "f"(x)); return y; }
__device__ __forceinline__ uint32_t opaque_zero() { uint32_t z; asm volatile("mov.u32 %0, %%ctaid.y;" : "=r"(z)); return z; }
__device__ __forceinline__ int fresh_tid() { int t; asm volatile("mov.u32 %0, %%tid.x;" : "=r"(t)); return t; }

__device__ __forceinline__ void first_kstep(float (&d)[128], uint32_t a, uint32_t b) {
  asm volatile("{\n.reg .u32 t;\n.reg .u64 da, db;\nwgmma.fence.sync.aligned;\n"
    "add.u32 t, %128, 0;\nmov.b64 da, {t, %130};\nadd.u32 t, %129, 0;\nmov.b64 db, {t, %130};\n"
    "wgmma.mma_async.sync.aligned.m64n256k16.f32.bf16.bf16 {%0, %1, %2, %3, %4, %5, %6, %7, %8, %9, %10, %11, %12, %13, %14, %15, %16, %17, %18, %19, %20, %21, %22, %23, %24, %25, %26, %27, %28, %29, %30, %31, %32, %33, %34, %35, %36, %37, %38, %39, %40, %41, %42, %43, %44, %45, %46, %47, %48, %49, %50, %51, %52, %53, %54, %55, %56, %57, %58, %59, %60, %61, %62, %63, %64, %65, %66, %67, %68, %69, %70, %71, %72, %73, %74, %75, %76, %77, %78, %79, %80, %81, %82, %83, %84, %85, %86, %87, %88, %89, %90, %91, %92, %93, %94, %95, %96, %97, %98, %99, %100, %101, %102, %103, %104, %105, %106, %107, %108, %109, %110, %111, %112, %113, %114, %115, %116, %117, %118, %119, %120, %121, %122, %123, %124, %125, %126, %127}, da, db, 0, 1, 1, 0, 1;\nwgmma.commit_group.sync.aligned;\n"
    "add.u32 t, %128, 2;\nmov.b64 da, {t, %130};\nadd.u32 t, %129, 128;\nmov.b64 db, {t, %130};\n"
    "wgmma.mma_async.sync.aligned.m64n256k16.f32.bf16.bf16 {%0, %1, %2, %3, %4, %5, %6, %7, %8, %9, %10, %11, %12, %13, %14, %15, %16, %17, %18, %19, %20, %21, %22, %23, %24, %25, %26, %27, %28, %29, %30, %31, %32, %33, %34, %35, %36, %37, %38, %39, %40, %41, %42, %43, %44, %45, %46, %47, %48, %49, %50, %51, %52, %53, %54, %55, %56, %57, %58, %59, %60, %61, %62, %63, %64, %65, %66, %67, %68, %69, %70, %71, %72, %73, %74, %75, %76, %77, %78, %79, %80, %81, %82, %83, %84, %85, %86, %87, %88, %89, %90, %91, %92, %93, %94, %95, %96, %97, %98, %99, %100, %101, %102, %103, %104, %105, %106, %107, %108, %109, %110, %111, %112, %113, %114, %115, %116, %117, %118, %119, %120, %121, %122, %123, %124, %125, %126, %127}, da, db, 1, 1, 1, 0, 1;\n"
    "add.u32 t, %128, 4;\nmov.b64 da, {t, %130};\nadd.u32 t, %129, 1024;\nmov.b64 db, {t, %130};\n"
    "wgmma.mma_async.sync.aligned.m64n256k16.f32.bf16.bf16 {%0, %1, %2, %3, %4, %5, %6, %7, %8, %9, %10, %11, %12, %13, %14, %15, %16, %17, %18, %19, %20, %21, %22, %23, %24, %25, %26, %27, %28, %29, %30, %31, %32, %33, %34, %35, %36, %37, %38, %39, %40, %41, %42, %43, %44, %45, %46, %47, %48, %49, %50, %51, %52, %53, %54, %55, %56, %57, %58, %59, %60, %61, %62, %63, %64, %65, %66, %67, %68, %69, %70, %71, %72, %73, %74, %75, %76, %77, %78, %79, %80, %81, %82, %83, %84, %85, %86, %87, %88, %89, %90, %91, %92, %93, %94, %95, %96, %97, %98, %99, %100, %101, %102, %103, %104, %105, %106, %107, %108, %109, %110, %111, %112, %113, %114, %115, %116, %117, %118, %119, %120, %121, %122, %123, %124, %125, %126, %127}, da, db, 1, 1, 1, 0, 1;\n"
    "add.u32 t, %128, 6;\nmov.b64 da, {t, %130};\nadd.u32 t, %129, 1152;\nmov.b64 db, {t, %130};\n"
    "wgmma.mma_async.sync.aligned.m64n256k16.f32.bf16.bf16 {%0, %1, %2, %3, %4, %5, %6, %7, %8, %9, %10, %11, %12, %13, %14, %15, %16, %17, %18, %19, %20, %21, %22, %23, %24, %25, %26, %27, %28, %29, %30, %31, %32, %33, %34, %35, %36, %37, %38, %39, %40, %41, %42, %43, %44, %45, %46, %47, %48, %49, %50, %51, %52, %53, %54, %55, %56, %57, %58, %59, %60, %61, %62, %63, %64, %65, %66, %67, %68, %69, %70, %71, %72, %73, %74, %75, %76, %77, %78, %79, %80, %81, %82, %83, %84, %85, %86, %87, %88, %89, %90, %91, %92, %93, %94, %95, %96, %97, %98, %99, %100, %101, %102, %103, %104, %105, %106, %107, %108, %109, %110, %111, %112, %113, %114, %115, %116, %117, %118, %119, %120, %121, %122, %123, %124, %125, %126, %127}, da, db, 1, 1, 1, 0, 1;\nwgmma.commit_group.sync.aligned;\n"
    "}\n"
    : "=f"(d[0]), "=f"(d[1]), "=f"(d[2]), "=f"(d[3]), "=f"(d[4]), "=f"(d[5]), "=f"(d[6]), "=f"(d[7]), "=f"(d[8]), "=f"(d[9]), "=f"(d[10]), "=f"(d[11]), "=f"(d[12]), "=f"(d[13]), "=f"(d[14]), "=f"(d[15]), "=f"(d[16]), "=f"(d[17]), "=f"(d[18]), "=f"(d[19]), "=f"(d[20]), "=f"(d[21]), "=f"(d[22]), "=f"(d[23]), "=f"(d[24]), "=f"(d[25]), "=f"(d[26]), "=f"(d[27]), "=f"(d[28]), "=f"(d[29]), "=f"(d[30]), "=f"(d[31]), "=f"(d[32]), "=f"(d[33]), "=f"(d[34]), "=f"(d[35]), "=f"(d[36]), "=f"(d[37]), "=f"(d[38]), "=f"(d[39]), "=f"(d[40]), "=f"(d[41]), "=f"(d[42]), "=f"(d[43]), "=f"(d[44]), "=f"(d[45]), "=f"(d[46]), "=f"(d[47]), "=f"(d[48]), "=f"(d[49]), "=f"(d[50]), "=f"(d[51]), "=f"(d[52]), "=f"(d[53]), "=f"(d[54]), "=f"(d[55]), "=f"(d[56]), "=f"(d[57]), "=f"(d[58]), "=f"(d[59]), "=f"(d[60]), "=f"(d[61]), "=f"(d[62]), "=f"(d[63]), "=f"(d[64]), "=f"(d[65]), "=f"(d[66]), "=f"(d[67]), "=f"(d[68]), "=f"(d[69]), "=f"(d[70]), "=f"(d[71]), "=f"(d[72]), "=f"(d[73]), "=f"(d[74]), "=f"(d[75]), "=f"(d[76]), "=f"(d[77]), "=f"(d[78]), "=f"(d[79]), "=f"(d[80]), "=f"(d[81]), "=f"(d[82]), "=f"(d[83]), "=f"(d[84]), "=f"(d[85]), "=f"(d[86]), "=f"(d[87]), "=f"(d[88]), "=f"(d[89]), "=f"(d[90]), "=f"(d[91]), "=f"(d[92]), "=f"(d[93]), "=f"(d[94]), "=f"(d[95]), "=f"(d[96]), "=f"(d[97]), "=f"(d[98]), "=f"(d[99]), "=f"(d[100]), "=f"(d[101]), "=f"(d[102]), "=f"(d[103]), "=f"(d[104]), "=f"(d[105]), "=f"(d[106]), "=f"(d[107]), "=f"(d[108]), "=f"(d[109]), "=f"(d[110]), "=f"(d[111]), "=f"(d[112]), "=f"(d[113]), "=f"(d[114]), "=f"(d[115]), "=f"(d[116]), "=f"(d[117]), "=f"(d[118]), "=f"(d[119]), "=f"(d[120]), "=f"(d[121]), "=f"(d[122]), "=f"(d[123]), "=f"(d[124]), "=f"(d[125]), "=f"(d[126]), "=f"(d[127])
    : "r"(a), "r"(b), "n"(0x40000040) : "memory");
}
__device__ __forceinline__ void kstep(float (&d)[128], uint32_t a, uint32_t b) {
  asm volatile("{\n.reg .u32 t;\n.reg .u64 da, db;\nwgmma.fence.sync.aligned;\n"
    "add.u32 t, %128, 0;\nmov.b64 da, {t, %130};\nadd.u32 t, %129, 0;\nmov.b64 db, {t, %130};\n"
    "wgmma.mma_async.sync.aligned.m64n256k16.f32.bf16.bf16 {%0, %1, %2, %3, %4, %5, %6, %7, %8, %9, %10, %11, %12, %13, %14, %15, %16, %17, %18, %19, %20, %21, %22, %23, %24, %25, %26, %27, %28, %29, %30, %31, %32, %33, %34, %35, %36, %37, %38, %39, %40, %41, %42, %43, %44, %45, %46, %47, %48, %49, %50, %51, %52, %53, %54, %55, %56, %57, %58, %59, %60, %61, %62, %63, %64, %65, %66, %67, %68, %69, %70, %71, %72, %73, %74, %75, %76, %77, %78, %79, %80, %81, %82, %83, %84, %85, %86, %87, %88, %89, %90, %91, %92, %93, %94, %95, %96, %97, %98, %99, %100, %101, %102, %103, %104, %105, %106, %107, %108, %109, %110, %111, %112, %113, %114, %115, %116, %117, %118, %119, %120, %121, %122, %123, %124, %125, %126, %127}, da, db, 1, 1, 1, 0, 1;\nwgmma.commit_group.sync.aligned;\n"
    "add.u32 t, %128, 2;\nmov.b64 da, {t, %130};\nadd.u32 t, %129, 128;\nmov.b64 db, {t, %130};\n"
    "wgmma.mma_async.sync.aligned.m64n256k16.f32.bf16.bf16 {%0, %1, %2, %3, %4, %5, %6, %7, %8, %9, %10, %11, %12, %13, %14, %15, %16, %17, %18, %19, %20, %21, %22, %23, %24, %25, %26, %27, %28, %29, %30, %31, %32, %33, %34, %35, %36, %37, %38, %39, %40, %41, %42, %43, %44, %45, %46, %47, %48, %49, %50, %51, %52, %53, %54, %55, %56, %57, %58, %59, %60, %61, %62, %63, %64, %65, %66, %67, %68, %69, %70, %71, %72, %73, %74, %75, %76, %77, %78, %79, %80, %81, %82, %83, %84, %85, %86, %87, %88, %89, %90, %91, %92, %93, %94, %95, %96, %97, %98, %99, %100, %101, %102, %103, %104, %105, %106, %107, %108, %109, %110, %111, %112, %113, %114, %115, %116, %117, %118, %119, %120, %121, %122, %123, %124, %125, %126, %127}, da, db, 1, 1, 1, 0, 1;\n"
    "add.u32 t, %128, 4;\nmov.b64 da, {t, %130};\nadd.u32 t, %129, 1024;\nmov.b64 db, {t, %130};\n"
    "wgmma.mma_async.sync.aligned.m64n256k16.f32.bf16.bf16 {%0, %1, %2, %3, %4, %5, %6, %7, %8, %9, %10, %11, %12, %13, %14, %15, %16, %17, %18, %19, %20, %21, %22, %23, %24, %25, %26, %27, %28, %29, %30, %31, %32, %33, %34, %35, %36, %37, %38, %39, %40, %41, %42, %43, %44, %45, %46, %47, %48, %49, %50, %51, %52, %53, %54, %55, %56, %57, %58, %59, %60, %61, %62, %63, %64, %65, %66, %67, %68, %69, %70, %71, %72, %73, %74, %75, %76, %77, %78, %79, %80, %81, %82, %83, %84, %85, %86, %87, %88, %89, %90, %91, %92, %93, %94, %95, %96, %97, %98, %99, %100, %101, %102, %103, %104, %105, %106, %107, %108, %109, %110, %111, %112, %113, %114, %115, %116, %117, %118, %119, %120, %121, %122, %123, %124, %125, %126, %127}, da, db, 1, 1, 1, 0, 1;\n"
    "add.u32 t, %128, 6;\nmov.b64 da, {t, %130};\nadd.u32 t, %129, 1152;\nmov.b64 db, {t, %130};\n"
    "wgmma.mma_async.sync.aligned.m64n256k16.f32.bf16.bf16 {%0, %1, %2, %3, %4, %5, %6, %7, %8, %9, %10, %11, %12, %13, %14, %15, %16, %17, %18, %19, %20, %21, %22, %23, %24, %25, %26, %27, %28, %29, %30, %31, %32, %33, %34, %35, %36, %37, %38, %39, %40, %41, %42, %43, %44, %45, %46, %47, %48, %49, %50, %51, %52, %53, %54, %55, %56, %57, %58, %59, %60, %61, %62, %63, %64, %65, %66, %67, %68, %69, %70, %71, %72, %73, %74, %75, %76, %77, %78, %79, %80, %81, %82, %83, %84, %85, %86, %87, %88, %89, %90, %91, %92, %93, %94, %95, %96, %97, %98, %99, %100, %101, %102, %103, %104, %105, %106, %107, %108, %109, %110, %111, %112, %113, %114, %115, %116, %117, %118, %119, %120, %121, %122, %123, %124, %125, %126, %127}, da, db, 1, 1, 1, 0, 1;\nwgmma.commit_group.sync.aligned;\n"
    "}\n"
    : "+f"(d[0]), "+f"(d[1]), "+f"(d[2]), "+f"(d[3]), "+f"(d[4]), "+f"(d[5]), "+f"(d[6]), "+f"(d[7]), "+f"(d[8]), "+f"(d[9]), "+f"(d[10]), "+f"(d[11]), "+f"(d[12]), "+f"(d[13]), "+f"(d[14]), "+f"(d[15]), "+f"(d[16]), "+f"(d[17]), "+f"(d[18]), "+f"(d[19]), "+f"(d[20]), "+f"(d[21]), "+f"(d[22]), "+f"(d[23]), "+f"(d[24]), "+f"(d[25]), "+f"(d[26]), "+f"(d[27]), "+f"(d[28]), "+f"(d[29]), "+f"(d[30]), "+f"(d[31]), "+f"(d[32]), "+f"(d[33]), "+f"(d[34]), "+f"(d[35]), "+f"(d[36]), "+f"(d[37]), "+f"(d[38]), "+f"(d[39]), "+f"(d[40]), "+f"(d[41]), "+f"(d[42]), "+f"(d[43]), "+f"(d[44]), "+f"(d[45]), "+f"(d[46]), "+f"(d[47]), "+f"(d[48]), "+f"(d[49]), "+f"(d[50]), "+f"(d[51]), "+f"(d[52]), "+f"(d[53]), "+f"(d[54]), "+f"(d[55]), "+f"(d[56]), "+f"(d[57]), "+f"(d[58]), "+f"(d[59]), "+f"(d[60]), "+f"(d[61]), "+f"(d[62]), "+f"(d[63]), "+f"(d[64]), "+f"(d[65]), "+f"(d[66]), "+f"(d[67]), "+f"(d[68]), "+f"(d[69]), "+f"(d[70]), "+f"(d[71]), "+f"(d[72]), "+f"(d[73]), "+f"(d[74]), "+f"(d[75]), "+f"(d[76]), "+f"(d[77]), "+f"(d[78]), "+f"(d[79]), "+f"(d[80]), "+f"(d[81]), "+f"(d[82]), "+f"(d[83]), "+f"(d[84]), "+f"(d[85]), "+f"(d[86]), "+f"(d[87]), "+f"(d[88]), "+f"(d[89]), "+f"(d[90]), "+f"(d[91]), "+f"(d[92]), "+f"(d[93]), "+f"(d[94]), "+f"(d[95]), "+f"(d[96]), "+f"(d[97]), "+f"(d[98]), "+f"(d[99]), "+f"(d[100]), "+f"(d[101]), "+f"(d[102]), "+f"(d[103]), "+f"(d[104]), "+f"(d[105]), "+f"(d[106]), "+f"(d[107]), "+f"(d[108]), "+f"(d[109]), "+f"(d[110]), "+f"(d[111]), "+f"(d[112]), "+f"(d[113]), "+f"(d[114]), "+f"(d[115]), "+f"(d[116]), "+f"(d[117]), "+f"(d[118]), "+f"(d[119]), "+f"(d[120]), "+f"(d[121]), "+f"(d[122]), "+f"(d[123]), "+f"(d[124]), "+f"(d[125]), "+f"(d[126]), "+f"(d[127])
    : "r"(a), "r"(b), "n"(0x40000040) : "memory");
}
__device__ __forceinline__ void first_kstep(float (&d)[96], uint32_t a, uint32_t b) {
  asm volatile("{\n.reg .u32 t;\n.reg .u64 da, db;\nwgmma.fence.sync.aligned;\n"
    "add.u32 t, %96, 0;\nmov.b64 da, {t, %98};\nadd.u32 t, %97, 0;\nmov.b64 db, {t, %98};\n"
    "wgmma.mma_async.sync.aligned.m64n192k16.f32.bf16.bf16 {%0, %1, %2, %3, %4, %5, %6, %7, %8, %9, %10, %11, %12, %13, %14, %15, %16, %17, %18, %19, %20, %21, %22, %23, %24, %25, %26, %27, %28, %29, %30, %31, %32, %33, %34, %35, %36, %37, %38, %39, %40, %41, %42, %43, %44, %45, %46, %47, %48, %49, %50, %51, %52, %53, %54, %55, %56, %57, %58, %59, %60, %61, %62, %63, %64, %65, %66, %67, %68, %69, %70, %71, %72, %73, %74, %75, %76, %77, %78, %79, %80, %81, %82, %83, %84, %85, %86, %87, %88, %89, %90, %91, %92, %93, %94, %95}, da, db, 0, 1, 1, 0, 1;\nwgmma.commit_group.sync.aligned;\n"
    "add.u32 t, %96, 2;\nmov.b64 da, {t, %98};\nadd.u32 t, %97, 128;\nmov.b64 db, {t, %98};\n"
    "wgmma.mma_async.sync.aligned.m64n192k16.f32.bf16.bf16 {%0, %1, %2, %3, %4, %5, %6, %7, %8, %9, %10, %11, %12, %13, %14, %15, %16, %17, %18, %19, %20, %21, %22, %23, %24, %25, %26, %27, %28, %29, %30, %31, %32, %33, %34, %35, %36, %37, %38, %39, %40, %41, %42, %43, %44, %45, %46, %47, %48, %49, %50, %51, %52, %53, %54, %55, %56, %57, %58, %59, %60, %61, %62, %63, %64, %65, %66, %67, %68, %69, %70, %71, %72, %73, %74, %75, %76, %77, %78, %79, %80, %81, %82, %83, %84, %85, %86, %87, %88, %89, %90, %91, %92, %93, %94, %95}, da, db, 1, 1, 1, 0, 1;\n"
    "add.u32 t, %96, 4;\nmov.b64 da, {t, %98};\nadd.u32 t, %97, 1024;\nmov.b64 db, {t, %98};\n"
    "wgmma.mma_async.sync.aligned.m64n192k16.f32.bf16.bf16 {%0, %1, %2, %3, %4, %5, %6, %7, %8, %9, %10, %11, %12, %13, %14, %15, %16, %17, %18, %19, %20, %21, %22, %23, %24, %25, %26, %27, %28, %29, %30, %31, %32, %33, %34, %35, %36, %37, %38, %39, %40, %41, %42, %43, %44, %45, %46, %47, %48, %49, %50, %51, %52, %53, %54, %55, %56, %57, %58, %59, %60, %61, %62, %63, %64, %65, %66, %67, %68, %69, %70, %71, %72, %73, %74, %75, %76, %77, %78, %79, %80, %81, %82, %83, %84, %85, %86, %87, %88, %89, %90, %91, %92, %93, %94, %95}, da, db, 1, 1, 1, 0, 1;\n"
    "add.u32 t, %96, 6;\nmov.b64 da, {t, %98};\nadd.u32 t, %97, 1152;\nmov.b64 db, {t, %98};\n"
    "wgmma.mma_async.sync.aligned.m64n192k16.f32.bf16.bf16 {%0, %1, %2, %3, %4, %5, %6, %7, %8, %9, %10, %11, %12, %13, %14, %15, %16, %17, %18, %19, %20, %21, %22, %23, %24, %25, %26, %27, %28, %29, %30, %31, %32, %33, %34, %35, %36, %37, %38, %39, %40, %41, %42, %43, %44, %45, %46, %47, %48, %49, %50, %51, %52, %53, %54, %55, %56, %57, %58, %59, %60, %61, %62, %63, %64, %65, %66, %67, %68, %69, %70, %71, %72, %73, %74, %75, %76, %77, %78, %79, %80, %81, %82, %83, %84, %85, %86, %87, %88, %89, %90, %91, %92, %93, %94, %95}, da, db, 1, 1, 1, 0, 1;\nwgmma.commit_group.sync.aligned;\n"
    "}\n"
    : "=f"(d[0]), "=f"(d[1]), "=f"(d[2]), "=f"(d[3]), "=f"(d[4]), "=f"(d[5]), "=f"(d[6]), "=f"(d[7]), "=f"(d[8]), "=f"(d[9]), "=f"(d[10]), "=f"(d[11]), "=f"(d[12]), "=f"(d[13]), "=f"(d[14]), "=f"(d[15]), "=f"(d[16]), "=f"(d[17]), "=f"(d[18]), "=f"(d[19]), "=f"(d[20]), "=f"(d[21]), "=f"(d[22]), "=f"(d[23]), "=f"(d[24]), "=f"(d[25]), "=f"(d[26]), "=f"(d[27]), "=f"(d[28]), "=f"(d[29]), "=f"(d[30]), "=f"(d[31]), "=f"(d[32]), "=f"(d[33]), "=f"(d[34]), "=f"(d[35]), "=f"(d[36]), "=f"(d[37]), "=f"(d[38]), "=f"(d[39]), "=f"(d[40]), "=f"(d[41]), "=f"(d[42]), "=f"(d[43]), "=f"(d[44]), "=f"(d[45]), "=f"(d[46]), "=f"(d[47]), "=f"(d[48]), "=f"(d[49]), "=f"(d[50]), "=f"(d[51]), "=f"(d[52]), "=f"(d[53]), "=f"(d[54]), "=f"(d[55]), "=f"(d[56]), "=f"(d[57]), "=f"(d[58]), "=f"(d[59]), "=f"(d[60]), "=f"(d[61]), "=f"(d[62]), "=f"(d[63]), "=f"(d[64]), "=f"(d[65]), "=f"(d[66]), "=f"(d[67]), "=f"(d[68]), "=f"(d[69]), "=f"(d[70]), "=f"(d[71]), "=f"(d[72]), "=f"(d[73]), "=f"(d[74]), "=f"(d[75]), "=f"(d[76]), "=f"(d[77]), "=f"(d[78]), "=f"(d[79]), "=f"(d[80]), "=f"(d[81]), "=f"(d[82]), "=f"(d[83]), "=f"(d[84]), "=f"(d[85]), "=f"(d[86]), "=f"(d[87]), "=f"(d[88]), "=f"(d[89]), "=f"(d[90]), "=f"(d[91]), "=f"(d[92]), "=f"(d[93]), "=f"(d[94]), "=f"(d[95])
    : "r"(a), "r"(b), "n"(0x40000040) : "memory");
}
__device__ __forceinline__ void kstep(float (&d)[96], uint32_t a, uint32_t b) {
  asm volatile("{\n.reg .u32 t;\n.reg .u64 da, db;\nwgmma.fence.sync.aligned;\n"
    "add.u32 t, %96, 0;\nmov.b64 da, {t, %98};\nadd.u32 t, %97, 0;\nmov.b64 db, {t, %98};\n"
    "wgmma.mma_async.sync.aligned.m64n192k16.f32.bf16.bf16 {%0, %1, %2, %3, %4, %5, %6, %7, %8, %9, %10, %11, %12, %13, %14, %15, %16, %17, %18, %19, %20, %21, %22, %23, %24, %25, %26, %27, %28, %29, %30, %31, %32, %33, %34, %35, %36, %37, %38, %39, %40, %41, %42, %43, %44, %45, %46, %47, %48, %49, %50, %51, %52, %53, %54, %55, %56, %57, %58, %59, %60, %61, %62, %63, %64, %65, %66, %67, %68, %69, %70, %71, %72, %73, %74, %75, %76, %77, %78, %79, %80, %81, %82, %83, %84, %85, %86, %87, %88, %89, %90, %91, %92, %93, %94, %95}, da, db, 1, 1, 1, 0, 1;\nwgmma.commit_group.sync.aligned;\n"
    "add.u32 t, %96, 2;\nmov.b64 da, {t, %98};\nadd.u32 t, %97, 128;\nmov.b64 db, {t, %98};\n"
    "wgmma.mma_async.sync.aligned.m64n192k16.f32.bf16.bf16 {%0, %1, %2, %3, %4, %5, %6, %7, %8, %9, %10, %11, %12, %13, %14, %15, %16, %17, %18, %19, %20, %21, %22, %23, %24, %25, %26, %27, %28, %29, %30, %31, %32, %33, %34, %35, %36, %37, %38, %39, %40, %41, %42, %43, %44, %45, %46, %47, %48, %49, %50, %51, %52, %53, %54, %55, %56, %57, %58, %59, %60, %61, %62, %63, %64, %65, %66, %67, %68, %69, %70, %71, %72, %73, %74, %75, %76, %77, %78, %79, %80, %81, %82, %83, %84, %85, %86, %87, %88, %89, %90, %91, %92, %93, %94, %95}, da, db, 1, 1, 1, 0, 1;\n"
    "add.u32 t, %96, 4;\nmov.b64 da, {t, %98};\nadd.u32 t, %97, 1024;\nmov.b64 db, {t, %98};\n"
    "wgmma.mma_async.sync.aligned.m64n192k16.f32.bf16.bf16 {%0, %1, %2, %3, %4, %5, %6, %7, %8, %9, %10, %11, %12, %13, %14, %15, %16, %17, %18, %19, %20, %21, %22, %23, %24, %25, %26, %27, %28, %29, %30, %31, %32, %33, %34, %35, %36, %37, %38, %39, %40, %41, %42, %43, %44, %45, %46, %47, %48, %49, %50, %51, %52, %53, %54, %55, %56, %57, %58, %59, %60, %61, %62, %63, %64, %65, %66, %67, %68, %69, %70, %71, %72, %73, %74, %75, %76, %77, %78, %79, %80, %81, %82, %83, %84, %85, %86, %87, %88, %89, %90, %91, %92, %93, %94, %95}, da, db, 1, 1, 1, 0, 1;\n"
    "add.u32 t, %96, 6;\nmov.b64 da, {t, %98};\nadd.u32 t, %97, 1152;\nmov.b64 db, {t, %98};\n"
    "wgmma.mma_async.sync.aligned.m64n192k16.f32.bf16.bf16 {%0, %1, %2, %3, %4, %5, %6, %7, %8, %9, %10, %11, %12, %13, %14, %15, %16, %17, %18, %19, %20, %21, %22, %23, %24, %25, %26, %27, %28, %29, %30, %31, %32, %33, %34, %35, %36, %37, %38, %39, %40, %41, %42, %43, %44, %45, %46, %47, %48, %49, %50, %51, %52, %53, %54, %55, %56, %57, %58, %59, %60, %61, %62, %63, %64, %65, %66, %67, %68, %69, %70, %71, %72, %73, %74, %75, %76, %77, %78, %79, %80, %81, %82, %83, %84, %85, %86, %87, %88, %89, %90, %91, %92, %93, %94, %95}, da, db, 1, 1, 1, 0, 1;\nwgmma.commit_group.sync.aligned;\n"
    "}\n"
    : "+f"(d[0]), "+f"(d[1]), "+f"(d[2]), "+f"(d[3]), "+f"(d[4]), "+f"(d[5]), "+f"(d[6]), "+f"(d[7]), "+f"(d[8]), "+f"(d[9]), "+f"(d[10]), "+f"(d[11]), "+f"(d[12]), "+f"(d[13]), "+f"(d[14]), "+f"(d[15]), "+f"(d[16]), "+f"(d[17]), "+f"(d[18]), "+f"(d[19]), "+f"(d[20]), "+f"(d[21]), "+f"(d[22]), "+f"(d[23]), "+f"(d[24]), "+f"(d[25]), "+f"(d[26]), "+f"(d[27]), "+f"(d[28]), "+f"(d[29]), "+f"(d[30]), "+f"(d[31]), "+f"(d[32]), "+f"(d[33]), "+f"(d[34]), "+f"(d[35]), "+f"(d[36]), "+f"(d[37]), "+f"(d[38]), "+f"(d[39]), "+f"(d[40]), "+f"(d[41]), "+f"(d[42]), "+f"(d[43]), "+f"(d[44]), "+f"(d[45]), "+f"(d[46]), "+f"(d[47]), "+f"(d[48]), "+f"(d[49]), "+f"(d[50]), "+f"(d[51]), "+f"(d[52]), "+f"(d[53]), "+f"(d[54]), "+f"(d[55]), "+f"(d[56]), "+f"(d[57]), "+f"(d[58]), "+f"(d[59]), "+f"(d[60]), "+f"(d[61]), "+f"(d[62]), "+f"(d[63]), "+f"(d[64]), "+f"(d[65]), "+f"(d[66]), "+f"(d[67]), "+f"(d[68]), "+f"(d[69]), "+f"(d[70]), "+f"(d[71]), "+f"(d[72]), "+f"(d[73]), "+f"(d[74]), "+f"(d[75]), "+f"(d[76]), "+f"(d[77]), "+f"(d[78]), "+f"(d[79]), "+f"(d[80]), "+f"(d[81]), "+f"(d[82]), "+f"(d[83]), "+f"(d[84]), "+f"(d[85]), "+f"(d[86]), "+f"(d[87]), "+f"(d[88]), "+f"(d[89]), "+f"(d[90]), "+f"(d[91]), "+f"(d[92]), "+f"(d[93]), "+f"(d[94]), "+f"(d[95])
    : "r"(a), "r"(b), "n"(0x40000040) : "memory");
}
__device__ __forceinline__ void half_kstep0(float (&d)[64], uint32_t a, uint32_t b) {
  asm volatile("{\n.reg .u32 t;\n.reg .u64 da, db;\nwgmma.fence.sync.aligned;\n"
    "add.u32 t, %64, 0;\nmov.b64 da, {t, %66};\nadd.u32 t, %65, 0;\nmov.b64 db, {t, %66};\n"
    "wgmma.mma_async.sync.aligned.m64n128k16.f32.bf16.bf16 {%0, %1, %2, %3, %4, %5, %6, %7, %8, %9, %10, %11, %12, %13, %14, %15, %16, %17, %18, %19, %20, %21, %22, %23, %24, %25, %26, %27, %28, %29, %30, %31, %32, %33, %34, %35, %36, %37, %38, %39, %40, %41, %42, %43, %44, %45, %46, %47, %48, %49, %50, %51, %52, %53, %54, %55, %56, %57, %58, %59, %60, %61, %62, %63}, da, db, 1, 1, 1, 0, 1;\n"
    "add.u32 t, %64, 2;\nmov.b64 da, {t, %66};\nadd.u32 t, %65, 128;\nmov.b64 db, {t, %66};\n"
    "wgmma.mma_async.sync.aligned.m64n128k16.f32.bf16.bf16 {%0, %1, %2, %3, %4, %5, %6, %7, %8, %9, %10, %11, %12, %13, %14, %15, %16, %17, %18, %19, %20, %21, %22, %23, %24, %25, %26, %27, %28, %29, %30, %31, %32, %33, %34, %35, %36, %37, %38, %39, %40, %41, %42, %43, %44, %45, %46, %47, %48, %49, %50, %51, %52, %53, %54, %55, %56, %57, %58, %59, %60, %61, %62, %63}, da, db, 1, 1, 1, 0, 1;\n"
    "add.u32 t, %64, 4;\nmov.b64 da, {t, %66};\nadd.u32 t, %65, 1024;\nmov.b64 db, {t, %66};\n"
    "wgmma.mma_async.sync.aligned.m64n128k16.f32.bf16.bf16 {%0, %1, %2, %3, %4, %5, %6, %7, %8, %9, %10, %11, %12, %13, %14, %15, %16, %17, %18, %19, %20, %21, %22, %23, %24, %25, %26, %27, %28, %29, %30, %31, %32, %33, %34, %35, %36, %37, %38, %39, %40, %41, %42, %43, %44, %45, %46, %47, %48, %49, %50, %51, %52, %53, %54, %55, %56, %57, %58, %59, %60, %61, %62, %63}, da, db, 1, 1, 1, 0, 1;\n"
    "add.u32 t, %64, 6;\nmov.b64 da, {t, %66};\nadd.u32 t, %65, 1152;\nmov.b64 db, {t, %66};\n"
    "wgmma.mma_async.sync.aligned.m64n128k16.f32.bf16.bf16 {%0, %1, %2, %3, %4, %5, %6, %7, %8, %9, %10, %11, %12, %13, %14, %15, %16, %17, %18, %19, %20, %21, %22, %23, %24, %25, %26, %27, %28, %29, %30, %31, %32, %33, %34, %35, %36, %37, %38, %39, %40, %41, %42, %43, %44, %45, %46, %47, %48, %49, %50, %51, %52, %53, %54, %55, %56, %57, %58, %59, %60, %61, %62, %63}, da, db, 1, 1, 1, 0, 1;\n"
    "wgmma.commit_group.sync.aligned;\n}\n"
    : "+f"(d[0]), "+f"(d[1]), "+f"(d[2]), "+f"(d[3]), "+f"(d[4]), "+f"(d[5]), "+f"(d[6]), "+f"(d[7]), "+f"(d[8]), "+f"(d[9]), "+f"(d[10]), "+f"(d[11]), "+f"(d[12]), "+f"(d[13]), "+f"(d[14]), "+f"(d[15]), "+f"(d[16]), "+f"(d[17]), "+f"(d[18]), "+f"(d[19]), "+f"(d[20]), "+f"(d[21]), "+f"(d[22]), "+f"(d[23]), "+f"(d[24]), "+f"(d[25]), "+f"(d[26]), "+f"(d[27]), "+f"(d[28]), "+f"(d[29]), "+f"(d[30]), "+f"(d[31]), "+f"(d[32]), "+f"(d[33]), "+f"(d[34]), "+f"(d[35]), "+f"(d[36]), "+f"(d[37]), "+f"(d[38]), "+f"(d[39]), "+f"(d[40]), "+f"(d[41]), "+f"(d[42]), "+f"(d[43]), "+f"(d[44]), "+f"(d[45]), "+f"(d[46]), "+f"(d[47]), "+f"(d[48]), "+f"(d[49]), "+f"(d[50]), "+f"(d[51]), "+f"(d[52]), "+f"(d[53]), "+f"(d[54]), "+f"(d[55]), "+f"(d[56]), "+f"(d[57]), "+f"(d[58]), "+f"(d[59]), "+f"(d[60]), "+f"(d[61]), "+f"(d[62]), "+f"(d[63])
    : "r"(a), "r"(b), "n"(0x40000040) : "memory");
}
__device__ __forceinline__ void half_kstep1(float (&d)[64], uint32_t a, uint32_t b) {
  asm volatile("{\n.reg .u32 t;\n.reg .u64 da, db;\nwgmma.fence.sync.aligned;\n"
    "add.u32 t, %64, 0;\nmov.b64 da, {t, %66};\nadd.u32 t, %65, 512;\nmov.b64 db, {t, %66};\n"
    "wgmma.mma_async.sync.aligned.m64n128k16.f32.bf16.bf16 {%0, %1, %2, %3, %4, %5, %6, %7, %8, %9, %10, %11, %12, %13, %14, %15, %16, %17, %18, %19, %20, %21, %22, %23, %24, %25, %26, %27, %28, %29, %30, %31, %32, %33, %34, %35, %36, %37, %38, %39, %40, %41, %42, %43, %44, %45, %46, %47, %48, %49, %50, %51, %52, %53, %54, %55, %56, %57, %58, %59, %60, %61, %62, %63}, da, db, 1, 1, 1, 0, 1;\n"
    "add.u32 t, %64, 2;\nmov.b64 da, {t, %66};\nadd.u32 t, %65, 640;\nmov.b64 db, {t, %66};\n"
    "wgmma.mma_async.sync.aligned.m64n128k16.f32.bf16.bf16 {%0, %1, %2, %3, %4, %5, %6, %7, %8, %9, %10, %11, %12, %13, %14, %15, %16, %17, %18, %19, %20, %21, %22, %23, %24, %25, %26, %27, %28, %29, %30, %31, %32, %33, %34, %35, %36, %37, %38, %39, %40, %41, %42, %43, %44, %45, %46, %47, %48, %49, %50, %51, %52, %53, %54, %55, %56, %57, %58, %59, %60, %61, %62, %63}, da, db, 1, 1, 1, 0, 1;\n"
    "add.u32 t, %64, 4;\nmov.b64 da, {t, %66};\nadd.u32 t, %65, 1536;\nmov.b64 db, {t, %66};\n"
    "wgmma.mma_async.sync.aligned.m64n128k16.f32.bf16.bf16 {%0, %1, %2, %3, %4, %5, %6, %7, %8, %9, %10, %11, %12, %13, %14, %15, %16, %17, %18, %19, %20, %21, %22, %23, %24, %25, %26, %27, %28, %29, %30, %31, %32, %33, %34, %35, %36, %37, %38, %39, %40, %41, %42, %43, %44, %45, %46, %47, %48, %49, %50, %51, %52, %53, %54, %55, %56, %57, %58, %59, %60, %61, %62, %63}, da, db, 1, 1, 1, 0, 1;\n"
    "add.u32 t, %64, 6;\nmov.b64 da, {t, %66};\nadd.u32 t, %65, 1664;\nmov.b64 db, {t, %66};\n"
    "wgmma.mma_async.sync.aligned.m64n128k16.f32.bf16.bf16 {%0, %1, %2, %3, %4, %5, %6, %7, %8, %9, %10, %11, %12, %13, %14, %15, %16, %17, %18, %19, %20, %21, %22, %23, %24, %25, %26, %27, %28, %29, %30, %31, %32, %33, %34, %35, %36, %37, %38, %39, %40, %41, %42, %43, %44, %45, %46, %47, %48, %49, %50, %51, %52, %53, %54, %55, %56, %57, %58, %59, %60, %61, %62, %63}, da, db, 1, 1, 1, 0, 1;\n"
    "wgmma.commit_group.sync.aligned;\n}\n"
    : "+f"(d[0]), "+f"(d[1]), "+f"(d[2]), "+f"(d[3]), "+f"(d[4]), "+f"(d[5]), "+f"(d[6]), "+f"(d[7]), "+f"(d[8]), "+f"(d[9]), "+f"(d[10]), "+f"(d[11]), "+f"(d[12]), "+f"(d[13]), "+f"(d[14]), "+f"(d[15]), "+f"(d[16]), "+f"(d[17]), "+f"(d[18]), "+f"(d[19]), "+f"(d[20]), "+f"(d[21]), "+f"(d[22]), "+f"(d[23]), "+f"(d[24]), "+f"(d[25]), "+f"(d[26]), "+f"(d[27]), "+f"(d[28]), "+f"(d[29]), "+f"(d[30]), "+f"(d[31]), "+f"(d[32]), "+f"(d[33]), "+f"(d[34]), "+f"(d[35]), "+f"(d[36]), "+f"(d[37]), "+f"(d[38]), "+f"(d[39]), "+f"(d[40]), "+f"(d[41]), "+f"(d[42]), "+f"(d[43]), "+f"(d[44]), "+f"(d[45]), "+f"(d[46]), "+f"(d[47]), "+f"(d[48]), "+f"(d[49]), "+f"(d[50]), "+f"(d[51]), "+f"(d[52]), "+f"(d[53]), "+f"(d[54]), "+f"(d[55]), "+f"(d[56]), "+f"(d[57]), "+f"(d[58]), "+f"(d[59]), "+f"(d[60]), "+f"(d[61]), "+f"(d[62]), "+f"(d[63])
    : "r"(a), "r"(b), "n"(0x40000040) : "memory");
}

__device__ __forceinline__ void sum_columns(float (&d)[4], uint32_t a, uint32_t b) {
  asm volatile("{\n.reg .u32 t;\n.reg .u64 da, db;\nmov.b64 db, {%5, 0};\nwgmma.fence.sync.aligned;\n"
               "add.u32 t, %4, 0;\nmov.b64 da, {t, %6};\nwgmma.mma_async.sync.aligned.m64n8k16.f32.bf16.bf16 {%0, %1, %2, %3}, da, db, 1, 1, 1, 1, 0;\n"
               "add.u32 t, %4, 128;\nmov.b64 da, {t, %6};\nwgmma.mma_async.sync.aligned.m64n8k16.f32.bf16.bf16 {%0, %1, %2, %3}, da, db, 1, 1, 1, 1, 0;\n"
               "add.u32 t, %4, 256;\nmov.b64 da, {t, %6};\nwgmma.mma_async.sync.aligned.m64n8k16.f32.bf16.bf16 {%0, %1, %2, %3}, da, db, 1, 1, 1, 1, 0;\n"
               "add.u32 t, %4, 384;\nmov.b64 da, {t, %6};\nwgmma.mma_async.sync.aligned.m64n8k16.f32.bf16.bf16 {%0, %1, %2, %3}, da, db, 1, 1, 1, 1, 0;\n"
               "add.u32 t, %4, 512;\nmov.b64 da, {t, %6};\nwgmma.mma_async.sync.aligned.m64n8k16.f32.bf16.bf16 {%0, %1, %2, %3}, da, db, 1, 1, 1, 1, 0;\n"
               "add.u32 t, %4, 640;\nmov.b64 da, {t, %6};\nwgmma.mma_async.sync.aligned.m64n8k16.f32.bf16.bf16 {%0, %1, %2, %3}, da, db, 1, 1, 1, 1, 0;\n"
               "add.u32 t, %4, 768;\nmov.b64 da, {t, %6};\nwgmma.mma_async.sync.aligned.m64n8k16.f32.bf16.bf16 {%0, %1, %2, %3}, da, db, 1, 1, 1, 1, 0;\n"
               "add.u32 t, %4, 896;\nmov.b64 da, {t, %6};\nwgmma.mma_async.sync.aligned.m64n8k16.f32.bf16.bf16 {%0, %1, %2, %3}, da, db, 1, 1, 1, 1, 0;\n"
               "add.u32 t, %4, 1024;\nmov.b64 da, {t, %6};\nwgmma.mma_async.sync.aligned.m64n8k16.f32.bf16.bf16 {%0, %1, %2, %3}, da, db, 1, 1, 1, 1, 0;\n"
               "add.u32 t, %4, 1152;\nmov.b64 da, {t, %6};\nwgmma.mma_async.sync.aligned.m64n8k16.f32.bf16.bf16 {%0, %1, %2, %3}, da, db, 1, 1, 1, 1, 0;\n"
               "add.u32 t, %4, 1280;\nmov.b64 da, {t, %6};\nwgmma.mma_async.sync.aligned.m64n8k16.f32.bf16.bf16 {%0, %1, %2, %3}, da, db, 1, 1, 1, 1, 0;\n"
               "add.u32 t, %4, 1408;\nmov.b64 da, {t, %6};\nwgmma.mma_async.sync.aligned.m64n8k16.f32.bf16.bf16 {%0, %1, %2, %3}, da, db, 1, 1, 1, 1, 0;\n"
               "add.u32 t, %4, 1536;\nmov.b64 da, {t, %6};\nwgmma.mma_async.sync.aligned.m64n8k16.f32.bf16.bf16 {%0, %1, %2, %3}, da, db, 1, 1, 1, 1, 0;\n"
               "add.u32 t, %4, 1664;\nmov.b64 da, {t, %6};\nwgmma.mma_async.sync.aligned.m64n8k16.f32.bf16.bf16 {%0, %1, %2, %3}, da, db, 1, 1, 1, 1, 0;\n"
               "add.u32 t, %4, 1792;\nmov.b64 da, {t, %6};\nwgmma.mma_async.sync.aligned.m64n8k16.f32.bf16.bf16 {%0, %1, %2, %3}, da, db, 1, 1, 1, 1, 0;\n"
               "add.u32 t, %4, 1920;\nmov.b64 da, {t, %6};\nwgmma.mma_async.sync.aligned.m64n8k16.f32.bf16.bf16 {%0, %1, %2, %3}, da, db, 1, 1, 1, 1, 0;\n"
               "wgmma.commit_group.sync.aligned;\nwgmma.wait_group.sync.aligned 0;\n}"
               : "+f"(d[0]), "+f"(d[1]), "+f"(d[2]), "+f"(d[3]) : "r"(a), "r"(b), "n"(0x40000040) : "memory");
}
struct Job {
  uint32_t type, layer, R, col, nk;
  __device__ __forceinline__ explicit Job(uint32_t j) : type(j & 3), layer((j >> 2) & 1), R((j >> 3) & 7), col((j >> 6) & 63), nk((j >> 12) & 63) {}
  __device__ __forceinline__ uint32_t inst() const { return layer * 2 + (type >> 1); }
};
struct Smem {
  char* scratch;
  uint32_t base;
  __device__ __forceinline__ uint32_t stage(uint32_t s) const { return base + (s & (NSTAGE - 1)) * STAGE; }
  __device__ __forceinline__ uint32_t slot(uint32_t c) const { return base + STG_OFF + c * SLOT; }
  __device__ __forceinline__ uint32_t full(uint32_t s) const { return base + BAR_OFF + (s & (NSTAGE - 1)) * 8; }
  __device__ __forceinline__ uint32_t empty(uint32_t s) const { return base + BAR_OFF + 32 + (s & (NSTAGE - 1)) * 8; }
  __device__ __forceinline__ uint32_t filled(uint32_t u) const { return base + BAR_OFF + 64 + u * 8; }
  __device__ __forceinline__ uint32_t vacant(uint32_t u) const { return base + BAR_OFF + 96 + u * 8; }
  __device__ __forceinline__ uint32_t summed(uint32_t s) const { return base + BAR_OFF + 128 + (s & (NSTAGE - 1)) * 8; }
  __device__ __forceinline__ uint32_t aux_full() const { return base + BAR_OFF + 160; }
  __device__ __forceinline__ uint32_t boot() const { return base + BAR_OFF + 168; }
  __device__ __forceinline__ uint32_t xchg_full() const { return base + BAR_OFF + 176; }
  __device__ __forceinline__ uint32_t wgmma_done() const { return base + BAR_OFF + 184; }
  __device__ __forceinline__ uint32_t mma_done() const { return base + BAR_OFF + 192; }
  __device__ __forceinline__ uint32_t kv_ready(int w) const { return base + BAR_OFF + 208 + w * 8; }
  __device__ __forceinline__ uint32_t pair_id() const { return base + BAR_OFF + 280; }
  __device__ __forceinline__ uint32_t stats() const { return base + AUX_OFF; }
  __device__ __forceinline__ uint32_t sums() const { return base + AUX_OFF + 1088; }
  __device__ __forceinline__ uint32_t xchg() const { return base + AUX_OFF + 1600; }
};
__device__ __forceinline__ uint32_t par(uint32_t s) { return (s / NSTAGE) & 1; }

__device__ __forceinline__ void st_word(u64* p, uint32_t lo, uint32_t hi) {
  asm volatile("st.relaxed.gpu.global.u64 [%0], %1;" ::"l"(p), "l"(((u64)hi << 32) | lo) : "memory");
}
__device__ __forceinline__ uint2 ld_word(const u64* p) {
  u64 v;
  asm volatile("ld.relaxed.gpu.global.u64 %0, [%1];" : "=l"(v) : "l"(p) : "memory");
  return make_uint2((uint32_t)v, (uint32_t)(v >> 32));
}
__device__ __forceinline__ void add_moments(uint4 v, float (&m)[4]) {
  const uint32_t w[4] = {v.x, v.y, v.z, v.w};
#pragma unroll
  for (int c = 0; c < 4; c++) {
    const float lo = bf_lo(w[c]), hi = bf_hi(w[c]);
    m[0] += lo; m[1] += hi; m[2] = fmaf(lo, lo, m[2]); m[3] = fmaf(hi, hi, m[3]);
  }
}
__device__ __forceinline__ void publish_stats(const Smem& sm, float s, float q, uint32_t idx, bool valid, uint32_t e1) {
  const float mean = s * (1.f / D), var = fmaxf(q * (1.f / D) - mean * mean, 0.f);
  const u64 word = ((u64)((__float_as_uint(-bf_round(mean)) & 0xffff0000u) | (e1 & 0xffff)) << 32) | __float_as_uint(rcp(bf_round(sqrt_fast(bf_round(bf_round(var) + 1e-5f)))));
  asm volatile("{\n.reg .pred p;\nsetp.ne.u32 p, %2, 0;\n@p st.relaxed.gpu.global.u64 [%0], %1;\n}" ::"l"(SCR(sm, stats, idx * 8)), "l"(word), "r"((uint32_t)valid) : "memory");
}
__device__ __forceinline__ void stats_task(const Smem& sm, uint32_t jw, int rank, int w, uint32_t e1, const bf16* x) {
  const uint32_t inst = (jw >> 22) & 3, lane = fresh_tid() & 31, steps = (jw >> 31) * 2 + 2;
  uint32_t row = ((jw >> 24) & 127) * 8 + (w - 1) * 4 + (lane >> 3);
  wait_count(counter(C_X + inst * 16 + (row >> 7) * 2 + rank, lane & 7), e1 * (inst & 1 ? 56 : 16));
  const uint4* p = at(reinterpret_cast<const uint4*>(x), (row * 2 + rank) * (D * 2) + (lane & 7) * 16);
  uint4 v[8];
  float m[4] = {0.f, 0.f, 0.f, 0.f};
#pragma unroll
  for (int i = 0; i < 8; i++) v[i] = ldg128(p + i * 8);
#pragma unroll 1
  for (uint32_t it = 1; it <= steps; it++) {
    p = at(p, it & 1 ? 1024 : 8 * D * 4 - 1024);
#pragma unroll
    for (int i = 0; i < 8; i++) {
      add_moments(v[i], m);
      if (it < steps) v[i] = ldg128(p + i * 8);
    }
    if (!(it & 1)) {
      m[0] += m[1]; m[2] += m[3];
#pragma unroll
      for (int o = 1; o <= 4; o <<= 1) { m[0] += __shfl_xor_sync(~0u, m[0], o); m[2] += __shfl_xor_sync(~0u, m[2], o); }
      publish_stats(sm, m[0], m[2], (inst + 1) * S + rank * (S / 2) + row, (lane & 7) == 0, e1);
      m[0] = m[1] = m[2] = m[3] = 0.f;
      row += 8;
    }
  }
}
struct Stager {
  uint2 st[5], cs[4];
  __device__ __forceinline__ void load(const Smem& sm, const Job& J, int rank, int lane, bool sums) {
#pragma unroll
    for (int i = 0; i < 5; i++) st[i] = ld_word(SCR(sm, stats, (J.inst() * S + rank * (S / 2) + J.R * 128 + min(max(lane - 8 + 32 * i, J.R && J.type == T_Q ? -8 : 0), 127)) * 8));
#pragma unroll
    for (int i = 0; i < 4; i++)
      if (sums && (i < 3 || J.type == T_G)) cs[i] = ld_word(SCR(sm, cs, ((J.col + J.type * 8) * 128 + lane) * 8) + i * 32);
  }
  __device__ __forceinline__ void store(const Smem& sm, const Job& J, int rank, int lane, bool sums, uint32_t e1) {
    for (uint32_t n = 0;; n++) {
      uint32_t bad = (st[1].y ^ e1) | (st[2].y ^ e1) | (st[3].y ^ e1);
      bad |= (st[0].y ^ e1) | (st[4].y ^ e1);
      if (sums) bad |= (cs[0].y ^ e1) | (cs[1].y ^ e1) | (cs[2].y ^ e1);
      if (J.type == T_G) bad |= cs[3].y ^ e1;
      if (__all_sync(~0u, (bad & 0xffff) == 0)) break;
      __nanosleep(V_SL2);
      if (n > SPIN_LIMIT) __trap();
      load(sm, J, rank, lane, sums);
    }
#pragma unroll
    for (int i = 0; i < 5; i++) {
      if (i < 4 || lane < 8) sts64(sm.stats() + (lane + 32 * i) * 8, st[i]);
      if (i < 4 && sums && (i < 3 || J.type == T_G)) sts32(sm.sums() + (lane + 32 * i) * 4, cs[i].x);
    }
  }
};
__device__ __forceinline__ void add_cols(float (&a)[8], uint4 x, uint4 y) {
  const uint4 t = add8(x, y);
  a[0] += bf_lo(t.x); a[1] += bf_hi(t.x); a[2] += bf_lo(t.y); a[3] += bf_hi(t.y);
  a[4] += bf_lo(t.z); a[5] += bf_hi(t.z); a[6] += bf_lo(t.w); a[7] += bf_hi(t.w);
}
__device__ __forceinline__ void reduce_cols(float (&a)[8], int lane) {
#pragma unroll
  for (int i = 0; i < 4; i++) { const bool up = lane & 16; const float o = __shfl_xor_sync(~0u, up ? a[i] : a[i + 4], 16); a[i] = (up ? a[i + 4] : a[i]) + o; }
#pragma unroll
  for (int i = 0; i < 2; i++) { const bool up = lane & 8; const float o = __shfl_xor_sync(~0u, up ? a[i] : a[i + 2], 8); a[i] = (up ? a[i + 2] : a[i]) + o; }
}
template <class Fn>
__device__ __forceinline__ uint32_t qkv_col_sums(const Smem& sm, int rank, int w, int lane, Fn between) {
  float a[8] = {0.f, 0.f, 0.f, 0.f, 0.f, 0.f, 0.f, 0.f};
#pragma unroll 1
  for (int s = 0; s < D / 64; s++) {
    between(s);
    const uint32_t p = sm.stage(s) + SLOT + rank * SLOT + w * 4096 + (lane >> 3) * 128 + (((lane & 7) ^ (lane >> 3)) << 4);
    uint4 v[8];
    mbar_wait(sm.full(s), par(s));
#pragma unroll
    for (int j = 0; j < 8; j++) v[j] = lds128((p ^ ((j & 1) * 64)) + j * 512);
    __syncwarp();
    mbar_arrive_cl_if(lane < 2, mapa(sm.summed(s), lane & 1));
    add_cols(a, add8(v[0], v[1]), add8(v[2], v[3]));
    add_cols(a, add8(v[4], v[5]), add8(v[6], v[7]));
  }
  reduce_cols(a, lane);
  const uint32_t slot = sm.xchg() + (w * 32 + lane) * 8;
  asm volatile("st.async.weak.shared::cluster.mbarrier::complete_tx::bytes.v2.b32 [%0], {%1, %2}, [%3];"
               ::"r"(mapa(slot, rank ^ 1)), "r"(__float_as_uint(a[0])), "r"(__float_as_uint(a[1])), "r"(mapa(sm.xchg_full(), rank ^ 1)) : "memory");
  mbar_wait(sm.xchg_full(), 0);
  const uint2 o = lds64(slot);
  return pack_bf16(a[0] + __uint_as_float(o.x), a[1] + __uint_as_float(o.y));
}

constexpr float LOGIT_SCALE = 0.17677669529663687f * 1.4426950408889634f;
constexpr float MASKED = -1e30f;
enum { A_CS = 16, A_NM = 40, A_KT = 42, A_KU = 44, A_CT = 46, A_CU = 48, A_BIAS = 50, A_MASK = 52, A_ZERO = 53 };
__device__ __forceinline__ void attention_prepare(uint32_t (&r)[64], const Smem& sm, int W, int lane, bool first) {
  const int i = lane >> 2, c = (lane & 3) * 2;
  r[A_ZERO] = opaque_zero();
  r[A_MASK] = (c > i ? 0xffffu : 0u) | (c + 1 > i ? 0xffff0000u : 0u);
  const uint32_t a = sm.stats() + W * 128;
  const uint2 r0 = lds64(a + 64 + i * 8), r1 = lds64(a + 128 + i * 8);
#pragma unroll
  for (int y = 0; y < 2; y++) {
    const uint32_t k = a + (c + y + (c + y > i ? 0 : 8)) * 8;
    const float kt = lds32f(k), ku = lds32f(k + 64);
    r[A_KT + y] = __float_as_uint(kt); r[A_CT + y] = __float_as_uint(__uint_as_float(r0.x) * LOGIT_SCALE * kt);
    r[A_KU + y] = __float_as_uint(ku); r[A_CU + y] = __float_as_uint(__uint_as_float(r1.x) * LOGIT_SCALE * ku);
    r[A_BIAS + y] = __float_as_uint(first && W == 0 && c + y > i ? MASKED : 0.f);
  }
#pragma unroll
  for (int j = 0; j < 6; j++) {
    const uint4 v = lds128(sm.sums() + c * 48 + j * 16);
    r[A_CS + 4 * j] = v.x; r[A_CS + 4 * j + 1] = v.y; r[A_CS + 4 * j + 2] = v.z; r[A_CS + 4 * j + 3] = v.w;
  }
  r[A_NM] = dup_hi(r0.y); r[A_NM + 1] = dup_hi(r1.y);
}
__device__ __forceinline__ bool attention(const float (&acc)[96], uint32_t (&r)[64], const Smem& sm, int W, int lane, uint32_t t8, uint32_t t16,
                                          bool halo, uint32_t block, uint32_t tag, uint32_t parity, uint32_t next_bar, uint32_t next_parity, int ji) {
#define TRW W
  const uint32_t own = (W >> 2) * SLOT;
  const uint32_t pk = W == 0 ? (halo ? 4096 : 1024) : W == 4 ? 7168 : own - 1024;
  const uint32_t pv = W == 0 && halo ? 6144 : pk + 8192;
  uint32_t x[48];
  auto pack = [&](int j0, int step, int count) {
#pragma unroll
    for (int j = j0; j < j0 + step * count; j += step) x[j] = bf2_fma(r[A_NM + j % 2], r[A_CS + j / 2], pack_bf16(acc[2 * j], acc[2 * j + 1]));
  };
  auto put8 = [&](uint32_t a, int j) {
    stsm4(t8 + a, x[j], x[j + 2], x[j + 4], x[j + 6]);
    stsm4((t8 ^ 64) + a, x[j + 8], x[j + 10], x[j + 12], x[j + 14]);
  };
  uint32_t k0[2][4], v0[2][4], v12[4][4];
  pack(17, 2, 8);
  put8(own + 1024, 17);
  pack(32, 1, 16);
#pragma unroll
  for (int j = 0; j < 4; j++) stsm4((t16 ^ (j << 5)) + (own + 8192), x[32 + 4 * j], x[33 + 4 * j], x[34 + 4 * j], x[35 + 4 * j]);
  mbar_arrive_warp(sm.kv_ready(W));
  pack(16, 2, 8);
  pack(0, 1, 16);
  if (W == 0) {
    put8(0, 16);
#pragma unroll
    for (int j = 0; j < 4; j++) stsm4(lane & 8 ? sm.xchg() : (t16 ^ (j << 5)) + 2048, x[4 * j], x[4 * j + 1], x[4 * j + 2], x[4 * j + 3]);
  }
  mbar_wait(sm.kv_ready(W - 1), parity);
#pragma unroll
  for (int h = 0; h < 2; h++) ldsm4((t8 ^ (h * 64)) + pk, k0[h]);
#pragma unroll
  for (int j = 0; j < 4; j++) ldsm4t((t16 ^ (j << 5)) + (own + 8192), v12[j]);
#pragma unroll
  for (int h = 0; h < 2; h++) ldsm4t((t8 ^ (h * 64)) + pv, v0[h]);
  if (W < 4) mbar_wait(sm.wgmma_done(), parity);
  const bool next_full = mbar_test(next_bar, next_parity);
  TRC(ji, 20);
  float s0[2][4], s1[2][4], s2[2][4];
#pragma unroll
  for (int h = 0; h < 2; h++) {
#pragma unroll
    for (int y = 0; y < 4; y++) s0[h][y] = s1[h][y] = s2[h][y] = 0.f;
  }
#pragma unroll
  for (int ks = 0; ks < 2; ks++)
#pragma unroll
    for (int h = 0; h < 2; h++) {
      const int n = 8 * h + 4 * ks;
      mma16816(s1[h], x[n], x[n + 1], x[n + 2], x[n + 3], x[16 + n], x[18 + n]);
      mma16816(s2[h], x[n], x[n + 1], x[n + 2], x[n + 3], x[17 + n], x[19 + n]);
      mma16816(s0[h], x[n], x[n + 1], x[n + 2], x[n + 3], k0[h][2 * ks], k0[h][2 * ks + 1]);
    }
  const uint32_t mask = r[A_MASK];
  const bool after[2] = {(mask & 1) != 0, (int)mask < 0};
  float lt[2][2], lu[2][2], mt[2], mu[2];
#pragma unroll
  for (int h = 0; h < 2; h++) {
#pragma unroll
    for (int y = 0; y < 2; y++) {
      lt[h][y] = fmaf(after[y] ? s0[h][y] : s1[h][y], __uint_as_float(r[A_CT + y]), __uint_as_float(r[A_BIAS + y]));
      lu[h][y] = (after[y] ? s1[h][2 + y] : s2[h][2 + y]) * __uint_as_float(r[A_CU + y]);
    }
    mt[h] = fmaxf(lt[h][0], lt[h][1]);
    mu[h] = fmaxf(lu[h][0], lu[h][1]);
  }
#pragma unroll
  for (int d = 1; d <= 2; d++)
#pragma unroll
    for (int h = 0; h < 2; h++) {
      mt[h] = fmaxf(mt[h], __shfl_xor_sync(~0u, mt[h], d));
      mu[h] = fmaxf(mu[h], __shfl_xor_sync(~0u, mu[h], d));
    }
  float o[2][4][4];
#pragma unroll
  for (int h = 0; h < 2; h++) {
#pragma unroll
    for (int y = 0; y < 2; y++) { lt[h][y] = ex2(lt[h][y] - mt[h]); lu[h][y] = ex2(lu[h][y] - mu[h]); }
    const uint32_t pt = pack_bf16(lt[h][0] * __uint_as_float(r[A_KT]), lt[h][1] * __uint_as_float(r[A_KT + 1]));
    const uint32_t pu = pack_bf16(lu[h][0] * __uint_as_float(r[A_KU]), lu[h][1] * __uint_as_float(r[A_KU + 1]));
#pragma unroll
    for (int n = 0; n < 4; n++) {
      o[h][n][0] = o[h][n][1] = o[h][n][2] = o[h][n][3] = 0.f;
      mma16816(o[h][n], pt & ~mask, pu & mask, 0u, pu & ~mask, v12[2 * h + n / 2][n % 2 * 2], v12[2 * h + n / 2][n % 2 * 2 + 1]);
    }
#pragma unroll
    for (int n = 0; n < 4; n++) mma1688(o[h][n], pt & mask, 0u, v0[h][n]);
    mt[h] = lt[h][0] + lt[h][1];
    mu[h] = lu[h][0] + lu[h][1];
  }
#pragma unroll
  for (int d = 1; d <= 2; d++)
#pragma unroll
    for (int h = 0; h < 2; h++) {
      mt[h] += __shfl_xor_sync(~0u, mt[h], d);
      mu[h] += __shfl_xor_sync(~0u, mu[h], d);
    }
  uint32_t dep = 0;
#pragma unroll
  for (int n = 0; n < 3; n++) dep |= __float_as_uint(o[n % 2][n / 2][0]);
  mbar_arrive_warp(sm.mma_done() + (dep & r[A_ZERO]));
  TRC(ji, 22);
  if (W == 7) {
    ulonglong2* exp = SCR(sm, halo, (block * 256 + lane) * 16);
#pragma unroll
    for (int m = 0; m < 8; m++)
      asm volatile("st.relaxed.gpu.global.v2.u64 [%0], {%1,%2};" ::"l"(exp + m * 32), "l"(((u64)tag << 32) | x[17 + 4 * m]), "l"(((u64)tag << 32) | x[19 + 4 * m]) : "memory");
  }
#pragma unroll
  for (int h = 0; h < 2; h++) {
    const float rt = rcp(mt[h]), ru = rcp(mu[h]);
#pragma unroll
    for (int n = 0; n < 4; n++) {
      r[8 * h + 2 * n] = pack_bf16(o[h][n][0] * rt, o[h][n][1] * rt);
      r[8 * h + 2 * n + 1] = pack_bf16(o[h][n][2] * ru, o[h][n][3] * ru);
    }
  }
  return next_full;
}
__device__ __forceinline__ void import_halo(const Smem& sm, const ulonglong2* halo, uint32_t tag, int lane) {
  u64 x[16];
  for (uint32_t n = 0;; n++) {
#pragma unroll
    for (int m = 0; m < 8; m++)
      asm volatile("ld.relaxed.gpu.global.v2.u64 {%0,%1}, [%2];" : "=l"(x[2 * m]), "=l"(x[2 * m + 1]) : "l"(halo + m * 32) : "memory");
    uint32_t bad = 0;
#pragma unroll
    for (int m = 0; m < 16; m++) bad |= (uint32_t)(x[m] >> 32) ^ tag;
    if (__all_sync(~0u, bad == 0)) break;
    __nanosleep(V_SL3);
    if (n > SPIN_LIMIT) __trap();
  }
  const uint32_t a = sm.slot(0) + 4096 + (lane & 7) * 128 + (((lane >> 3) ^ (lane & 7)) << 4);
#pragma unroll
  for (int m = 0; m < 4; m++) stsm4((a ^ ((m & 1) * 64)) + (m >> 1) * 2048, (uint32_t)x[4 * m], (uint32_t)x[4 * m + 1], (uint32_t)x[4 * m + 2], (uint32_t)x[4 * m + 3]);
}
__device__ __forceinline__ void unpack8(uint4 v, float* f) {
  f[0] = bf_lo(v.x); f[1] = bf_hi(v.x); f[2] = bf_lo(v.y); f[3] = bf_hi(v.y);
  f[4] = bf_lo(v.z); f[5] = bf_hi(v.z); f[6] = bf_lo(v.w); f[7] = bf_hi(v.w);
}
__device__ __forceinline__ void boundary_rows(const Smem& sm, int h, int lane, uint32_t out) {
  const int i = lane >> 2, u = h * 4 + (lane & 3);
  uint4 r[8];
  float x[8], l[8], ik[8];
  unpack8(lds128(sm.slot(0) + 2048 + i * 128 + ((u ^ i) << 4)), x);
#pragma unroll
  for (int j = 0; j < 8; j++) {
    r[j] = lds128(sm.slot(0) + j * 128 + (j > i ? 4096 : 0) + ((u ^ j) << 4));
    ik[j] = lds32f(sm.stats() + j * 8 + (j > i ? 0 : 64));
  }
  const float cq = lds32f(sm.stats() + 64 + i * 8) * LOGIT_SCALE;
#pragma unroll
  for (int j = 0; j < 8; j++) {
    float kf[8];
    unpack8(r[j], kf);
    r[j] = lds128(sm.slot(0) + j * 128 + (j > i ? 6144 : 8192) + ((u ^ j) << 4));
    l[j] = 0.f;
#pragma unroll
    for (int d = 0; d < 8; d++) l[j] = fmaf(x[d], kf[d], l[j]);
  }
#pragma unroll
  for (int d = 1; d <= 2; d++)
#pragma unroll
    for (int j = 0; j < 8; j++) l[j] += __shfl_xor_sync(~0u, l[j], d);
  float m = MASKED, sum = 0.f;
#pragma unroll
  for (int j = 0; j < 8; j++) { l[j] *= cq * ik[j]; m = fmaxf(m, l[j]); }
#pragma unroll
  for (int j = 0; j < 8; j++) { l[j] = ex2(l[j] - m); sum += l[j]; }
  const float rs = rcp(sum);
#pragma unroll
  for (int d = 0; d < 8; d++) x[d] = 0.f;
#pragma unroll
  for (int j = 0; j < 8; j++) {
    const float pw = l[j] * ik[j] * rs;
    float vf[8];
    unpack8(r[j], vf);
#pragma unroll
    for (int d = 0; d < 8; d++) x[d] = fmaf(pw, vf[d], x[d]);
  }
  stg128(SCR(sm, o, out + i * (2 * D) + u * 16), make_uint4(pack_bf16(x[0], x[1]), pack_bf16(x[2], x[3]), pack_bf16(x[4], x[5]), pack_bf16(x[6], x[7])));
}
__device__ __forceinline__ uint32_t swiglu2(uint32_t g, uint32_t u, float hinv, float hinv2) {
  const float a = bf_lo(g) * hinv, b = bf_hi(g) * hinv, a2 = bf_lo(g) * hinv2, b2 = bf_hi(g) * hinv2;
  return bf2_mul(pack_bf16(fmaf(a2, tanh_fast(a), a2), fmaf(b2, tanh_fast(b), b2)), u);
}

__device__ __forceinline__ const uint32_t* dep_counter(const Smem& sm, uint32_t jw, int rank, uint32_t k) {
  const Job J(jw);
  const uint32_t b = J.R * 2 + rank;
  const uint32_t line = J.type == T_O ? C_O + J.layer * 16 + b : J.type == T_D ? C_H + J.layer * 16 + b : C_X + max((int)J.inst() - 1, 0) * 16 + b;
  return counter(line, J.type & 1 ? k >> (J.type >> 1) : (k >> 2) * 2 + (k & 1));
}
__device__ __forceinline__ void producer(const Params& P, const Smem& sm, const uint32_t* jobs, const uint8_t* kseq, int rank, int lane, uint32_t launches) {
  const uint32_t e1 = __shfl_sync(~0u, launches, 0) + 1;
  uint32_t s = (jobs[0] & JOB_C) ? 0 : NSTAGE;
  uint32_t end = 0, poll = 0;
  uint64_t keep, stream;
  asm("createpolicy.fractional.L2::evict_unchanged.b64 %0, 1.0;" : "=l"(keep));
  asm("createpolicy.fractional.L2::evict_first.b64 %0, 1.0;" : "=l"(stream));
  const uint32_t* dep = counter(0, 0);
  const uint32_t summed_end = (jobs[0] & JOB_C) ? 0 : D / 64 + NSTAGE;
  for (int ji = 0;; ji++) {
    const uint32_t jw = jobs[ji];
    const Job J(jw);
    if (J.nk == 0) break;
    const bool isC = jw & JOB_C, isX = isC && (jw & JOB_X);
    const uint32_t target = (jw & 7) == 0 ? 0 : e1 * (J.type == T_Q ? 56 : J.type == T_G ? 16 : 1);
    const uint32_t g = J.col * 2 + rank;
    const CUtensorMap* tmA = &P.a[isC ? 4 + isX : (jw & 7) == 4 ? 2 : J.type];
    const CUtensorMap* tmB = &P.w[J.type];
    const uint32_t bytes = isC ? 32768 : J.type == T_Q ? 40960 : STAGE, bcol = J.col << (J.type == T_Q ? 0 : J.type == T_G ? 1 : 2);
    const uint32_t a0 = isX ? 0 : (g >> 2) * 128 + (g & 1) * 64, a1 = isX ? g * 64 : J.R * 128, ak = isX ? 0 : 256, a2 = isC ? (g >> 1) & 1 : rank;
    end += J.nk;
    uint32_t sa = s, spins = 0;
    auto issue_a = [&](uint32_t k) { TRS(sa, 1); tma3d(sm.stage(sa), tmA, isC ? a0 : (k & 63) * 64, isC ? a1 + k * ak : a1, isX ? k * 4 : a2, sm.full(sa), (k & K_LAST_A) ? stream : keep); };
    auto issue_b = [&](uint32_t k) {
      mbar_expect_tx(sm.full(s), bytes);
      TRS(s, 0);
      if (!isC) tma4d_mc(sm.stage(s) + SLOT + rank * SLOT, tmB, (k & 63) * 64 + rank * 32, bcol, sm.full(s), (k & K_LAST_B) ? stream : keep);
    };
    TRI(lane == 0, ji, 6);
    TRK(lane == 0, ji, 24);
    while (true) {
      const uint32_t missing = __ballot_sync(~0u, (int)(poll - target) < 0 && lane < J.nk);
      uint32_t lim = end;
      if (missing) lim += __ffs(missing) - 1 - J.nk;
      if (lim > sa) {
        fence_acquire();
        fence_proxy_async();
        TRI(sa == end - J.nk && lane == 0, ji, 7);
#pragma unroll 1
        for (; sa < min(lim, s); sa++) {
          const uint32_t k = kseq[sa];
          if (elect()) issue_a(k);
        }
#pragma unroll 1
        for (int phase = 0;; phase++) {
          const uint32_t upto = phase == 2 ? lim : phase == 1 ? lim - LOOK : min((int)lim - LOOK, (int)sa + MID);
#pragma unroll 1
          for (; (int)sa < (int)upto; sa++, s++) {
            const uint32_t k = kseq[s];
            uint32_t stage = sm.stage(s), bar = sm.full(s), c0 = isC ? a0 : (k & 63) * 64, c1 = isC ? a1 + k * ak : a1, kb = (k & 63) * 64 + rank * 32, c2 = isX ? k * 4 : a2;
            uint64_t pa = (k & K_LAST_A) ? stream : keep, pb = (k & K_LAST_B) ? stream : keep;
            asm volatile("" : "+r"(stage), "+r"(bar), "+r"(c0), "+r"(c1), "+r"(kb), "+r"(c2), "+l"(pa), "+l"(pb));
            if (s < summed_end) mbar_wait(sm.summed(s), par(s) ^ 1);
            mbar_wait(bar + 32, par(s) ^ 1);
            TRS(s, 0);
            asm volatile("{\n.reg .pred p, q;\nelect.sync _|p, -1;\nsetp.eq.and.u32 q, %14, 0, p;\n"
                         "@q cp.async.bulk.tensor.4d.shared::cluster.global.mbarrier::complete_tx::bytes.multicast::cluster.L2::cache_hint [%3], [%4, {%5, %6, %7, %5}], [%0], %8, %9;\n"
                         "@p cp.async.bulk.tensor.3d.shared::cluster.global.mbarrier::complete_tx::bytes.L2::cache_hint [%2], [%10, {%11, %12, %13}], [%0], %15;\n"
                         "@p mbarrier.arrive.expect_tx.shared::cta.b64 _, [%0], %1;\n}"
                         ::"r"(bar), "r"(bytes), "r"(stage), "r"(stage + SLOT + rank * SLOT), "l"(tmB), "r"(0), "r"(kb), "r"(bcol), "h"((uint16_t)3), "l"(pb),
                           "l"(tmA), "r"(c0), "r"(c1), "r"(c2), "r"((uint32_t)isC), "l"(pa) : "memory");
            TRS(s, 1);
          }
          if (phase == 2) break;
          if (phase == 1) poll = ld_relaxed(dep);
          else if (lim == end) dep = dep_counter(sm, jobs[ji + 1], rank, (reinterpret_cast<const uint32_t*>(kseq)[(end + lane) >> 2] >> ((end + lane) % 4 * 8)) & 63);
        }
        if (lim == end) break;
      } else {
        if (s < min(end, sa + NSTAGE) && __all_sync(~0u, mbar_test(sm.empty(s), par(s) ^ 1))) {
          const uint32_t k = kseq[s];
          if (s < summed_end) mbar_wait(sm.summed(s), par(s) ^ 1);
          if (elect()) issue_b(k);
          s++;
        }
        poll = ld_relaxed(dep);
        if (++spins > SPIN_LIMIT) __trap();
      }
    }
    TRI(lane == 0, ji, 8);
  }
}

__global__ void __cluster_dims__(2, 1, 1) __launch_bounds__(384, 1) mega_kernel(char* scratch, uint32_t by_place, const __grid_constant__ Params P) {
#undef TRW
#define TRW warp
  extern __shared__ __align__(1024) uint8_t smem_raw[];
  TRX(threadIdx.x == 320, JMAX - 1, 0, 1, "%%globaltimer_lo");
  TRX(threadIdx.x == 320, JMAX - 1, 0, 25, "%%clock");
  TRX(threadIdx.x == 320, JMAX - 1, 0, 28, "%%smid");
  Smem sm;
  sm.scratch = scratch;
  sm.base = smem_u32(smem_raw);
  if ((sm.base & 0x3FFFF) != SMEM_BASE) __trap();
  const int warp = __shfl_sync(~0u, threadIdx.x >> 5, 0);
  const int rank = blockIdx.x & 1;
  uint32_t smid;
  asm("mov.u32 %0, %%smid;" : "=r"(smid));
  const uint32_t pair = !by_place ? blockIdx.x >> 1 : smid < 2 * NPAIR - 8 ? (smid >> 1) + 4 : (smid >> 1) + 4 - NPAIR;
  const uint32_t* jobs = P.jobs[pair];
  const uint32_t launches = ld_relaxed(counter(C_EP, blockIdx.x + threadIdx.y));
  if (warp == 10) {
    if (elect()) {
      for (int i = 0; i < NSTAGE; i++) mbar_init(sm.full(i), 1);
      mbar_init(sm.boot(), 1);
      asm volatile("fence.mbarrier_init.release.cluster;" ::: "memory");
    }
    cluster_arrive();
    const uint32_t first = jobs[0];
    const bool isC = first & JOB_C;
    if (elect()) {
      prefetch_tm(&P.a[0]);
      prefetch_tm(&P.w[0]);
    }
    uint64_t keep;
    asm("createpolicy.fractional.L2::evict_unchanged.b64 %0, 1.0;" : "=l"(keep));
    const Job J(first);
    if (!isC) {
      if (elect()) {
        mbar_expect_tx(sm.full(0), 40960);
        tma3d(sm.stage(0), &P.a[0], 0, J.R * 128, rank, sm.full(0), keep);
        TRS(0, 1);
      }
      TRX(threadIdx.x == 320, JMAX - 1, 0, 26, "%%clock");
      cluster_wait();
      TRX(threadIdx.x == 320, JMAX - 1, 0, 27, "%%clock");
      if (elect()) {
        tma4d_mc(sm.stage(0) + SLOT + rank * SLOT, &P.w[0], rank * 32, J.col, sm.full(0), keep);
        TRS(0, 0);
      }
#pragma unroll 1
      for (int k = 1; k < NSTAGE; k++) {
        if (elect()) {
          tma4d_mc(sm.stage(k) + SLOT + rank * SLOT, &P.w[0], k * 64 + rank * 32, J.col, sm.full(k), keep);
          TRS(k, 0);
          mbar_expect_tx(sm.full(k), 40960);
          tma3d(sm.stage(k), &P.a[0], k * 64, J.R * 128, rank, sm.full(k), keep);
          TRS(k, 1);
        }
      }
    } else {
      cluster_wait();
      if (!(first & JOB_X)) mbar_wait(sm.boot(), 0);
    }
  } else {
    if (warp < 8 && elect()) {
      mbar_init(sm.kv_ready(warp), 1);
      if (warp == 3) {
        mbar_init(sm.aux_full(), 3); mbar_init(sm.wgmma_done(), 4); mbar_init(sm.mma_done(), 8); mbar_init(sm.xchg_full(), 1); mbar_init(sm.kv_ready(-1), 1);
        mbar_expect_tx(sm.xchg_full(), 768);
      } else if (warp > 3) {
        mbar_init(sm.empty(warp), 4); mbar_init(sm.summed(warp), 6); mbar_init(sm.filled(warp - 4), 4); mbar_init(sm.vacant(warp - 4), 3);
      }
      asm volatile("fence.mbarrier_init.release.cluster;" ::: "memory");
    }
    cluster_arrive();
  }
  TRI(threadIdx.x == 0, JMAX - 1, 0);

  if (warp < 8) {
    asm volatile("setmaxnreg.inc.sync.aligned.u32 208;");
    const uint32_t e1 = launches + 1;
    cluster_wait();
    const uint32_t wg = warp >> 2;
    uint32_t rel = (threadIdx.x & 95) == 0 ? mapa(sm.empty(0), (threadIdx.x & 32) ? rank ^ 1 : rank) : 0;
    uint32_t dst = sm.slot(0) + (warp & 3) * 2048 + (threadIdx.x & 15) * 128 + ((((threadIdx.x >> 4) & 1) ^ (threadIdx.x & 7)) << 4);
    uint32_t t8 = sm.slot(0) + (warp & 3) * 2048 + (threadIdx.x & 7) * 128 + ((((threadIdx.x >> 3) & 3) ^ (threadIdx.x & 7)) << 4);
    rel = __shfl_sync(~0u, rel, threadIdx.x);
    dst = __shfl_sync(~0u, dst, threadIdx.x);
    t8 = __shfl_sync(~0u, t8, threadIdx.x);
    const uint32_t da0 = ((SMEM_BASE >> 4) | (1 << 16)) + wg * 512, dba = (255 << 16) + 1024 - wg * 512;
    uint32_t pend[64], todo = 0, pbar = 0, vbar = sm.vacant(0), ppar = 0, poff = 0, direct = 0;
    uint32_t s = 0, na = 0, nb = 0, ready = 0;
    auto release = [&](uint32_t st) { mbar_arrive_cl_if(rel, rel + (st & (NSTAGE - 1)) * 8); };
    auto flush = [&](bool vacant) {
      if (__all_sync(~0u, vacant)) {
        const uint32_t a = dst + poff;
        if (todo & 2) {
#pragma unroll
          for (int j = 0; j < 4; j++) stsm4(a ^ (j << 5), pend[4 * j], pend[4 * j + 1], pend[4 * j + 2], pend[4 * j + 3]);
          if (todo == 2) {
#pragma unroll
            for (int j = 0; j < 4; j++) stsm4((a ^ (j << 5)) + 8192, pend[16 + 4 * j], pend[17 + 4 * j], pend[18 + 4 * j], pend[19 + 4 * j]);
          }
        } else {
#pragma unroll
          for (int j = 0; j < 8; j++) stsm4((a ^ ((j & 3) << 5)) + (j >> 2) * 8192, pend[32 + 4 * j], pend[33 + 4 * j], pend[34 + 4 * j], pend[35 + 4 * j]);
        }
        mbar_arrive_warp(pbar);
        pbar += 16; vbar += 16; ppar = ~nb & 1;
        todo = todo == 2;
      }
    };
    uint32_t jw = jobs[0];
#pragma unroll
    for (int i = 0; i < 64; i++) pend[i] = 0;
    for (int ji = 0;; ji++) {
      const uint32_t cur = jw, nk = (jw >> 12) & 63, isQ = (jw & 3) == T_Q;
      jw = jobs[ji + 1];
      if (__builtin_expect((cur & JOB_C) || !ready, 0)) {
        for (uint32_t spins = 0; todo && ((cur & JOB_C) || !ready);) {
          if (direct && todo == 1) {
            vbar = sm.empty(s); ppar = par(s) ^ 1; poff = sm.stage(s) - sm.slot(0) + wg * SLOT;
          }
          flush(mbar_test(vbar, ppar));
          ready = __all_sync(~0u, mbar_test(sm.full(s), par(s)));
          if (++spins > SPIN_LIMIT) __trap();
        }
        if (cur & JOB_C) {
          if (nk == 0) break;
          TRC(ji, 16);
          constexpr uint32_t ONES = 0x3f803f80;
          const uint32_t lane = fresh_tid() & 31, g = ((cur >> 6) & 63) * 2 + rank;
          if (!(cur & JOB_X)) {
            float d[4] = {0.f, 0.f, 0.f, 0.f};
            sts32(sm.xchg() + 128 + lane * 4, ONES);
            fence_proxy_async_smem();
            bar_sync<9, 256>();
#pragma unroll 1
            for (int i = 0; i < 4; i++, s++) {
              mbar_wait(sm.full(s), par(s));
              if (!wg) sum_columns(d, da0 + (s & (NSTAGE - 1)) * (STAGE / 16), (SMEM_BASE + AUX_OFF + 1600 + 128) >> 4);
              release(s);
            }
            const float c = lane & 1 ? d[2] : d[0], c1 = __shfl_down_sync(~0u, c, 4);
            asm volatile("{\n.reg .pred p;\nsetp.eq.u32 p, %2, 0;\n@p st.relaxed.gpu.global.u64 [%0], %1;\n}"
                         ::"l"(SCR(sm, cs, (16 * 128 + g * 32 + (warp & 3) * 8 + (lane & 1) * 4 + (lane >> 3)) * 8)), "l"(((u64)e1 << 32) | pack_bf16(c, c1)), "r"((lane & 6) | wg) : "memory");
          } else {
            float a[6][4];
#pragma unroll
            for (int n = 0; n < 24; n++) pend[n] = 0;
#pragma unroll 1
            for (int i = 0;; i++) {
              const uint32_t p = dst - sm.slot(0) + sm.stage(s) + wg * SLOT;
              mbar_wait(sm.full(s), par(s));
              uint32_t v[8][4];
#pragma unroll
              for (int n = 0; n < 24; n++) a[n / 4][n % 4] = __uint_as_float(pend[n]);
#pragma unroll
              for (int j = 0; j < 8; j++) ldsm4((p ^ ((j & 3) << 5)) + (j >> 2) * 8192, v[j]);
#pragma unroll
              for (int j = 0; j < 8; j++) {
                mma16816(a[4 + (j & 1)], v[j][0], v[j][1], v[j][2], v[j][3], ONES, ONES);
#pragma unroll
                for (int n = 0; n < 4; n++) mma1688(a[n], v[j][n & 2], v[j][(n & 2) + 1], v[j][n]);
              }
#pragma unroll
              for (int n = 0; n < 24; n++) pend[n] = __float_as_uint(a[n / 4][n % 4]);
              if (i == 3) break;
              bar_sync<9, 256>();
              release(s++);
            }
            const uint32_t part = sm.stage(s) + 2 * SLOT + lane * 8, row = g * 64 + (warp & 3) * 16 + wg * 8 + (lane >> 2);
            const bool odd = lane & 4;
            const float s0 = a[4][0] + a[5][0], q0 = odd ? a[0][1] + a[2][1] : a[0][0] + a[2][0];
            const float s1 = a[4][2] + a[5][2], q1 = odd ? a[1][3] + a[3][3] : a[1][2] + a[3][2];
            sts64(part + warp * 256, make_uint2(__float_as_uint(wg ? s0 : s1), __float_as_uint(wg ? q0 : q1)));
            bar_sync<9, 256>();
            const uint2 o = lds64(part + (warp ^ 4) * 256);
            fence_proxy_async_smem();
            bar_sync<9, 256>();
            release(s++);
            publish_stats(sm, (wg ? s1 : s0) + __uint_as_float(o.x), (wg ? q1 : q0) + __uint_as_float(o.y), (row & 1) * (S / 2) + (row >> 1), (lane & 3) == lane >> 3, e1);
          }
          ready = 0;
          TRC(ji, 18);
          continue;
        }
        if (!ready) mbar_wait(sm.full(s), par(s));
      }
      auto mainloop = [&](auto& acc, uint32_t nk, uint32_t last_lead, auto near_end) {
        const uint32_t lead = (jw >> 12) % 64 == 0 ? min(last_lead, nk - 2) : 2, turn = wg ? lead : nk - 2, hurry = nk - lead - wg;
        uint32_t owed = 0;
        uint32_t da = da0 + (s & (NSTAGE - 1)) * (STAGE / 16);
        if (todo == 3) mbar_wait(vbar, ppar);
        if (wg) bar_sync<13, 256>();
        TRC(ji, 16);
        first_kstep(acc, da, da + dba);
        if (!wg) bar_arrive<13, 256>();
        constexpr uint32_t CLEAR = sizeof(acc) == 96 * 4 ? PREP + 2 : 3;
        for (uint32_t left = nk - 1;; left--) {
          for (uint32_t spins = 0;; spins++) {
            const bool vacant = mbar_test(vbar, ppar), next_full = mbar_test(sm.full(s + 1), par(s + 1));
            wg_wait<2>();
            mbar_arrive_cl_if(owed, owed + ((s - 1) & (NSTAGE - 1)) * 8);
            owed = 0;
            ready = __all_sync(~0u, next_full);
            if (!todo) {
              near_end(left, vacant);
              break;
            }
            const bool go = ready && left >= max(CLEAR, lead + 1);
            if (!(go && spins)) flush(vacant);
            if (go) break;
            if (spins > SPIN_LIMIT) __trap();
          }
          if (left == 0) break;
          if (!ready) mbar_wait(sm.full(s + 1), par(s + 1));
          owed = rel;
          if (left == turn) {
            wg_wait<0>();
            release(s);
            owed = 0;
            if (wg) bar_sync<1, 256>();
          }
          if (left - lead < hurry) wg_wait<1>();
          s++;
          da = da0 + (s & (NSTAGE - 1)) * (STAGE / 16);
          kstep(acc, da, da + dba);
          if (left == 1 + wg * 64) bar_arrive<1, 256>();
        }
      };
      if (isQ) {
        float acc[96];
        const uint32_t lane = (((dst - SMEM_BASE) >> 7) & 15) | ((dst ^ (dst >> 3)) & 16), qpar = (na ^ nb) & 1;
        uint32_t prepare_at = PREP;
        mainloop(acc, nk, LAST_LEAD, [&](uint32_t left, bool aux_full) {
          if (left == PREP + 1) {
            vbar = sm.aux_full(); ppar = qpar;
          } else if (left == prepare_at) {
            if (left == 0) mbar_wait(vbar, ppar);
            if (left == 0 || __all_sync(~0u, aux_full)) attention_prepare(pend, sm, warp, lane, !(cur & 0x38));
            else prepare_at--;
          }
        });
        wg_wait<0>();
        release(s);
        u64 token = 0;
        asm volatile("{\n.reg .pred p;\nsetp.eq.u32 p, %2, 0;\n@p mbarrier.arrive.shared::cta.b64 %0, [%1];\n}" : "+l"(token) : "r"(sm.wgmma_done()), "r"(lane + 1 - wg) : "memory");
        pend[A_NM + 1] |= (uint32_t)token & pend[A_ZERO];
        TRC(ji, 18);
        ready = __all_sync(~0u, attention(acc, pend, sm, warp, lane, t8, dst, cur & JOB_EARLY, (((cur >> 2) & 1) * 16 + ((cur >> 3) & 7) * 2 + rank) * 16 + ((cur >> 6) & 15), e1, qpar,
                                          sm.full(s + 1), par(s + 1), ji));
        todo = 3; pbar = sm.filled(wg); vbar = sm.mma_done(); ppar = qpar; poff = SLOT + wg * 8192;
      } else {
        float acc[128];
        direct = (cur & 1) && (jw >> 12) % 64 == 0;
        const bool split = direct && nk >= SPLIT_MIN;
        mainloop(acc, split ? nk - 3 : nk, split ? 0 : LAST_LEAD, [](uint32_t, bool) {});
        pbar = sm.filled(wg); vbar = pbar + 32; ppar = na & 1; poff = wg * SLOT;
        nb++;
        todo = 2;
        if (__builtin_expect(split, 0)) {
          const uint32_t s0 = s;
          uint32_t d[3];
#pragma unroll
          for (int i = 0; i < 3; i++) d[i] = da0 + ((s0 + 1 + i) & (NSTAGE - 1)) * (STAGE / 16);
          wg_wait<0>();
          release(s0);
          float lo[64], hi[64];
#pragma unroll
          for (int i = 0; i < 64; i++) {
            asm volatile("mov.b32 %0, %1;" : "=f"(lo[i]) : "f"(acc[i]));
            asm volatile("mov.b32 %0, %1;" : "=f"(hi[i]) : "f"(acc[64 + i]));
          }
          if (wg) {
            bar_sync<1, 256>();
            bar_sync<3, 256>();
          }
          mbar_wait(sm.full(s0 + 1), par(s0 + 1));
          half_kstep0(lo, d[0], d[0] + dba);
          mbar_wait(sm.full(s0 + 2), par(s0 + 2));
          half_kstep0(lo, d[1], d[1] + dba);
          half_kstep1(hi, d[0], d[0] + dba);
          mbar_wait(sm.full(s0 + 3), par(s0 + 3));
          half_kstep0(lo, d[2], d[2] + dba);
          half_kstep1(hi, d[1], d[1] + dba);
          half_kstep1(hi, d[2], d[2] + dba);
          if (!wg) bar_arrive<3, 256>();
          s += 3;
          wg_wait<2>();
#pragma unroll
          for (int i = 0; i < 32; i++) pend[i] = pack_bf16(lo[2 * i], lo[2 * i + 1]);
          mbar_wait(vbar, ppar);
          flush(true);
          wg_wait<0>();
          TRC(ji, 18);
#pragma unroll
          for (int i = 0; i < 32; i++) pend[32 + i] = pack_bf16(hi[2 * i], hi[2 * i + 1]);
        } else {
          wg_wait<0>();
          release(s);
          const bool next_full = mbar_test(sm.full(s + 1), par(s + 1));
          TRC(ji, 18);
#pragma unroll
          for (int i = 0; i < 64; i++) {
            const int j = (i & 15) + (i & 16) * 2 + (i >> 5) * 16;
            pend[i] = pack_bf16(acc[2 * j], acc[2 * j + 1]);
          }
          ready = __all_sync(~0u, next_full);
        }
      }
      na++;
      s++;
    }
  } else {
    asm volatile("setmaxnreg.dec.sync.aligned.u32 88;");
    if (warp == 10) {
      producer(P, sm, jobs, P.kseq[pair], rank, threadIdx.x & 31, launches);
    } else {
      const uint32_t e1 = __shfl_sync(~0u, launches, 0) + 1;
      const int w = min(warp - 8, 2);
      cluster_wait();
      if (w == 1) asm volatile("st.shared::cluster.u32 [%0], %1;" ::"r"(mapa(sm.pair_id(), rank ^ 1)), "r"(pair) : "memory");
      auto copy_rows = [&](uint32_t step) {
        constexpr int IN = 2 * SLOT / BOOT_PIECES, OUT = 2 * SLOT / BOOT_OUT;
        if (step == BOOT_STEP) mbar_wait(sm.boot(), 0);
        if (elect()) {
          if (step == 0) mbar_expect_tx(sm.boot(), blockIdx.x < S / 16 ? 2 * SLOT : 0);
          if (step < BOOT_PIECES && blockIdx.x < S / 16)
            asm volatile("cp.async.bulk.shared::cluster.global.mbarrier::complete_tx::bytes [%0], [%1], %2, [%3];"
                         ::"r"(sm.slot(0) + step * IN), "l"(at(P.x0, blockIdx.x * 32768 + step * IN)), "n"(IN), "r"(sm.boot()) : "memory");
          if (step - BOOT_STEP < BOOT_OUT && blockIdx.x < S / 16) {
            asm volatile("cp.async.bulk.global.shared::cta.bulk_group [%0], [%1], %2;"
                         ::"l"(at(P.out, blockIdx.x * 32768 + (step - BOOT_STEP) * OUT)), "r"(sm.slot(0) + (step - BOOT_STEP) * OUT), "n"(OUT) : "memory");
            bulk_commit();
          }
        }
        if (step == BOOT_STEP + BOOT_OUT) {
          bulk_wait();
          if (elect()) {
            mbar_arrive_n(sm.vacant(0), 3);
            mbar_arrive_n(sm.vacant(1), 3);
          }
        }
      };
      if (jobs[0] & JOB_C) {
        if (w == 2) {
          if (jobs[0] & JOB_X) mbar_wait(sm.full(3), 0);
#pragma unroll 1
          for (int i = 0; i <= BOOT_STEP + BOOT_OUT; i++) {
            copy_rows(i);
            bulk_wait_read<0>();
          }
        }
      } else {
        const int lane = threadIdx.x & 31, word = (lane >> 3) * 24 + w * 8 + (lane & 7);
        Stager st;
        const uint32_t cs = qkv_col_sums(sm, rank, w, lane, [&](int s) {
          if (w == 2) copy_rows(s - 1);
          if (w == 0 && s == ST_STEP) st.load(sm, Job(jobs[0]), rank, lane, false);
          if (w == 0 && s == ST_STEP + 2) st.store(sm, Job(jobs[0]), rank, lane, false, e1);
        });
        sts32(sm.sums() + word * 4, cs);
        mbar_arrive_warp(sm.aux_full());
        if ((jobs[0] & 0x38) == 0 && rank == 0) st_word(SCR(sm, cs, (((jobs[0] >> 6) & 15) * 128 + word) * 8), cs, e1);
      }
      bar_sync<2, 96>();
      if (w == 2 && blockIdx.x < S / 16 && elect()) {
        red_release(counter(C_RD + (blockIdx.x >> 4) * 2, 0), 1);
        red_relaxed(counter(C_RD + (blockIdx.x >> 4) * 2 + 1, 0), 1);
      }
      uint32_t na = 0, nb = 0, stages = 0;
      for (int ji = 0;; ji++) {
        const uint32_t jw = jobs[ji];
        const Job J(jw);
        if (J.nk == 0) break;
        stages += J.nk;
        if (w != 0 && ((jw >> 22) & 3) != 3) {
          stats_task(sm, jw, rank, w, e1, P.out);
          TRI(threadIdx.x == 11 * 32, ji, 10);
        }
        if (jw & JOB_C) continue;
        const int lane = fresh_tid() & 31;
        const uint32_t b = J.R * 2 + rank;
        if (w == 0 && !(J.type & 1) && ji != 0) {
          Stager st;
          st.load(sm, J, rank, lane, true);
          st.store(sm, J, rank, lane, true, e1);
          TRI(lane == 0, ji, 9);
        }
        if (J.type == T_G) {
          bar_sync<2, 96>();
          constexpr int PER = 16 / NG;
          const uint32_t swap = P.swap, never = jw, ac = sm.sums() + (lane & 7) * 16;
          uint32_t ag[NG], au[NG], as = sm.stats() + 64 + w * NG * 32 + (lane >> 3) * 8;
          uint32_t ho = (rank * (S / 2) + J.R * 128 + w * NG * 4 + (lane >> 3)) * (F * 2) + J.col * 256 + (lane & 7) * 16;
          uint4 cg = lds128(ac + (swap >> 5)), cu = lds128(ac + 256 - (swap >> 5)), g4[NG], u4[NG];
          uint2 st[NG];
          auto load = [&] {
#pragma unroll
            for (int i = 0; i < NG; i++) { st[i] = lds64v(as + i * 32); g4[i] = lds128v(ag[i]); u4[i] = lds128v(au[i]); }
          };
#pragma unroll
          for (int i = 0; i < NG; i++) {
            const uint32_t a = (sm.slot(0) + (w * NG + i) * 512 + (lane >> 3) * 128 + (((lane & 7) ^ (lane >> 3)) << 4)) ^ (((w * NG + i) & 1) << 6);
            ag[i] = a + swap; au[i] = a + (swap ^ 8192);
          }
          mbar_wait(sm.filled(0), na & 1);
          mbar_wait(sm.filled(1), na & 1);
          load();
          if (w == 2 && elect()) red_relaxed(counter(C_RD + J.inst() * 16 + b, 0), 1);
          TRI(threadIdx.x == 11 * 32, ji, 3);
#pragma unroll 1
          for (uint32_t g = w; g < 4 * PER; g += 3) {
            float hinv[NG], hinv2[NG];
            uint4 gc[NG], uc[NG];
            const bool turn = ((g + 3) ^ g) & PER, half = ((g + 3) ^ g) & (2 * PER);
#pragma unroll
            for (int i = 0; i < NG; i++) {
              hinv[i] = 0.5f * __uint_as_float(st[i].x);
              hinv2[i] = hinv[i] * __uint_as_float(st[i].x);
              asm volatile("" : "+f"(hinv[i]), "+f"(hinv2[i]));
              gc[i] = fma8(dup_hi(st[i].y), cg, g4[i]);
              uc[i] = fma8(dup_hi(st[i].y), cu, u4[i]);
              ag[i] = (ag[i] + NG * 1536) ^ ((NG & 1) << 6);
              au[i] = (au[i] + NG * 1536) ^ ((NG & 1) << 6);
            }
            as += NG * 96;
            if (turn) {
              mbar_arrive_warp(sm.vacant((g / PER) ^ 2));
              if (half) {
                cg = lds128(ac + (swap >> 5) + 128); cu = lds128(ac + 384 - (swap >> 5));
                as -= 1024;
              }
#pragma unroll
              for (int i = 0; i < NG; i++) { ag[i] += half ? -3 * 8192 : 8192; au[i] += half ? -3 * 8192 : 8192; }
              TRX(threadIdx.x == 11 * 32 && g < 3 * PER, ji, 25, 25 + g / PER * 2, "%%clock");
              if (g < 3 * PER) mbar_wait(sm.filled(g / PER + 1), (g < PER ? na : nb) & 1);
              TRX(threadIdx.x == 11 * 32 && g < 3 * PER, ji, 25, 26 + g / PER * 2, "%%clock");
            }
            load();
            if (g == never) mbar_wait(sm.boot(), 0);
            bf16* out = SCR(sm, h, ho);
#pragma unroll
            for (int i = 0; i < NG; i++)
              stg128(out + i * 4 * F, make_uint4(swiglu2(gc[i].x, uc[i].x, hinv[i], hinv2[i]), swiglu2(gc[i].y, uc[i].y, hinv[i], hinv2[i]),
                                                 swiglu2(gc[i].z, uc[i].z, hinv[i], hinv2[i]), swiglu2(gc[i].w, uc[i].w, hinv[i], hinv2[i])));
            ho += NG * 12 * F * 2 - (half ? 128 * F * 2 - 128 : 0);
          }
          bar_sync<2, 96>();
          TRI(threadIdx.x == 11 * 32, ji, 4);
          if (w == 2 && elect()) red_release(counter(C_H + J.layer * 16 + b, J.col), 1);
          TRI(threadIdx.x == 11 * 32, ji, 5);
        } else if (J.type == T_Q) {
          const bool late = J.R > 0 && !(jw & JOB_EARLY);
          if (w == 0) {
            __syncwarp();
            if (ji != 0 && elect()) mbar_arrive_n(sm.aux_full(), 3);
#pragma unroll 1
            for (int phase = 0; phase < 2; phase++) {
              if (J.R > 0 && phase == late) import_halo(sm, SCR(sm, halo, (((J.layer * 16 + b - 2) * 16 + J.col) * 256 + lane) * 16), e1, lane);
              if (phase == 0) {
                mbar_arrive_warp(sm.kv_ready(-1));
                TRI(lane == 0, ji, 11);
#pragma unroll 1
                for (int h = 0; h < 2; h++) {
                  mbar_wait(sm.filled(h), na & 1);
                  TRI(lane == 0, ji, 3);
                  fence_proxy_async_smem();
                  bulk_wait_read<0>();
                  if (elect()) {
                    tma3d_store(&P.ow, J.col * 64, J.R * 128 + h * 64, rank, sm.slot(1) + h * 8192);
                    bulk_commit();
                  }
                }
                if (J.layer && elect()) red_relaxed(counter(C_RD + 32 + b, 0), 1);
              }
            }
            bulk_wait();
          }
          if (late && w < 2) {
            bar_sync<7, 64>();
            boundary_rows(sm, w, lane, rank * O_PLANE + J.R * 128 * (D * 2) + J.col * 128);
            bar_sync<7, 64>();
          }
          TRI(threadIdx.x == 256, ji, 4);
          if (w == 0 && elect()) {
            mbar_arrive_n(sm.vacant(0), 3);
            mbar_arrive_n(sm.vacant(1), 3);
            red_release(counter(C_O + J.layer * 16 + b, J.col), 1);
          }
          TRI(threadIdx.x == 256, ji, 5);
        } else if (w == 0) {
          wait_count(counter(C_RD + J.inst() * 16 + b, 0), e1 * (J.type == T_D ? 28 : 16));
          fence_proxy_async();
          const bool last = Job(jobs[ji + 1]).nk == 0, split = last && J.nk >= SPLIT_MIN;
#pragma unroll 1
          for (uint32_t v = 0; v < 4; v++) {
            const uint32_t u = last ? (v >> 1) + (v & 1) * 2 : v;
            mbar_wait(sm.filled(u), (u & 2 ? nb : na) & 1);
            TRI(u == 0 && lane == 0, ji, 3);
            fence_proxy_async_smem();
            const uint32_t src = (last && (u & 2) ? sm.stage(stages) : sm.slot(0)) + (u & 1) * SLOT;
#pragma unroll 1
            for (uint32_t p = 0; p < 16384 / PIECE; p++) {
              if (elect()) {
                tma3d_reduce_add(&P.xr, J.col * 256 + (split ? (u & 2) * 64 + p * PIECE / 8192 * 64 : (u & 2) * 32 + p * PIECE / 8192 * 128), J.R * 128 + (u & 1) * 64 + p * PIECE % 8192 / 128, rank, src + p * PIECE);
                bulk_commit();
              }
              if (!last) bulk_wait_read<DEPTH - 1>();
            }
            if (!last) {
              bulk_wait();
              if (elect()) mbar_arrive_n(sm.vacant(u ^ 2), 3);
            }
            if (u == 1 && J.inst() != 3) bar_arrive<8, 64>();
          }
          bulk_wait();
        }
        if ((J.type & 1) && J.inst() != 3 && w < 2) {
          if (w == 1) bar_sync<8, 64>();
          TRX(lane == 0, ji, 4, w ? 12 : 4, "%%globaltimer_lo");
          if (elect()) red_release(counter(C_X + J.inst() * 16 + b, J.col * 2 + 1 - w), J.nk);
          TRX(lane == 0, ji, 5, w ? 13 : 5, "%%globaltimer_lo");
          if (w == 1) bar_arrive<10, 64>(); else bar_sync<10, 64>();
        }
        na++;
        nb += J.type != T_Q;
      }
      TRI(threadIdx.x == 8 * 32, JMAX - 1, 6);
      TRK(threadIdx.x == 8 * 32, JMAX - 1, 24);
      if (w == 0 && elect()) red_relaxed(counter(C_EP, blockIdx.x), 1);
      if (w == 2 && __float_as_uint(lds32f(sm.pair_id())) != pair) __trap();
    }
  }
  cluster_arrive();
  cluster_wait();
}

typedef CUresult (*EncodeFn)(CUtensorMap*, CUtensorMapDataType, cuuint32_t, void*, const cuuint64_t*, const cuuint64_t*, const cuuint32_t*,
                             const cuuint32_t*, CUtensorMapInterleave, CUtensorMapSwizzle, CUtensorMapL2promotion, CUtensorMapFloatOOBfill);
struct Dim { cuuint64_t size, stride; cuuint32_t box; };
template <int N> void encode(EncodeFn fn, CUtensorMap* m, const void* ptr, const Dim (&d)[N]) {
  cuuint64_t dims[N], strides[N];
  cuuint32_t box[N], es[N];
  for (int i = 0; i < N; i++) { dims[i] = d[i].size; strides[i] = d[i].stride; box[i] = d[i].box; es[i] = 1; }
  fn(m, CU_TENSOR_MAP_DATA_TYPE_BFLOAT16, N, const_cast<void*>(ptr), dims, strides + 1, box, es, CU_TENSOR_MAP_INTERLEAVE_NONE,
     CU_TENSOR_MAP_SWIZZLE_128B, CU_TENSOR_MAP_L2_PROMOTION_L2_128B, CU_TENSOR_MAP_FLOAT_OOB_FILL_NONE);
}

}

extern "C" void kernel_launch(void* const* d_in, const int* in_sizes, int n_in, void* d_out, int out_size) {
  (void)in_sizes; (void)n_in; (void)out_size;
  static EncodeFn fn = nullptr;
  static Scratch* scr;
  static int sms;
  if (!fn) {
    void* p = nullptr;
    cudaDriverEntryPointQueryResult q;
    cudaGetDriverEntryPoint("cuTensorMapEncodeTiled", &p, cudaEnableDefault, &q);
    fn = (EncodeFn)p;
    scr = scratch_base();
    int device = 0;
    cudaGetDevice(&device);
    cudaDeviceGetAttribute(&sms, cudaDevAttrMultiProcessorCount, device);
    cudaFuncSetAttribute(mega_kernel, cudaFuncAttributeMaxDynamicSharedMemorySize, SMEM_BYTES);
  }
  static Params P;
  const char *wg = (const char*)d_in[4], *wu = (const char*)d_in[5], *w0 = wg < wu ? wg : wu;
  const cuuint64_t plane = wg < wu ? wu - wg : wg - wu;
  P.swap = wg < wu ? 0 : 8192;
  encode(fn, &P.a[0], d_in[0], {{D, 2, 64}, {S / 2, D * 4, 128}, {2, D * 2, 1}});
  encode(fn, &P.a[1], scr->o, {{D, 2, 64}, {S / 2, D * 2, 128}, {2, O_PLANE, 1}});
  encode(fn, &P.ow, scr->o, {{D, 2, 64}, {S / 2, D * 2, 64}, {2, O_PLANE, 1}});
  encode(fn, &P.a[2], d_out, {{D, 2, 64}, {S / 2, D * 4, 128}, {2, D * 2, 1}});
  encode(fn, &P.a[3], scr->h, {{F, 2, 64}, {S / 2, F * 2, 128}, {2, (cuuint64_t)F * S, 1}});
  encode(fn, &P.a[4], w0, {{F, 2, 64}, {D, F * 2, 256}, {2, plane, 1}});
  encode(fn, &P.a[5], d_in[0], {{64, 2, 64}, {S, D * 2, 64}, {16, 128, 4}});
  encode(fn, &P.w[T_Q], d_in[1], {{64, 2, 64}, {D, 3 * D * 2, 32}, {16, 128, 1}, {3, D * 2, 3}});
  encode(fn, &P.w[T_O], d_in[2], {{64, 2, 64}, {D, D * 2, 32}, {16, 128, 4}, {1, (cuuint64_t)D * D * 2, 1}});
  encode(fn, &P.w[T_G], w0, {{64, 2, 64}, {D, F * 2, 32}, {F / 64, 128, 2}, {2, plane, 2}});
  encode(fn, &P.w[T_D], d_in[6], {{64, 2, 64}, {F, D * 2, 32}, {16, 128, 4}, {1, (cuuint64_t)F * D * 2, 1}});
  encode(fn, &P.xr, d_out, {{D, 2, 64}, {S / 2, D * 4, PIECE / 128}, {2, D * 2, 1}});
  memcpy(P.jobs, kJobs, sizeof(kJobs));
  memcpy(P.kseq, kSeq, sizeof(kSeq));
  P.x0 = (const bf16*)d_in[0];
  P.wqkv = (const bf16*)d_in[1];
  P.out = (bf16*)d_out;
  mega_kernel<<<2 * NPAIR, 384, SMEM_BYTES>>>((char*)scr, sms == 2 * NPAIR, P);
}
```

```cpp
#include <cuda_runtime.h>
#include <cuda_bf16.h>
#include <cuda.h>
#include <stddef.h>
#include <stdint.h>
#include <string.h>

namespace {

typedef __nv_bfloat16 bf16;
typedef unsigned long long u64;
constexpr int S = 2048, D = 1024, F = 3584;
constexpr int STAGE = 49152, NSTAGE = 4, SLOT = 16384;
constexpr int STG_OFF = NSTAGE * STAGE, BAR_OFF = STG_OFF + 2 * SLOT, AUX_OFF = BAR_OFF + 336;
constexpr int SMEM_BYTES = AUX_OFF + 2736;
constexpr int SMEM_BASE = 1024;
constexpr int NPAIR = 66, JMAX = 24, KMAX = 296;
constexpr int T_Q = 0, T_O = 1, T_G = 2, T_D = 3;
constexpr uint32_t JOB_C = 1u << 18;
constexpr uint32_t K_LAST_A = 64, K_LAST_B = 128;
constexpr uint32_t JOB_EARLY = 1u << 21;
constexpr uint32_t JOB_X = JOB_EARLY;
#define V_BOOTP 4
#define V_BOOTS 5
#define V_BOOTO 8
#define V_STS 9
constexpr int BOOT_PIECES = V_BOOTP, BOOT_OUT = V_BOOTO, BOOT_STEP = V_BOOTS, ST_STEP = V_STS;
constexpr int SPLIT_MIN = 6;
#define V_PREP 3
constexpr int PREP = V_PREP, LAST_LEAD = 3;
#define V_LOOK 2
#define V_MID 7
constexpr int LOOK = V_LOOK, MID = V_MID;
#define V_PIECE 8192
#define V_DEPTH 2
constexpr int NG = 2, PIECE = V_PIECE, DEPTH = V_DEPTH;
#define V_SL1 200
#define V_SL2 300
#define V_SL3 300
constexpr uint32_t SPIN_LIMIT = 1u << 21;

constexpr int C_X = 0;
constexpr int C_O = C_X + 48;
constexpr int C_H = C_O + 32;
constexpr int C_RD = C_H + 32;
constexpr int C_EP = C_RD + 64;
constexpr int C_LINES = C_EP + 5;

struct Scratch {
  bf16 h[S * F];
  uint32_t cnt[256 * 32];
  bf16 o[S / 2 * D];
  u64 stats[4 * S];
  bf16 o1[S / 2 * D];
  u64 cs[44 * 128];
  ulonglong2 halo[2 * 16 * 16 * 8 * 32];
};
constexpr uint32_t O_PLANE = offsetof(Scratch, o1) - offsetof(Scratch, o);
static_assert(C_LINES <= 256, "");
constexpr size_t PAGE = 2 << 20;
__device__ __align__(1024) char g_scratch[sizeof(Scratch) + PAGE];
Scratch* scratch_base() {
  char* p;
  cudaGetSymbolAddress((void**)&p, g_scratch);
  return (Scratch*)(p + (-(size_t)p & (PAGE - 1)));
}

uint32_t kJobs[NPAIR][JMAX] = {
  {0xe44200,0xc10020,0xc44040,0xc08009,0xc10082,0x4101001a,0xc10022,0xc1800b,0x184170b3,0x46610054,0x5b610034,0x7d41000e,0xc1001e,0xc10076,0xc10096,0xc14037,0xc40000,0xc40000,0xc40000,0xc40000,0xc40000,0xc40000,0xc40000,0xc40000},
  {0xe44000,0xc10018,0xc44080,0xc08009,0xc10021,0x22010052,0xc10092,0xc100aa,0xc09013,0x16410004,0x2d61004c,0x3461002c,0x4e410086,0xc10056,0x618100ae,0xc100b6,0xc1b02f,0xc40000,0xc40000,0xc40000,0xc40000,0xc40000,0xc40000,0xc40000},
  {0xc10000,0xc44140,0xc04001,0xc10042,0x3a01004a,0xc1006a,0xc100b2,0xc1201b,0x26413033,0x6440b00d,0x681001d,0x3281002d,0xd48100a6,0xc101be,0xc1e007,0xc40000,0xc40000,0xc40000,0xc40000,0xc40000,0xc40000,0xc40000,0xc40000,0xc40000},
  {0xc10010,0xc440c0,0xc04001,0xc10002,0x3b01008a,0xc1019a,0xc101aa,0xc0800b,0x1a40d01b,0xc10014,0x66410064,0x2810006,0xc1008e,0xc10066,0xc1007e,0xc0e087,0xc1003f,0xc40000,0xc40000,0xc40000,0xc40000,0xc40000,0xc40000,0xc40000},
  {0xc10048,0xe10058,0xe10070,0xc05039,0x21010012,0x7a01b003,0xc1003a,0x29410044,0x3561001c,0x4f61005c,0x5761003c,0x7e41004e,0x6081009e,0xc100be,0xc1c00f,0xc40000,0xc40000,0xc40000,0xc40000,0xc40000,0xc40000,0xc40000,0xc40000,0xc40000},
  {0xe44240,0xc443c0,0xe10158,0xc10130,0xc040e1,0x170101ca,0x620101da,0xc101f2,0x641905b,0xc07063,0x324100c5,0x7a61016c,0x12a1013c,0x288101d6,0xc101ee,0xc10236,0xc1a04f,0xc40000,0xc40000,0xc40000,0xc40000,0xc40000,0xc40000,0xc40000},
  {0xe44280,0xc44780,0xc10228,0x1f044840,0xe10270,0xc103ca,0x5e01039a,0xc103b2,0xc1042a,0xc103ba,0x6d4180bb,0x8810506,0xc100b5,0xd2810426,0xc103be,0xc1f097,0xc40000,0xc40000,0xc40000,0xc40000,0xc40000,0xc40000,0xc40000,0xc40000},
  {0xe44380,0xc102d0,0xc040c1,0xc10091,0x1101044a,0x67010452,0xc1046a,0xc104f2,0x2c4170ab,0x5240e0bb,0x5810486,0xc104ce,0xc10466,0xc1047e,0xc1f09f,0xc40000,0xc40000,0xc40000,0xc40000,0xc40000,0xc40000,0xc40000,0xc40000,0xc40000},
  {0xe442c0,0xc10320,0xc040c1,0x1d210338,0xc1054a,0x610105e2,0x7301e0cb,0xc10344,0xc1030c,0xc040bb,0x6041036c,0x1ca1033c,0x29810596,0x6c8105a6,0xc106f6,0xc1d0df,0xc40000,0xc40000,0xc40000,0xc40000,0xc40000,0xc40000,0xc40000,0xc40000},
  {0xe443c0,0xc10390,0xc44d80,0xc100d1,0x1501060a,0x64010612,0x720180c3,0x24106ba,0xc1038c,0x404103dc,0xc103f4,0x2c80c0e5,0x4d810656,0xc1066e,0xc1069e,0xc1a0ef,0xc40000,0xc40000,0xc40000,0xc40000,0xc40000,0xc40000,0xc40000,0xc40000},
  {0xc10088,0xe100e0,0xc10011,0x270100ca,0x6c01015a,0x7c01800b,0xc0d023,0x2140f0b3,0x516100dc,0xc10106,0xc1010e,0xc10166,0xc1013e,0xc1f017,0xc40000,0xc40000,0xc40000,0xc40000,0xc40000,0xc40000,0xc40000,0xc40000,0xc40000,0xc40000},
  {0xc10198,0xc101b0,0x1b0445c0,0xc44600,0xc446c0,0xc1030a,0x5d010322,0xc102f2,0xc0e04b,0xc101c4,0xc1707b,0x79410055,0xc07065,0xb0810075,0xd0810326,0xc10336,0xc1d05f,0xc40000,0xc40000,0xc40000,0xc40000,0xc40000,0xc40000,0xc40000},
  {0xc10050,0xc10060,0xc10038,0x29210078,0x3e010062,0xc10032,0x441901b,0x2461000c,0x36610024,0x5d410074,0x228100ad,0x5b810026,0xc1006e,0xc1005e,0xc1203f,0xc40000,0xc40000,0xc40000,0xc40000,0xc40000,0xc40000,0xc40000,0xc40000,0xc40000},
  {0xe44040,0xc444c0,0xc10168,0xc10049,0x1601024a,0x63010252,0xc10262,0xc1027a,0xc18073,0x55410045,0x48101c6,0xc1034e,0xc1035e,0xc1023e,0xc1e04f,0xc40000,0xc40000,0xc40000,0xc40000,0xc40000,0xc40000,0xc40000,0xc40000,0xc40000},
  {0xe44080,0xc44700,0xe10220,0xc09089,0xc103c2,0x5a010412,0xc10512,0xc103f2,0x1e41c0a3,0x4961021c,0x58410234,0x36a1027c,0x4881041e,0x7281051e,0xc10436,0xc1909f,0xc40000,0xc40000,0xc40000,0xc40000,0xc40000,0xc40000,0xc40000,0xc40000},
  {0xe44180,0xc44880,0xe102a0,0xc04081,0x1c2102f8,0xc104ca,0x66010462,0xc104ea,0xc104ba,0xc104fa,0xc102d4,0xc102ac,0x1d8104c6,0xc104d6,0x6d8104a6,0xc1053e,0xc0f087,0xc0c0b7,0xc40000,0xc40000,0xc40000,0xc40000,0xc40000,0xc40000},
  {0xe440c0,0xc44ac0,0xc10328,0xc07041,0xc080c9,0xc0c0e1,0xb2010592,0xc105aa,0xc106e2,0x1d4130db,0xc090e3,0x484100fb,0xc810546,0x3f81054e,0x5d810566,0xc1057e,0xc200c7,0xc40000,0xc40000,0xc40000,0xc40000,0xc40000,0xc40000,0xc40000},
  {0xe441c0,0xc44c40,0xc10398,0xc44d40,0xe103f0,0xc100f1,0xd0010692,0xc10632,0xc10672,0xc1067a,0x6f6103cc,0x736103a4,0x13810606,0xc1064e,0xc10626,0xc1067e,0xc0f0e7,0xc0e0ff,0xc40000,0xc40000,0xc40000,0xc40000,0xc40000,0xc40000},
  {0xe44300,0xc100a0,0xc04001,0xc100c2,0x3c010112,0x7b01d003,0x741013a,0x234100c4,0x374100d4,0xc100ac,0x39a100fc,0xc10156,0x6981012e,0xc1019e,0xc1b01f,0xc40000,0xc40000,0xc40000,0xc40000,0xc40000,0xc40000,0xc40000,0xc40000,0xc40000},
  {0xe44340,0xc101d8,0xc09041,0xc10051,0x24010352,0xc1032a,0xc1b053,0x12410073,0xe101dc,0xe101ac,0xc10286,0x40810296,0x758102a6,0xc102e6,0xc19057,0xc40000,0xc40000,0xc40000,0xc40000,0xc40000,0xc40000,0xc40000,0xc40000,0xc40000},
  {0xc10008,0xc44000,0xc44100,0xe10068,0xc10029,0x3601009a,0xc1002a,0xc100a2,0xc1007a,0x3041803b,0xc0b095,0x10810046,0x41810016,0x7881002e,0xc1003e,0xc19037,0xc40000,0xc40000,0xc40000,0xc40000,0xc40000,0xc40000,0xc40000,0xc40000},
  {0xc10110,0xc44440,0xe10160,0xc101c2,0x4201021a,0xc10222,0xc10272,0xc101fa,0x3f410104,0x5e610114,0xc100dd,0x2081024e,0x5c8101e6,0xc101fe,0xc10047,0xc1007f,0xc40000,0xc40000,0xc40000,0xc40000,0xc40000,0xc40000,0xc40000,0xc40000},
  {0xc10200,0xc44a00,0xc10260,0x3010402,0x4301050a,0xc10422,0xc0808b,0xc10432,0xc10244,0xe10214,0xc0b08d,0x7810386,0xc1050e,0x5f8103e6,0xc103fe,0xc1f0a7,0xc40000,0xc40000,0xc40000,0xc40000,0xc40000,0xc40000,0xc40000,0xc40000},
  {0xc102c0,0xc44900,0xc102b0,0x40449c0,0x120100b1,0x3801045a,0xc10472,0xa41a093,0x3d8102c4,0x4fa10294,0xe102e4,0xe102bc,0xc10516,0xc104e6,0xc104fe,0xc1b08f,0xc40000,0xc40000,0xc40000,0xc40000,0xc40000,0xc40000,0xc40000,0xc40000},
  {0xc10308,0xe10350,0xc44b00,0xe10378,0xc070f9,0x3f01059a,0xc105f2,0xc105ba,0x134105fa,0xe1034c,0xe10364,0xc106c6,0xc10556,0xc1055e,0xc105f6,0xc1e0ef,0xc40000,0xc40000,0xc40000,0xc40000,0xc40000,0xc40000,0xc40000,0xc40000},
  {0xc10388,0xe103e0,0xc44d00,0xc10682,0x5801065a,0xc106aa,0xc41b0d3,0xc110eb,0x4a4130fb,0x3810686,0xc106ce,0xc106ee,0xc106a6,0xc1e0d7,0xc40000,0xc40000,0xc40000,0xc40000,0xc40000,0xc40000,0xc40000,0xc40000,0xc40000,0xc40000},
  {0xe44100,0xc44180,0xe100d8,0xc44280,0xc10019,0x1001010a,0xc0b039,0xc10172,0xc1016a,0x1441a02b,0x4241009c,0xb8100f4,0x24810146,0x5981003d,0xf08100f6,0xc19017,0xc0c03f,0xc40000,0xc40000,0xc40000,0xc40000,0xc40000,0xc40000,0xc40000},
  {0xe44140,0xc101a0,0xc44640,0xc10059,0x1301028a,0x6501029a,0xc08079,0x71014053,0xc180e3,0xc0e07b,0xc101b4,0x37a101bc,0x4981007d,0x668102b6,0xc1033e,0xc1806f,0xc40000,0xc40000,0xc40000,0xc40000,0xc40000,0xc40000,0xc40000,0xc40000},
  {0x2e010040,0xe10028,0xe10030,0xc1000a,0x6801005a,0xc10072,0x40f013,0x104100ba,0x56410005,0x7161006c,0x14a1007c,0x2a810035,0x68810036,0xc1018e,0xc18027,0xc40000,0xc40000,0xc40000,0xc40000,0xc40000,0xc40000,0xc40000,0xc40000,0xc40000},
  {0xc10150,0xe10118,0xc44680,0xc10069,0x2f0101d2,0x7701c043,0x541023a,0x2241006b,0x4741011c,0xc10174,0x2f81020e,0xc1025e,0x7a8101f6,0xc10256,0xc0c05f,0xc0a077,0xc40000,0xc40000,0xc40000,0xc40000,0xc40000,0xc40000,0xc40000,0xc40000},
  {0xc10208,0xc44740,0xc447c0,0xc04081,0xc07089,0x100a9,0xb00103da,0x7501d083,0x34103fa,0xe1020c,0xe10254,0xe1022c,0xc1038e,0xc1039e,0x768103b6,0xc1d08f,0xc0a0bf,0xc40000,0xc40000,0xc40000,0xc40000,0xc40000,0xc40000,0xc40000},
  {0xc10290,0xc44940,0xc102f0,0x5010099,0x200080b9,0xd201049a,0xc104a2,0xc1047a,0xc0e09b,0x3e6102cc,0x5f40707b,0xc102f4,0x2b81048e,0xc1049e,0x7b8104b6,0xc104de,0xc160b7,0xc40000,0xc40000,0xc40000,0xc40000,0xc40000,0xc40000,0xc40000},
  {0xc10318,0xc10358,0xc44b80,0xc10542,0x59010552,0xc1056a,0xc10572,0xc1c0eb,0x4b610314,0x59610374,0x7f61037c,0x158100fd,0x648105ae,0xc105e6,0xc180c7,0xc40000,0xc40000,0xc40000,0xc40000,0xc40000,0xc40000,0xc40000,0xc40000,0xc40000},
  {0xc103c0,0xc44c00,0xc103e8,0x6010602,0x4401061a,0xc090f9,0x7401a0cb,0xc170e3,0xc0d0fb,0xc103ec,0xc040e5,0x2e81068e,0xc1065e,0x7e8106b6,0xc1b0df,0xc0a0ff,0xc40000,0xc40000,0xc40000,0xc40000,0xc40000,0xc40000,0xc40000,0xc40000},
  {0xc100c8,0xc44240,0xc100b0,0x7010102,0x450100da,0xc1012a,0xc100f2,0xc100fa,0xe1008c,0xe10094,0xc0500d,0x1810186,0xc10196,0x6781016e,0xc100fe,0xc1d02f,0xc40000,0xc40000,0xc40000,0xc40000,0xc40000,0xc40000,0xc40000,0xc40000},
  {0xc101d0,0xe101e0,0xc100a1,0x250102ca,0x6e01031a,0x7e0102b2,0xc102ba,0xc0a06b,0x3161018c,0x676101ec,0x744102c6,0xc102d6,0x6f8102ae,0xc1032e,0xc1b067,0xc40000,0xc40000,0xc40000,0xc40000,0xc40000,0xc40000,0xc40000,0xc40000,0xc40000},
  {0xc10108,0xe10170,0xe10138,0xc08079,0x3701025a,0xc10232,0xc1404b,0x1b410144,0x2e610154,0x38610164,0x68410206,0xc101ce,0xc10226,0xc1037e,0xc1d067,0xc40000,0xc40000,0xc40000,0xc40000,0xc40000,0xc40000,0xc40000,0xc40000,0xc40000},
  {0xc10218,0xc10258,0xc10278,0x2a01040a,0xc080b9,0xc103ea,0xc1308b,0x1f41053a,0xc10085,0x7c61026c,0x16810406,0x478103d6,0x738103ae,0xc1042e,0xc19097,0xc40000,0xc40000,0xc40000,0xc40000,0xc40000,0xc40000,0xc40000,0xc40000,0xc40000},
  {0xc102c8,0xe102a8,0xc04081,0x1010482,0x5b010492,0x7601b083,0x941809b,0xe1028c,0xe102a4,0xc05095,0x11810446,0x42810496,0xc1046e,0xc104be,0xc190a7,0xc40000,0xc40000,0xc40000,0xc40000,0xc40000,0xc40000,0xc40000,0xc40000,0xc40000},
  {0xc10348,0xc44bc0,0xc10370,0x80105c2,0x4601058a,0x790200c3,0x14160db,0x3c410354,0x61610324,0x754105c6,0xc105d6,0x658106e6,0xc105fe,0xc1d0cf,0xc40000,0xc40000,0xc40000,0xc40000,0xc40000,0xc40000,0xc40000,0xc40000,0xc40000,0xc40000},
  {0xc103d0,0xc103a8,0xc103f8,0x2b01064a,0x6901062a,0xc1069a,0xc106b2,0x27410384,0x394103d4,0x7b6103e4,0x17810646,0x448106d6,0xc106ae,0xc106be,0xc1a0e7,0xc40000,0xc40000,0xc40000,0xc40000,0xc40000,0xc40000,0xc40000,0xc40000,0xc40000},
  {0xc100d0,0xe100a8,0xc100d9,0x2801018a,0x6d010132,0x7d010162,0xc1017a,0xc1102b,0x4140d03b,0xfa100ec,0x1b8100ce,0xc1015e,0x7d810136,0xc1a007,0xc0b037,0xc40000,0xc40000,0xc40000,0xc40000,0xc40000,0xc40000,0xc40000,0xc40000,0xc40000},
  {0xc10190,0xc44580,0xc101f0,0x9010282,0x47010292,0xc102da,0xc102e2,0xc1033a,0xc10073,0x536101e4,0xc10306,0xc10356,0xc1029e,0xc102be,0xc1f057,0xc40000,0xc40000,0xc40000,0xc40000,0xc40000,0xc40000,0xc40000,0xc40000,0xc40000},
  {0xc10148,0xc44400,0xc10128,0xa010202,0x4801020a,0xc101ea,0xc1604b,0x1c41037a,0x6e61010c,0x76610124,0x18810246,0xc10216,0x63810266,0xc1027e,0xc13047,0xc0a0bf,0xc40000,0xc40000,0xc40000,0xc40000,0xc40000,0xc40000,0xc40000,0xc40000},
  {0xc10248,0xc44a40,0xc10268,0xb010382,0x490103d2,0xc103aa,0xc10532,0xc1043a,0xc120b3,0x50410264,0x8103c6,0xc10396,0xc103a6,0xc1043e,0xc1e0af,0xc40000,0xc40000,0xc40000,0xc40000,0xc40000,0xc40000,0xc40000,0xc40000,0xc40000},
  {0xc10288,0x2c2102d8,0xe102b8,0xc1048a,0x6a0104d2,0xc104aa,0xc1052a,0x284150ab,0x5440e0bb,0xa81009d,0x34a102fc,0x4a81045e,0xc10476,0xc104ee,0xc110bf,0xc40000,0xc40000,0xc40000,0xc40000,0xc40000,0xc40000,0xc40000,0xc40000,0xc40000},
  {0xc10340,0xc44a80,0xc10368,0xc010582,0x4a0106da,0xc105d2,0xc105ea,0xc106fa,0xc130f3,0x654100cd,0x1f810586,0xc105ce,0x6e8105ee,0xc105be,0xc0f0e7,0xc0c0f7,0xc40000,0xc40000,0xc40000,0xc40000,0xc40000,0xc40000,0xc40000,0xc40000},
  {0xc103d8,0xc44cc0,0xc040c1,0xc103b8,0x140106ca,0x5f010662,0xc106a2,0xc106ea,0xc1d0f3,0xc080fb,0xe8100d5,0x2381060e,0x5881061e,0xc10636,0xc106fe,0xc120ff,0xc40000,0xc40000,0xc40000,0xc40000,0xc40000,0xc40000,0xc40000,0xc40000},
  {0xc10080,0xc441c0,0xc04001,0xc10142,0x3d0100d2,0xc101a2,0xc101ba,0xc12023,0x2540d02b,0x4340c03b,0x72410015,0x2681014e,0xc1011e,0xc100ee,0xc101a6,0xc0a027,0xc0a03f,0xc40000,0xc40000,0xc40000,0xc40000,0xc40000,0xc40000,0xc40000},
  {0xc10180,0xc44500,0xc101f8,0xd010302,0x4b0102d2,0x7801c043,0x8420063,0xc080f3,0x6241004d,0x1e809065,0x218100f5,0xd6810366,0xc102f6,0xc2006f,0xc40000,0xc40000,0xc40000,0xc40000,0xc40000,0xc40000,0xc40000,0xc40000,0xc40000,0xc40000},
  {0xc10140,0xc44380,0xc10120,0xe010342,0x4c01035a,0xc1022a,0xc1026a,0xc1e06b,0x4540c07b,0xc10134,0x3581006d,0x458101de,0x7c810276,0xc10376,0xc15077,0xc40000,0xc40000,0xc40000,0xc40000,0xc40000,0xc40000,0xc40000,0xc40000,0xc40000},
  {0xc10240,0xc44800,0xe10230,0xc10502,0x4d010392,0xc1041a,0xc103a2,0xc1209b,0x2040c0ab,0x4441025c,0xd810274,0x2581040e,0xc103de,0x7f8103f6,0xc10526,0xc130bf,0xc40000,0xc40000,0xc40000,0xc40000,0xc40000,0xc40000,0xc40000,0xc40000},
  {0xc10298,0xc448c0,0xc102e8,0xf010442,0x4e0104da,0xc10522,0xc104b2,0xc1c0a3,0x4c41029c,0x706102b4,0x1981044e,0x5a8100bd,0x6a810536,0xc1052e,0xc160b7,0xc40000,0xc40000,0xc40000,0xc40000,0xc40000,0xc40000,0xc40000,0xc40000,0xc40000},
  {0xc10300,0xe10330,0xc44dc0,0xc100e9,0xb401055a,0xc105a2,0xc105b2,0xc106f2,0xc0b0eb,0x4d61035c,0x5a61032c,0xc1058e,0xc1059e,0x7781056e,0xc105de,0xc170f7,0xc40000,0xc40000,0xc40000,0xc40000,0xc40000,0xc40000,0xc40000,0xc40000},
  {0xc103c8,0xe103a0,0xc04081,0x2010642,0x5c010652,0xc10622,0xb41d0d3,0x3c8103c4,0x4ba1039c,0xe103b4,0xe103bc,0xc10616,0xc1062e,0xc1063e,0xc1a0d7,0xc40000,0xc40000,0xc40000,0xc40000,0xc40000,0xc40000,0xc40000,0xc40000,0xc40000},
  {0xc100c0,0xc442c0,0xc100b8,0x192100f8,0x2301014a,0xc100e2,0xc100ea,0xc19023,0x336100cc,0x694100e4,0x3aa100bc,0xc10116,0xc101ae,0xc1017e,0xc1d01f,0xc40000,0xc40000,0xc40000,0xc40000,0xc40000,0xc40000,0xc40000,0xc40000,0xc40000},
  {0xc10188,0xe101a8,0xc080c9,0x18010071,0x400102a2,0xc102ea,0xc10332,0x11410184,0x2f6101d4,0x3a6101a4,0x6a410346,0xc102ce,0xc102de,0xc1036e,0xc15047,0xc0a07f,0xc40000,0xc40000,0xc40000,0xc40000,0xc40000,0xc40000,0xc40000,0xc40000},
  {0xc10100,0xc44480,0xc10178,0xc10242,0x4f010212,0xc101e2,0xe41f05b,0x2b61014c,0x3b61015c,0x6b61012c,0x7761017c,0x1a81021e,0x7481022e,0xc1026e,0xc19077,0xc40000,0xc40000,0xc40000,0xc40000,0xc40000,0xc40000,0xc40000,0xc40000,0xc40000},
  {0xc10210,0x2d210250,0xe10238,0xc1038a,0x6b0103e2,0x7001d08b,0x19410204,0xe1024c,0xe10224,0xe1023c,0xc040a5,0x4e8103ce,0xc103ee,0xc10416,0xc1a0af,0xc40000,0xc40000,0xc40000,0xc40000,0xc40000,0xc40000,0xc40000,0xc40000,0xc40000},
  {0xc10280,0xc44980,0xc102e0,0xc104c2,0x5401051a,0xc104e2,0xd41e093,0xc10284,0xc102dc,0xc102ec,0xc0c0a5,0x3e810456,0x6b8104ae,0xc104f6,0xc1b087,0xc40000,0xc40000,0xc40000,0xc40000,0xc40000,0xc40000,0xc40000,0xc40000,0xc40000},
  {0xc10310,0xc44b40,0xc10360,0xc106c2,0x550105ca,0xc10562,0xc105da,0xc1057a,0xc10304,0xc1031c,0xc10334,0x278100ed,0x438106de,0xc10576,0xc105b6,0xc150f7,0xc40000,0xc40000,0xc40000,0xc40000,0xc40000,0xc40000,0xc40000,0xc40000},
  {0xc10380,0xc44c80,0xc040c1,0x1e2103b0,0xc1068a,0x600106d2,0xc1066a,0xc1063a,0xc0f0db,0x3d610394,0x6c4103ac,0x3ba103fc,0xc10696,0xc10666,0xc10676,0xc0f0cf,0xc0e0ff,0xc40000,0xc40000,0xc40000,0xc40000,0xc40000,0xc40000,0xc40000},
  {0xc10090,0xc44200,0xc100e8,0x1a044340,0xc10031,0x39010152,0xc10122,0xc101b2,0x17410084,0xc11033,0x5c40703b,0xc100b4,0x2d810025,0x468100de,0x79810176,0xc101b6,0xc16027,0xc40000,0xc40000,0xc40000,0xc40000,0xc40000,0xc40000,0xc40000},
  {0xc101c8,0xc101e8,0xc10061,0x2601034a,0x6f0102aa,0x7f01036a,0xc102fa,0xe101cc,0xc1019c,0xc101f4,0x38a101fc,0x4c810316,0xc102ee,0xc1030e,0xc0c0cf,0xc0e07f,0xc40000,0xc40000,0xc40000,0xc40000,0xc40000,0xc40000,0xc40000,0xc40000},
  {0xc10098,0xc44300,0xc100f0,0xc10182,0x56010192,0xc1011a,0xf420013,0x2a414033,0x636100a4,0x784100c6,0xc100d6,0x628100e6,0xc10126,0xc1c00f,0xc40000,0xc40000,0xc40000,0xc40000,0xc40000,0xc40000,0xc40000,0xc40000,0xc40000,0xc40000},
  {0xc101c0,0xc44540,0xc101b8,0xc102c2,0x57010312,0xc10362,0xc10372,0xc09053,0x15411063,0xc10194,0xc0508d,0x981005d,0x3381028e,0x5e81031e,0xc102fe,0xc0f05f,0xc1007f,0xc40000,0xc40000,0xc40000,0xc40000,0xc40000,0xc40000,0xc40000},
};
uint8_t kSeq[NPAIR][KMAX] = {
  {0,1,2,3,0,1,2,3,4,5,6,7,8,9,10,11,12,13,14,15,0,1,2,3,64,67,72,78,76,70,66,74,64,66,76,78,65,67,77,79,68,70,69,71,72,74,73,75,4,6,0,2,5,7,1,3,12,14,8,10,13,15,9,11,4,6,8,10,0,2,5,7,9,11,12,14,1,3,13,15,88,89,94,95,116,117,118,119,106,107,78,79,82,83,112,113,84,85,102,103,98,99,72,73,72,73,80,81,98,99,74,75,110,111,112,113,86,87,92,93,78,79,64,65,66,67,84,68,70,69,71,76,78,72,74,64,66,77,79,73,75,65,67,68,70,72,74,69,71,64,66,76,78,73,75,65,67,77,79,8,10,0,2,9,11,12,14,1,3,4,6,13,15,5,7,12,14,8,10,4,6,0,2,13,15,9,11,5,7,1,3,12,14,8,10,13,15,4,6,9,11,5,7,0,2,1,3,200,202,73,75,196,198,192,194,204,206,197,199,193,195,205,207,71,66,67,112,113,98,99,86,87,110,111,114,115,88,89,118,119,196,197,230,0,0,0,0,0,0,0,0,0,0,0,0,0,0,0,0,0,0,0,0,0,0,0,0,0,0,0,0,0,0,0,0,0,0,0,0,0,0,0,0,0,0,0,0,0,0,0,0,0,0,0,0,0},
  {0,1,2,3,0,1,2,3,4,5,6,7,8,9,10,11,12,13,14,15,0,1,2,3,77,69,73,79,65,68,75,71,70,64,76,66,74,72,79,71,78,67,69,65,75,77,68,73,12,14,8,10,13,15,9,11,0,2,4,6,1,3,5,7,76,78,72,74,77,79,73,75,64,66,68,70,65,67,69,71,4,6,12,14,8,10,0,2,5,7,13,15,9,11,1,3,114,115,100,101,74,75,116,117,118,0,2,4,6,8,10,1,3,5,7,12,14,9,11,13,15,76,78,68,70,77,79,64,66,72,74,69,71,65,67,73,75,12,14,4,6,0,2,13,15,5,7,8,10,1,3,9,11,8,10,12,14,0,2,9,11,13,15,1,3,4,6,5,7,8,10,9,11,4,6,0,2,12,14,5,7,1,3,13,15,4,6,12,14,8,10,5,7,13,15,9,11,0,2,1,3,12,14,8,10,13,15,4,6,9,11,5,7,128,130,1,3,99,64,65,80,81,92,93,108,109,106,107,70,71,66,67,90,91,88,89,82,83,224,225,232,233,230,231,0,0,0,0,0,0,0,0,0,0,0,0,0,0,0,0,0,0,0,0,0,0,0,0,0,0,0,0,0,0,0,0,0,0,0,0,0,0,0,0,0,0,0,0,0,0,0,0,0,0,0,0},
  {64,65,66,67,68,69,70,71,72,73,74,75,76,77,78,79,0,1,2,3,79,75,77,73,0,2,12,14,1,3,13,15,4,6,5,7,8,10,9,11,64,66,72,74,65,67,73,75,76,78,68,70,77,79,69,71,4,6,12,14,8,10,0,2,5,7,13,15,9,11,1,3,0,2,8,10,4,6,12,14,1,3,9,11,5,7,13,15,83,98,99,108,109,92,93,78,79,84,85,100,101,66,67,74,75,88,66,67,84,85,68,69,90,91,104,105,70,71,210,211,228,229,106,107,222,71,72,69,66,64,78,74,77,76,75,73,64,71,78,77,69,72,75,70,74,79,76,73,68,67,66,65,64,71,78,74,77,70,73,69,66,72,76,79,68,65,67,75,4,6,5,7,8,10,12,14,9,11,13,15,0,2,1,3,4,6,12,14,8,10,5,7,13,15,0,2,9,11,1,3,106,107,104,105,92,93,88,89,72,73,90,91,100,101,78,79,116,117,64,65,118,119,208,209,94,95,76,77,240,241,0,0,0,0,0,0,0,0,0,0,0,0,0,0,0,0,0,0,0,0,0,0,0,0,0,0,0,0,0,0,0,0,0,0,0,0,0,0,0,0,0,0,0,0,0,0,0,0,0,0,0,0,0,0,0,0,0,0,0,0,0,0,0,0,0,0},
  {0,1,2,3,4,5,6,7,8,9,10,11,12,13,14,15,0,1,2,3,66,74,68,64,0,2,12,14,1,3,13,15,4,6,5,7,8,10,9,11,64,66,72,74,65,67,73,75,76,78,68,70,77,79,69,71,4,6,0,2,5,7,1,3,12,14,8,10,13,15,9,11,4,6,12,14,8,10,128,130,5,7,13,15,9,11,129,131,92,93,64,65,100,101,96,97,89,76,77,96,97,86,87,72,73,116,117,110,111,4,6,5,7,12,14,8,10,0,2,13,15,9,11,1,3,0,2,1,3,4,6,8,10,12,14,5,7,9,11,13,15,8,10,12,14,0,2,9,11,13,15,1,3,4,6,5,7,8,10,0,2,9,11,12,14,1,3,4,6,13,15,5,7,4,6,5,7,8,10,12,14,9,11,13,15,0,2,1,3,4,6,12,14,8,10,5,7,13,15,0,2,9,11,1,3,77,112,113,110,111,82,83,70,71,68,69,102,103,108,80,81,66,67,90,91,96,97,242,243,202,203,70,199,238,239,0,0,0,0,0,0,0,0,0,0,0,0,0,0,0,0,0,0,0,0,0,0,0,0,0,0,0,0,0,0,0,0,0,0,0,0,0,0,0,0,0,0,0,0,0,0,0,0,0,0,0,0,0,0,0,0,0,0,0,0,0},
  {64,65,66,67,68,69,70,71,72,73,74,75,76,77,78,79,64,65,66,67,68,69,70,71,72,73,74,75,76,77,78,79,64,65,66,67,68,69,70,71,72,73,74,75,76,77,78,79,198,69,194,199,204,12,14,8,10,13,15,9,11,0,2,4,6,1,3,5,7,70,71,64,65,98,99,92,93,78,79,112,113,94,95,72,73,80,81,84,85,114,115,116,117,106,107,66,136,138,128,130,137,139,129,131,140,142,141,143,132,134,133,135,0,2,4,6,8,10,1,3,5,7,12,14,9,11,13,15,4,6,5,7,0,2,8,10,12,14,1,3,9,11,13,15,68,70,69,71,64,66,72,74,76,78,65,67,73,75,77,79,132,134,128,130,133,135,129,131,136,138,140,142,137,139,141,143,8,10,0,2,9,11,12,14,1,3,4,6,13,15,5,7,12,14,8,10,4,6,0,2,13,15,9,11,5,7,1,3,4,6,12,14,8,10,5,7,13,15,0,2,137,139,1,3,92,93,108,109,98,99,80,81,100,101,70,71,116,117,96,97,74,75,64,65,112,113,82,83,234,235,212,213,0,0,0,0,0,0,0,0,0,0,0,0,0,0,0,0,0,0,0,0,0,0,0,0,0,0,0,0,0,0,0,0,0,0,0,0,0,0,0,0,0,0,0,0},
  {0,1,2,3,0,1,2,3,0,1,2,3,4,5,6,7,8,9,10,11,12,13,14,15,0,1,2,3,4,5,6,7,8,9,10,11,12,13,14,15,70,64,76,66,0,2,8,10,1,3,9,11,12,14,4,6,13,15,5,7,4,6,0,2,5,7,1,3,12,14,8,10,13,15,9,11,0,2,8,10,4,6,12,14,1,3,9,11,5,7,13,15,93,78,79,84,85,100,101,66,67,74,75,88,89,76,77,96,97,86,87,72,73,116,117,110,111,84,85,88,89,114,115,110,66,71,70,77,69,73,72,64,65,78,67,75,79,74,76,68,12,14,4,6,0,2,13,15,5,7,8,10,1,3,9,11,132,134,128,130,133,135,129,131,136,138,140,142,137,139,141,143,8,10,9,11,4,6,0,2,12,14,5,7,1,3,13,15,4,6,12,14,8,10,5,7,13,15,9,11,0,2,1,3,140,142,136,138,141,143,132,134,137,139,133,135,128,130,129,131,72,73,86,87,102,103,90,91,118,119,68,69,206,207,114,115,66,67,110,111,94,95,88,217,204,205,0,0,0,0,0,0,0,0,0,0,0,0,0,0,0,0,0,0,0,0,0,0,0,0,0,0,0,0,0,0,0,0,0,0,0,0,0,0,0,0,0,0,0,0,0,0,0,0,0,0},
  {0,1,2,3,0,1,2,3,0,1,2,3,4,5,6,7,8,9,10,11,12,13,14,15,0,1,2,3,0,1,2,3,4,5,6,7,8,9,10,11,12,13,14,15,0,2,8,10,1,3,9,11,12,14,4,6,13,15,5,7,4,6,0,2,5,7,1,3,12,14,8,10,13,15,9,11,0,2,8,10,4,6,12,14,1,3,9,11,5,7,13,15,4,6,12,14,8,10,0,2,5,7,13,15,137,11,1,3,136,138,128,130,137,139,129,131,140,142,141,143,132,134,133,135,204,205,236,237,240,241,210,211,226,227,228,229,192,193,200,201,208,209,202,203,212,213,214,215,8,10,12,14,0,2,9,11,13,15,1,3,4,6,5,7,78,74,77,71,70,64,66,69,79,200,75,68,204,73,195,65,4,6,5,7,8,10,12,14,9,11,13,15,0,2,1,3,132,134,140,142,136,138,133,135,141,143,128,130,137,139,129,131,99,102,103,86,87,104,105,78,79,118,119,114,115,88,89,112,113,100,101,64,65,84,85,94,95,224,225,82,83,196,197,0,0,0,0,0,0,0,0,0,0,0,0,0,0,0,0,0,0,0,0,0,0,0,0,0,0,0,0,0,0,0,0,0,0,0,0,0,0,0,0,0,0,0,0,0,0,0,0,0,0,0,0,0},
  {0,1,2,3,0,1,2,3,4,5,6,7,8,9,10,11,12,13,14,15,66,74,68,64,64,74,76,66,68,70,65,72,79,67,69,71,78,75,77,73,0,2,8,10,1,3,9,11,12,14,4,6,13,15,5,7,12,14,8,10,13,15,9,11,0,2,4,6,1,3,5,7,4,6,12,14,8,10,0,2,5,7,13,15,9,11,1,3,0,2,8,10,4,6,12,14,1,3,9,11,5,7,13,15,99,100,101,90,91,70,71,76,77,68,69,110,111,82,83,74,75,96,97,118,119,104,105,238,239,242,243,232,233,218,219,220,221,230,231,196,197,8,10,12,14,0,2,9,11,13,15,1,3,4,6,5,7,8,10,0,2,9,11,12,14,1,3,4,6,13,15,5,7,4,6,5,7,8,10,12,14,9,11,13,15,0,2,1,3,4,6,140,142,136,138,133,135,141,143,128,130,137,139,129,131,80,81,96,97,92,93,108,109,70,71,82,83,100,101,78,79,74,75,114,115,94,95,118,119,200,201,192,193,240,241,226,0,0,0,0,0,0,0,0,0,0,0,0,0,0,0,0,0,0,0,0,0,0,0,0,0,0,0,0,0,0,0,0,0,0,0,0,0,0,0,0,0,0,0,0,0,0,0,0,0,0,0,0,0,0,0,0,0,0,0,0},
  {0,1,2,3,0,1,2,3,4,5,6,7,8,9,10,11,12,13,14,15,69,76,67,65,0,1,2,3,4,5,6,7,8,9,10,11,12,13,14,15,0,2,8,10,1,3,9,11,12,14,4,6,13,15,5,7,4,6,8,10,0,2,5,7,9,11,12,14,1,3,13,15,88,89,94,95,116,117,118,119,106,107,78,79,82,83,112,113,84,85,102,103,98,99,72,73,92,93,64,65,100,101,0,2,4,6,8,10,1,3,5,7,12,14,9,11,13,15,12,14,4,6,13,15,0,2,8,10,5,7,1,3,9,11,222,223,244,245,12,14,4,6,0,2,13,15,5,7,8,10,1,3,9,11,132,134,128,130,133,135,129,131,136,138,140,142,137,139,141,143,8,10,9,11,4,6,0,2,12,14,5,7,1,3,13,15,4,6,5,7,8,10,12,14,9,11,13,15,0,2,1,3,12,14,8,10,13,15,4,6,9,11,5,7,0,2,1,3,65,112,113,98,99,88,89,86,87,84,85,90,91,106,235,68,69,104,105,76,77,116,117,110,111,102,103,194,195,0,0,0,0,0,0,0,0,0,0,0,0,0,0,0,0,0,0,0,0,0,0,0,0,0,0,0,0,0,0,0,0,0,0,0,0,0,0,0,0,0,0,0,0,0,0,0,0,0},
  {0,1,2,3,0,1,2,3,4,5,6,7,8,9,10,11,12,13,14,15,0,1,2,3,64,74,76,66,68,70,65,72,79,67,69,71,78,75,77,73,0,2,8,10,1,3,9,11,12,14,4,6,13,15,5,7,12,14,8,10,13,15,9,11,0,2,4,6,1,3,5,7,96,97,82,83,74,75,110,111,76,77,88,89,118,119,68,69,100,101,104,105,102,103,90,91,136,138,128,130,9,11,129,131,140,142,141,143,132,134,133,135,12,14,4,6,13,15,0,2,8,10,5,7,1,3,9,11,4,6,5,7,0,2,8,10,12,14,1,3,9,11,13,15,4,6,8,10,5,7,0,2,12,14,9,11,1,3,13,15,77,69,78,72,76,68,66,73,79,67,75,65,8,10,9,11,4,6,0,2,12,14,5,7,1,3,13,15,4,6,12,14,8,10,5,7,13,15,9,11,0,2,1,3,12,14,8,10,132,134,0,2,141,143,9,11,133,135,129,131,64,65,80,81,92,93,108,109,106,107,70,71,66,67,90,91,88,89,82,83,96,97,232,233,230,231,0,0,0,0,0,0,0,0,0,0,0,0,0,0,0,0,0,0,0,0,0,0,0,0,0,0,0,0,0,0,0,0,0,0,0,0,0,0,0,0,0,0,0,0,0,0,0,0,0,0},
  {64,65,66,67,68,69,70,71,72,73,74,75,76,77,78,79,0,1,2,3,4,5,6,7,8,9,10,11,12,13,14,15,64,74,76,66,68,70,65,72,79,67,69,71,78,75,77,73,0,2,8,10,1,3,9,11,12,14,4,6,13,15,5,7,4,6,0,2,5,7,1,3,12,14,8,10,13,15,9,11,114,115,76,77,70,71,86,87,90,91,74,75,66,67,68,69,80,81,108,109,110,111,104,105,84,85,88,89,114,115,110,111,98,99,66,67,94,85,68,69,90,91,104,105,70,71,210,211,100,101,234,235,4,6,5,7,0,2,8,10,12,14,1,3,9,11,13,15,8,10,12,14,0,2,9,11,13,15,1,3,4,6,5,7,8,10,0,2,9,11,12,14,1,3,4,6,13,15,5,7,4,6,5,7,8,10,12,14,9,11,13,15,0,2,1,3,4,6,12,14,8,10,133,135,13,15,0,2,137,139,1,3,99,102,103,86,87,104,105,78,79,118,119,114,115,88,89,112,113,100,101,64,65,84,85,94,95,224,225,210,211,196,197,0,0,0,0,0,0,0,0,0,0,0,0,0,0,0,0,0,0,0,0,0,0,0,0,0,0,0,0,0,0,0,0,0,0,0,0,0,0,0,0,0,0,0,0,0,0,0,0,0,0,0,0,0},
  {0,1,2,3,4,5,6,7,8,9,10,11,12,13,14,15,0,1,2,3,4,5,6,7,8,9,10,11,12,13,14,15,0,1,2,3,0,1,2,3,0,1,2,3,0,2,8,10,1,3,9,11,12,14,4,6,13,15,5,7,4,6,8,10,0,2,5,7,9,11,12,14,1,3,13,15,0,2,8,10,4,6,12,14,1,3,9,11,5,7,13,15,72,73,92,93,64,65,100,101,96,97,114,115,76,77,0,2,4,6,8,10,1,3,5,7,12,14,9,11,13,15,204,205,108,109,112,113,210,211,226,227,228,229,192,193,200,201,208,209,202,203,212,213,214,71,69,72,78,64,77,75,74,79,73,67,76,70,68,66,65,68,66,73,79,67,75,65,78,74,77,71,70,64,194,69,207,200,75,196,204,73,195,65,4,6,5,7,8,10,12,14,9,11,13,15,0,2,1,3,12,14,8,10,13,15,4,6,9,11,5,7,0,2,1,3,65,112,113,98,99,88,89,86,87,84,85,90,91,106,107,68,69,104,105,76,77,116,117,238,239,102,103,194,195,0,0,0,0,0,0,0,0,0,0,0,0,0,0,0,0,0,0,0,0,0,0,0,0,0,0,0,0,0,0,0,0,0,0,0,0,0,0,0,0,0,0,0,0,0,0,0,0,0,0,0},
  {0,1,2,3,4,5,6,7,8,9,10,11,12,13,14,15,0,1,2,3,4,5,6,7,8,9,10,11,12,13,14,15,0,1,2,3,4,5,6,7,8,9,10,11,12,13,14,15,64,65,66,67,68,69,70,71,72,73,74,75,76,77,78,79,4,6,8,10,0,2,5,7,9,11,12,14,1,3,13,15,0,2,8,10,4,6,12,14,1,3,9,11,5,7,13,15,64,65,70,71,80,81,112,113,90,91,102,103,118,119,104,105,114,115,106,107,94,95,68,69,82,12,14,4,6,13,15,0,2,8,10,5,7,1,3,9,11,0,2,1,3,4,6,8,10,12,14,5,7,9,11,13,15,68,70,72,74,69,71,64,66,76,78,73,75,65,67,77,79,64,71,78,74,77,70,73,69,66,72,76,79,68,65,67,75,4,6,5,7,8,10,12,14,9,11,13,15,0,2,1,3,4,6,12,14,8,10,5,7,13,15,9,11,0,2,1,3,204,206,200,202,196,198,192,194,205,207,201,203,197,199,193,195,78,79,106,107,86,87,94,95,76,77,220,221,72,73,98,227,212,213,0,0,0,0,0,0,0,0,0,0,0,0,0,0,0,0,0,0,0,0,0,0,0,0,0,0,0,0,0,0,0,0,0,0,0,0,0,0,0,0,0,0,0,0,0},
  {0,1,2,3,0,1,2,3,0,1,2,3,4,5,6,7,8,9,10,11,12,13,14,15,64,67,72,77,69,73,78,76,70,66,74,79,65,68,75,71,0,2,8,10,1,3,9,11,12,14,4,6,13,15,5,7,12,14,8,10,13,15,9,11,0,2,4,6,1,3,5,7,4,6,8,10,0,2,5,7,9,11,12,14,1,3,13,15,136,138,128,130,137,139,129,131,140,142,141,143,132,134,133,135,78,79,64,65,66,67,84,85,68,69,90,91,104,105,70,71,210,211,100,101,106,107,222,223,66,71,70,77,69,73,72,64,65,78,67,75,79,74,76,68,8,10,12,14,0,2,9,11,13,15,1,3,4,6,5,7,8,10,0,2,9,11,12,14,1,3,4,6,13,15,5,7,12,14,8,10,4,6,0,2,13,15,9,11,5,7,1,3,4,6,12,14,8,10,5,7,141,143,0,2,137,139,1,3,92,93,108,109,98,99,80,81,100,101,70,71,116,117,96,97,74,75,64,65,112,113,82,83,106,107,212,213,232,233,0,0,0,0,0,0,0,0,0,0,0,0,0,0,0,0,0,0,0,0,0,0,0,0,0,0,0,0,0,0,0,0,0,0,0,0,0,0,0,0,0,0,0,0,0,0,0,0,0,0,0,0,0,0,0,0,0,0},
  {0,1,2,3,0,1,2,3,0,1,2,3,4,5,6,7,8,9,10,11,12,13,14,15,64,67,72,77,69,73,78,76,70,64,66,76,78,65,67,77,79,68,70,69,71,72,74,73,75,12,14,8,10,13,15,9,11,0,2,4,6,1,3,5,7,76,78,72,74,77,79,73,75,64,66,68,70,65,67,69,71,0,2,8,10,4,6,12,14,1,3,9,11,5,7,13,15,84,85,88,89,114,115,110,111,98,99,66,67,94,95,70,71,76,77,106,107,96,97,64,65,78,79,90,91,4,6,5,7,0,2,8,10,12,14,1,3,9,11,13,15,4,6,8,10,5,7,0,2,12,14,9,11,1,3,13,15,132,134,128,130,133,135,129,131,136,138,140,142,137,139,141,143,12,14,8,10,4,6,0,2,13,15,9,11,5,7,1,3,12,14,8,10,4,6,0,2,13,15,9,11,5,7,1,3,12,14,8,10,13,15,132,134,9,11,133,135,128,130,129,131,99,88,89,86,87,84,85,90,91,234,235,68,69,104,105,76,77,116,117,110,111,102,103,194,195,0,0,0,0,0,0,0,0,0,0,0,0,0,0,0,0,0,0,0,0,0,0,0,0,0,0,0,0,0,0,0,0,0,0,0,0,0,0,0,0,0,0,0,0,0,0,0,0,0,0},
  {0,1,2,3,0,1,2,3,0,1,2,3,4,5,6,7,8,9,10,11,12,13,14,15,79,75,77,73,0,1,2,3,4,5,6,7,8,9,10,11,12,13,14,15,0,2,8,10,1,3,9,11,12,14,4,6,13,15,5,7,4,6,8,10,0,2,5,7,9,11,12,14,1,3,13,15,4,6,12,14,8,10,0,2,5,7,13,15,9,11,1,3,136,138,128,130,137,139,129,131,140,142,141,143,132,134,133,135,136,138,128,130,137,139,129,131,140,142,141,143,132,134,133,135,4,6,5,7,12,14,8,10,0,2,13,15,9,11,1,3,12,14,4,6,0,2,13,15,5,7,8,10,1,3,9,11,8,10,12,14,0,2,9,11,13,15,1,3,4,6,5,7,8,10,9,11,4,6,0,2,12,14,5,7,1,3,13,15,4,6,5,7,8,10,12,14,9,11,13,15,0,2,1,3,4,6,12,14,8,10,5,7,13,15,0,2,9,11,1,3,109,86,87,114,115,98,99,66,67,84,85,96,97,74,75,102,103,80,81,96,97,76,77,218,219,236,237,0,0,0,0,0,0,0,0,0,0,0,0,0,0,0,0,0,0,0,0,0,0,0,0,0,0,0,0,0,0,0,0,0,0,0,0,0,0,0,0,0,0,0,0,0,0,0,0,0},
  {0,1,2,3,0,1,2,3,0,1,2,3,4,5,6,7,8,9,10,11,12,13,14,15,72,78,70,71,66,74,68,70,66,74,79,65,68,75,71,74,72,79,71,78,67,69,65,75,77,68,73,12,14,8,10,13,15,9,11,0,2,4,6,1,3,5,7,4,6,12,14,8,10,0,2,5,7,13,15,9,11,1,3,4,6,8,10,0,2,5,7,9,11,12,14,1,3,13,15,68,69,82,83,98,99,108,109,92,93,78,79,84,85,100,101,66,67,74,75,86,87,92,93,118,119,68,69,216,217,198,199,206,207,246,247,194,195,238,239,242,243,232,233,8,10,12,14,0,2,9,11,13,15,1,3,4,6,5,7,8,10,0,2,9,11,12,14,1,3,4,6,13,15,5,7,4,6,5,7,8,10,12,14,9,11,13,15,0,2,1,3,132,134,140,142,136,138,133,135,141,143,128,130,137,139,129,131,106,107,104,105,92,93,88,89,72,73,90,91,100,101,78,79,116,117,64,65,118,119,208,209,94,95,76,77,240,241,238,239,0,0,0,0,0,0,0,0,0,0,0,0,0,0,0,0,0,0,0,0,0,0,0,0,0,0,0,0,0,0,0,0,0,0,0,0,0,0,0,0,0,0,0,0,0,0,0,0,0,0,0,0,0,0,0,0,0},
  {0,1,2,3,0,1,2,3,0,1,2,3,4,5,6,7,8,9,10,11,12,13,14,15,0,1,2,3,0,1,2,3,4,5,6,7,8,9,10,11,12,13,14,15,76,69,70,72,74,66,71,75,67,77,68,73,79,206,64,65,12,14,8,10,13,15,9,11,0,2,4,6,1,3,5,7,0,2,8,10,4,6,12,14,1,3,9,11,5,7,13,15,0,2,8,10,4,6,12,14,1,3,9,11,5,7,13,15,136,138,128,130,137,139,129,131,140,142,141,143,132,134,133,135,12,14,4,6,13,15,0,2,8,10,5,7,1,3,9,11,0,2,1,3,4,6,8,10,12,14,5,7,9,11,13,15,8,10,12,14,0,2,9,11,13,15,1,3,4,6,5,7,8,10,0,2,9,11,12,14,1,3,4,6,13,15,5,7,4,6,5,7,8,10,12,14,9,11,13,15,0,2,1,3,4,6,140,142,136,138,5,7,141,143,0,2,137,139,129,131,75,98,99,66,67,80,81,92,93,114,115,112,113,88,89,110,111,82,83,68,69,104,105,108,109,102,103,244,245,0,0,0,0,0,0,0,0,0,0,0,0,0,0,0,0,0,0,0,0,0,0,0,0,0,0,0,0,0,0,0,0,0,0,0,0,0,0,0,0,0,0,0,0,0,0,0},
  {0,1,2,3,0,1,2,3,4,5,6,7,8,9,10,11,12,13,14,15,69,76,67,65,0,2,12,14,1,3,13,15,4,6,5,7,8,10,9,11,12,14,8,10,13,15,9,11,0,2,4,6,1,3,5,7,67,108,109,86,87,96,97,82,83,74,75,110,111,76,77,88,89,118,119,68,69,100,101,104,105,102,103,90,91,136,138,128,130,137,139,129,131,140,142,141,143,132,134,133,135,0,2,4,6,8,10,1,3,5,7,12,14,9,11,13,15,4,6,5,7,12,14,8,10,0,2,13,15,9,11,1,3,12,14,4,6,0,2,13,15,5,7,8,10,1,3,9,11,132,134,128,130,133,135,129,131,136,138,140,142,137,139,141,143,8,10,9,11,4,6,0,2,12,14,5,7,1,3,13,15,4,6,12,14,8,10,5,7,13,15,9,11,0,2,1,3,12,14,8,10,4,6,0,2,13,15,9,11,5,7,1,3,80,81,96,97,92,93,108,109,70,71,82,83,100,101,206,207,74,75,114,115,94,95,118,119,200,201,192,0,0,0,0,0,0,0,0,0,0,0,0,0,0,0,0,0,0,0,0,0,0,0,0,0,0,0,0,0,0,0,0,0,0,0,0,0,0,0,0,0,0,0,0,0,0,0,0,0,0,0,0,0,0,0,0},
  {0,1,2,3,0,1,2,3,4,5,6,7,8,9,10,11,12,13,14,15,64,79,75,77,73,69,76,67,65,64,74,76,66,68,70,65,72,79,67,69,71,78,75,77,73,12,14,8,10,13,15,9,11,0,2,4,6,1,3,5,7,4,6,12,14,8,10,0,2,5,7,13,15,9,11,1,3,76,77,88,89,106,107,78,79,96,97,108,109,114,115,100,101,74,75,116,117,118,119,82,83,112,113,98,72,73,80,81,98,99,74,75,110,111,112,113,86,87,92,93,4,6,5,7,0,2,8,10,12,14,1,3,9,11,13,15,12,14,4,6,0,2,13,15,5,7,8,10,1,3,9,11,8,10,12,14,0,2,9,11,13,15,1,3,4,6,5,7,8,10,9,11,4,6,0,2,12,14,5,7,1,3,13,15,4,6,5,7,8,10,12,14,9,11,13,15,0,2,1,3,132,134,133,135,136,138,140,142,137,139,141,143,128,130,129,131,90,91,106,107,92,93,116,117,72,73,76,77,108,109,110,111,208,209,70,71,66,67,202,203,226,0,0,0,0,0,0,0,0,0,0,0,0,0,0,0,0,0,0,0,0,0,0,0,0,0,0,0,0,0,0,0,0,0,0,0,0,0,0,0,0,0,0,0,0,0,0,0,0,0,0,0,0,0,0,0},
  {64,65,66,67,68,69,70,71,72,73,74,75,76,77,78,79,0,1,2,3,0,1,2,3,64,65,66,67,68,69,70,71,72,73,74,75,76,77,78,79,72,76,64,70,66,74,71,78,67,79,65,197,75,68,73,77,4,6,0,2,5,7,1,3,12,14,8,10,13,15,9,11,4,6,12,14,8,10,0,2,5,7,13,15,9,11,1,3,68,70,72,74,64,66,69,71,73,75,76,78,65,67,77,79,136,138,128,130,137,139,129,131,140,142,141,143,132,134,133,135,76,77,108,109,112,113,82,83,226,227,100,101,64,65,200,201,208,209,202,203,212,213,214,215,71,69,72,78,64,77,75,74,79,73,67,8,10,12,14,0,2,9,11,13,15,1,3,4,6,5,7,8,10,9,11,4,6,0,2,12,14,5,7,1,3,13,15,4,6,12,14,8,10,5,7,13,15,9,11,0,2,1,3,132,134,140,142,136,138,133,135,141,143,128,130,137,139,129,131,64,65,84,85,92,93,104,105,74,75,78,79,100,101,82,83,72,73,116,117,222,223,234,235,198,0,0,0,0,0,0,0,0,0,0,0,0,0,0,0,0,0,0,0,0,0,0,0,0,0,0,0,0,0,0,0,0,0,0,0,0,0,0,0,0,0,0,0,0,0,0,0,0,0,0,0,0},
  {0,1,2,3,4,5,6,7,8,9,10,11,12,13,14,15,0,1,2,3,64,65,66,67,68,69,70,71,72,73,74,75,76,77,78,79,64,66,76,78,65,67,77,79,68,70,69,71,72,74,73,75,4,6,0,2,5,7,1,3,12,14,8,10,13,15,9,11,4,6,8,10,0,2,5,7,9,11,12,14,1,3,13,15,0,2,8,10,4,6,12,14,1,3,9,11,5,7,13,15,136,138,128,130,137,139,129,131,140,142,141,143,132,134,133,135,64,66,68,70,72,74,65,67,69,71,76,78,73,75,77,79,68,70,69,71,76,78,72,74,64,66,77,79,73,75,65,67,64,71,78,77,69,72,75,70,74,79,76,73,68,67,66,65,8,10,0,2,9,11,12,14,1,3,4,6,13,15,5,7,4,6,5,7,8,10,12,14,9,11,13,15,0,2,1,3,132,134,140,142,136,138,133,135,141,143,128,130,137,139,129,131,106,107,104,105,92,93,88,89,72,73,90,91,100,101,78,79,84,85,80,81,66,67,90,91,96,97,242,243,202,203,198,199,0,0,0,0,0,0,0,0,0,0,0,0,0,0,0,0,0,0,0,0,0,0,0,0,0,0,0,0,0,0,0,0,0,0,0,0,0,0,0,0,0,0,0,0,0,0,0,0,0,0,0,0},
  {64,65,66,67,68,69,70,71,72,73,74,75,76,77,78,79,0,1,2,3,64,65,66,67,68,69,70,71,72,73,74,75,76,77,78,79,64,66,76,78,65,67,77,79,68,70,69,71,72,74,73,75,64,66,72,74,65,67,73,75,76,78,68,70,77,79,69,71,4,6,8,10,0,2,5,7,9,11,12,14,1,3,13,15,80,81,108,109,110,111,104,105,0,2,8,10,4,6,12,14,1,3,9,11,5,7,13,15,0,2,4,6,8,10,1,3,5,7,12,14,9,11,13,15,4,6,5,7,12,14,8,10,0,2,13,15,9,11,1,3,71,72,69,66,64,78,74,77,76,75,73,8,10,12,14,0,2,9,11,13,15,1,3,4,6,5,7,8,10,0,2,9,11,12,14,1,3,4,6,13,15,5,7,4,6,5,7,8,10,12,14,9,11,13,15,0,2,1,3,132,134,140,142,136,138,133,135,141,143,128,130,137,139,129,131,64,65,78,79,90,91,106,107,94,95,68,69,96,97,74,75,98,99,66,67,80,81,220,221,242,243,112,113,216,217,236,0,0,0,0,0,0,0,0,0,0,0,0,0,0,0,0,0,0,0,0,0,0,0,0,0,0,0,0,0,0,0,0,0,0,0,0,0,0,0,0,0,0,0,0,0,0,0,0,0,0},
  {64,65,66,67,68,69,70,71,72,73,74,75,76,77,78,79,0,1,2,3,0,1,2,3,4,5,6,7,8,9,10,11,12,13,14,15,0,1,2,3,76,69,70,72,74,66,71,75,67,77,68,73,79,78,64,65,4,6,0,2,5,7,1,3,12,14,8,10,13,15,9,11,0,2,8,10,4,6,12,14,1,3,9,11,5,7,13,15,108,109,114,115,100,101,74,75,116,117,118,119,82,83,112,113,98,99,102,103,68,69,110,111,104,105,0,2,4,6,8,10,1,3,5,7,12,14,9,11,13,15,4,6,5,7,12,14,8,10,0,2,13,15,9,11,1,3,64,66,65,67,68,70,72,74,76,78,69,71,73,75,77,79,132,134,128,130,133,135,129,131,136,138,140,142,137,139,141,143,8,10,9,11,4,6,0,2,12,14,5,7,1,3,13,15,4,6,5,7,8,10,12,14,9,11,13,15,0,2,1,3,4,6,12,14,8,10,5,7,13,15,0,2,9,11,1,3,105,72,73,86,87,102,103,90,91,118,119,68,69,78,79,114,115,66,67,110,111,94,95,216,217,204,205,0,0,0,0,0,0,0,0,0,0,0,0,0,0,0,0,0,0,0,0,0,0,0,0,0,0,0,0,0,0,0,0,0,0,0,0,0,0,0,0,0,0,0},
  {64,65,66,67,68,69,70,71,72,73,74,75,76,77,78,79,64,65,66,67,68,69,70,71,72,73,74,75,76,77,78,79,0,1,2,3,0,1,2,3,4,5,6,7,8,9,10,11,12,13,14,15,198,197,194,199,204,203,206,4,6,0,2,5,7,1,3,12,14,8,10,13,15,9,11,0,2,8,10,4,6,12,14,1,3,9,11,5,7,13,15,136,138,128,130,9,11,129,131,140,142,141,143,132,134,133,135,136,138,128,130,137,139,129,131,140,142,141,143,132,134,133,135,12,14,4,6,13,15,0,2,8,10,5,7,1,3,9,11,0,2,1,3,4,6,8,10,12,14,5,7,9,11,13,15,8,10,12,14,0,2,9,11,13,15,1,3,4,6,5,7,8,10,9,11,4,6,0,2,12,14,5,7,1,3,13,15,12,14,8,10,4,6,0,2,13,15,9,11,5,7,1,3,12,14,8,10,13,15,4,6,9,11,5,7,0,2,1,3,118,119,76,77,74,75,68,69,72,73,100,101,110,111,84,85,206,207,116,117,94,95,242,243,86,87,240,241,226,227,0,0,0,0,0,0,0,0,0,0,0,0,0,0,0,0,0,0,0,0,0,0,0,0,0,0,0,0,0,0,0,0,0,0,0,0,0,0,0,0,0,0,0,0,0,0,0},
  {64,65,66,67,68,69,70,71,72,73,74,75,76,77,78,79,0,1,2,3,4,5,6,7,8,9,10,11,12,13,14,15,0,1,2,3,64,66,76,78,65,67,77,79,68,70,69,71,72,74,73,75,4,6,0,2,5,7,1,3,12,14,8,10,13,15,9,11,4,6,12,14,8,10,0,2,5,7,13,15,9,11,1,3,97,108,109,114,115,100,101,74,75,116,117,118,119,82,83,112,113,98,99,102,103,68,69,110,111,104,105,114,115,102,103,98,99,100,101,90,91,70,71,76,77,68,69,110,193,200,201,208,209,202,203,212,213,214,215,222,223,244,245,234,235,224,225,8,10,12,14,0,2,9,11,13,15,1,3,4,6,5,7,8,10,0,2,9,11,12,14,1,3,4,6,13,15,5,7,4,6,12,14,8,10,5,7,13,15,9,11,0,2,1,3,4,6,5,7,8,10,140,142,9,11,13,15,0,2,1,3,90,91,106,107,92,93,116,117,72,73,76,77,108,109,110,111,80,81,70,71,66,67,74,75,98,99,102,103,214,215,0,0,0,0,0,0,0,0,0,0,0,0,0,0,0,0,0,0,0,0,0,0,0,0,0,0,0,0,0,0,0,0,0,0,0,0,0,0,0,0,0,0,0,0,0,0,0,0,0,0,0,0,0,0,0},
  {0,1,2,3,0,1,2,3,0,1,2,3,4,5,6,7,8,9,10,11,12,13,14,15,0,1,2,3,74,66,76,79,70,72,64,67,71,69,78,68,75,65,77,73,0,2,8,10,1,3,9,11,12,14,4,6,13,15,5,7,203,206,200,202,196,201,207,205,195,192,193,0,2,8,10,4,6,12,14,1,3,9,11,5,7,13,15,4,6,12,14,8,10,0,2,5,7,13,15,137,139,129,131,112,113,84,85,88,89,66,67,78,79,92,93,72,73,80,81,106,107,116,117,236,237,64,65,94,95,4,6,5,7,0,2,8,10,12,14,1,3,9,11,13,15,4,6,8,10,5,7,0,2,12,14,9,11,1,3,13,15,72,74,76,78,64,66,73,75,77,79,65,67,68,70,69,71,72,79,194,76,192,67,202,196,199,206,198,197,205,201,193,203,12,14,8,10,13,15,4,6,9,11,5,7,0,2,1,3,90,91,106,107,92,93,116,117,72,73,76,77,108,109,110,111,80,81,70,71,66,67,74,75,98,82,83,68,69,104,105,108,109,102,103,244,245,0,0,0,0,0,0,0,0,0,0,0,0,0,0,0,0,0,0,0,0,0,0,0,0,0,0,0,0,0,0,0,0,0,0,0,0,0,0,0,0,0,0,0,0,0,0,0,0,0,0},
  {0,1,2,3,0,1,2,3,4,5,6,7,8,9,10,11,12,13,14,15,0,1,2,3,74,66,76,79,70,72,64,67,71,69,78,68,75,65,77,73,0,2,8,10,1,3,9,11,12,14,4,6,13,15,5,7,4,6,0,2,5,7,1,3,12,14,8,10,13,15,9,11,202,196,201,207,205,195,192,193,90,91,70,71,72,73,66,67,64,65,84,85,92,93,80,81,86,87,94,95,84,85,88,89,114,115,110,111,98,99,66,67,94,95,70,71,76,77,106,107,96,97,64,65,215,222,223,244,245,234,235,224,225,216,217,198,199,206,4,6,8,10,5,7,0,2,12,14,9,11,1,3,13,15,132,134,128,130,133,135,129,131,136,138,140,142,137,139,141,143,72,79,194,76,192,67,202,196,199,206,198,197,205,201,193,203,12,14,8,10,13,15,4,6,9,11,5,7,0,2,1,3,4,6,12,14,136,138,5,7,13,15,128,130,137,139,129,131,80,81,92,93,108,109,106,107,70,71,66,67,90,91,88,89,82,83,224,225,232,233,230,231,0,0,0,0,0,0,0,0,0,0,0,0,0,0,0,0,0,0,0,0,0,0,0,0,0,0,0,0,0,0,0,0,0,0,0,0,0,0,0,0,0,0,0,0,0,0,0,0,0,0,0,0,0,0},
  {64,65,66,67,68,69,70,71,72,73,74,75,76,77,78,79,0,1,2,3,4,5,6,7,8,9,10,11,12,13,14,15,64,65,66,67,68,69,70,71,72,73,74,75,76,77,78,79,0,2,8,10,1,3,9,11,12,14,4,6,13,15,5,7,4,6,0,2,5,7,1,3,12,14,8,10,13,15,9,11,0,2,8,10,4,6,12,14,1,3,9,11,5,7,13,15,119,82,83,112,113,98,99,102,103,68,69,110,111,104,105,200,202,192,194,201,203,193,195,204,206,205,207,196,198,197,199,66,71,70,77,69,73,72,64,65,78,67,75,79,74,76,68,76,78,68,70,64,66,77,79,69,71,72,74,65,67,73,75,132,134,128,130,133,135,129,131,136,138,140,142,137,139,141,143,78,74,77,71,70,64,194,69,207,200,75,196,204,73,195,65,12,14,8,10,13,15,4,6,9,11,5,7,0,2,1,3,72,74,64,66,73,75,76,78,65,67,196,198,77,79,197,199,68,69,96,97,74,75,98,99,66,67,80,81,92,93,114,115,112,113,88,89,108,109,246,247,0,0,0,0,0,0,0,0,0,0,0,0,0,0,0,0,0,0,0,0,0,0,0,0,0,0,0,0,0,0,0,0,0,0,0,0,0,0,0,0,0,0,0,0,0,0,0,0,0},
  {0,1,2,3,4,5,6,7,8,9,10,11,12,13,14,15,64,65,66,67,68,69,70,71,72,73,74,75,76,77,78,79,0,1,2,3,72,76,64,70,66,74,71,78,67,79,65,197,75,68,73,77,12,14,8,10,13,15,9,11,0,2,4,6,1,3,5,7,108,109,86,87,96,97,82,83,74,75,110,111,76,77,88,89,118,119,68,69,100,101,104,105,102,103,90,91,136,138,128,130,137,139,129,131,140,142,141,143,132,134,133,135,76,77,68,69,110,111,82,83,74,75,96,97,118,119,104,105,4,6,5,7,0,2,8,10,12,14,1,3,9,11,13,15,4,6,8,10,5,7,0,2,12,14,9,11,1,3,13,15,8,10,0,2,9,11,12,14,1,3,4,6,13,15,5,7,12,14,8,10,4,6,0,2,13,15,9,11,5,7,1,3,12,14,8,10,13,15,132,134,9,11,5,7,0,2,1,3,136,138,9,11,132,134,0,2,140,142,133,135,129,131,141,143,79,74,75,114,115,94,95,118,119,72,73,64,208,209,96,97,76,77,218,219,236,237,0,0,0,0,0,0,0,0,0,0,0,0,0,0,0,0,0,0,0,0,0,0,0,0,0,0,0,0,0,0,0,0,0,0,0,0,0,0,0,0,0,0,0,0,0,0,0,0,0,0},
  {64,65,66,67,68,69,70,71,72,73,74,75,76,77,78,79,0,1,2,3,0,1,2,3,66,74,68,64,66,74,79,65,68,75,71,72,76,64,70,66,74,71,78,67,79,65,69,75,68,73,77,4,6,0,2,5,7,1,3,12,14,8,10,13,15,9,11,70,71,64,65,98,99,92,93,78,79,112,113,94,95,72,73,80,81,84,85,114,115,116,117,106,107,66,67,108,136,138,128,130,137,139,129,131,140,142,141,143,132,134,133,135,12,14,4,6,13,15,0,2,8,10,5,7,1,3,9,11,4,6,5,7,12,14,8,10,0,2,13,15,9,11,1,3,76,78,4,6,0,2,13,15,5,7,8,10,1,3,9,11,8,10,0,2,9,11,12,14,1,3,4,6,13,15,5,7,12,14,8,10,4,6,0,2,13,15,9,11,5,7,1,3,12,14,8,10,13,15,4,6,9,11,5,7,0,2,1,3,92,93,108,109,98,99,80,81,100,101,70,71,116,117,96,97,74,75,64,65,112,113,82,83,234,235,84,85,104,112,113,228,229,192,193,216,217,246,247,0,0,0,0,0,0,0,0,0,0,0,0,0,0,0,0,0,0,0,0,0,0,0,0,0,0,0,0,0,0,0,0,0,0,0,0,0,0,0,0,0,0,0,0,0,0,0,0,0},
  {0,1,2,3,4,5,6,7,8,9,10,11,12,13,14,15,0,1,2,3,0,1,2,3,4,5,6,7,8,9,10,11,12,13,14,15,74,66,76,79,70,72,64,67,71,69,78,68,75,65,77,73,198,194,204,206,200,202,196,192,4,6,0,2,5,7,1,3,12,14,8,10,13,15,9,11,4,6,8,10,0,2,5,7,9,11,12,14,1,3,13,15,136,138,128,130,137,139,129,131,140,142,141,143,132,134,133,135,88,89,76,77,96,97,86,87,72,73,116,117,110,111,12,14,4,6,13,15,0,2,8,10,5,7,1,3,9,11,219,220,221,230,231,196,197,4,6,8,10,5,7,0,2,12,14,9,11,1,3,13,15,8,10,0,2,9,11,12,14,1,3,4,6,13,15,5,7,12,14,8,10,4,6,0,2,13,15,9,11,5,7,1,3,12,14,8,10,13,15,4,6,9,11,5,7,0,2,1,3,12,14,8,10,132,134,0,2,13,15,9,11,133,135,1,3,64,65,84,85,92,93,104,105,74,75,206,207,100,101,82,83,200,201,116,117,222,223,0,0,0,0,0,0,0,0,0,0,0,0,0,0,0,0,0,0,0,0,0,0,0,0,0,0,0,0,0,0,0,0,0,0,0,0,0,0,0,0,0,0,0,0,0,0,0,0,0},
  {0,1,2,3,4,5,6,7,8,9,10,11,12,13,14,15,64,65,66,67,68,69,70,71,72,73,74,75,76,77,78,79,0,1,2,3,64,66,76,78,65,67,77,79,68,70,69,71,72,74,73,75,12,14,8,10,13,15,9,11,0,2,4,6,1,3,5,7,4,6,12,14,8,10,0,2,5,7,13,15,9,11,1,3,0,2,8,10,4,6,12,14,1,3,9,11,5,7,13,15,112,113,84,85,88,89,66,67,78,79,92,93,72,73,80,81,106,107,116,117,108,109,64,65,94,95,86,87,4,6,5,7,12,14,8,10,0,2,13,15,9,11,1,3,4,6,8,10,5,7,0,2,12,14,9,11,1,3,13,15,132,134,128,130,133,135,129,131,136,138,140,142,137,139,141,143,200,207,194,204,192,195,202,196,199,206,198,197,205,201,193,203,4,6,12,14,8,10,5,7,13,15,9,11,0,2,1,3,4,6,5,7,136,138,140,142,9,11,141,143,128,130,129,131,82,83,70,71,68,69,102,103,108,109,86,87,114,115,98,99,66,67,84,85,224,225,202,203,0,0,0,0,0,0,0,0,0,0,0,0,0,0,0,0,0,0,0,0,0,0,0,0,0,0,0,0,0,0,0,0,0,0,0,0,0,0,0,0,0,0,0,0,0,0,0,0},
  {64,65,66,67,68,69,70,71,72,73,74,75,76,77,78,79,0,1,2,3,0,1,2,3,4,5,6,7,8,9,10,11,12,13,14,15,64,66,76,78,65,67,77,79,68,70,69,71,72,74,73,75,4,6,0,2,5,7,1,3,12,14,8,10,13,15,9,11,200,202,196,201,207,205,195,192,193,96,97,114,115,76,77,70,71,86,87,90,91,74,75,66,67,68,69,80,81,108,109,110,111,104,105,78,79,90,91,80,81,102,103,104,105,108,109,112,113,72,73,116,117,82,83,100,101,74,204,205,236,237,240,241,210,211,226,227,228,229,192,12,14,4,6,0,2,13,15,5,7,8,10,1,3,9,11,64,71,70,74,8,10,0,2,9,11,12,14,1,3,4,6,13,15,5,7,12,14,8,10,4,6,0,2,13,15,9,11,5,7,1,3,12,14,8,10,13,15,4,6,9,11,5,7,0,2,1,3,80,81,96,97,92,93,108,109,70,71,82,83,100,101,78,79,74,75,114,115,94,95,118,119,72,73,64,112,113,228,229,192,193,216,217,246,247,0,0,0,0,0,0,0,0,0,0,0,0,0,0,0,0,0,0,0,0,0,0,0,0,0,0,0,0,0,0,0,0,0,0,0,0,0,0,0,0,0,0,0,0,0,0,0,0,0,0,0,0},
  {64,65,66,67,68,69,70,71,72,73,74,75,76,77,78,79,0,1,2,3,0,1,2,3,4,5,6,7,8,9,10,11,12,13,14,15,64,66,76,78,65,67,77,79,68,70,69,71,72,74,73,75,4,6,0,2,5,7,1,3,12,14,8,10,13,15,9,11,4,6,12,14,8,10,0,2,5,7,13,15,9,11,1,3,0,2,8,10,4,6,12,14,1,3,9,11,5,7,13,15,136,138,128,130,137,139,129,131,140,142,141,143,132,134,133,135,12,14,4,6,13,15,0,2,8,10,5,7,1,3,9,11,68,70,69,71,76,78,72,74,64,66,77,79,73,75,65,67,79,68,65,67,70,8,10,12,14,0,2,9,11,13,15,1,3,4,6,5,7,8,10,9,11,4,6,0,2,12,14,5,7,1,3,13,15,4,6,12,14,8,10,5,7,13,15,9,11,0,2,1,3,132,134,140,142,136,138,133,135,141,143,128,130,137,139,129,131,118,119,76,77,74,75,68,69,72,73,100,101,110,111,84,85,206,207,116,117,94,95,242,243,214,215,240,241,226,0,0,0,0,0,0,0,0,0,0,0,0,0,0,0,0,0,0,0,0,0,0,0,0,0,0,0,0,0,0,0,0,0,0,0,0,0,0,0,0,0,0,0,0,0,0,0,0,0,0},
  {0,1,2,3,4,5,6,7,8,9,10,11,12,13,14,15,0,1,2,3,4,5,6,7,8,9,10,11,12,13,14,15,70,64,76,66,74,72,79,71,78,67,69,65,75,77,68,73,0,2,8,10,1,3,9,11,12,14,4,6,13,15,5,7,4,6,0,2,5,7,1,3,12,14,8,10,13,15,9,11,0,2,8,10,4,6,12,14,1,3,9,11,5,7,13,15,136,138,128,130,137,139,129,131,140,142,141,143,132,134,133,135,112,113,84,85,88,89,66,67,78,79,76,78,68,70,77,79,64,66,72,74,69,71,65,67,73,75,12,14,4,6,0,2,13,15,5,7,8,10,1,3,9,11,8,10,12,14,0,2,9,11,13,15,1,3,4,6,5,7,8,10,9,11,4,6,0,2,12,14,5,7,1,3,13,15,4,6,12,14,8,10,5,7,13,15,9,11,0,2,1,3,4,6,12,14,8,10,5,7,13,15,9,11,128,130,1,3,89,108,109,118,119,82,83,70,71,100,101,102,103,84,85,116,117,72,73,214,215,238,239,232,233,204,205,0,0,0,0,0,0,0,0,0,0,0,0,0,0,0,0,0,0,0,0,0,0,0,0,0,0,0,0,0,0,0,0,0,0,0,0,0,0,0,0,0,0,0,0,0,0,0,0,0,0,0},
  {64,65,66,67,68,69,70,71,72,73,74,75,76,77,78,79,0,1,2,3,4,5,6,7,8,9,10,11,12,13,14,15,0,1,2,3,4,5,6,7,8,9,10,11,12,13,14,15,198,197,194,199,204,203,206,200,4,6,0,2,5,7,1,3,12,14,8,10,13,15,9,11,0,2,8,10,4,6,12,14,1,3,9,11,5,7,13,15,70,71,86,87,90,91,74,75,66,67,68,69,80,81,108,109,110,111,104,105,0,2,4,6,8,10,1,3,5,7,12,14,9,11,13,15,4,6,5,7,12,14,8,10,0,2,13,15,9,11,1,3,0,2,1,3,4,6,8,10,12,14,5,7,9,11,13,15,8,10,12,14,0,2,9,11,13,15,1,3,4,6,5,7,8,10,0,2,9,11,12,14,1,3,4,6,13,15,5,7,4,6,5,7,8,10,12,14,9,11,13,15,0,2,1,3,4,6,12,14,8,10,5,7,13,15,0,2,9,11,1,3,64,65,78,79,90,91,106,107,94,95,68,69,96,97,74,75,98,99,66,67,208,209,92,93,242,243,240,241,216,0,0,0,0,0,0,0,0,0,0,0,0,0,0,0,0,0,0,0,0,0,0,0,0,0,0,0,0,0,0,0,0,0,0,0,0,0,0,0,0,0,0,0,0,0,0,0},
  {0,1,2,3,4,5,6,7,8,9,10,11,12,13,14,15,64,65,66,67,68,69,70,71,72,73,74,75,76,77,78,79,0,1,2,3,4,5,6,7,8,9,10,11,12,13,14,15,0,2,8,10,1,3,9,11,12,14,4,6,13,15,5,7,197,199,203,201,207,205,195,193,4,6,12,14,8,10,0,2,5,7,13,15,9,11,1,3,88,89,94,95,116,117,118,119,106,107,78,79,82,83,112,113,84,85,102,136,138,128,130,137,139,129,131,140,142,141,143,132,134,133,135,66,71,70,77,69,73,72,64,65,78,67,75,79,74,76,68,12,14,4,6,0,2,13,15,5,7,8,10,1,3,9,11,8,10,12,14,0,2,9,11,13,15,1,3,4,6,5,7,8,10,9,11,4,6,0,2,12,14,5,7,1,3,13,15,4,6,12,14,8,10,5,7,13,15,9,11,0,2,1,3,4,6,12,14,136,138,5,7,13,15,137,139,128,130,129,131,90,91,106,107,92,93,116,117,72,73,76,77,108,109,110,111,80,81,198,199,66,67,202,203,226,0,0,0,0,0,0,0,0,0,0,0,0,0,0,0,0,0,0,0,0,0,0,0,0,0,0,0,0,0,0,0,0,0,0,0,0,0,0,0,0,0,0,0,0,0,0,0,0,0,0,0,0},
  {64,65,66,67,68,69,70,71,72,73,74,75,76,77,78,79,0,1,2,3,4,5,6,7,8,9,10,11,12,13,14,15,72,78,70,71,64,66,76,78,65,67,77,79,68,70,69,71,72,74,73,75,12,14,8,10,13,15,9,11,0,2,4,6,1,3,5,7,109,86,87,96,97,82,83,74,75,110,111,76,77,88,89,118,119,68,69,100,101,104,105,102,103,90,91,64,65,70,71,80,81,112,113,90,91,102,103,118,119,104,105,114,115,106,107,94,95,68,69,12,14,4,6,13,15,0,2,8,10,5,7,1,3,9,11,0,2,1,3,4,6,8,10,12,14,5,7,9,11,13,15,76,70,68,66,65,8,10,12,14,0,2,9,11,13,15,1,3,4,6,5,7,8,10,9,11,4,6,0,2,12,14,5,7,1,3,13,15,4,6,12,14,8,10,5,7,13,15,9,11,0,2,1,3,132,134,140,142,136,138,133,135,141,143,128,130,137,139,129,131,109,118,119,82,83,70,71,100,101,102,103,84,85,116,117,72,73,86,87,110,111,232,233,204,205,0,0,0,0,0,0,0,0,0,0,0,0,0,0,0,0,0,0,0,0,0,0,0,0,0,0,0,0,0,0,0,0,0,0,0,0,0,0,0,0,0,0,0,0,0,0,0,0,0,0,0},
  {64,65,66,67,68,69,70,71,72,73,74,75,76,77,78,79,0,1,2,3,0,1,2,3,4,5,6,7,8,9,10,11,12,13,14,15,64,66,76,78,65,67,77,79,68,70,69,71,72,74,73,75,64,66,72,74,65,67,73,75,76,78,68,70,77,79,69,71,70,71,64,65,98,99,92,93,78,79,112,113,94,95,72,73,80,81,84,85,114,115,116,117,106,107,66,67,108,109,86,87,64,65,70,71,80,81,112,113,90,91,102,103,118,119,104,105,114,115,106,107,94,95,4,6,5,7,12,14,8,10,0,2,13,15,9,11,1,3,0,2,1,3,4,6,8,10,12,14,5,7,9,11,13,15,8,10,12,14,0,2,9,11,13,15,1,3,4,6,5,7,8,10,9,11,4,6,0,2,12,14,5,7,1,3,13,15,4,6,5,7,8,10,12,14,9,11,13,15,0,2,1,3,4,6,12,14,8,10,5,7,13,15,0,2,9,11,1,3,85,104,105,72,73,86,87,102,103,90,91,118,119,68,69,206,207,114,115,66,67,110,111,94,95,216,217,204,205,0,0,0,0,0,0,0,0,0,0,0,0,0,0,0,0,0,0,0,0,0,0,0,0,0,0,0,0,0,0,0,0,0,0,0,0,0,0,0,0,0,0,0,0,0,0,0,0,0},
  {0,1,2,3,4,5,6,7,8,9,10,11,12,13,14,15,0,1,2,3,4,5,6,7,8,9,10,11,12,13,14,15,0,1,2,3,4,5,6,7,8,9,10,11,12,13,14,15,0,2,8,10,1,3,9,11,12,14,4,6,13,15,5,7,4,6,12,14,8,10,0,2,5,7,13,15,9,11,1,3,4,6,0,2,5,7,1,3,12,14,8,10,13,15,9,11,0,2,8,10,4,6,12,14,1,3,137,139,5,7,141,143,0,2,4,6,8,10,1,3,5,7,12,14,9,11,13,15,4,6,5,7,12,14,8,10,0,2,13,15,9,11,1,3,0,2,1,3,4,6,8,10,12,14,5,7,9,11,13,15,8,10,12,14,0,2,9,11,13,15,1,3,4,6,5,7,8,10,9,11,4,6,0,2,12,14,5,7,1,3,13,15,4,6,12,14,8,10,5,7,13,15,9,11,0,2,1,3,4,6,140,142,136,138,5,7,141,143,128,130,137,139,129,131,108,109,118,119,82,83,70,71,100,101,102,103,84,85,116,117,72,73,86,87,110,111,232,233,204,205,0,0,0,0,0,0,0,0,0,0,0,0,0,0,0,0,0,0,0,0,0,0,0,0,0,0,0,0,0,0,0,0,0,0,0,0,0,0,0,0,0,0,0,0,0,0},
  {0,1,2,3,4,5,6,7,8,9,10,11,12,13,14,15,0,1,2,3,4,5,6,7,8,9,10,11,12,13,14,15,74,66,76,79,70,72,64,67,71,69,78,68,75,65,77,73,0,2,8,10,1,3,9,11,12,14,4,6,13,15,5,7,0,2,8,10,4,6,12,14,1,3,9,11,5,7,13,15,4,6,8,10,0,2,5,7,9,11,12,14,1,3,13,15,136,138,128,130,137,139,129,131,140,142,141,143,132,134,133,135,86,87,114,115,102,103,98,99,100,101,90,91,70,71,204,205,68,206,207,246,247,194,195,238,239,242,243,232,233,218,76,78,68,70,64,66,77,79,69,71,72,74,65,67,73,75,8,10,0,2,9,11,12,14,1,3,4,6,13,15,5,7,12,14,8,10,4,6,0,2,13,15,9,11,5,7,1,3,12,14,8,10,13,15,4,6,9,11,5,7,0,2,1,3,110,111,82,83,70,71,68,69,102,103,108,109,86,87,114,115,98,99,66,67,84,85,96,97,74,75,103,208,209,96,97,76,77,218,219,236,237,0,0,0,0,0,0,0,0,0,0,0,0,0,0,0,0,0,0,0,0,0,0,0,0,0,0,0,0,0,0,0,0,0,0,0,0,0,0,0,0,0,0,0,0,0,0,0,0,0,0,0,0,0},
  {0,1,2,3,4,5,6,7,8,9,10,11,12,13,14,15,0,1,2,3,0,1,2,3,4,5,6,7,8,9,10,11,12,13,14,15,64,66,76,78,65,67,77,79,68,70,69,71,72,74,73,75,12,14,8,10,13,15,9,11,0,2,4,6,1,3,5,7,4,6,0,2,5,7,1,3,12,14,8,10,13,15,9,11,4,6,8,10,0,2,5,7,9,11,12,14,1,3,13,15,136,138,128,130,137,139,129,131,140,142,141,143,132,134,133,135,108,109,204,205,88,89,114,115,96,97,102,103,116,117,246,247,0,2,1,3,4,6,8,10,12,14,5,7,9,11,13,15,8,10,12,14,0,2,9,11,13,15,1,3,4,6,5,7,8,10,9,11,4,6,0,2,12,14,5,7,1,3,13,15,12,14,8,10,4,6,0,2,13,15,9,11,5,7,1,3,132,134,140,142,136,138,133,135,141,143,128,130,137,139,129,131,99,102,103,86,87,104,105,78,79,118,119,114,115,88,89,112,113,100,101,64,65,84,85,94,95,224,225,210,211,196,197,0,0,0,0,0,0,0,0,0,0,0,0,0,0,0,0,0,0,0,0,0,0,0,0,0,0,0,0,0,0,0,0,0,0,0,0,0,0,0,0,0,0,0,0,0,0,0,0,0,0,0,0,0},
  {64,65,66,67,68,69,70,71,72,73,74,75,76,77,78,79,0,1,2,3,0,1,2,3,4,5,6,7,8,9,10,11,12,13,14,15,64,66,76,78,65,67,77,79,68,70,69,71,72,74,73,75,64,66,72,74,65,67,73,75,76,78,68,70,77,79,69,71,4,6,12,14,8,10,0,2,5,7,13,15,9,11,1,3,88,89,94,95,116,117,118,119,106,107,78,79,82,83,112,113,84,85,102,103,98,99,136,138,128,130,137,139,129,131,140,142,141,143,132,134,133,135,12,14,4,6,13,15,0,2,8,10,5,7,1,3,9,11,0,2,1,3,4,6,8,10,12,14,5,7,9,11,13,15,8,10,12,14,0,2,9,11,13,15,1,3,4,6,5,7,8,10,9,11,4,6,0,2,12,14,5,7,1,3,13,15,4,6,5,7,8,10,12,14,9,11,13,15,0,2,1,3,4,6,12,14,8,10,5,7,13,15,0,2,9,11,1,3,69,102,103,108,109,86,87,114,115,98,99,66,67,84,85,96,97,74,75,68,69,104,105,108,109,102,103,244,245,0,0,0,0,0,0,0,0,0,0,0,0,0,0,0,0,0,0,0,0,0,0,0,0,0,0,0,0,0,0,0,0,0,0,0,0,0,0,0,0,0,0,0,0,0,0,0,0,0},
  {64,65,66,67,68,69,70,71,72,73,74,75,76,77,78,79,0,1,2,3,0,1,2,3,4,5,6,7,8,9,10,11,12,13,14,15,64,66,76,78,65,67,77,79,68,70,69,71,72,74,73,75,12,14,8,10,13,15,9,11,0,2,4,6,1,3,5,7,4,6,12,14,8,10,0,2,5,7,13,15,9,11,1,3,0,2,8,10,4,6,12,14,1,3,9,11,5,7,13,15,136,138,128,130,137,139,129,131,140,142,141,143,132,134,133,135,94,95,108,109,76,77,88,89,114,115,96,97,102,103,116,117,118,119,0,2,1,3,4,6,8,10,12,14,5,7,9,11,13,15,8,10,12,14,0,2,9,11,13,15,1,3,4,6,5,7,8,10,9,11,4,6,0,2,12,14,5,7,1,3,13,15,4,6,5,7,8,10,12,14,9,11,13,15,0,2,1,3,4,6,12,14,8,10,5,7,13,15,0,2,9,11,1,3,118,119,76,77,74,75,68,69,72,73,100,101,110,111,84,85,78,79,116,117,94,95,242,243,214,215,240,241,226,227,0,0,0,0,0,0,0,0,0,0,0,0,0,0,0,0,0,0,0,0,0,0,0,0,0,0,0,0,0,0,0,0,0,0,0,0,0,0,0,0,0,0,0,0,0,0,0,0,0,0,0,0},
  {64,65,66,67,68,69,70,71,72,73,74,75,76,77,78,79,64,65,66,67,68,69,70,71,72,73,74,75,76,77,78,79,0,1,2,3,4,5,6,7,8,9,10,11,12,13,14,15,0,2,8,10,1,3,9,11,12,14,4,6,13,15,5,7,12,14,8,10,13,15,9,11,0,2,4,6,1,3,5,7,4,6,12,14,8,10,0,2,5,7,13,15,9,11,1,3,68,70,76,78,72,74,64,66,69,71,77,79,73,75,65,67,72,73,80,81,106,107,116,117,108,109,64,65,94,95,86,87,114,115,102,103,226,234,235,224,225,216,217,198,199,206,207,246,247,194,195,64,71,78,77,69,72,75,70,74,79,76,73,68,67,66,65,196,198,192,194,197,199,193,195,200,202,204,206,201,203,205,207,12,14,8,10,4,6,0,2,13,15,9,11,5,7,1,3,12,14,8,10,13,15,132,134,9,11,133,135,128,130,1,3,196,198,204,206,200,202,69,71,205,207,201,203,192,194,193,195,81,66,67,90,91,96,97,114,115,74,75,198,199,238,239,210,211,0,0,0,0,0,0,0,0,0,0,0,0,0,0,0,0,0,0,0,0,0,0,0,0,0,0,0,0,0,0,0,0,0,0,0,0,0,0,0,0,0,0,0,0,0,0,0,0,0,0,0,0},
  {64,65,66,67,68,69,70,71,72,73,74,75,76,77,78,79,0,1,2,3,0,1,2,3,4,5,6,7,8,9,10,11,12,13,14,15,64,66,76,78,65,67,77,79,68,70,69,71,72,74,73,75,4,6,0,2,5,7,1,3,12,14,8,10,13,15,9,11,76,78,72,74,77,79,73,75,64,66,68,70,65,67,69,71,4,6,12,14,8,10,0,2,5,7,13,15,9,11,1,3,8,10,128,130,9,11,1,3,140,142,13,15,132,134,133,135,107,94,95,108,109,76,77,88,89,114,115,96,97,102,103,116,117,118,119,71,72,69,66,64,78,74,77,76,75,73,79,68,65,67,70,8,10,12,14,0,2,9,11,13,15,1,3,4,6,5,7,8,10,0,2,9,11,12,14,1,3,4,6,13,15,5,7,4,6,12,14,8,10,5,7,13,15,9,11,0,2,1,3,4,6,12,14,8,10,5,7,13,15,0,2,9,11,1,3,64,65,78,79,90,91,106,107,94,95,68,69,96,97,74,102,103,208,209,96,97,76,77,218,219,236,237,0,0,0,0,0,0,0,0,0,0,0,0,0,0,0,0,0,0,0,0,0,0,0,0,0,0,0,0,0,0,0,0,0,0,0,0,0,0,0,0,0,0,0,0,0,0,0,0,0,0,0,0,0,0},
  {0,1,2,3,4,5,6,7,8,9,10,11,12,13,14,15,0,1,2,3,79,75,77,73,0,1,2,3,4,5,6,7,8,9,10,11,12,13,14,15,0,2,8,10,1,3,9,11,12,14,4,6,13,15,5,7,4,6,8,10,0,2,5,7,9,11,12,14,1,3,13,15,4,6,8,10,0,2,5,7,9,11,12,14,1,3,13,15,4,6,12,14,8,10,0,2,5,7,13,15,9,11,1,3,72,73,80,81,98,99,74,75,110,111,112,113,86,87,92,93,78,79,64,65,66,67,84,85,68,69,90,91,104,218,219,220,221,230,231,196,197,71,69,72,78,64,77,75,74,79,73,67,76,70,68,66,65,8,10,0,2,9,11,12,14,1,3,4,6,13,15,5,7,12,14,8,10,4,6,0,2,13,15,9,11,5,7,1,3,12,14,8,10,13,15,4,6,9,11,5,7,0,2,1,3,196,198,204,206,200,202,197,199,205,207,192,194,201,203,193,195,78,79,106,235,86,87,94,95,76,77,220,221,200,201,98,99,212,213,0,0,0,0,0,0,0,0,0,0,0,0,0,0,0,0,0,0,0,0,0,0,0,0,0,0,0,0,0,0,0,0,0,0,0,0,0,0,0,0,0,0,0,0,0,0,0,0,0,0,0,0,0,0,0,0,0},
  {64,65,66,67,68,69,70,71,72,73,74,75,76,77,78,79,0,1,2,3,72,78,70,71,0,2,12,14,1,3,13,15,4,6,5,7,8,10,9,11,12,14,8,10,13,15,9,11,0,2,4,6,1,3,5,7,4,6,8,10,0,2,5,7,9,11,12,14,1,3,13,15,8,10,0,2,9,11,1,3,12,14,13,15,132,134,5,7,95,70,71,76,77,106,107,96,97,64,65,78,79,90,91,80,81,102,69,110,111,82,83,74,75,96,97,118,119,104,105,94,223,244,245,234,235,224,225,216,217,198,199,71,69,72,78,64,77,75,74,79,73,67,76,70,68,66,65,8,10,0,2,9,11,12,14,1,3,4,6,13,15,5,7,12,14,8,10,4,6,0,2,13,15,9,11,5,7,1,3,4,6,12,14,8,10,5,7,13,15,9,11,0,2,1,3,68,70,69,71,200,202,204,206,201,203,205,207,192,194,193,195,64,65,78,79,90,91,106,107,94,95,112,113,228,229,64,193,216,217,246,247,0,0,0,0,0,0,0,0,0,0,0,0,0,0,0,0,0,0,0,0,0,0,0,0,0,0,0,0,0,0,0,0,0,0,0,0,0,0,0,0,0,0,0,0,0,0,0,0,0,0,0,0,0,0,0,0,0,0,0,0,0,0,0,0,0},
  {64,65,66,67,68,69,70,71,72,73,74,75,76,77,78,79,0,1,2,3,0,1,2,3,4,5,6,7,8,9,10,11,12,13,14,15,64,66,76,78,65,67,77,79,68,70,69,71,72,74,73,75,12,14,8,10,13,15,9,11,0,2,4,6,1,3,5,7,70,71,64,65,98,99,92,93,78,79,112,113,94,95,72,73,80,81,84,85,114,115,116,117,106,107,66,67,111,98,99,66,67,94,95,70,71,76,77,106,107,96,97,64,65,78,79,90,91,80,81,102,103,104,105,236,237,240,241,72,105,70,71,210,211,100,101,106,71,72,69,66,64,78,74,77,76,75,73,79,68,65,67,70,64,71,70,74,77,69,78,72,76,78,74,77,71,70,64,66,69,207,200,75,68,204,73,195,65,4,6,5,7,8,10,12,14,9,11,13,15,0,2,1,3,12,14,8,10,13,15,132,134,9,11,133,135,0,2,1,3,118,119,76,77,74,75,68,69,72,73,100,101,110,111,84,85,206,207,116,117,94,95,114,115,214,215,112,113,98,99,192,193,0,0,0,0,0,0,0,0,0,0,0,0,0,0,0,0,0,0,0,0,0,0,0,0,0,0,0,0,0,0,0,0,0,0,0,0,0,0,0,0,0,0,0,0,0,0,0,0,0,0,0,0,0,0,0},
  {64,65,66,67,68,69,70,71,72,73,74,75,76,77,78,79,0,1,2,3,64,65,66,67,68,69,70,71,72,73,74,75,76,77,78,79,64,66,76,78,65,67,77,79,68,70,69,71,72,74,73,75,4,6,0,2,5,7,1,3,12,14,8,10,13,15,9,11,4,6,12,14,8,10,0,2,5,7,13,15,9,11,1,3,4,6,12,14,8,10,0,2,5,7,13,15,137,139,129,131,92,93,72,73,80,81,106,107,116,117,108,109,64,65,94,95,86,87,114,115,102,103,98,99,100,101,90,91,70,71,207,246,247,194,195,238,239,242,243,232,233,218,4,6,8,10,5,7,0,2,12,14,9,11,1,3,13,15,64,71,78,74,77,70,73,69,66,72,76,79,68,65,67,75,12,14,8,10,4,6,0,2,13,15,9,11,5,7,1,3,12,14,8,10,13,15,4,6,9,11,5,7,0,2,1,3,204,206,200,202,205,207,196,198,201,203,197,199,192,194,193,195,71,66,67,112,113,98,99,86,87,110,111,114,115,88,89,118,119,68,69,230,231,0,0,0,0,0,0,0,0,0,0,0,0,0,0,0,0,0,0,0,0,0,0,0,0,0,0,0,0,0,0,0,0,0,0,0,0,0,0,0,0,0,0,0,0,0,0,0,0,0,0,0,0,0},
  {64,65,66,67,68,69,70,71,72,73,74,75,76,77,78,79,0,1,2,3,0,1,2,3,4,5,6,7,8,9,10,11,12,13,14,15,64,66,76,78,65,67,77,79,68,70,69,71,72,74,73,75,12,14,8,10,13,15,9,11,0,2,4,6,1,3,5,7,4,6,0,2,5,7,1,3,12,14,8,10,13,15,9,11,4,6,8,10,0,2,5,7,9,11,12,14,1,3,13,15,82,83,98,99,108,109,92,93,78,79,84,85,100,101,66,67,74,75,112,113,84,85,88,89,66,67,78,79,92,93,4,6,5,7,0,2,8,10,12,14,1,3,9,11,13,15,4,6,8,10,5,7,0,2,12,14,9,11,1,3,13,15,8,10,0,2,9,11,12,14,1,3,4,6,13,15,5,7,12,14,8,10,4,6,0,2,13,15,9,11,5,7,1,3,12,14,8,10,13,15,132,134,9,11,5,7,0,2,1,3,196,198,69,71,200,202,204,206,201,203,205,207,192,194,193,195,78,79,106,107,86,87,94,95,76,77,220,221,200,201,98,99,212,213,208,0,0,0,0,0,0,0,0,0,0,0,0,0,0,0,0,0,0,0,0,0,0,0,0,0,0,0,0,0,0,0,0,0,0,0,0,0,0,0,0,0,0,0,0,0,0,0,0,0,0,0},
  {0,1,2,3,4,5,6,7,8,9,10,11,12,13,14,15,0,1,2,3,0,1,2,3,4,5,6,7,8,9,10,11,12,13,14,15,64,66,76,78,65,67,77,79,68,70,69,71,72,74,73,75,4,6,0,2,5,7,1,3,12,14,8,10,13,15,9,11,4,6,8,10,0,2,5,7,9,11,12,14,1,3,13,15,0,2,8,10,4,6,12,14,1,3,137,139,5,7,13,15,80,81,102,103,104,105,108,109,112,113,72,73,116,117,82,83,100,101,74,75,86,87,92,93,118,119,68,69,4,6,5,7,0,2,8,10,12,14,1,3,9,11,13,15,4,6,8,10,5,7,0,2,12,14,9,11,1,3,13,15,8,10,0,2,9,11,12,14,1,3,4,6,13,15,5,7,200,207,194,204,192,195,202,196,199,206,198,197,205,201,193,203,12,14,8,10,13,15,4,6,9,11,5,7,0,2,1,3,132,134,12,14,136,138,133,135,13,15,137,139,128,130,129,131,106,107,70,71,66,67,112,113,98,99,86,87,110,111,242,243,88,89,118,119,196,197,0,0,0,0,0,0,0,0,0,0,0,0,0,0,0,0,0,0,0,0,0,0,0,0,0,0,0,0,0,0,0,0,0,0,0,0,0,0,0,0,0,0,0,0,0,0,0,0,0,0},
  {64,65,66,67,68,69,70,71,72,73,74,75,76,77,78,79,0,1,2,3,4,5,6,7,8,9,10,11,12,13,14,15,0,1,2,3,72,76,64,70,66,74,71,78,67,79,65,69,75,68,73,77,4,6,0,2,5,7,1,3,12,14,8,10,13,15,9,11,4,6,8,10,0,2,5,7,9,11,12,14,1,3,13,15,0,2,8,10,4,6,12,14,1,3,137,139,5,7,141,143,192,194,200,202,68,70,204,206,193,195,201,203,197,199,205,207,111,82,83,74,75,96,97,118,119,104,105,4,6,5,7,0,2,8,10,12,14,1,3,9,11,13,15,76,78,68,70,0,2,13,15,5,7,8,10,1,3,9,11,8,10,0,2,9,11,12,14,1,3,4,6,13,15,5,7,12,14,8,10,4,6,0,2,13,15,9,11,5,7,1,3,4,6,12,14,8,10,5,7,13,15,9,11,0,2,1,3,12,14,136,138,132,134,0,2,141,143,137,139,133,135,129,131,64,65,84,85,92,93,104,105,74,75,206,207,100,101,82,83,200,201,116,117,222,223,234,0,0,0,0,0,0,0,0,0,0,0,0,0,0,0,0,0,0,0,0,0,0,0,0,0,0,0,0,0,0,0,0,0,0,0,0,0,0,0,0,0,0,0,0,0,0,0,0,0,0},
  {64,65,66,67,68,69,70,71,72,73,74,75,76,77,78,79,0,1,2,3,4,5,6,7,8,9,10,11,12,13,14,15,69,76,67,65,64,66,76,78,65,67,77,79,68,70,69,71,72,74,73,75,12,14,8,10,13,15,9,11,0,2,4,6,1,3,5,7,4,6,8,10,0,2,5,7,9,11,12,14,1,3,13,15,90,91,70,71,72,73,66,67,64,65,84,85,92,93,80,81,86,87,94,95,76,77,88,89,106,107,78,79,96,0,2,4,6,8,10,1,3,5,7,12,14,9,11,13,15,4,6,5,7,0,2,8,10,12,14,1,3,9,11,13,15,4,6,8,10,5,7,0,2,12,14,9,11,1,3,13,15,132,134,128,130,133,135,129,131,136,138,140,142,137,139,141,143,8,10,9,11,4,6,0,2,12,14,5,7,1,3,13,15,4,6,12,14,8,10,5,7,13,15,9,11,0,2,1,3,132,134,140,142,136,138,133,135,141,143,128,130,137,139,129,131,104,105,78,79,118,119,114,115,88,89,112,113,100,101,64,65,84,85,94,95,96,97,210,211,196,197,0,0,0,0,0,0,0,0,0,0,0,0,0,0,0,0,0,0,0,0,0,0,0,0,0,0,0,0,0,0,0,0,0,0,0,0,0,0,0,0,0,0,0,0,0},
  {64,65,66,67,68,69,70,71,72,73,74,75,76,77,78,79,0,1,2,3,0,1,2,3,4,5,6,7,8,9,10,11,12,13,14,15,0,1,2,3,4,5,6,7,8,9,10,11,12,13,14,15,0,2,8,10,1,3,9,11,12,14,4,6,13,15,5,7,4,6,8,10,0,2,5,7,9,11,12,14,1,3,13,15,4,6,12,14,8,10,0,2,5,7,13,15,9,11,1,3,103,104,105,108,109,112,113,72,73,116,117,82,83,100,101,74,75,86,87,92,93,118,119,68,69,76,78,68,70,77,79,64,66,72,74,69,71,65,67,73,75,0,2,1,3,4,6,8,10,12,14,5,7,9,11,13,15,132,134,128,130,133,135,129,131,136,138,140,142,137,139,141,143,8,10,9,11,4,6,0,2,12,14,5,7,1,3,13,15,4,6,12,14,8,10,5,7,13,15,9,11,0,2,1,3,132,134,140,142,136,138,133,135,141,143,128,130,137,139,129,131,65,112,113,98,99,88,89,86,87,84,85,90,91,106,107,68,69,104,105,76,77,116,117,110,111,102,103,194,195,0,0,0,0,0,0,0,0,0,0,0,0,0,0,0,0,0,0,0,0,0,0,0,0,0,0,0,0,0,0,0,0,0,0,0,0,0,0,0,0,0,0,0,0,0,0},
  {64,65,66,67,68,69,70,71,72,73,74,75,76,77,78,79,0,1,2,3,4,5,6,7,8,9,10,11,12,13,14,15,64,67,72,77,69,73,78,76,76,69,70,72,74,66,71,75,67,77,68,73,79,206,64,65,4,6,8,10,0,2,5,7,9,11,12,14,1,3,13,15,4,6,12,14,8,10,0,2,5,7,13,15,9,11,1,3,0,2,8,10,4,6,12,14,1,3,9,11,5,7,13,15,0,2,4,6,8,10,1,3,5,7,12,14,9,11,13,15,4,6,5,7,12,14,8,10,0,2,13,15,9,11,1,3,0,2,1,3,4,6,8,10,12,14,5,7,9,11,13,15,8,10,12,14,0,2,9,11,13,15,1,3,4,6,5,7,8,10,0,2,9,11,12,14,1,3,4,6,13,15,5,7,12,14,8,10,4,6,0,2,13,15,9,11,5,7,1,3,4,6,12,14,8,10,5,7,13,15,9,11,0,2,1,3,116,117,64,65,118,119,80,81,94,95,76,77,112,113,110,111,82,83,70,71,68,112,113,228,229,64,65,88,217,246,247,0,0,0,0,0,0,0,0,0,0,0,0,0,0,0,0,0,0,0,0,0,0,0,0,0,0,0,0,0,0,0,0,0,0,0,0,0,0,0,0,0,0,0,0,0,0,0,0,0},
  {64,65,66,67,68,69,70,71,72,73,74,75,76,77,78,79,0,1,2,3,0,1,2,3,4,5,6,7,8,9,10,11,12,13,14,15,64,66,76,78,65,67,77,79,68,70,69,71,72,74,73,75,12,14,8,10,13,15,9,11,0,2,4,6,1,3,5,7,4,6,8,10,0,2,5,7,9,11,12,14,1,3,13,15,64,65,70,71,80,81,112,113,90,91,102,103,118,119,104,105,114,115,106,107,94,95,68,69,82,83,98,99,108,109,92,12,14,4,6,13,15,0,2,8,10,5,7,1,3,9,11,4,6,5,7,0,2,8,10,12,14,1,3,9,11,13,15,76,78,68,70,64,66,77,79,69,71,72,74,65,67,73,75,132,134,128,130,133,135,129,131,136,138,140,142,137,139,141,143,12,14,8,10,4,6,0,2,13,15,9,11,5,7,1,3,4,6,12,14,8,10,5,7,13,15,9,11,0,2,1,3,4,6,12,14,136,138,5,7,13,15,137,139,128,130,129,131,64,65,84,85,92,93,104,105,74,75,206,207,100,101,82,83,72,73,116,117,222,223,234,235,198,0,0,0,0,0,0,0,0,0,0,0,0,0,0,0,0,0,0,0,0,0,0,0,0,0,0,0,0,0,0,0,0,0,0,0,0,0,0,0,0,0,0,0,0},
  {0,1,2,3,4,5,6,7,8,9,10,11,12,13,14,15,64,65,66,67,68,69,70,71,72,73,74,75,76,77,78,79,0,1,2,3,4,5,6,7,8,9,10,11,12,13,14,15,0,2,8,10,1,3,9,11,12,14,4,6,13,15,5,7,4,6,8,10,0,2,5,7,9,11,12,14,1,3,13,15,103,98,99,72,73,92,93,64,65,100,101,96,97,114,115,76,77,70,71,86,87,90,91,74,75,66,67,68,69,0,2,4,6,8,10,1,3,5,7,12,14,9,11,13,15,12,14,4,6,13,15,0,2,8,10,5,7,1,3,9,11,0,2,1,3,4,6,8,10,12,14,5,7,9,11,13,15,132,134,128,130,133,135,129,131,136,138,140,142,137,139,141,143,79,67,75,65,8,10,0,2,9,11,12,14,1,3,4,6,13,15,5,7,4,6,12,14,8,10,5,7,13,15,9,11,0,2,1,3,8,10,9,11,4,6,0,2,140,142,133,135,1,3,141,143,64,65,80,81,92,93,108,109,106,107,70,71,66,67,90,91,88,89,82,83,224,225,232,233,230,231,0,0,0,0,0,0,0,0,0,0,0,0,0,0,0,0,0,0,0,0,0,0,0,0,0,0,0,0,0,0,0,0,0,0,0,0,0,0,0,0,0,0,0,0,0},
  {64,65,66,67,68,69,70,71,72,73,74,75,76,77,78,79,0,1,2,3,64,65,66,67,68,69,70,71,72,73,74,75,76,77,78,79,64,66,76,78,65,67,77,79,68,70,69,71,72,74,73,75,4,6,0,2,5,7,1,3,12,14,8,10,13,15,9,11,4,6,8,10,0,2,5,7,9,11,12,14,1,3,13,15,90,91,70,71,72,73,66,67,64,65,84,85,92,93,80,81,86,87,94,95,76,77,88,89,106,107,78,79,96,97,0,2,4,6,8,10,1,3,5,7,12,14,9,11,13,15,4,6,5,7,0,2,8,10,12,14,1,3,9,11,13,15,12,14,4,6,0,2,13,15,5,7,8,10,1,3,9,11,64,71,70,74,77,69,78,72,76,68,66,73,8,10,9,11,4,6,0,2,12,14,5,7,1,3,13,15,4,6,12,14,8,10,5,7,13,15,9,11,0,2,1,3,12,14,8,10,13,15,4,6,9,11,5,7,0,2,1,3,106,107,104,105,92,93,88,89,72,73,90,91,100,101,206,207,116,117,64,65,118,119,80,209,222,223,204,0,0,0,0,0,0,0,0,0,0,0,0,0,0,0,0,0,0,0,0,0,0,0,0,0,0,0,0,0,0,0,0,0,0,0,0,0,0,0,0,0,0,0,0,0,0,0},
  {0,1,2,3,4,5,6,7,8,9,10,11,12,13,14,15,0,1,2,3,64,65,66,67,68,69,70,71,72,73,74,75,76,77,78,79,64,66,76,78,65,67,77,79,68,70,69,71,72,74,73,75,64,66,72,74,65,67,73,75,76,78,68,70,77,79,69,71,4,6,8,10,0,2,5,7,9,11,12,14,1,3,13,15,68,70,64,66,69,71,65,67,76,78,72,74,77,79,73,75,136,138,128,130,137,139,129,131,140,142,141,143,132,134,133,135,64,66,68,70,72,74,65,67,69,71,76,78,73,75,77,79,4,6,5,7,0,2,8,10,12,14,1,3,9,11,13,15,4,6,8,10,5,7,0,2,12,14,9,11,1,3,13,15,64,71,78,74,77,70,73,69,66,72,76,79,68,65,67,75,12,14,8,10,4,6,0,2,13,15,9,11,5,7,1,3,12,14,8,10,13,15,132,134,9,11,133,135,0,2,1,3,204,206,200,202,205,207,196,198,201,203,197,199,192,194,193,195,107,70,71,66,67,112,113,98,99,86,87,110,111,242,243,88,89,118,119,196,197,0,0,0,0,0,0,0,0,0,0,0,0,0,0,0,0,0,0,0,0,0,0,0,0,0,0,0,0,0,0,0,0,0,0,0,0,0,0,0,0,0,0,0,0,0,0,0},
  {64,65,66,67,68,69,70,71,72,73,74,75,76,77,78,79,0,1,2,3,72,78,70,71,0,1,2,3,4,5,6,7,8,9,10,11,12,13,14,15,0,2,8,10,1,3,9,11,12,14,4,6,13,15,5,7,12,14,8,10,13,15,9,11,0,2,4,6,1,3,5,7,4,6,12,14,8,10,0,2,5,7,13,15,9,11,1,3,136,138,128,130,137,139,129,131,140,142,141,143,132,134,133,135,75,88,89,76,77,96,97,86,87,72,73,116,117,110,111,4,6,5,7,12,14,8,10,0,2,13,15,9,11,1,3,12,14,4,6,0,2,13,15,5,7,8,10,1,3,9,11,132,134,128,130,133,135,129,131,136,138,140,142,137,139,141,143,8,10,9,11,4,6,0,2,12,14,5,7,1,3,13,15,4,6,5,7,8,10,12,14,9,11,13,15,0,2,1,3,12,14,8,10,13,15,132,134,9,11,133,135,128,130,129,131,116,117,96,97,74,75,64,65,112,113,82,83,106,107,84,80,81,66,67,90,91,96,97,242,243,74,75,198,199,0,0,0,0,0,0,0,0,0,0,0,0,0,0,0,0,0,0,0,0,0,0,0,0,0,0,0,0,0,0,0,0,0,0,0,0,0,0,0,0,0,0,0,0,0,0,0,0,0,0,0,0},
  {0,1,2,3,4,5,6,7,8,9,10,11,12,13,14,15,0,1,2,3,0,1,2,3,4,5,6,7,8,9,10,11,12,13,14,15,0,1,2,3,76,69,70,72,74,66,71,75,67,77,68,73,79,78,64,65,12,14,8,10,13,15,9,11,0,2,4,6,1,3,5,7,4,6,8,10,0,2,5,7,9,11,12,14,1,3,13,15,128,130,136,138,4,6,140,142,129,131,137,139,133,135,141,143,0,2,4,6,8,10,1,3,5,7,12,14,9,11,13,15,95,108,109,76,77,88,89,114,115,96,97,102,103,244,245,246,247,219,220,221,230,231,196,197,4,6,8,10,5,7,0,2,12,14,9,11,1,3,13,15,64,71,70,74,77,69,78,72,76,68,66,73,79,67,75,65,12,14,8,10,4,6,0,2,13,15,9,11,5,7,1,3,12,14,8,10,13,15,4,6,9,11,5,7,0,2,1,3,76,78,72,74,77,79,68,70,73,75,69,71,64,66,65,67,82,83,70,71,100,101,102,103,84,85,116,117,72,73,86,87,110,111,232,233,204,205,0,0,0,0,0,0,0,0,0,0,0,0,0,0,0,0,0,0,0,0,0,0,0,0,0,0,0,0,0,0,0,0,0,0,0,0,0,0,0,0,0,0,0,0,0,0,0,0,0,0},
  {64,65,66,67,68,69,70,71,72,73,74,75,76,77,78,79,0,1,2,3,4,5,6,7,8,9,10,11,12,13,14,15,70,64,76,66,74,72,79,71,78,67,69,65,75,77,68,73,0,2,8,10,1,3,9,11,12,14,4,6,13,15,5,7,4,6,12,14,8,10,0,2,5,7,13,15,9,11,1,3,4,6,12,14,8,10,0,2,5,7,13,15,9,11,1,3,136,138,128,130,137,139,129,131,140,142,141,143,132,134,133,135,12,14,4,6,13,15,0,2,8,10,5,7,1,3,9,11,4,6,5,7,0,2,8,10,12,14,1,3,9,11,13,15,4,6,8,10,5,7,0,2,12,14,9,11,1,3,13,15,132,134,128,130,133,135,129,131,136,138,140,142,137,139,141,143,8,10,9,11,4,6,0,2,12,14,5,7,1,3,13,15,4,6,12,14,8,10,5,7,13,15,9,11,0,2,1,3,8,10,0,2,9,11,140,142,1,3,132,134,141,143,133,135,92,93,108,109,98,99,80,81,100,101,70,71,110,111,82,83,68,69,104,105,108,109,102,103,244,245,0,0,0,0,0,0,0,0,0,0,0,0,0,0,0,0,0,0,0,0,0,0,0,0,0,0,0,0,0,0,0,0,0,0,0,0,0,0,0,0,0,0,0,0,0,0},
  {0,1,2,3,4,5,6,7,8,9,10,11,12,13,14,15,0,1,2,3,0,1,2,3,4,5,6,7,8,9,10,11,12,13,14,15,64,66,76,78,65,67,77,79,68,70,69,71,72,74,73,75,12,14,8,10,13,15,9,11,0,2,4,6,1,3,5,7,4,6,0,2,5,7,1,3,12,14,8,10,13,15,9,11,90,91,70,71,72,73,66,67,64,65,84,85,92,93,80,81,86,87,94,95,76,77,88,89,106,107,78,79,96,97,108,109,72,73,80,81,98,99,74,75,110,111,240,241,86,87,92,93,206,207,192,193,0,2,1,3,4,6,8,10,12,14,5,7,9,11,13,15,8,10,12,14,0,2,9,11,13,15,1,3,4,6,5,7,8,10,9,11,4,6,0,2,12,14,5,7,1,3,13,15,4,6,5,7,8,10,12,14,9,11,13,15,0,2,1,3,132,134,5,7,136,138,140,142,9,11,141,143,128,130,129,131,104,105,72,73,86,87,102,103,90,91,118,119,68,69,206,207,114,115,66,67,110,111,222,223,216,217,204,205,0,0,0,0,0,0,0,0,0,0,0,0,0,0,0,0,0,0,0,0,0,0,0,0,0,0,0,0,0,0,0,0,0,0,0,0,0,0,0,0,0,0,0,0,0,0,0,0,0,0,0,0},
  {64,65,66,67,68,69,70,71,72,73,74,75,76,77,78,79,0,1,2,3,0,1,2,3,4,5,6,7,8,9,10,11,12,13,14,15,64,66,76,78,65,67,77,79,68,70,69,71,72,74,73,75,12,14,8,10,13,15,9,11,0,2,4,6,1,3,5,7,4,6,8,10,0,2,5,7,9,11,12,14,1,3,13,15,0,2,8,10,4,6,12,14,1,3,9,11,5,7,13,15,99,102,103,68,69,110,111,104,105,73,116,117,82,83,100,101,74,75,86,87,92,93,118,119,68,69,4,6,5,7,12,14,8,10,0,2,13,15,9,11,1,3,79,68,65,67,70,64,71,78,77,69,72,75,70,74,79,76,73,68,67,66,65,8,10,0,2,9,11,12,14,1,3,4,6,13,15,5,7,12,14,8,10,4,6,0,2,13,15,9,11,5,7,1,3,4,6,12,14,8,10,5,7,13,15,0,2,9,11,1,3,80,81,96,97,92,93,108,109,70,71,82,83,100,101,78,206,207,106,107,86,87,94,95,76,77,220,221,200,201,226,227,0,0,0,0,0,0,0,0,0,0,0,0,0,0,0,0,0,0,0,0,0,0,0,0,0,0,0,0,0,0,0,0,0,0,0,0,0,0,0,0,0,0,0,0,0,0,0,0,0,0,0,0,0,0},
};

struct alignas(64) Params {
  CUtensorMap a[6];
  CUtensorMap w[4];
  CUtensorMap ow;
  CUtensorMap xr;
  const bf16 *x0, *wqkv;
  bf16* out;
  uint32_t swap;
  uint32_t jobs[NPAIR][JMAX];
  uint8_t kseq[NPAIR][KMAX];
};

template <class T> __device__ __forceinline__ T* at(T* base, uint32_t bytes) {
  T* r;
  asm("{\n.reg .u32 lo, hi;\nmov.b64 {lo, hi}, %1;\nadd.cc.u32 lo, lo, %2;\naddc.u32 hi, hi, 0;\nmov.b64 %0, {lo, hi};\n}" : "=l"(r) : "l"(base), "r"(bytes));
  return r;
}
#define SCR(sm, member, bytes) reinterpret_cast<decltype(&scratch_base()->member[0])>(at((sm).scratch, offsetof(Scratch, member) + (bytes)))
#define counter(line, word) SCR(sm, cnt, (line) * 128 + (word) * 4)
#define TRS(st, slot) do {} while (0)
#define TRX(cond, job, bit, slot, reg) do {} while (0)
#define TR(job, slot) do {} while (0)
#define TRI(cond, job, slot) do {} while (0)
#define TRK(cond, job, slot) do {} while (0)
#define TRC(job, slot) do {} while (0)

__device__ __forceinline__ uint32_t smem_u32(const void* p) { return (uint32_t)__cvta_generic_to_shared(p); }
__device__ __forceinline__ void mbar_init(uint32_t bar, uint32_t cnt) { asm volatile("mbarrier.init.shared::cta.b64 [%0], %1;" ::"r"(bar), "r"(cnt) : "memory"); }
__device__ __forceinline__ void mbar_expect_tx(uint32_t bar, uint32_t bytes) { asm volatile("mbarrier.arrive.expect_tx.shared::cta.b64 _, [%0], %1;" ::"r"(bar), "r"(bytes) : "memory"); }
__device__ __forceinline__ void mbar_arrive_n(uint32_t bar, uint32_t cnt) { asm volatile("mbarrier.arrive.shared::cta.b64 _, [%0], %1;" ::"r"(bar), "r"(cnt) : "memory"); }
__device__ __forceinline__ void mbar_arrive_cl_if(uint32_t cond, uint32_t bar) {
  asm volatile("{\n.reg .pred p;\nsetp.ne.u32 p, %1, 0;\n@p mbarrier.arrive.shared::cluster.b64 _, [%0];\n}" ::"r"(bar), "r"(cond) : "memory");
}
__device__ __forceinline__ void mbar_arrive_warp(uint32_t bar) {
  asm volatile("{\n.reg .pred p;\nbar.warp.sync -1;\nelect.sync _|p, -1;\n@p mbarrier.arrive.shared::cta.b64 _, [%0];\n}" ::"r"(bar) : "memory");
}
__device__ __forceinline__ uint32_t mapa(uint32_t addr, uint32_t cta) { uint32_t r; asm("mapa.shared::cluster.u32 %0, %1, %2;" : "=r"(r) : "r"(addr), "r"(cta)); return r; }
__device__ __forceinline__ bool mbar_test(uint32_t bar, uint32_t parity) {
  uint32_t ok;
  asm volatile("{\n.reg .pred p;\nmbarrier.test_wait.parity.shared::cta.b64 p, [%1], %2;\nselp.u32 %0, 1, 0, p;\n}\n" : "=r"(ok) : "r"(bar), "r"(parity) : "memory");
  return ok;
}
__device__ __forceinline__ void mbar_wait(uint32_t bar, uint32_t parity) {
  asm volatile(
      "{\n.reg .pred p;\n.reg .u32 n;\nmov.u32 n, 0;\n"
      "WAIT:\nmbarrier.try_wait.parity.shared::cta.b64 p, [%0], %1;\n@p bra DONE;\n"
      "add.u32 n, n, 1;\nsetp.lt.u32 p, n, %2;\n@p bra WAIT;\ntrap;\nDONE:\n}\n" ::"r"(bar), "r"(parity), "n"(SPIN_LIMIT) : "memory");
}
template <int ID, int N> __device__ __forceinline__ void bar_sync() { asm volatile("bar.sync %0, %1;" ::"n"(ID), "n"(N) : "memory"); }
template <int ID, int N> __device__ __forceinline__ void bar_arrive() { asm volatile("bar.arrive %0, %1;" ::"n"(ID), "n"(N) : "memory"); }
__device__ __forceinline__ uint32_t ld_relaxed(const uint32_t* p) { uint32_t v; asm volatile("ld.relaxed.gpu.global.u32 %0, [%1];" : "=r"(v) : "l"(p) : "memory"); return v; }
__device__ __forceinline__ void red_relaxed(uint32_t* p, uint32_t v) { asm volatile("red.relaxed.gpu.global.add.u32 [%0], %1;" ::"l"(p), "r"(v) : "memory"); }
__device__ __forceinline__ void red_release(uint32_t* p, uint32_t v) {
  asm volatile("fence.release.gpu;\nred.relaxed.gpu.global.add.u32 [%0], %1;" ::"l"(p), "r"(v) : "memory");
}
__device__ __forceinline__ bool elect() {
  uint32_t p;
  asm volatile("{\n.reg .pred P;\nelect.sync _|P, 0xffffffff;\nselp.u32 %0, 1, 0, P;\n}\n" : "=r"(p));
  return p;
}
__device__ __forceinline__ void fence_acquire() { asm volatile("fence.acquire.gpu;" ::: "memory"); }
__device__ __forceinline__ void wait_count(const uint32_t* p, uint32_t target) {
  for (uint32_t n = 0; !__all_sync(~0u, (int)(ld_relaxed(p) - target) >= 0); n++) {
    __nanosleep(V_SL1);
    if (n > SPIN_LIMIT) __trap();
  }
  fence_acquire();
}
__device__ __forceinline__ void fence_proxy_async() { asm volatile("fence.proxy.async.global;" ::: "memory"); }
__device__ __forceinline__ void fence_proxy_async_smem() { asm volatile("fence.proxy.async.shared::cta;" ::: "memory"); }
__device__ __forceinline__ void tma4d_mc(uint32_t dst, const CUtensorMap* tm, int c1, int c2, uint32_t bar, uint64_t pol) {
  asm volatile("cp.async.bulk.tensor.4d.shared::cluster.global.mbarrier::complete_tx::bytes.multicast::cluster.L2::cache_hint [%0], [%1, {%3, %4, %5, %3}], [%2], %6, %7;"
               ::"r"(dst), "l"(tm), "r"(bar), "r"(0), "r"(c1), "r"(c2), "h"((uint16_t)3), "l"(pol) : "memory");
}
__device__ __forceinline__ void tma3d(uint32_t dst, const CUtensorMap* tm, int c0, int c1, int c2, uint32_t bar, uint64_t pol) {
  asm volatile("cp.async.bulk.tensor.3d.shared::cluster.global.mbarrier::complete_tx::bytes.L2::cache_hint [%0], [%1, {%3, %4, %5}], [%2], %6;"
               ::"r"(dst), "l"(tm), "r"(bar), "r"(c0), "r"(c1), "r"(c2), "l"(pol) : "memory");
}
__device__ __forceinline__ void tma3d_reduce_add(const CUtensorMap* tm, int c0, int c1, int c2, uint32_t src) {
  asm volatile("cp.reduce.async.bulk.tensor.3d.global.shared::cta.add.tile.bulk_group [%0, {%2, %3, %4}], [%1];"
               ::"l"(tm), "r"(src), "r"(c0), "r"(c1), "r"(c2) : "memory");
}
__device__ __forceinline__ void tma3d_store(const CUtensorMap* tm, int c0, int c1, int c2, uint32_t src) {
  asm volatile("cp.async.bulk.tensor.3d.global.shared::cta.tile.bulk_group [%0, {%2, %3, %4}], [%1];"
               ::"l"(tm), "r"(src), "r"(c0), "r"(c1), "r"(c2) : "memory");
}
__device__ __forceinline__ void bulk_commit() { asm volatile("cp.async.bulk.commit_group;" ::: "memory"); }
template <int N> __device__ __forceinline__ void bulk_wait_read() { asm volatile("cp.async.bulk.wait_group.read %0;" ::"n"(N) : "memory"); }
__device__ __forceinline__ void bulk_wait() { asm volatile("cp.async.bulk.wait_group 0;" ::: "memory"); }
__device__ __forceinline__ uint2 lds64(uint32_t a) { uint2 v; asm volatile("ld.shared.v2.u32 {%0,%1}, [%2];" : "=r"(v.x), "=r"(v.y) : "r"(a) : "memory"); return v; }
__device__ __forceinline__ float lds32f(uint32_t a) { float v; asm volatile("ld.shared.f32 %0, [%1];" : "=f"(v) : "r"(a) : "memory"); return v; }
__device__ __forceinline__ uint4 lds128(uint32_t a) { uint4 v; asm volatile("ld.shared.v4.u32 {%0,%1,%2,%3}, [%4];" : "=r"(v.x), "=r"(v.y), "=r"(v.z), "=r"(v.w) : "r"(a) : "memory"); return v; }
__device__ __forceinline__ uint2 lds64v(uint32_t a) { uint2 v; asm volatile("ld.volatile.shared.v2.u32 {%0,%1}, [%2];" : "=r"(v.x), "=r"(v.y) : "r"(a) : "memory"); return v; }
__device__ __forceinline__ uint4 lds128v(uint32_t a) { uint4 v; asm volatile("ld.volatile.shared.v4.u32 {%0,%1,%2,%3}, [%4];" : "=r"(v.x), "=r"(v.y), "=r"(v.z), "=r"(v.w) : "r"(a) : "memory"); return v; }
__device__ __forceinline__ void sts32(uint32_t a, uint32_t v) { asm volatile("st.shared.u32 [%0], %1;" ::"r"(a), "r"(v) : "memory"); }
__device__ __forceinline__ void sts64(uint32_t a, uint2 v) { asm volatile("st.shared.v2.u32 [%0], {%1,%2};" ::"r"(a), "r"(v.x), "r"(v.y) : "memory"); }
__device__ __forceinline__ void stg128(void* p, uint4 v) { asm volatile("st.global.L1::no_allocate.v4.u32 [%0], {%1,%2,%3,%4};" ::"l"(p), "r"(v.x), "r"(v.y), "r"(v.z), "r"(v.w) : "memory"); }
__device__ __forceinline__ uint4 ldg128(const void* p) { uint4 v; asm volatile("ld.relaxed.gpu.global.v4.u32 {%0,%1,%2,%3}, [%4];" : "=r"(v.x), "=r"(v.y), "=r"(v.z), "=r"(v.w) : "l"(p) : "memory"); return v; }
__device__ __forceinline__ void prefetch_tm(const CUtensorMap* tm) { asm volatile("prefetch.tensormap [%0];" ::"l"(tm) : "memory"); }
template <int N> __device__ __forceinline__ void wg_wait() { asm volatile("wgmma.wait_group.sync.aligned %0;" ::"n"(N) : "memory"); }
__device__ __forceinline__ void cluster_arrive() { asm volatile("barrier.cluster.arrive.relaxed.aligned;" ::: "memory"); }
__device__ __forceinline__ void cluster_wait() { asm volatile("barrier.cluster.wait.acquire.aligned;" ::: "memory"); }
__device__ __forceinline__ uint32_t pack_bf16(float lo, float hi) { uint32_t r; asm("cvt.rn.bf16x2.f32 %0, %1, %2;" : "=r"(r) : "f"(hi), "f"(lo)); return r; }
__device__ __forceinline__ float bf_lo(uint32_t v) { return __uint_as_float(v << 16); }
__device__ __forceinline__ float bf_hi(uint32_t v) { return __uint_as_float(v & 0xffff0000u); }
__device__ __forceinline__ uint32_t dup_hi(uint32_t v) { return __byte_perm(v, 0, 0x3232); }
__device__ __forceinline__ float bf_round(float x) { return __bfloat162float(__float2bfloat16_rn(x)); }
__device__ __forceinline__ uint32_t bf2_add(uint32_t a, uint32_t b) { uint32_t r; asm("add.rn.bf16x2 %0, %1, %2;" : "=r"(r) : "r"(a), "r"(b)); return r; }
__device__ __forceinline__ uint32_t bf2_mul(uint32_t a, uint32_t b) { uint32_t r; asm("mul.rn.bf16x2 %0, %1, %2;" : "=r"(r) : "r"(a), "r"(b)); return r; }
__device__ __forceinline__ uint32_t bf2_fma(uint32_t a, uint32_t b, uint32_t c) { uint32_t r; asm("fma.rn.bf16x2 %0, %1, %2, %3;" : "=r"(r) : "r"(a), "r"(b), "r"(c)); return r; }
__device__ __forceinline__ uint4 add8(uint4 a, uint4 b) { return make_uint4(bf2_add(a.x, b.x), bf2_add(a.y, b.y), bf2_add(a.z, b.z), bf2_add(a.w, b.w)); }
__device__ __forceinline__ uint4 fma8(uint32_t a, uint4 b, uint4 c) { return make_uint4(bf2_fma(a, b.x, c.x), bf2_fma(a, b.y, c.y), bf2_fma(a, b.z, c.z), bf2_fma(a, b.w, c.w)); }
__device__ __forceinline__ void stsm4(uint32_t a, uint32_t r0, uint32_t r1, uint32_t r2, uint32_t r3) {
  asm volatile("stmatrix.sync.aligned.m8n8.x4.shared.b16 [%0], {%1,%2,%3,%4};" ::"r"(a), "r"(r0), "r"(r1), "r"(r2), "r"(r3) : "memory");
}
__device__ __forceinline__ void ldsm4(uint32_t a, uint32_t (&r)[4]) {
  asm volatile("ldmatrix.sync.aligned.m8n8.x4.shared.b16 {%0,%1,%2,%3}, [%4];" : "=r"(r[0]), "=r"(r[1]), "=r"(r[2]), "=r"(r[3]) : "r"(a) : "memory");
}
__device__ __forceinline__ void ldsm4t(uint32_t a, uint32_t (&r)[4]) {
  asm volatile("ldmatrix.sync.aligned.m8n8.x4.trans.shared.b16 {%0,%1,%2,%3}, [%4];" : "=r"(r[0]), "=r"(r[1]), "=r"(r[2]), "=r"(r[3]) : "r"(a) : "memory");
}
__device__ __forceinline__ void mma16816(float (&c)[4], uint32_t a0, uint32_t a1, uint32_t a2, uint32_t a3, uint32_t b0, uint32_t b1) {
  asm volatile("mma.sync.aligned.m16n8k16.row.col.f32.bf16.bf16.f32 {%0,%1,%2,%3}, {%4,%5,%6,%7}, {%8,%9}, {%0,%1,%2,%3};"
               : "+f"(c[0]), "+f"(c[1]), "+f"(c[2]), "+f"(c[3]) : "r"(a0), "r"(a1), "r"(a2), "r"(a3), "r"(b0), "r"(b1));
}
__device__ __forceinline__ void mma1688(float (&c)[4], uint32_t a0, uint32_t a1, uint32_t b0) {
  asm volatile("mma.sync.aligned.m16n8k8.row.col.f32.bf16.bf16.f32 {%0,%1,%2,%3}, {%4,%5}, {%6}, {%0,%1,%2,%3};"
               : "+f"(c[0]), "+f"(c[1]), "+f"(c[2]), "+f"(c[3]) : "r"(a0), "r"(a1), "r"(b0));
}
__device__ __forceinline__ float ex2(float x) { float y; asm("ex2.approx.ftz.f32 %0, %1;" : "=f"(y) : "f"(x)); return y; }
__device__ __forceinline__ float sqrt_fast(float x) { float y; asm("sqrt.approx.f32 %0, %1;" : "=f"(y) : "f"(x)); return y; }
__device__ __forceinline__ float tanh_fast(float x) { float y; asm("tanh.approx.f32 %0, %1;" : "=f"(y) : "f"(x)); return y; }
__device__ __forceinline__ float rcp(float x) { float y; asm("rcp.approx.ftz.f32 %0, %1;" : "=f"(y) : "f"(x)); return y; }
__device__ __forceinline__ uint32_t opaque_zero() { uint32_t z; asm volatile("mov.u32 %0, %%ctaid.y;" : "=r"(z)); return z; }
__device__ __forceinline__ int fresh_tid() { int t; asm volatile("mov.u32 %0, %%tid.x;" : "=r"(t)); return t; }

__device__ __forceinline__ void first_kstep(float (&d)[128], uint32_t a, uint32_t b) {
  asm volatile("{\n.reg .u32 t;\n.reg .u64 da, db;\nwgmma.fence.sync.aligned;\n"
    "add.u32 t, %128, 0;\nmov.b64 da, {t, %130};\nadd.u32 t, %129, 0;\nmov.b64 db, {t, %130};\n"
    "wgmma.mma_async.sync.aligned.m64n256k16.f32.bf16.bf16 {%0, %1, %2, %3, %4, %5, %6, %7, %8, %9, %10, %11, %12, %13, %14, %15, %16, %17, %18, %19, %20, %21, %22, %23, %24, %25, %26, %27, %28, %29, %30, %31, %32, %33, %34, %35, %36, %37, %38, %39, %40, %41, %42, %43, %44, %45, %46, %47, %48, %49, %50, %51, %52, %53, %54, %55, %56, %57, %58, %59, %60, %61, %62, %63, %64, %65, %66, %67, %68, %69, %70, %71, %72, %73, %74, %75, %76, %77, %78, %79, %80, %81, %82, %83, %84, %85, %86, %87, %88, %89, %90, %91, %92, %93, %94, %95, %96, %97, %98, %99, %100, %101, %102, %103, %104, %105, %106, %107, %108, %109, %110, %111, %112, %113, %114, %115, %116, %117, %118, %119, %120, %121, %122, %123, %124, %125, %126, %127}, da, db, 0, 1, 1, 0, 1;\nwgmma.commit_group.sync.aligned;\n"
    "add.u32 t, %128, 2;\nmov.b64 da, {t, %130};\nadd.u32 t, %129, 128;\nmov.b64 db, {t, %130};\n"
    "wgmma.mma_async.sync.aligned.m64n256k16.f32.bf16.bf16 {%0, %1, %2, %3, %4, %5, %6, %7, %8, %9, %10, %11, %12, %13, %14, %15, %16, %17, %18, %19, %20, %21, %22, %23, %24, %25, %26, %27, %28, %29, %30, %31, %32, %33, %34, %35, %36, %37, %38, %39, %40, %41, %42, %43, %44, %45, %46, %47, %48, %49, %50, %51, %52, %53, %54, %55, %56, %57, %58, %59, %60, %61, %62, %63, %64, %65, %66, %67, %68, %69, %70, %71, %72, %73, %74, %75, %76, %77, %78, %79, %80, %81, %82, %83, %84, %85, %86, %87, %88, %89, %90, %91, %92, %93, %94, %95, %96, %97, %98, %99, %100, %101, %102, %103, %104, %105, %106, %107, %108, %109, %110, %111, %112, %113, %114, %115, %116, %117, %118, %119, %120, %121, %122, %123, %124, %125, %126, %127}, da, db, 1, 1, 1, 0, 1;\n"
    "add.u32 t, %128, 4;\nmov.b64 da, {t, %130};\nadd.u32 t, %129, 1024;\nmov.b64 db, {t, %130};\n"
    "wgmma.mma_async.sync.aligned.m64n256k16.f32.bf16.bf16 {%0, %1, %2, %3, %4, %5, %6, %7, %8, %9, %10, %11, %12, %13, %14, %15, %16, %17, %18, %19, %20, %21, %22, %23, %24, %25, %26, %27, %28, %29, %30, %31, %32, %33, %34, %35, %36, %37, %38, %39, %40, %41, %42, %43, %44, %45, %46, %47, %48, %49, %50, %51, %52, %53, %54, %55, %56, %57, %58, %59, %60, %61, %62, %63, %64, %65, %66, %67, %68, %69, %70, %71, %72, %73, %74, %75, %76, %77, %78, %79, %80, %81, %82, %83, %84, %85, %86, %87, %88, %89, %90, %91, %92, %93, %94, %95, %96, %97, %98, %99, %100, %101, %102, %103, %104, %105, %106, %107, %108, %109, %110, %111, %112, %113, %114, %115, %116, %117, %118, %119, %120, %121, %122, %123, %124, %125, %126, %127}, da, db, 1, 1, 1, 0, 1;\n"
    "add.u32 t, %128, 6;\nmov.b64 da, {t, %130};\nadd.u32 t, %129, 1152;\nmov.b64 db, {t, %130};\n"
    "wgmma.mma_async.sync.aligned.m64n256k16.f32.bf16.bf16 {%0, %1, %2, %3, %4, %5, %6, %7, %8, %9, %10, %11, %12, %13, %14, %15, %16, %17, %18, %19, %20, %21, %22, %23, %24, %25, %26, %27, %28, %29, %30, %31, %32, %33, %34, %35, %36, %37, %38, %39, %40, %41, %42, %43, %44, %45, %46, %47, %48, %49, %50, %51, %52, %53, %54, %55, %56, %57, %58, %59, %60, %61, %62, %63, %64, %65, %66, %67, %68, %69, %70, %71, %72, %73, %74, %75, %76, %77, %78, %79, %80, %81, %82, %83, %84, %85, %86, %87, %88, %89, %90, %91, %92, %93, %94, %95, %96, %97, %98, %99, %100, %101, %102, %103, %104, %105, %106, %107, %108, %109, %110, %111, %112, %113, %114, %115, %116, %117, %118, %119, %120, %121, %122, %123, %124, %125, %126, %127}, da, db, 1, 1, 1, 0, 1;\nwgmma.commit_group.sync.aligned;\n"
    "}\n"
    : "=f"(d[0]), "=f"(d[1]), "=f"(d[2]), "=f"(d[3]), "=f"(d[4]), "=f"(d[5]), "=f"(d[6]), "=f"(d[7]), "=f"(d[8]), "=f"(d[9]), "=f"(d[10]), "=f"(d[11]), "=f"(d[12]), "=f"(d[13]), "=f"(d[14]), "=f"(d[15]), "=f"(d[16]), "=f"(d[17]), "=f"(d[18]), "=f"(d[19]), "=f"(d[20]), "=f"(d[21]), "=f"(d[22]), "=f"(d[23]), "=f"(d[24]), "=f"(d[25]), "=f"(d[26]), "=f"(d[27]), "=f"(d[28]), "=f"(d[29]), "=f"(d[30]), "=f"(d[31]), "=f"(d[32]), "=f"(d[33]), "=f"(d[34]), "=f"(d[35]), "=f"(d[36]), "=f"(d[37]), "=f"(d[38]), "=f"(d[39]), "=f"(d[40]), "=f"(d[41]), "=f"(d[42]), "=f"(d[43]), "=f"(d[44]), "=f"(d[45]), "=f"(d[46]), "=f"(d[47]), "=f"(d[48]), "=f"(d[49]), "=f"(d[50]), "=f"(d[51]), "=f"(d[52]), "=f"(d[53]), "=f"(d[54]), "=f"(d[55]), "=f"(d[56]), "=f"(d[57]), "=f"(d[58]), "=f"(d[59]), "=f"(d[60]), "=f"(d[61]), "=f"(d[62]), "=f"(d[63]), "=f"(d[64]), "=f"(d[65]), "=f"(d[66]), "=f"(d[67]), "=f"(d[68]), "=f"(d[69]), "=f"(d[70]), "=f"(d[71]), "=f"(d[72]), "=f"(d[73]), "=f"(d[74]), "=f"(d[75]), "=f"(d[76]), "=f"(d[77]), "=f"(d[78]), "=f"(d[79]), "=f"(d[80]), "=f"(d[81]), "=f"(d[82]), "=f"(d[83]), "=f"(d[84]), "=f"(d[85]), "=f"(d[86]), "=f"(d[87]), "=f"(d[88]), "=f"(d[89]), "=f"(d[90]), "=f"(d[91]), "=f"(d[92]), "=f"(d[93]), "=f"(d[94]), "=f"(d[95]), "=f"(d[96]), "=f"(d[97]), "=f"(d[98]), "=f"(d[99]), "=f"(d[100]), "=f"(d[101]), "=f"(d[102]), "=f"(d[103]), "=f"(d[104]), "=f"(d[105]), "=f"(d[106]), "=f"(d[107]), "=f"(d[108]), "=f"(d[109]), "=f"(d[110]), "=f"(d[111]), "=f"(d[112]), "=f"(d[113]), "=f"(d[114]), "=f"(d[115]), "=f"(d[116]), "=f"(d[117]), "=f"(d[118]), "=f"(d[119]), "=f"(d[120]), "=f"(d[121]), "=f"(d[122]), "=f"(d[123]), "=f"(d[124]), "=f"(d[125]), "=f"(d[126]), "=f"(d[127])
    : "r"(a), "r"(b), "n"(0x40000040) : "memory");
}
__device__ __forceinline__ void kstep(float (&d)[128], uint32_t a, uint32_t b) {
  asm volatile("{\n.reg .u32 t;\n.reg .u64 da, db;\nwgmma.fence.sync.aligned;\n"
    "add.u32 t, %128, 0;\nmov.b64 da, {t, %130};\nadd.u32 t, %129, 0;\nmov.b64 db, {t, %130};\n"
    "wgmma.mma_async.sync.aligned.m64n256k16.f32.bf16.bf16 {%0, %1, %2, %3, %4, %5, %6, %7, %8, %9, %10, %11, %12, %13, %14, %15, %16, %17, %18, %19, %20, %21, %22, %23, %24, %25, %26, %27, %28, %29, %30, %31, %32, %33, %34, %35, %36, %37, %38, %39, %40, %41, %42, %43, %44, %45, %46, %47, %48, %49, %50, %51, %52, %53, %54, %55, %56, %57, %58, %59, %60, %61, %62, %63, %64, %65, %66, %67, %68, %69, %70, %71, %72, %73, %74, %75, %76, %77, %78, %79, %80, %81, %82, %83, %84, %85, %86, %87, %88, %89, %90, %91, %92, %93, %94, %95, %96, %97, %98, %99, %100, %101, %102, %103, %104, %105, %106, %107, %108, %109, %110, %111, %112, %113, %114, %115, %116, %117, %118, %119, %120, %121, %122, %123, %124, %125, %126, %127}, da, db, 1, 1, 1, 0, 1;\nwgmma.commit_group.sync.aligned;\n"
    "add.u32 t, %128, 2;\nmov.b64 da, {t, %130};\nadd.u32 t, %129, 128;\nmov.b64 db, {t, %130};\n"
    "wgmma.mma_async.sync.aligned.m64n256k16.f32.bf16.bf16 {%0, %1, %2, %3, %4, %5, %6, %7, %8, %9, %10, %11, %12, %13, %14, %15, %16, %17, %18, %19, %20, %21, %22, %23, %24, %25, %26, %27, %28, %29, %30, %31, %32, %33, %34, %35, %36, %37, %38, %39, %40, %41, %42, %43, %44, %45, %46, %47, %48, %49, %50, %51, %52, %53, %54, %55, %56, %57, %58, %59, %60, %61, %62, %63, %64, %65, %66, %67, %68, %69, %70, %71, %72, %73, %74, %75, %76, %77, %78, %79, %80, %81, %82, %83, %84, %85, %86, %87, %88, %89, %90, %91, %92, %93, %94, %95, %96, %97, %98, %99, %100, %101, %102, %103, %104, %105, %106, %107, %108, %109, %110, %111, %112, %113, %114, %115, %116, %117, %118, %119, %120, %121, %122, %123, %124, %125, %126, %127}, da, db, 1, 1, 1, 0, 1;\n"
    "add.u32 t, %128, 4;\nmov.b64 da, {t, %130};\nadd.u32 t, %129, 1024;\nmov.b64 db, {t, %130};\n"
    "wgmma.mma_async.sync.aligned.m64n256k16.f32.bf16.bf16 {%0, %1, %2, %3, %4, %5, %6, %7, %8, %9, %10, %11, %12, %13, %14, %15, %16, %17, %18, %19, %20, %21, %22, %23, %24, %25, %26, %27, %28, %29, %30, %31, %32, %33, %34, %35, %36, %37, %38, %39, %40, %41, %42, %43, %44, %45, %46, %47, %48, %49, %50, %51, %52, %53, %54, %55, %56, %57, %58, %59, %60, %61, %62, %63, %64, %65, %66, %67, %68, %69, %70, %71, %72, %73, %74, %75, %76, %77, %78, %79, %80, %81, %82, %83, %84, %85, %86, %87, %88, %89, %90, %91, %92, %93, %94, %95, %96, %97, %98, %99, %100, %101, %102, %103, %104, %105, %106, %107, %108, %109, %110, %111, %112, %113, %114, %115, %116, %117, %118, %119, %120, %121, %122, %123, %124, %125, %126, %127}, da, db, 1, 1, 1, 0, 1;\n"
    "add.u32 t, %128, 6;\nmov.b64 da, {t, %130};\nadd.u32 t, %129, 1152;\nmov.b64 db, {t, %130};\n"
    "wgmma.mma_async.sync.aligned.m64n256k16.f32.bf16.bf16 {%0, %1, %2, %3, %4, %5, %6, %7, %8, %9, %10, %11, %12, %13, %14, %15, %16, %17, %18, %19, %20, %21, %22, %23, %24, %25, %26, %27, %28, %29, %30, %31, %32, %33, %34, %35, %36, %37, %38, %39, %40, %41, %42, %43, %44, %45, %46, %47, %48, %49, %50, %51, %52, %53, %54, %55, %56, %57, %58, %59, %60, %61, %62, %63, %64, %65, %66, %67, %68, %69, %70, %71, %72, %73, %74, %75, %76, %77, %78, %79, %80, %81, %82, %83, %84, %85, %86, %87, %88, %89, %90, %91, %92, %93, %94, %95, %96, %97, %98, %99, %100, %101, %102, %103, %104, %105, %106, %107, %108, %109, %110, %111, %112, %113, %114, %115, %116, %117, %118, %119, %120, %121, %122, %123, %124, %125, %126, %127}, da, db, 1, 1, 1, 0, 1;\nwgmma.commit_group.sync.aligned;\n"
    "}\n"
    : "+f"(d[0]), "+f"(d[1]), "+f"(d[2]), "+f"(d[3]), "+f"(d[4]), "+f"(d[5]), "+f"(d[6]), "+f"(d[7]), "+f"(d[8]), "+f"(d[9]), "+f"(d[10]), "+f"(d[11]), "+f"(d[12]), "+f"(d[13]), "+f"(d[14]), "+f"(d[15]), "+f"(d[16]), "+f"(d[17]), "+f"(d[18]), "+f"(d[19]), "+f"(d[20]), "+f"(d[21]), "+f"(d[22]), "+f"(d[23]), "+f"(d[24]), "+f"(d[25]), "+f"(d[26]), "+f"(d[27]), "+f"(d[28]), "+f"(d[29]), "+f"(d[30]), "+f"(d[31]), "+f"(d[32]), "+f"(d[33]), "+f"(d[34]), "+f"(d[35]), "+f"(d[36]), "+f"(d[37]), "+f"(d[38]), "+f"(d[39]), "+f"(d[40]), "+f"(d[41]), "+f"(d[42]), "+f"(d[43]), "+f"(d[44]), "+f"(d[45]), "+f"(d[46]), "+f"(d[47]), "+f"(d[48]), "+f"(d[49]), "+f"(d[50]), "+f"(d[51]), "+f"(d[52]), "+f"(d[53]), "+f"(d[54]), "+f"(d[55]), "+f"(d[56]), "+f"(d[57]), "+f"(d[58]), "+f"(d[59]), "+f"(d[60]), "+f"(d[61]), "+f"(d[62]), "+f"(d[63]), "+f"(d[64]), "+f"(d[65]), "+f"(d[66]), "+f"(d[67]), "+f"(d[68]), "+f"(d[69]), "+f"(d[70]), "+f"(d[71]), "+f"(d[72]), "+f"(d[73]), "+f"(d[74]), "+f"(d[75]), "+f"(d[76]), "+f"(d[77]), "+f"(d[78]), "+f"(d[79]), "+f"(d[80]), "+f"(d[81]), "+f"(d[82]), "+f"(d[83]), "+f"(d[84]), "+f"(d[85]), "+f"(d[86]), "+f"(d[87]), "+f"(d[88]), "+f"(d[89]), "+f"(d[90]), "+f"(d[91]), "+f"(d[92]), "+f"(d[93]), "+f"(d[94]), "+f"(d[95]), "+f"(d[96]), "+f"(d[97]), "+f"(d[98]), "+f"(d[99]), "+f"(d[100]), "+f"(d[101]), "+f"(d[102]), "+f"(d[103]), "+f"(d[104]), "+f"(d[105]), "+f"(d[106]), "+f"(d[107]), "+f"(d[108]), "+f"(d[109]), "+f"(d[110]), "+f"(d[111]), "+f"(d[112]), "+f"(d[113]), "+f"(d[114]), "+f"(d[115]), "+f"(d[116]), "+f"(d[117]), "+f"(d[118]), "+f"(d[119]), "+f"(d[120]), "+f"(d[121]), "+f"(d[122]), "+f"(d[123]), "+f"(d[124]), "+f"(d[125]), "+f"(d[126]), "+f"(d[127])
    : "r"(a), "r"(b), "n"(0x40000040) : "memory");
}
__device__ __forceinline__ void first_kstep(float (&d)[96], uint32_t a, uint32_t b) {
  asm volatile("{\n.reg .u32 t;\n.reg .u64 da, db;\nwgmma.fence.sync.aligned;\n"
    "add.u32 t, %96, 0;\nmov.b64 da, {t, %98};\nadd.u32 t, %97, 0;\nmov.b64 db, {t, %98};\n"
    "wgmma.mma_async.sync.aligned.m64n192k16.f32.bf16.bf16 {%0, %1, %2, %3, %4, %5, %6, %7, %8, %9, %10, %11, %12, %13, %14, %15, %16, %17, %18, %19, %20, %21, %22, %23, %24, %25, %26, %27, %28, %29, %30, %31, %32, %33, %34, %35, %36, %37, %38, %39, %40, %41, %42, %43, %44, %45, %46, %47, %48, %49, %50, %51, %52, %53, %54, %55, %56, %57, %58, %59, %60, %61, %62, %63, %64, %65, %66, %67, %68, %69, %70, %71, %72, %73, %74, %75, %76, %77, %78, %79, %80, %81, %82, %83, %84, %85, %86, %87, %88, %89, %90, %91, %92, %93, %94, %95}, da, db, 0, 1, 1, 0, 1;\nwgmma.commit_group.sync.aligned;\n"
    "add.u32 t, %96, 2;\nmov.b64 da, {t, %98};\nadd.u32 t, %97, 128;\nmov.b64 db, {t, %98};\n"
    "wgmma.mma_async.sync.aligned.m64n192k16.f32.bf16.bf16 {%0, %1, %2, %3, %4, %5, %6, %7, %8, %9, %10, %11, %12, %13, %14, %15, %16, %17, %18, %19, %20, %21, %22, %23, %24, %25, %26, %27, %28, %29, %30, %31, %32, %33, %34, %35, %36, %37, %38, %39, %40, %41, %42, %43, %44, %45, %46, %47, %48, %49, %50, %51, %52, %53, %54, %55, %56, %57, %58, %59, %60, %61, %62, %63, %64, %65, %66, %67, %68, %69, %70, %71, %72, %73, %74, %75, %76, %77, %78, %79, %80, %81, %82, %83, %84, %85, %86, %87, %88, %89, %90, %91, %92, %93, %94, %95}, da, db, 1, 1, 1, 0, 1;\n"
    "add.u32 t, %96, 4;\nmov.b64 da, {t, %98};\nadd.u32 t, %97, 1024;\nmov.b64 db, {t, %98};\n"
    "wgmma.mma_async.sync.aligned.m64n192k16.f32.bf16.bf16 {%0, %1, %2, %3, %4, %5, %6, %7, %8, %9, %10, %11, %12, %13, %14, %15, %16, %17, %18, %19, %20, %21, %22, %23, %24, %25, %26, %27, %28, %29, %30, %31, %32, %33, %34, %35, %36, %37, %38, %39, %40, %41, %42, %43, %44, %45, %46, %47, %48, %49, %50, %51, %52, %53, %54, %55, %56, %57, %58, %59, %60, %61, %62, %63, %64, %65, %66, %67, %68, %69, %70, %71, %72, %73, %74, %75, %76, %77, %78, %79, %80, %81, %82, %83, %84, %85, %86, %87, %88, %89, %90, %91, %92, %93, %94, %95}, da, db, 1, 1, 1, 0, 1;\n"
    "add.u32 t, %96, 6;\nmov.b64 da, {t, %98};\nadd.u32 t, %97, 1152;\nmov.b64 db, {t, %98};\n"
    "wgmma.mma_async.sync.aligned.m64n192k16.f32.bf16.bf16 {%0, %1, %2, %3, %4, %5, %6, %7, %8, %9, %10, %11, %12, %13, %14, %15, %16, %17, %18, %19, %20, %21, %22, %23, %24, %25, %26, %27, %28, %29, %30, %31, %32, %33, %34, %35, %36, %37, %38, %39, %40, %41, %42, %43, %44, %45, %46, %47, %48, %49, %50, %51, %52, %53, %54, %55, %56, %57, %58, %59, %60, %61, %62, %63, %64, %65, %66, %67, %68, %69, %70, %71, %72, %73, %74, %75, %76, %77, %78, %79, %80, %81, %82, %83, %84, %85, %86, %87, %88, %89, %90, %91, %92, %93, %94, %95}, da, db, 1, 1, 1, 0, 1;\nwgmma.commit_group.sync.aligned;\n"
    "}\n"
    : "=f"(d[0]), "=f"(d[1]), "=f"(d[2]), "=f"(d[3]), "=f"(d[4]), "=f"(d[5]), "=f"(d[6]), "=f"(d[7]), "=f"(d[8]), "=f"(d[9]), "=f"(d[10]), "=f"(d[11]), "=f"(d[12]), "=f"(d[13]), "=f"(d[14]), "=f"(d[15]), "=f"(d[16]), "=f"(d[17]), "=f"(d[18]), "=f"(d[19]), "=f"(d[20]), "=f"(d[21]), "=f"(d[22]), "=f"(d[23]), "=f"(d[24]), "=f"(d[25]), "=f"(d[26]), "=f"(d[27]), "=f"(d[28]), "=f"(d[29]), "=f"(d[30]), "=f"(d[31]), "=f"(d[32]), "=f"(d[33]), "=f"(d[34]), "=f"(d[35]), "=f"(d[36]), "=f"(d[37]), "=f"(d[38]), "=f"(d[39]), "=f"(d[40]), "=f"(d[41]), "=f"(d[42]), "=f"(d[43]), "=f"(d[44]), "=f"(d[45]), "=f"(d[46]), "=f"(d[47]), "=f"(d[48]), "=f"(d[49]), "=f"(d[50]), "=f"(d[51]), "=f"(d[52]), "=f"(d[53]), "=f"(d[54]), "=f"(d[55]), "=f"(d[56]), "=f"(d[57]), "=f"(d[58]), "=f"(d[59]), "=f"(d[60]), "=f"(d[61]), "=f"(d[62]), "=f"(d[63]), "=f"(d[64]), "=f"(d[65]), "=f"(d[66]), "=f"(d[67]), "=f"(d[68]), "=f"(d[69]), "=f"(d[70]), "=f"(d[71]), "=f"(d[72]), "=f"(d[73]), "=f"(d[74]), "=f"(d[75]), "=f"(d[76]), "=f"(d[77]), "=f"(d[78]), "=f"(d[79]), "=f"(d[80]), "=f"(d[81]), "=f"(d[82]), "=f"(d[83]), "=f"(d[84]), "=f"(d[85]), "=f"(d[86]), "=f"(d[87]), "=f"(d[88]), "=f"(d[89]), "=f"(d[90]), "=f"(d[91]), "=f"(d[92]), "=f"(d[93]), "=f"(d[94]), "=f"(d[95])
    : "r"(a), "r"(b), "n"(0x40000040) : "memory");
}
__device__ __forceinline__ void kstep(float (&d)[96], uint32_t a, uint32_t b) {
  asm volatile("{\n.reg .u32 t;\n.reg .u64 da, db;\nwgmma.fence.sync.aligned;\n"
    "add.u32 t, %96, 0;\nmov.b64 da, {t, %98};\nadd.u32 t, %97, 0;\nmov.b64 db, {t, %98};\n"
    "wgmma.mma_async.sync.aligned.m64n192k16.f32.bf16.bf16 {%0, %1, %2, %3, %4, %5, %6, %7, %8, %9, %10, %11, %12, %13, %14, %15, %16, %17, %18, %19, %20, %21, %22, %23, %24, %25, %26, %27, %28, %29, %30, %31, %32, %33, %34, %35, %36, %37, %38, %39, %40, %41, %42, %43, %44, %45, %46, %47, %48, %49, %50, %51, %52, %53, %54, %55, %56, %57, %58, %59, %60, %61, %62, %63, %64, %65, %66, %67, %68, %69, %70, %71, %72, %73, %74, %75, %76, %77, %78, %79, %80, %81, %82, %83, %84, %85, %86, %87, %88, %89, %90, %91, %92, %93, %94, %95}, da, db, 1, 1, 1, 0, 1;\nwgmma.commit_group.sync.aligned;\n"
    "add.u32 t, %96, 2;\nmov.b64 da, {t, %98};\nadd.u32 t, %97, 128;\nmov.b64 db, {t, %98};\n"
    "wgmma.mma_async.sync.aligned.m64n192k16.f32.bf16.bf16 {%0, %1, %2, %3, %4, %5, %6, %7, %8, %9, %10, %11, %12, %13, %14, %15, %16, %17, %18, %19, %20, %21, %22, %23, %24, %25, %26, %27, %28, %29, %30, %31, %32, %33, %34, %35, %36, %37, %38, %39, %40, %41, %42, %43, %44, %45, %46, %47, %48, %49, %50, %51, %52, %53, %54, %55, %56, %57, %58, %59, %60, %61, %62, %63, %64, %65, %66, %67, %68, %69, %70, %71, %72, %73, %74, %75, %76, %77, %78, %79, %80, %81, %82, %83, %84, %85, %86, %87, %88, %89, %90, %91, %92, %93, %94, %95}, da, db, 1, 1, 1, 0, 1;\n"
    "add.u32 t, %96, 4;\nmov.b64 da, {t, %98};\nadd.u32 t, %97, 1024;\nmov.b64 db, {t, %98};\n"
    "wgmma.mma_async.sync.aligned.m64n192k16.f32.bf16.bf16 {%0, %1, %2, %3, %4, %5, %6, %7, %8, %9, %10, %11, %12, %13, %14, %15, %16, %17, %18, %19, %20, %21, %22, %23, %24, %25, %26, %27, %28, %29, %30, %31, %32, %33, %34, %35, %36, %37, %38, %39, %40, %41, %42, %43, %44, %45, %46, %47, %48, %49, %50, %51, %52, %53, %54, %55, %56, %57, %58, %59, %60, %61, %62, %63, %64, %65, %66, %67, %68, %69, %70, %71, %72, %73, %74, %75, %76, %77, %78, %79, %80, %81, %82, %83, %84, %85, %86, %87, %88, %89, %90, %91, %92, %93, %94, %95}, da, db, 1, 1, 1, 0, 1;\n"
    "add.u32 t, %96, 6;\nmov.b64 da, {t, %98};\nadd.u32 t, %97, 1152;\nmov.b64 db, {t, %98};\n"
    "wgmma.mma_async.sync.aligned.m64n192k16.f32.bf16.bf16 {%0, %1, %2, %3, %4, %5, %6, %7, %8, %9, %10, %11, %12, %13, %14, %15, %16, %17, %18, %19, %20, %21, %22, %23, %24, %25, %26, %27, %28, %29, %30, %31, %32, %33, %34, %35, %36, %37, %38, %39, %40, %41, %42, %43, %44, %45, %46, %47, %48, %49, %50, %51, %52, %53, %54, %55, %56, %57, %58, %59, %60, %61, %62, %63, %64, %65, %66, %67, %68, %69, %70, %71, %72, %73, %74, %75, %76, %77, %78, %79, %80, %81, %82, %83, %84, %85, %86, %87, %88, %89, %90, %91, %92, %93, %94, %95}, da, db, 1, 1, 1, 0, 1;\nwgmma.commit_group.sync.aligned;\n"
    "}\n"
    : "+f"(d[0]), "+f"(d[1]), "+f"(d[2]), "+f"(d[3]), "+f"(d[4]), "+f"(d[5]), "+f"(d[6]), "+f"(d[7]), "+f"(d[8]), "+f"(d[9]), "+f"(d[10]), "+f"(d[11]), "+f"(d[12]), "+f"(d[13]), "+f"(d[14]), "+f"(d[15]), "+f"(d[16]), "+f"(d[17]), "+f"(d[18]), "+f"(d[19]), "+f"(d[20]), "+f"(d[21]), "+f"(d[22]), "+f"(d[23]), "+f"(d[24]), "+f"(d[25]), "+f"(d[26]), "+f"(d[27]), "+f"(d[28]), "+f"(d[29]), "+f"(d[30]), "+f"(d[31]), "+f"(d[32]), "+f"(d[33]), "+f"(d[34]), "+f"(d[35]), "+f"(d[36]), "+f"(d[37]), "+f"(d[38]), "+f"(d[39]), "+f"(d[40]), "+f"(d[41]), "+f"(d[42]), "+f"(d[43]), "+f"(d[44]), "+f"(d[45]), "+f"(d[46]), "+f"(d[47]), "+f"(d[48]), "+f"(d[49]), "+f"(d[50]), "+f"(d[51]), "+f"(d[52]), "+f"(d[53]), "+f"(d[54]), "+f"(d[55]), "+f"(d[56]), "+f"(d[57]), "+f"(d[58]), "+f"(d[59]), "+f"(d[60]), "+f"(d[61]), "+f"(d[62]), "+f"(d[63]), "+f"(d[64]), "+f"(d[65]), "+f"(d[66]), "+f"(d[67]), "+f"(d[68]), "+f"(d[69]), "+f"(d[70]), "+f"(d[71]), "+f"(d[72]), "+f"(d[73]), "+f"(d[74]), "+f"(d[75]), "+f"(d[76]), "+f"(d[77]), "+f"(d[78]), "+f"(d[79]), "+f"(d[80]), "+f"(d[81]), "+f"(d[82]), "+f"(d[83]), "+f"(d[84]), "+f"(d[85]), "+f"(d[86]), "+f"(d[87]), "+f"(d[88]), "+f"(d[89]), "+f"(d[90]), "+f"(d[91]), "+f"(d[92]), "+f"(d[93]), "+f"(d[94]), "+f"(d[95])
    : "r"(a), "r"(b), "n"(0x40000040) : "memory");
}
__device__ __forceinline__ void half_kstep0(float (&d)[64], uint32_t a, uint32_t b) {
  asm volatile("{\n.reg .u32 t;\n.reg .u64 da, db;\nwgmma.fence.sync.aligned;\n"
    "add.u32 t, %64, 0;\nmov.b64 da, {t, %66};\nadd.u32 t, %65, 0;\nmov.b64 db, {t, %66};\n"
    "wgmma.mma_async.sync.aligned.m64n128k16.f32.bf16.bf16 {%0, %1, %2, %3, %4, %5, %6, %7, %8, %9, %10, %11, %12, %13, %14, %15, %16, %17, %18, %19, %20, %21, %22, %23, %24, %25, %26, %27, %28, %29, %30, %31, %32, %33, %34, %35, %36, %37, %38, %39, %40, %41, %42, %43, %44, %45, %46, %47, %48, %49, %50, %51, %52, %53, %54, %55, %56, %57, %58, %59, %60, %61, %62, %63}, da, db, 1, 1, 1, 0, 1;\n"
    "add.u32 t, %64, 2;\nmov.b64 da, {t, %66};\nadd.u32 t, %65, 128;\nmov.b64 db, {t, %66};\n"
    "wgmma.mma_async.sync.aligned.m64n128k16.f32.bf16.bf16 {%0, %1, %2, %3, %4, %5, %6, %7, %8, %9, %10, %11, %12, %13, %14, %15, %16, %17, %18, %19, %20, %21, %22, %23, %24, %25, %26, %27, %28, %29, %30, %31, %32, %33, %34, %35, %36, %37, %38, %39, %40, %41, %42, %43, %44, %45, %46, %47, %48, %49, %50, %51, %52, %53, %54, %55, %56, %57, %58, %59, %60, %61, %62, %63}, da, db, 1, 1, 1, 0, 1;\n"
    "add.u32 t, %64, 4;\nmov.b64 da, {t, %66};\nadd.u32 t, %65, 1024;\nmov.b64 db, {t, %66};\n"
    "wgmma.mma_async.sync.aligned.m64n128k16.f32.bf16.bf16 {%0, %1, %2, %3, %4, %5, %6, %7, %8, %9, %10, %11, %12, %13, %14, %15, %16, %17, %18, %19, %20, %21, %22, %23, %24, %25, %26, %27, %28, %29, %30, %31, %32, %33, %34, %35, %36, %37, %38, %39, %40, %41, %42, %43, %44, %45, %46, %47, %48, %49, %50, %51, %52, %53, %54, %55, %56, %57, %58, %59, %60, %61, %62, %63}, da, db, 1, 1, 1, 0, 1;\n"
    "add.u32 t, %64, 6;\nmov.b64 da, {t, %66};\nadd.u32 t, %65, 1152;\nmov.b64 db, {t, %66};\n"
    "wgmma.mma_async.sync.aligned.m64n128k16.f32.bf16.bf16 {%0, %1, %2, %3, %4, %5, %6, %7, %8, %9, %10, %11, %12, %13, %14, %15, %16, %17, %18, %19, %20, %21, %22, %23, %24, %25, %26, %27, %28, %29, %30, %31, %32, %33, %34, %35, %36, %37, %38, %39, %40, %41, %42, %43, %44, %45, %46, %47, %48, %49, %50, %51, %52, %53, %54, %55, %56, %57, %58, %59, %60, %61, %62, %63}, da, db, 1, 1, 1, 0, 1;\n"
    "wgmma.commit_group.sync.aligned;\n}\n"
    : "+f"(d[0]), "+f"(d[1]), "+f"(d[2]), "+f"(d[3]), "+f"(d[4]), "+f"(d[5]), "+f"(d[6]), "+f"(d[7]), "+f"(d[8]), "+f"(d[9]), "+f"(d[10]), "+f"(d[11]), "+f"(d[12]), "+f"(d[13]), "+f"(d[14]), "+f"(d[15]), "+f"(d[16]), "+f"(d[17]), "+f"(d[18]), "+f"(d[19]), "+f"(d[20]), "+f"(d[21]), "+f"(d[22]), "+f"(d[23]), "+f"(d[24]), "+f"(d[25]), "+f"(d[26]), "+f"(d[27]), "+f"(d[28]), "+f"(d[29]), "+f"(d[30]), "+f"(d[31]), "+f"(d[32]), "+f"(d[33]), "+f"(d[34]), "+f"(d[35]), "+f"(d[36]), "+f"(d[37]), "+f"(d[38]), "+f"(d[39]), "+f"(d[40]), "+f"(d[41]), "+f"(d[42]), "+f"(d[43]), "+f"(d[44]), "+f"(d[45]), "+f"(d[46]), "+f"(d[47]), "+f"(d[48]), "+f"(d[49]), "+f"(d[50]), "+f"(d[51]), "+f"(d[52]), "+f"(d[53]), "+f"(d[54]), "+f"(d[55]), "+f"(d[56]), "+f"(d[57]), "+f"(d[58]), "+f"(d[59]), "+f"(d[60]), "+f"(d[61]), "+f"(d[62]), "+f"(d[63])
    : "r"(a), "r"(b), "n"(0x40000040) : "memory");
}
__device__ __forceinline__ void half_kstep1(float (&d)[64], uint32_t a, uint32_t b) {
  asm volatile("{\n.reg .u32 t;\n.reg .u64 da, db;\nwgmma.fence.sync.aligned;\n"
    "add.u32 t, %64, 0;\nmov.b64 da, {t, %66};\nadd.u32 t, %65, 512;\nmov.b64 db, {t, %66};\n"
    "wgmma.mma_async.sync.aligned.m64n128k16.f32.bf16.bf16 {%0, %1, %2, %3, %4, %5, %6, %7, %8, %9, %10, %11, %12, %13, %14, %15, %16, %17, %18, %19, %20, %21, %22, %23, %24, %25, %26, %27, %28, %29, %30, %31, %32, %33, %34, %35, %36, %37, %38, %39, %40, %41, %42, %43, %44, %45, %46, %47, %48, %49, %50, %51, %52, %53, %54, %55, %56, %57, %58, %59, %60, %61, %62, %63}, da, db, 1, 1, 1, 0, 1;\n"
    "add.u32 t, %64, 2;\nmov.b64 da, {t, %66};\nadd.u32 t, %65, 640;\nmov.b64 db, {t, %66};\n"
    "wgmma.mma_async.sync.aligned.m64n128k16.f32.bf16.bf16 {%0, %1, %2, %3, %4, %5, %6, %7, %8, %9, %10, %11, %12, %13, %14, %15, %16, %17, %18, %19, %20, %21, %22, %23, %24, %25, %26, %27, %28, %29, %30, %31, %32, %33, %34, %35, %36, %37, %38, %39, %40, %41, %42, %43, %44, %45, %46, %47, %48, %49, %50, %51, %52, %53, %54, %55, %56, %57, %58, %59, %60, %61, %62, %63}, da, db, 1, 1, 1, 0, 1;\n"
    "add.u32 t, %64, 4;\nmov.b64 da, {t, %66};\nadd.u32 t, %65, 1536;\nmov.b64 db, {t, %66};\n"
    "wgmma.mma_async.sync.aligned.m64n128k16.f32.bf16.bf16 {%0, %1, %2, %3, %4, %5, %6, %7, %8, %9, %10, %11, %12, %13, %14, %15, %16, %17, %18, %19, %20, %21, %22, %23, %24, %25, %26, %27, %28, %29, %30, %31, %32, %33, %34, %35, %36, %37, %38, %39, %40, %41, %42, %43, %44, %45, %46, %47, %48, %49, %50, %51, %52, %53, %54, %55, %56, %57, %58, %59, %60, %61, %62, %63}, da, db, 1, 1, 1, 0, 1;\n"
    "add.u32 t, %64, 6;\nmov.b64 da, {t, %66};\nadd.u32 t, %65, 1664;\nmov.b64 db, {t, %66};\n"
    "wgmma.mma_async.sync.aligned.m64n128k16.f32.bf16.bf16 {%0, %1, %2, %3, %4, %5, %6, %7, %8, %9, %10, %11, %12, %13, %14, %15, %16, %17, %18, %19, %20, %21, %22, %23, %24, %25, %26, %27, %28, %29, %30, %31, %32, %33, %34, %35, %36, %37, %38, %39, %40, %41, %42, %43, %44, %45, %46, %47, %48, %49, %50, %51, %52, %53, %54, %55, %56, %57, %58, %59, %60, %61, %62, %63}, da, db, 1, 1, 1, 0, 1;\n"
    "wgmma.commit_group.sync.aligned;\n}\n"
    : "+f"(d[0]), "+f"(d[1]), "+f"(d[2]), "+f"(d[3]), "+f"(d[4]), "+f"(d[5]), "+f"(d[6]), "+f"(d[7]), "+f"(d[8]), "+f"(d[9]), "+f"(d[10]), "+f"(d[11]), "+f"(d[12]), "+f"(d[13]), "+f"(d[14]), "+f"(d[15]), "+f"(d[16]), "+f"(d[17]), "+f"(d[18]), "+f"(d[19]), "+f"(d[20]), "+f"(d[21]), "+f"(d[22]), "+f"(d[23]), "+f"(d[24]), "+f"(d[25]), "+f"(d[26]), "+f"(d[27]), "+f"(d[28]), "+f"(d[29]), "+f"(d[30]), "+f"(d[31]), "+f"(d[32]), "+f"(d[33]), "+f"(d[34]), "+f"(d[35]), "+f"(d[36]), "+f"(d[37]), "+f"(d[38]), "+f"(d[39]), "+f"(d[40]), "+f"(d[41]), "+f"(d[42]), "+f"(d[43]), "+f"(d[44]), "+f"(d[45]), "+f"(d[46]), "+f"(d[47]), "+f"(d[48]), "+f"(d[49]), "+f"(d[50]), "+f"(d[51]), "+f"(d[52]), "+f"(d[53]), "+f"(d[54]), "+f"(d[55]), "+f"(d[56]), "+f"(d[57]), "+f"(d[58]), "+f"(d[59]), "+f"(d[60]), "+f"(d[61]), "+f"(d[62]), "+f"(d[63])
    : "r"(a), "r"(b), "n"(0x40000040) : "memory");
}

__device__ __forceinline__ void sum_columns(float (&d)[4], uint32_t a, uint32_t b) {
  asm volatile("{\n.reg .u32 t;\n.reg .u64 da, db;\nmov.b64 db, {%5, 0};\nwgmma.fence.sync.aligned;\n"
               "add.u32 t, %4, 0;\nmov.b64 da, {t, %6};\nwgmma.mma_async.sync.aligned.m64n8k16.f32.bf16.bf16 {%0, %1, %2, %3}, da, db, 1, 1, 1, 1, 0;\n"
               "add.u32 t, %4, 128;\nmov.b64 da, {t, %6};\nwgmma.mma_async.sync.aligned.m64n8k16.f32.bf16.bf16 {%0, %1, %2, %3}, da, db, 1, 1, 1, 1, 0;\n"
               "add.u32 t, %4, 256;\nmov.b64 da, {t, %6};\nwgmma.mma_async.sync.aligned.m64n8k16.f32.bf16.bf16 {%0, %1, %2, %3}, da, db, 1, 1, 1, 1, 0;\n"
               "add.u32 t, %4, 384;\nmov.b64 da, {t, %6};\nwgmma.mma_async.sync.aligned.m64n8k16.f32.bf16.bf16 {%0, %1, %2, %3}, da, db, 1, 1, 1, 1, 0;\n"
               "add.u32 t, %4, 512;\nmov.b64 da, {t, %6};\nwgmma.mma_async.sync.aligned.m64n8k16.f32.bf16.bf16 {%0, %1, %2, %3}, da, db, 1, 1, 1, 1, 0;\n"
               "add.u32 t, %4, 640;\nmov.b64 da, {t, %6};\nwgmma.mma_async.sync.aligned.m64n8k16.f32.bf16.bf16 {%0, %1, %2, %3}, da, db, 1, 1, 1, 1, 0;\n"
               "add.u32 t, %4, 768;\nmov.b64 da, {t, %6};\nwgmma.mma_async.sync.aligned.m64n8k16.f32.bf16.bf16 {%0, %1, %2, %3}, da, db, 1, 1, 1, 1, 0;\n"
               "add.u32 t, %4, 896;\nmov.b64 da, {t, %6};\nwgmma.mma_async.sync.aligned.m64n8k16.f32.bf16.bf16 {%0, %1, %2, %3}, da, db, 1, 1, 1, 1, 0;\n"
               "add.u32 t, %4, 1024;\nmov.b64 da, {t, %6};\nwgmma.mma_async.sync.aligned.m64n8k16.f32.bf16.bf16 {%0, %1, %2, %3}, da, db, 1, 1, 1, 1, 0;\n"
               "add.u32 t, %4, 1152;\nmov.b64 da, {t, %6};\nwgmma.mma_async.sync.aligned.m64n8k16.f32.bf16.bf16 {%0, %1, %2, %3}, da, db, 1, 1, 1, 1, 0;\n"
               "add.u32 t, %4, 1280;\nmov.b64 da, {t, %6};\nwgmma.mma_async.sync.aligned.m64n8k16.f32.bf16.bf16 {%0, %1, %2, %3}, da, db, 1, 1, 1, 1, 0;\n"
               "add.u32 t, %4, 1408;\nmov.b64 da, {t, %6};\nwgmma.mma_async.sync.aligned.m64n8k16.f32.bf16.bf16 {%0, %1, %2, %3}, da, db, 1, 1, 1, 1, 0;\n"
               "add.u32 t, %4, 1536;\nmov.b64 da, {t, %6};\nwgmma.mma_async.sync.aligned.m64n8k16.f32.bf16.bf16 {%0, %1, %2, %3}, da, db, 1, 1, 1, 1, 0;\n"
               "add.u32 t, %4, 1664;\nmov.b64 da, {t, %6};\nwgmma.mma_async.sync.aligned.m64n8k16.f32.bf16.bf16 {%0, %1, %2, %3}, da, db, 1, 1, 1, 1, 0;\n"
               "add.u32 t, %4, 1792;\nmov.b64 da, {t, %6};\nwgmma.mma_async.sync.aligned.m64n8k16.f32.bf16.bf16 {%0, %1, %2, %3}, da, db, 1, 1, 1, 1, 0;\n"
               "add.u32 t, %4, 1920;\nmov.b64 da, {t, %6};\nwgmma.mma_async.sync.aligned.m64n8k16.f32.bf16.bf16 {%0, %1, %2, %3}, da, db, 1, 1, 1, 1, 0;\n"
               "wgmma.commit_group.sync.aligned;\nwgmma.wait_group.sync.aligned 0;\n}"
               : "+f"(d[0]), "+f"(d[1]), "+f"(d[2]), "+f"(d[3]) : "r"(a), "r"(b), "n"(0x40000040) : "memory");
}
struct Job {
  uint32_t type, layer, R, col, nk;
  __device__ __forceinline__ explicit Job(uint32_t j) : type(j & 3), layer((j >> 2) & 1), R((j >> 3) & 7), col((j >> 6) & 63), nk((j >> 12) & 63) {}
  __device__ __forceinline__ uint32_t inst() const { return layer * 2 + (type >> 1); }
};
struct Smem {
  char* scratch;
  uint32_t base;
  __device__ __forceinline__ uint32_t stage(uint32_t s) const { return base + (s & (NSTAGE - 1)) * STAGE; }
  __device__ __forceinline__ uint32_t slot(uint32_t c) const { return base + STG_OFF + c * SLOT; }
  __device__ __forceinline__ uint32_t full(uint32_t s) const { return base + BAR_OFF + (s & (NSTAGE - 1)) * 8; }
  __device__ __forceinline__ uint32_t empty(uint32_t s) const { return base + BAR_OFF + 32 + (s & (NSTAGE - 1)) * 8; }
  __device__ __forceinline__ uint32_t filled(uint32_t u) const { return base + BAR_OFF + 64 + u * 8; }
  __device__ __forceinline__ uint32_t vacant(uint32_t u) const { return base + BAR_OFF + 96 + u * 8; }
  __device__ __forceinline__ uint32_t summed(uint32_t s) const { return base + BAR_OFF + 128 + (s & (NSTAGE - 1)) * 8; }
  __device__ __forceinline__ uint32_t aux_full() const { return base + BAR_OFF + 160; }
  __device__ __forceinline__ uint32_t boot() const { return base + BAR_OFF + 168; }
  __device__ __forceinline__ uint32_t xchg_full() const { return base + BAR_OFF + 176; }
  __device__ __forceinline__ uint32_t wgmma_done() const { return base + BAR_OFF + 184; }
  __device__ __forceinline__ uint32_t mma_done() const { return base + BAR_OFF + 192; }
  __device__ __forceinline__ uint32_t kv_ready(int w) const { return base + BAR_OFF + 208 + w * 8; }
  __device__ __forceinline__ uint32_t pair_id() const { return base + BAR_OFF + 280; }
  __device__ __forceinline__ uint32_t stats() const { return base + AUX_OFF; }
  __device__ __forceinline__ uint32_t sums() const { return base + AUX_OFF + 1088; }
  __device__ __forceinline__ uint32_t xchg() const { return base + AUX_OFF + 1600; }
};
__device__ __forceinline__ uint32_t par(uint32_t s) { return (s / NSTAGE) & 1; }

__device__ __forceinline__ void st_word(u64* p, uint32_t lo, uint32_t hi) {
  asm volatile("st.relaxed.gpu.global.u64 [%0], %1;" ::"l"(p), "l"(((u64)hi << 32) | lo) : "memory");
}
__device__ __forceinline__ uint2 ld_word(const u64* p) {
  u64 v;
  asm volatile("ld.relaxed.gpu.global.u64 %0, [%1];" : "=l"(v) : "l"(p) : "memory");
  return make_uint2((uint32_t)v, (uint32_t)(v >> 32));
}
__device__ __forceinline__ void add_moments(uint4 v, float (&m)[4]) {
  const uint32_t w[4] = {v.x, v.y, v.z, v.w};
#pragma unroll
  for (int c = 0; c < 4; c++) {
    const float lo = bf_lo(w[c]), hi = bf_hi(w[c]);
    m[0] += lo; m[1] += hi; m[2] = fmaf(lo, lo, m[2]); m[3] = fmaf(hi, hi, m[3]);
  }
}
__device__ __forceinline__ void publish_stats(const Smem& sm, float s, float q, uint32_t idx, bool valid, uint32_t e1) {
  const float mean = s * (1.f / D), var = fmaxf(q * (1.f / D) - mean * mean, 0.f);
  const u64 word = ((u64)((__float_as_uint(-bf_round(mean)) & 0xffff0000u) | (e1 & 0xffff)) << 32) | __float_as_uint(rcp(bf_round(sqrt_fast(bf_round(bf_round(var) + 1e-5f)))));
  asm volatile("{\n.reg .pred p;\nsetp.ne.u32 p, %2, 0;\n@p st.relaxed.gpu.global.u64 [%0], %1;\n}" ::"l"(SCR(sm, stats, idx * 8)), "l"(word), "r"((uint32_t)valid) : "memory");
}
__device__ __forceinline__ void stats_task(const Smem& sm, uint32_t jw, int rank, int w, uint32_t e1, const bf16* x) {
  const uint32_t inst = (jw >> 22) & 3, lane = fresh_tid() & 31, steps = (jw >> 31) * 2 + 2;
  uint32_t row = ((jw >> 24) & 127) * 8 + (w - 1) * 4 + (lane >> 3);
  wait_count(counter(C_X + inst * 16 + (row >> 7) * 2 + rank, lane & 7), e1 * (inst & 1 ? 56 : 16));
  const uint4* p = at(reinterpret_cast<const uint4*>(x), (row * 2 + rank) * (D * 2) + (lane & 7) * 16);
  uint4 v[8];
  float m[4] = {0.f, 0.f, 0.f, 0.f};
#pragma unroll
  for (int i = 0; i < 8; i++) v[i] = ldg128(p + i * 8);
#pragma unroll 1
  for (uint32_t it = 1; it <= steps; it++) {
    p = at(p, it & 1 ? 1024 : 8 * D * 4 - 1024);
#pragma unroll
    for (int i = 0; i < 8; i++) {
      add_moments(v[i], m);
      if (it < steps) v[i] = ldg128(p + i * 8);
    }
    if (!(it & 1)) {
      m[0] += m[1]; m[2] += m[3];
#pragma unroll
      for (int o = 1; o <= 4; o <<= 1) { m[0] += __shfl_xor_sync(~0u, m[0], o); m[2] += __shfl_xor_sync(~0u, m[2], o); }
      publish_stats(sm, m[0], m[2], (inst + 1) * S + rank * (S / 2) + row, (lane & 7) == 0, e1);
      m[0] = m[1] = m[2] = m[3] = 0.f;
      row += 8;
    }
  }
}
struct Stager {
  uint2 st[5], cs[4];
  __device__ __forceinline__ void load(const Smem& sm, const Job& J, int rank, int lane, bool sums) {
#pragma unroll
    for (int i = 0; i < 5; i++) st[i] = ld_word(SCR(sm, stats, (J.inst() * S + rank * (S / 2) + J.R * 128 + min(max(lane - 8 + 32 * i, J.R && J.type == T_Q ? -8 : 0), 127)) * 8));
#pragma unroll
    for (int i = 0; i < 4; i++)
      if (sums && (i < 3 || J.type == T_G)) cs[i] = ld_word(SCR(sm, cs, ((J.col + J.type * 8) * 128 + lane) * 8) + i * 32);
  }
  __device__ __forceinline__ void store(const Smem& sm, const Job& J, int rank, int lane, bool sums, uint32_t e1) {
    for (uint32_t n = 0;; n++) {
      uint32_t bad = (st[1].y ^ e1) | (st[2].y ^ e1) | (st[3].y ^ e1);
      bad |= (st[0].y ^ e1) | (st[4].y ^ e1);
      if (sums) bad |= (cs[0].y ^ e1) | (cs[1].y ^ e1) | (cs[2].y ^ e1);
      if (J.type == T_G) bad |= cs[3].y ^ e1;
      if (__all_sync(~0u, (bad & 0xffff) == 0)) break;
      __nanosleep(V_SL2);
      if (n > SPIN_LIMIT) __trap();
      load(sm, J, rank, lane, sums);
    }
#pragma unroll
    for (int i = 0; i < 5; i++) {
      if (i < 4 || lane < 8) sts64(sm.stats() + (lane + 32 * i) * 8, st[i]);
      if (i < 4 && sums && (i < 3 || J.type == T_G)) sts32(sm.sums() + (lane + 32 * i) * 4, cs[i].x);
    }
  }
};
__device__ __forceinline__ void add_cols(float (&a)[8], uint4 x, uint4 y) {
  const uint4 t = add8(x, y);
  a[0] += bf_lo(t.x); a[1] += bf_hi(t.x); a[2] += bf_lo(t.y); a[3] += bf_hi(t.y);
  a[4] += bf_lo(t.z); a[5] += bf_hi(t.z); a[6] += bf_lo(t.w); a[7] += bf_hi(t.w);
}
__device__ __forceinline__ void reduce_cols(float (&a)[8], int lane) {
#pragma unroll
  for (int i = 0; i < 4; i++) { const bool up = lane & 16; const float o = __shfl_xor_sync(~0u, up ? a[i] : a[i + 4], 16); a[i] = (up ? a[i + 4] : a[i]) + o; }
#pragma unroll
  for (int i = 0; i < 2; i++) { const bool up = lane & 8; const float o = __shfl_xor_sync(~0u, up ? a[i] : a[i + 2], 8); a[i] = (up ? a[i + 2] : a[i]) + o; }
}
template <class Fn>
__device__ __forceinline__ uint32_t qkv_col_sums(const Smem& sm, int rank, int w, int lane, Fn between) {
  float a[8] = {0.f, 0.f, 0.f, 0.f, 0.f, 0.f, 0.f, 0.f};
#pragma unroll 1
  for (int s = 0; s < D / 64; s++) {
    between(s);
    const uint32_t p = sm.stage(s) + SLOT + rank * SLOT + w * 4096 + (lane >> 3) * 128 + (((lane & 7) ^ (lane >> 3)) << 4);
    uint4 v[8];
    mbar_wait(sm.full(s), par(s));
#pragma unroll
    for (int j = 0; j < 8; j++) v[j] = lds128((p ^ ((j & 1) * 64)) + j * 512);
    __syncwarp();
    mbar_arrive_cl_if(lane < 2, mapa(sm.summed(s), lane & 1));
    add_cols(a, add8(v[0], v[1]), add8(v[2], v[3]));
    add_cols(a, add8(v[4], v[5]), add8(v[6], v[7]));
  }
  reduce_cols(a, lane);
  const uint32_t slot = sm.xchg() + (w * 32 + lane) * 8;
  asm volatile("st.async.weak.shared::cluster.mbarrier::complete_tx::bytes.v2.b32 [%0], {%1, %2}, [%3];"
               ::"r"(mapa(slot, rank ^ 1)), "r"(__float_as_uint(a[0])), "r"(__float_as_uint(a[1])), "r"(mapa(sm.xchg_full(), rank ^ 1)) : "memory");
  mbar_wait(sm.xchg_full(), 0);
  const uint2 o = lds64(slot);
  return pack_bf16(a[0] + __uint_as_float(o.x), a[1] + __uint_as_float(o.y));
}

constexpr float LOGIT_SCALE = 0.17677669529663687f * 1.4426950408889634f;
constexpr float MASKED = -1e30f;
enum { A_CS = 16, A_NM = 40, A_KT = 42, A_KU = 44, A_CT = 46, A_CU = 48, A_BIAS = 50, A_MASK = 52, A_ZERO = 53 };
__device__ __forceinline__ void attention_prepare(uint32_t (&r)[64], const Smem& sm, int W, int lane, bool first) {
  const int i = lane >> 2, c = (lane & 3) * 2;
  r[A_ZERO] = opaque_zero();
  r[A_MASK] = (c > i ? 0xffffu : 0u) | (c + 1 > i ? 0xffff0000u : 0u);
  const uint32_t a = sm.stats() + W * 128;
  const uint2 r0 = lds64(a + 64 + i * 8), r1 = lds64(a + 128 + i * 8);
#pragma unroll
  for (int y = 0; y < 2; y++) {
    const uint32_t k = a + (c + y + (c + y > i ? 0 : 8)) * 8;
    const float kt = lds32f(k), ku = lds32f(k + 64);
    r[A_KT + y] = __float_as_uint(kt); r[A_CT + y] = __float_as_uint(__uint_as_float(r0.x) * LOGIT_SCALE * kt);
    r[A_KU + y] = __float_as_uint(ku); r[A_CU + y] = __float_as_uint(__uint_as_float(r1.x) * LOGIT_SCALE * ku);
    r[A_BIAS + y] = __float_as_uint(first && W == 0 && c + y > i ? MASKED : 0.f);
  }
#pragma unroll
  for (int j = 0; j < 6; j++) {
    const uint4 v = lds128(sm.sums() + c * 48 + j * 16);
    r[A_CS + 4 * j] = v.x; r[A_CS + 4 * j + 1] = v.y; r[A_CS + 4 * j + 2] = v.z; r[A_CS + 4 * j + 3] = v.w;
  }
  r[A_NM] = dup_hi(r0.y); r[A_NM + 1] = dup_hi(r1.y);
}
__device__ __forceinline__ bool attention(const float (&acc)[96], uint32_t (&r)[64], const Smem& sm, int W, int lane, uint32_t t8, uint32_t t16,
                                          bool halo, uint32_t block, uint32_t tag, uint32_t parity, uint32_t next_bar, uint32_t next_parity, int ji) {
#define TRW W
  const uint32_t own = (W >> 2) * SLOT;
  const uint32_t pk = W == 0 ? (halo ? 4096 : 1024) : W == 4 ? 7168 : own - 1024;
  const uint32_t pv = W == 0 && halo ? 6144 : pk + 8192;
  uint32_t x[48];
  auto pack = [&](int j0, int step, int count) {
#pragma unroll
    for (int j = j0; j < j0 + step * count; j += step) x[j] = bf2_fma(r[A_NM + j % 2], r[A_CS + j / 2], pack_bf16(acc[2 * j], acc[2 * j + 1]));
  };
  auto put8 = [&](uint32_t a, int j) {
    stsm4(t8 + a, x[j], x[j + 2], x[j + 4], x[j + 6]);
    stsm4((t8 ^ 64) + a, x[j + 8], x[j + 10], x[j + 12], x[j + 14]);
  };
  uint32_t k0[2][4], v0[2][4], v12[4][4];
  pack(17, 2, 8);
  put8(own + 1024, 17);
  pack(32, 1, 16);
#pragma unroll
  for (int j = 0; j < 4; j++) stsm4((t16 ^ (j << 5)) + (own + 8192), x[32 + 4 * j], x[33 + 4 * j], x[34 + 4 * j], x[35 + 4 * j]);
  mbar_arrive_warp(sm.kv_ready(W));
  pack(16, 2, 8);
  pack(0, 1, 16);
  if (W == 0) {
    put8(0, 16);
#pragma unroll
    for (int j = 0; j < 4; j++) stsm4(lane & 8 ? sm.xchg() : (t16 ^ (j << 5)) + 2048, x[4 * j], x[4 * j + 1], x[4 * j + 2], x[4 * j + 3]);
  }
  mbar_wait(sm.kv_ready(W - 1), parity);
#pragma unroll
  for (int h = 0; h < 2; h++) ldsm4((t8 ^ (h * 64)) + pk, k0[h]);
#pragma unroll
  for (int j = 0; j < 4; j++) ldsm4t((t16 ^ (j << 5)) + (own + 8192), v12[j]);
#pragma unroll
  for (int h = 0; h < 2; h++) ldsm4t((t8 ^ (h * 64)) + pv, v0[h]);
  if (W < 4) mbar_wait(sm.wgmma_done(), parity);
  const bool next_full = mbar_test(next_bar, next_parity);
  TRC(ji, 20);
  float s0[2][4], s1[2][4], s2[2][4];
#pragma unroll
  for (int h = 0; h < 2; h++) {
#pragma unroll
    for (int y = 0; y < 4; y++) s0[h][y] = s1[h][y] = s2[h][y] = 0.f;
  }
#pragma unroll
  for (int ks = 0; ks < 2; ks++)
#pragma unroll
    for (int h = 0; h < 2; h++) {
      const int n = 8 * h + 4 * ks;
      mma16816(s1[h], x[n], x[n + 1], x[n + 2], x[n + 3], x[16 + n], x[18 + n]);
      mma16816(s2[h], x[n], x[n + 1], x[n + 2], x[n + 3], x[17 + n], x[19 + n]);
      mma16816(s0[h], x[n], x[n + 1], x[n + 2], x[n + 3], k0[h][2 * ks], k0[h][2 * ks + 1]);
    }
  const uint32_t mask = r[A_MASK];
  const bool after[2] = {(mask & 1) != 0, (int)mask < 0};
  float lt[2][2], lu[2][2], mt[2], mu[2];
#pragma unroll
  for (int h = 0; h < 2; h++) {
#pragma unroll
    for (int y = 0; y < 2; y++) {
      lt[h][y] = fmaf(after[y] ? s0[h][y] : s1[h][y], __uint_as_float(r[A_CT + y]), __uint_as_float(r[A_BIAS + y]));
      lu[h][y] = (after[y] ? s1[h][2 + y] : s2[h][2 + y]) * __uint_as_float(r[A_CU + y]);
    }
    mt[h] = fmaxf(lt[h][0], lt[h][1]);
    mu[h] = fmaxf(lu[h][0], lu[h][1]);
  }
#pragma unroll
  for (int d = 1; d <= 2; d++)
#pragma unroll
    for (int h = 0; h < 2; h++) {
      mt[h] = fmaxf(mt[h], __shfl_xor_sync(~0u, mt[h], d));
      mu[h] = fmaxf(mu[h], __shfl_xor_sync(~0u, mu[h], d));
    }
  float o[2][4][4];
#pragma unroll
  for (int h = 0; h < 2; h++) {
#pragma unroll
    for (int y = 0; y < 2; y++) { lt[h][y] = ex2(lt[h][y] - mt[h]); lu[h][y] = ex2(lu[h][y] - mu[h]); }
    const uint32_t pt = pack_bf16(lt[h][0] * __uint_as_float(r[A_KT]), lt[h][1] * __uint_as_float(r[A_KT + 1]));
    const uint32_t pu = pack_bf16(lu[h][0] * __uint_as_float(r[A_KU]), lu[h][1] * __uint_as_float(r[A_KU + 1]));
#pragma unroll
    for (int n = 0; n < 4; n++) {
      o[h][n][0] = o[h][n][1] = o[h][n][2] = o[h][n][3] = 0.f;
      mma16816(o[h][n], pt & ~mask, pu & mask, 0u, pu & ~mask, v12[2 * h + n / 2][n % 2 * 2], v12[2 * h + n / 2][n % 2 * 2 + 1]);
    }
#pragma unroll
    for (int n = 0; n < 4; n++) mma1688(o[h][n], pt & mask, 0u, v0[h][n]);
    mt[h] = lt[h][0] + lt[h][1];
    mu[h] = lu[h][0] + lu[h][1];
  }
#pragma unroll
  for (int d = 1; d <= 2; d++)
#pragma unroll
    for (int h = 0; h < 2; h++) {
      mt[h] += __shfl_xor_sync(~0u, mt[h], d);
      mu[h] += __shfl_xor_sync(~0u, mu[h], d);
    }
  uint32_t dep = 0;
#pragma unroll
  for (int n = 0; n < 3; n++) dep |= __float_as_uint(o[n % 2][n / 2][0]);
  mbar_arrive_warp(sm.mma_done() + (dep & r[A_ZERO]));
  TRC(ji, 22);
  if (W == 7) {
    ulonglong2* exp = SCR(sm, halo, (block * 256 + lane) * 16);
#pragma unroll
    for (int m = 0; m < 8; m++)
      asm volatile("st.relaxed.gpu.global.v2.u64 [%0], {%1,%2};" ::"l"(exp + m * 32), "l"(((u64)tag << 32) | x[17 + 4 * m]), "l"(((u64)tag << 32) | x[19 + 4 * m]) : "memory");
  }
#pragma unroll
  for (int h = 0; h < 2; h++) {
    const float rt = rcp(mt[h]), ru = rcp(mu[h]);
#pragma unroll
    for (int n = 0; n < 4; n++) {
      r[8 * h + 2 * n] = pack_bf16(o[h][n][0] * rt, o[h][n][1] * rt);
      r[8 * h + 2 * n + 1] = pack_bf16(o[h][n][2] * ru, o[h][n][3] * ru);
    }
  }
  return next_full;
}
__device__ __forceinline__ void import_halo(const Smem& sm, const ulonglong2* halo, uint32_t tag, int lane) {
  u64 x[16];
  for (uint32_t n = 0;; n++) {
#pragma unroll
    for (int m = 0; m < 8; m++)
      asm volatile("ld.relaxed.gpu.global.v2.u64 {%0,%1}, [%2];" : "=l"(x[2 * m]), "=l"(x[2 * m + 1]) : "l"(halo + m * 32) : "memory");
    uint32_t bad = 0;
#pragma unroll
    for (int m = 0; m < 16; m++) bad |= (uint32_t)(x[m] >> 32) ^ tag;
    if (__all_sync(~0u, bad == 0)) break;
    __nanosleep(V_SL3);
    if (n > SPIN_LIMIT) __trap();
  }
  const uint32_t a = sm.slot(0) + 4096 + (lane & 7) * 128 + (((lane >> 3) ^ (lane & 7)) << 4);
#pragma unroll
  for (int m = 0; m < 4; m++) stsm4((a ^ ((m & 1) * 64)) + (m >> 1) * 2048, (uint32_t)x[4 * m], (uint32_t)x[4 * m + 1], (uint32_t)x[4 * m + 2], (uint32_t)x[4 * m + 3]);
}
__device__ __forceinline__ void unpack8(uint4 v, float* f) {
  f[0] = bf_lo(v.x); f[1] = bf_hi(v.x); f[2] = bf_lo(v.y); f[3] = bf_hi(v.y);
  f[4] = bf_lo(v.z); f[5] = bf_hi(v.z); f[6] = bf_lo(v.w); f[7] = bf_hi(v.w);
}
__device__ __forceinline__ void boundary_rows(const Smem& sm, int h, int lane, uint32_t out) {
  const int i = lane >> 2, u = h * 4 + (lane & 3);
  uint4 r[8];
  float x[8], l[8], ik[8];
  unpack8(lds128(sm.slot(0) + 2048 + i * 128 + ((u ^ i) << 4)), x);
#pragma unroll
  for (int j = 0; j < 8; j++) {
    r[j] = lds128(sm.slot(0) + j * 128 + (j > i ? 4096 : 0) + ((u ^ j) << 4));
    ik[j] = lds32f(sm.stats() + j * 8 + (j > i ? 0 : 64));
  }
  const float cq = lds32f(sm.stats() + 64 + i * 8) * LOGIT_SCALE;
#pragma unroll
  for (int j = 0; j < 8; j++) {
    float kf[8];
    unpack8(r[j], kf);
    r[j] = lds128(sm.slot(0) + j * 128 + (j > i ? 6144 : 8192) + ((u ^ j) << 4));
    l[j] = 0.f;
#pragma unroll
    for (int d = 0; d < 8; d++) l[j] = fmaf(x[d], kf[d], l[j]);
  }
#pragma unroll
  for (int d = 1; d <= 2; d++)
#pragma unroll
    for (int j = 0; j < 8; j++) l[j] += __shfl_xor_sync(~0u, l[j], d);
  float m = MASKED, sum = 0.f;
#pragma unroll
  for (int j = 0; j < 8; j++) { l[j] *= cq * ik[j]; m = fmaxf(m, l[j]); }
#pragma unroll
  for (int j = 0; j < 8; j++) { l[j] = ex2(l[j] - m); sum += l[j]; }
  const float rs = rcp(sum);
#pragma unroll
  for (int d = 0; d < 8; d++) x[d] = 0.f;
#pragma unroll
  for (int j = 0; j < 8; j++) {
    const float pw = l[j] * ik[j] * rs;
    float vf[8];
    unpack8(r[j], vf);
#pragma unroll
    for (int d = 0; d < 8; d++) x[d] = fmaf(pw, vf[d], x[d]);
  }
  stg128(SCR(sm, o, out + i * (2 * D) + u * 16), make_uint4(pack_bf16(x[0], x[1]), pack_bf16(x[2], x[3]), pack_bf16(x[4], x[5]), pack_bf16(x[6], x[7])));
}
__device__ __forceinline__ uint32_t swiglu2(uint32_t g, uint32_t u, float hinv, float hinv2) {
  const float a = bf_lo(g) * hinv, b = bf_hi(g) * hinv, a2 = bf_lo(g) * hinv2, b2 = bf_hi(g) * hinv2;
  return bf2_mul(pack_bf16(fmaf(a2, tanh_fast(a), a2), fmaf(b2, tanh_fast(b), b2)), u);
}

__device__ __forceinline__ const uint32_t* dep_counter(const Smem& sm, uint32_t jw, int rank, uint32_t k) {
  const Job J(jw);
  const uint32_t b = J.R * 2 + rank;
  const uint32_t line = J.type == T_O ? C_O + J.layer * 16 + b : J.type == T_D ? C_H + J.layer * 16 + b : C_X + max((int)J.inst() - 1, 0) * 16 + b;
  return counter(line, J.type & 1 ? k >> (J.type >> 1) : (k >> 2) * 2 + (k & 1));
}
__device__ __forceinline__ void producer(const Params& P, const Smem& sm, const uint32_t* jobs, const uint8_t* kseq, int rank, int lane, uint32_t launches) {
  const uint32_t e1 = __shfl_sync(~0u, launches, 0) + 1;
  uint32_t s = (jobs[0] & JOB_C) ? 0 : NSTAGE;
  uint32_t end = 0, poll = 0;
  uint64_t keep, stream;
  asm("createpolicy.fractional.L2::evict_unchanged.b64 %0, 1.0;" : "=l"(keep));
  asm("createpolicy.fractional.L2::evict_first.b64 %0, 1.0;" : "=l"(stream));
  const uint32_t* dep = counter(0, 0);
  const uint32_t summed_end = (jobs[0] & JOB_C) ? 0 : D / 64 + NSTAGE;
  for (int ji = 0;; ji++) {
    const uint32_t jw = jobs[ji];
    const Job J(jw);
    if (J.nk == 0) break;
    const bool isC = jw & JOB_C, isX = isC && (jw & JOB_X);
    const uint32_t target = (jw & 7) == 0 ? 0 : e1 * (J.type == T_Q ? 56 : J.type == T_G ? 16 : 1);
    const uint32_t g = J.col * 2 + rank;
    const CUtensorMap* tmA = &P.a[isC ? 4 + isX : (jw & 7) == 4 ? 2 : J.type];
    const CUtensorMap* tmB = &P.w[J.type];
    const uint32_t bytes = isC ? 32768 : J.type == T_Q ? 40960 : STAGE, bcol = J.col << (J.type == T_Q ? 0 : J.type == T_G ? 1 : 2);
    const uint32_t a0 = isX ? 0 : (g >> 2) * 128 + (g & 1) * 64, a1 = isX ? g * 64 : J.R * 128, ak = isX ? 0 : 256, a2 = isC ? (g >> 1) & 1 : rank;
    end += J.nk;
    uint32_t sa = s, spins = 0;
    auto issue_a = [&](uint32_t k) { TRS(sa, 1); tma3d(sm.stage(sa), tmA, isC ? a0 : (k & 63) * 64, isC ? a1 + k * ak : a1, isX ? k * 4 : a2, sm.full(sa), (k & K_LAST_A) ? stream : keep); };
    auto issue_b = [&](uint32_t k) {
      mbar_expect_tx(sm.full(s), bytes);
      TRS(s, 0);
      if (!isC) tma4d_mc(sm.stage(s) + SLOT + rank * SLOT, tmB, (k & 63) * 64 + rank * 32, bcol, sm.full(s), (k & K_LAST_B) ? stream : keep);
    };
    TRI(lane == 0, ji, 6);
    TRK(lane == 0, ji, 24);
    while (true) {
      const uint32_t missing = __ballot_sync(~0u, (int)(poll - target) < 0 && lane < J.nk);
      uint32_t lim = end;
      if (missing) lim += __ffs(missing) - 1 - J.nk;
      if (lim > sa) {
        fence_acquire();
        fence_proxy_async();
        TRI(sa == end - J.nk && lane == 0, ji, 7);
#pragma unroll 1
        for (; sa < min(lim, s); sa++) {
          const uint32_t k = kseq[sa];
          if (elect()) issue_a(k);
        }
#pragma unroll 1
        for (int phase = 0;; phase++) {
          const uint32_t upto = phase == 2 ? lim : phase == 1 ? lim - LOOK : min((int)lim - LOOK, (int)sa + MID);
#pragma unroll 1
          for (; (int)sa < (int)upto; sa++, s++) {
            const uint32_t k = kseq[s];
            uint32_t stage = sm.stage(s), bar = sm.full(s), c0 = isC ? a0 : (k & 63) * 64, c1 = isC ? a1 + k * ak : a1, kb = (k & 63) * 64 + rank * 32, c2 = isX ? k * 4 : a2;
            uint64_t pa = (k & K_LAST_A) ? stream : keep, pb = (k & K_LAST_B) ? stream : keep;
            asm volatile("" : "+r"(stage), "+r"(bar), "+r"(c0), "+r"(c1), "+r"(kb), "+r"(c2), "+l"(pa), "+l"(pb));
            if (s < summed_end) mbar_wait(sm.summed(s), par(s) ^ 1);
            mbar_wait(bar + 32, par(s) ^ 1);
            TRS(s, 0);
            asm volatile("{\n.reg .pred p, q;\nelect.sync _|p, -1;\nsetp.eq.and.u32 q, %14, 0, p;\n"
                         "@q cp.async.bulk.tensor.4d.shared::cluster.global.mbarrier::complete_tx::bytes.multicast::cluster.L2::cache_hint [%3], [%4, {%5, %6, %7, %5}], [%0], %8, %9;\n"
                         "@p cp.async.bulk.tensor.3d.shared::cluster.global.mbarrier::complete_tx::bytes.L2::cache_hint [%2], [%10, {%11, %12, %13}], [%0], %15;\n"
                         "@p mbarrier.arrive.expect_tx.shared::cta.b64 _, [%0], %1;\n}"
                         ::"r"(bar), "r"(bytes), "r"(stage), "r"(stage + SLOT + rank * SLOT), "l"(tmB), "r"(0), "r"(kb), "r"(bcol), "h"((uint16_t)3), "l"(pb),
                           "l"(tmA), "r"(c0), "r"(c1), "r"(c2), "r"((uint32_t)isC), "l"(pa) : "memory");
            TRS(s, 1);
          }
          if (phase == 2) break;
          if (phase == 1) poll = ld_relaxed(dep);
          else if (lim == end) dep = dep_counter(sm, jobs[ji + 1], rank, (reinterpret_cast<const uint32_t*>(kseq)[(end + lane) >> 2] >> ((end + lane) % 4 * 8)) & 63);
        }
        if (lim == end) break;
      } else {
        if (s < min(end, sa + NSTAGE) && __all_sync(~0u, mbar_test(sm.empty(s), par(s) ^ 1))) {
          const uint32_t k = kseq[s];
          if (s < summed_end) mbar_wait(sm.summed(s), par(s) ^ 1);
          if (elect()) issue_b(k);
          s++;
        }
        poll = ld_relaxed(dep);
        if (++spins > SPIN_LIMIT) __trap();
      }
    }
    TRI(lane == 0, ji, 8);
  }
}

__global__ void __cluster_dims__(2, 1, 1) __launch_bounds__(384, 1) mega_kernel(char* scratch, uint32_t by_place, const __grid_constant__ Params P) {
#undef TRW
#define TRW warp
  extern __shared__ __align__(1024) uint8_t smem_raw[];
  TRX(threadIdx.x == 320, JMAX - 1, 0, 1, "%%globaltimer_lo");
  TRX(threadIdx.x == 320, JMAX - 1, 0, 25, "%%clock");
  TRX(threadIdx.x == 320, JMAX - 1, 0, 28, "%%smid");
  Smem sm;
  sm.scratch = scratch;
  sm.base = smem_u32(smem_raw);
  if ((sm.base & 0x3FFFF) != SMEM_BASE) __trap();
  const int warp = __shfl_sync(~0u, threadIdx.x >> 5, 0);
  const int rank = blockIdx.x & 1;
  uint32_t smid;
  asm("mov.u32 %0, %%smid;" : "=r"(smid));
  const uint32_t pair = !by_place ? blockIdx.x >> 1 : smid < 2 * NPAIR - 8 ? (smid >> 1) + 4 : (smid >> 1) + 4 - NPAIR;
  const uint32_t* jobs = P.jobs[pair];
  const uint32_t launches = ld_relaxed(counter(C_EP, blockIdx.x + threadIdx.y));
  if (warp == 10) {
    if (elect()) {
      for (int i = 0; i < NSTAGE; i++) mbar_init(sm.full(i), 1);
      mbar_init(sm.boot(), 1);
      asm volatile("fence.mbarrier_init.release.cluster;" ::: "memory");
    }
    cluster_arrive();
    const uint32_t first = jobs[0];
    const bool isC = first & JOB_C;
    if (elect()) {
      prefetch_tm(&P.a[0]);
      prefetch_tm(&P.w[0]);
    }
    uint64_t keep;
    asm("createpolicy.fractional.L2::evict_unchanged.b64 %0, 1.0;" : "=l"(keep));
    const Job J(first);
    if (!isC) {
      if (elect()) {
        mbar_expect_tx(sm.full(0), 40960);
        tma3d(sm.stage(0), &P.a[0], 0, J.R * 128, rank, sm.full(0), keep);
        TRS(0, 1);
      }
      TRX(threadIdx.x == 320, JMAX - 1, 0, 26, "%%clock");
      cluster_wait();
      TRX(threadIdx.x == 320, JMAX - 1, 0, 27, "%%clock");
      if (elect()) {
        tma4d_mc(sm.stage(0) + SLOT + rank * SLOT, &P.w[0], rank * 32, J.col, sm.full(0), keep);
        TRS(0, 0);
      }
#pragma unroll 1
      for (int k = 1; k < NSTAGE; k++) {
        if (elect()) {
          tma4d_mc(sm.stage(k) + SLOT + rank * SLOT, &P.w[0], k * 64 + rank * 32, J.col, sm.full(k), keep);
          TRS(k, 0);
          mbar_expect_tx(sm.full(k), 40960);
          tma3d(sm.stage(k), &P.a[0], k * 64, J.R * 128, rank, sm.full(k), keep);
          TRS(k, 1);
        }
      }
    } else {
      cluster_wait();
      if (!(first & JOB_X)) mbar_wait(sm.boot(), 0);
    }
  } else {
    if (warp < 8 && elect()) {
      mbar_init(sm.kv_ready(warp), 1);
      if (warp == 3) {
        mbar_init(sm.aux_full(), 3); mbar_init(sm.wgmma_done(), 4); mbar_init(sm.mma_done(), 8); mbar_init(sm.xchg_full(), 1); mbar_init(sm.kv_ready(-1), 1);
        mbar_expect_tx(sm.xchg_full(), 768);
      } else if (warp > 3) {
        mbar_init(sm.empty(warp), 4); mbar_init(sm.summed(warp), 6); mbar_init(sm.filled(warp - 4), 4); mbar_init(sm.vacant(warp - 4), 3);
      }
      asm volatile("fence.mbarrier_init.release.cluster;" ::: "memory");
    }
    cluster_arrive();
  }
  TRI(threadIdx.x == 0, JMAX - 1, 0);

  if (warp < 8) {
    asm volatile("setmaxnreg.inc.sync.aligned.u32 208;");
    const uint32_t e1 = launches + 1;
    cluster_wait();
    const uint32_t wg = warp >> 2;
    uint32_t rel = (threadIdx.x & 95) == 0 ? mapa(sm.empty(0), (threadIdx.x & 32) ? rank ^ 1 : rank) : 0;
    uint32_t dst = sm.slot(0) + (warp & 3) * 2048 + (threadIdx.x & 15) * 128 + ((((threadIdx.x >> 4) & 1) ^ (threadIdx.x & 7)) << 4);
    uint32_t t8 = sm.slot(0) + (warp & 3) * 2048 + (threadIdx.x & 7) * 128 + ((((threadIdx.x >> 3) & 3) ^ (threadIdx.x & 7)) << 4);
    rel = __shfl_sync(~0u, rel, threadIdx.x);
    dst = __shfl_sync(~0u, dst, threadIdx.x);
    t8 = __shfl_sync(~0u, t8, threadIdx.x);
    const uint32_t da0 = ((SMEM_BASE >> 4) | (1 << 16)) + wg * 512, dba = (255 << 16) + 1024 - wg * 512;
    uint32_t pend[64], todo = 0, pbar = 0, vbar = sm.vacant(0), ppar = 0, poff = 0, direct = 0;
    uint32_t s = 0, na = 0, nb = 0, ready = 0;
    auto release = [&](uint32_t st) { mbar_arrive_cl_if(rel, rel + (st & (NSTAGE - 1)) * 8); };
    auto flush = [&](bool vacant) {
      if (__all_sync(~0u, vacant)) {
        const uint32_t a = dst + poff;
        if (todo & 2) {
#pragma unroll
          for (int j = 0; j < 4; j++) stsm4(a ^ (j << 5), pend[4 * j], pend[4 * j + 1], pend[4 * j + 2], pend[4 * j + 3]);
          if (todo == 2) {
#pragma unroll
            for (int j = 0; j < 4; j++) stsm4((a ^ (j << 5)) + 8192, pend[16 + 4 * j], pend[17 + 4 * j], pend[18 + 4 * j], pend[19 + 4 * j]);
          }
        } else {
#pragma unroll
          for (int j = 0; j < 8; j++) stsm4((a ^ ((j & 3) << 5)) + (j >> 2) * 8192, pend[32 + 4 * j], pend[33 + 4 * j], pend[34 + 4 * j], pend[35 + 4 * j]);
        }
        mbar_arrive_warp(pbar);
        pbar += 16; vbar += 16; ppar = ~nb & 1;
        todo = todo == 2;
      }
    };
    uint32_t jw = jobs[0];
#pragma unroll
    for (int i = 0; i < 64; i++) pend[i] = 0;
    for (int ji = 0;; ji++) {
      const uint32_t cur = jw, nk = (jw >> 12) & 63, isQ = (jw & 3) == T_Q;
      jw = jobs[ji + 1];
      if (__builtin_expect((cur & JOB_C) || !ready, 0)) {
        for (uint32_t spins = 0; todo && ((cur & JOB_C) || !ready);) {
          if (direct && todo == 1) {
            vbar = sm.empty(s); ppar = par(s) ^ 1; poff = sm.stage(s) - sm.slot(0) + wg * SLOT;
          }
          flush(mbar_test(vbar, ppar));
          ready = __all_sync(~0u, mbar_test(sm.full(s), par(s)));
          if (++spins > SPIN_LIMIT) __trap();
        }
        if (cur & JOB_C) {
          if (nk == 0) break;
          TRC(ji, 16);
          constexpr uint32_t ONES = 0x3f803f80;
          const uint32_t lane = fresh_tid() & 31, g = ((cur >> 6) & 63) * 2 + rank;
          if (!(cur & JOB_X)) {
            float d[4] = {0.f, 0.f, 0.f, 0.f};
            sts32(sm.xchg() + 128 + lane * 4, ONES);
            fence_proxy_async_smem();
            bar_sync<9, 256>();
#pragma unroll 1
            for (int i = 0; i < 4; i++, s++) {
              mbar_wait(sm.full(s), par(s));
              if (!wg) sum_columns(d, da0 + (s & (NSTAGE - 1)) * (STAGE / 16), (SMEM_BASE + AUX_OFF + 1600 + 128) >> 4);
              release(s);
            }
            const float c = lane & 1 ? d[2] : d[0], c1 = __shfl_down_sync(~0u, c, 4);
            asm volatile("{\n.reg .pred p;\nsetp.eq.u32 p, %2, 0;\n@p st.relaxed.gpu.global.u64 [%0], %1;\n}"
                         ::"l"(SCR(sm, cs, (16 * 128 + g * 32 + (warp & 3) * 8 + (lane & 1) * 4 + (lane >> 3)) * 8)), "l"(((u64)e1 << 32) | pack_bf16(c, c1)), "r"((lane & 6) | wg) : "memory");
          } else {
            float a[6][4];
#pragma unroll
            for (int n = 0; n < 24; n++) pend[n] = 0;
#pragma unroll 1
            for (int i = 0;; i++) {
              const uint32_t p = dst - sm.slot(0) + sm.stage(s) + wg * SLOT;
              mbar_wait(sm.full(s), par(s));
              uint32_t v[8][4];
#pragma unroll
              for (int n = 0; n < 24; n++) a[n / 4][n % 4] = __uint_as_float(pend[n]);
#pragma unroll
              for (int j = 0; j < 8; j++) ldsm4((p ^ ((j & 3) << 5)) + (j >> 2) * 8192, v[j]);
#pragma unroll
              for (int j = 0; j < 8; j++) {
                mma16816(a[4 + (j & 1)], v[j][0], v[j][1], v[j][2], v[j][3], ONES, ONES);
#pragma unroll
                for (int n = 0; n < 4; n++) mma1688(a[n], v[j][n & 2], v[j][(n & 2) + 1], v[j][n]);
              }
#pragma unroll
              for (int n = 0; n < 24; n++) pend[n] = __float_as_uint(a[n / 4][n % 4]);
              if (i == 3) break;
              bar_sync<9, 256>();
              release(s++);
            }
            const uint32_t part = sm.stage(s) + 2 * SLOT + lane * 8, row = g * 64 + (warp & 3) * 16 + wg * 8 + (lane >> 2);
            const bool odd = lane & 4;
            const float s0 = a[4][0] + a[5][0], q0 = odd ? a[0][1] + a[2][1] : a[0][0] + a[2][0];
            const float s1 = a[4][2] + a[5][2], q1 = odd ? a[1][3] + a[3][3] : a[1][2] + a[3][2];
            sts64(part + warp * 256, make_uint2(__float_as_uint(wg ? s0 : s1), __float_as_uint(wg ? q0 : q1)));
            bar_sync<9, 256>();
            const uint2 o = lds64(part + (warp ^ 4) * 256);
            fence_proxy_async_smem();
            bar_sync<9, 256>();
            release(s++);
            publish_stats(sm, (wg ? s1 : s0) + __uint_as_float(o.x), (wg ? q1 : q0) + __uint_as_float(o.y), (row & 1) * (S / 2) + (row >> 1), (lane & 3) == lane >> 3, e1);
          }
          ready = 0;
          TRC(ji, 18);
          continue;
        }
        if (!ready) mbar_wait(sm.full(s), par(s));
      }
      auto mainloop = [&](auto& acc, uint32_t nk, uint32_t last_lead, auto near_end) {
        const uint32_t lead = (jw >> 12) % 64 == 0 ? min(last_lead, nk - 2) : 2, turn = wg ? lead : nk - 2, hurry = nk - lead - wg;
        uint32_t owed = 0;
        uint32_t da = da0 + (s & (NSTAGE - 1)) * (STAGE / 16);
        if (todo == 3) mbar_wait(vbar, ppar);
        if (wg) bar_sync<13, 256>();
        TRC(ji, 16);
        first_kstep(acc, da, da + dba);
        if (!wg) bar_arrive<13, 256>();
        constexpr uint32_t CLEAR = sizeof(acc) == 96 * 4 ? PREP + 2 : 3;
        for (uint32_t left = nk - 1;; left--) {
          for (uint32_t spins = 0;; spins++) {
            const bool vacant = mbar_test(vbar, ppar), next_full = mbar_test(sm.full(s + 1), par(s + 1));
            wg_wait<2>();
            mbar_arrive_cl_if(owed, owed + ((s - 1) & (NSTAGE - 1)) * 8);
            owed = 0;
            ready = __all_sync(~0u, next_full);
            if (!todo) {
              near_end(left, vacant);
              break;
            }
            const bool go = ready && left >= max(CLEAR, lead + 1);
            if (!(go && spins)) flush(vacant);
            if (go) break;
            if (spins > SPIN_LIMIT) __trap();
          }
          if (left == 0) break;
          if (!ready) mbar_wait(sm.full(s + 1), par(s + 1));
          owed = rel;
          if (left == turn) {
            wg_wait<0>();
            release(s);
            owed = 0;
            if (wg) bar_sync<1, 256>();
          }
          if (left - lead < hurry) wg_wait<1>();
          s++;
          da = da0 + (s & (NSTAGE - 1)) * (STAGE / 16);
          kstep(acc, da, da + dba);
          if (left == 1 + wg * 64) bar_arrive<1, 256>();
        }
      };
      if (isQ) {
        float acc[96];
        const uint32_t lane = (((dst - SMEM_BASE) >> 7) & 15) | ((dst ^ (dst >> 3)) & 16), qpar = (na ^ nb) & 1;
        uint32_t prepare_at = PREP;
        mainloop(acc, nk, LAST_LEAD, [&](uint32_t left, bool aux_full) {
          if (left == PREP + 1) {
            vbar = sm.aux_full(); ppar = qpar;
          } else if (left == prepare_at) {
            if (left == 0) mbar_wait(vbar, ppar);
            if (left == 0 || __all_sync(~0u, aux_full)) attention_prepare(pend, sm, warp, lane, !(cur & 0x38));
            else prepare_at--;
          }
        });
        wg_wait<0>();
        release(s);
        u64 token = 0;
        asm volatile("{\n.reg .pred p;\nsetp.eq.u32 p, %2, 0;\n@p mbarrier.arrive.shared::cta.b64 %0, [%1];\n}" : "+l"(token) : "r"(sm.wgmma_done()), "r"(lane + 1 - wg) : "memory");
        pend[A_NM + 1] |= (uint32_t)token & pend[A_ZERO];
        TRC(ji, 18);
        ready = __all_sync(~0u, attention(acc, pend, sm, warp, lane, t8, dst, cur & JOB_EARLY, (((cur >> 2) & 1) * 16 + ((cur >> 3) & 7) * 2 + rank) * 16 + ((cur >> 6) & 15), e1, qpar,
                                          sm.full(s + 1), par(s + 1), ji));
        todo = 3; pbar = sm.filled(wg); vbar = sm.mma_done(); ppar = qpar; poff = SLOT + wg * 8192;
      } else {
        float acc[128];
        direct = (cur & 1) && (jw >> 12) % 64 == 0;
        const bool split = direct && nk >= SPLIT_MIN;
        mainloop(acc, split ? nk - 3 : nk, split ? 0 : LAST_LEAD, [](uint32_t, bool) {});
        pbar = sm.filled(wg); vbar = pbar + 32; ppar = na & 1; poff = wg * SLOT;
        nb++;
        todo = 2;
        if (__builtin_expect(split, 0)) {
          const uint32_t s0 = s;
          uint32_t d[3];
#pragma unroll
          for (int i = 0; i < 3; i++) d[i] = da0 + ((s0 + 1 + i) & (NSTAGE - 1)) * (STAGE / 16);
          wg_wait<0>();
          release(s0);
          float lo[64], hi[64];
#pragma unroll
          for (int i = 0; i < 64; i++) {
            asm volatile("mov.b32 %0, %1;" : "=f"(lo[i]) : "f"(acc[i]));
            asm volatile("mov.b32 %0, %1;" : "=f"(hi[i]) : "f"(acc[64 + i]));
          }
          if (wg) {
            bar_sync<1, 256>();
            bar_sync<3, 256>();
          }
          mbar_wait(sm.full(s0 + 1), par(s0 + 1));
          half_kstep0(lo, d[0], d[0] + dba);
          mbar_wait(sm.full(s0 + 2), par(s0 + 2));
          half_kstep0(lo, d[1], d[1] + dba);
          half_kstep1(hi, d[0], d[0] + dba);
          mbar_wait(sm.full(s0 + 3), par(s0 + 3));
          half_kstep0(lo, d[2], d[2] + dba);
          half_kstep1(hi, d[1], d[1] + dba);
          half_kstep1(hi, d[2], d[2] + dba);
          if (!wg) bar_arrive<3, 256>();
          s += 3;
          wg_wait<2>();
#pragma unroll
          for (int i = 0; i < 32; i++) pend[i] = pack_bf16(lo[2 * i], lo[2 * i + 1]);
          mbar_wait(vbar, ppar);
          flush(true);
          wg_wait<0>();
          TRC(ji, 18);
#pragma unroll
          for (int i = 0; i < 32; i++) pend[32 + i] = pack_bf16(hi[2 * i], hi[2 * i + 1]);
        } else {
          wg_wait<0>();
          release(s);
          const bool next_full = mbar_test(sm.full(s + 1), par(s + 1));
          TRC(ji, 18);
#pragma unroll
          for (int i = 0; i < 64; i++) {
            const int j = (i & 15) + (i & 16) * 2 + (i >> 5) * 16;
            pend[i] = pack_bf16(acc[2 * j], acc[2 * j + 1]);
          }
          ready = __all_sync(~0u, next_full);
        }
      }
      na++;
      s++;
    }
  } else {
    asm volatile("setmaxnreg.dec.sync.aligned.u32 88;");
    if (warp == 10) {
      producer(P, sm, jobs, P.kseq[pair], rank, threadIdx.x & 31, launches);
    } else {
      const uint32_t e1 = __shfl_sync(~0u, launches, 0) + 1;
      const int w = min(warp - 8, 2);
      cluster_wait();
      if (w == 1) asm volatile("st.shared::cluster.u32 [%0], %1;" ::"r"(mapa(sm.pair_id(), rank ^ 1)), "r"(pair) : "memory");
      auto copy_rows = [&](uint32_t step) {
        constexpr int IN = 2 * SLOT / BOOT_PIECES, OUT = 2 * SLOT / BOOT_OUT;
        if (step == BOOT_STEP) mbar_wait(sm.boot(), 0);
        if (elect()) {
          if (step == 0) mbar_expect_tx(sm.boot(), blockIdx.x < S / 16 ? 2 * SLOT : 0);
          if (step < BOOT_PIECES && blockIdx.x < S / 16)
            asm volatile("cp.async.bulk.shared::cluster.global.mbarrier::complete_tx::bytes [%0], [%1], %2, [%3];"
                         ::"r"(sm.slot(0) + step * IN), "l"(at(P.x0, blockIdx.x * 32768 + step * IN)), "n"(IN), "r"(sm.boot()) : "memory");
          if (step - BOOT_STEP < BOOT_OUT && blockIdx.x < S / 16) {
            asm volatile("cp.async.bulk.global.shared::cta.bulk_group [%0], [%1], %2;"
                         ::"l"(at(P.out, blockIdx.x * 32768 + (step - BOOT_STEP) * OUT)), "r"(sm.slot(0) + (step - BOOT_STEP) * OUT), "n"(OUT) : "memory");
            bulk_commit();
          }
        }
        if (step == BOOT_STEP + BOOT_OUT) {
          bulk_wait();
          if (elect()) {
            mbar_arrive_n(sm.vacant(0), 3);
            mbar_arrive_n(sm.vacant(1), 3);
          }
        }
      };
      if (jobs[0] & JOB_C) {
        if (w == 2) {
          if (jobs[0] & JOB_X) mbar_wait(sm.full(3), 0);
#pragma unroll 1
          for (int i = 0; i <= BOOT_STEP + BOOT_OUT; i++) {
            copy_rows(i);
            bulk_wait_read<0>();
          }
        }
      } else {
        const int lane = threadIdx.x & 31, word = (lane >> 3) * 24 + w * 8 + (lane & 7);
        Stager st;
        const uint32_t cs = qkv_col_sums(sm, rank, w, lane, [&](int s) {
          if (w == 2) copy_rows(s - 1);
          if (w == 0 && s == ST_STEP) st.load(sm, Job(jobs[0]), rank, lane, false);
          if (w == 0 && s == ST_STEP + 2) st.store(sm, Job(jobs[0]), rank, lane, false, e1);
        });
        sts32(sm.sums() + word * 4, cs);
        mbar_arrive_warp(sm.aux_full());
        if ((jobs[0] & 0x38) == 0 && rank == 0) st_word(SCR(sm, cs, (((jobs[0] >> 6) & 15) * 128 + word) * 8), cs, e1);
      }
      bar_sync<2, 96>();
      if (w == 2 && blockIdx.x < S / 16 && elect()) {
        red_release(counter(C_RD + (blockIdx.x >> 4) * 2, 0), 1);
        red_relaxed(counter(C_RD + (blockIdx.x >> 4) * 2 + 1, 0), 1);
      }
      uint32_t na = 0, nb = 0, stages = 0;
      for (int ji = 0;; ji++) {
        const uint32_t jw = jobs[ji];
        const Job J(jw);
        if (J.nk == 0) break;
        stages += J.nk;
        if (w != 0 && ((jw >> 22) & 3) != 3) {
          stats_task(sm, jw, rank, w, e1, P.out);
          TRI(threadIdx.x == 11 * 32, ji, 10);
        }
        if (jw & JOB_C) continue;
        const int lane = fresh_tid() & 31;
        const uint32_t b = J.R * 2 + rank;
        if (w == 0 && !(J.type & 1) && ji != 0) {
          Stager st;
          st.load(sm, J, rank, lane, true);
          st.store(sm, J, rank, lane, true, e1);
          TRI(lane == 0, ji, 9);
        }
        if (J.type == T_G) {
          bar_sync<2, 96>();
          constexpr int PER = 16 / NG;
          const uint32_t swap = P.swap, never = jw, ac = sm.sums() + (lane & 7) * 16;
          uint32_t ag[NG], au[NG], as = sm.stats() + 64 + w * NG * 32 + (lane >> 3) * 8;
          uint32_t ho = (rank * (S / 2) + J.R * 128 + w * NG * 4 + (lane >> 3)) * (F * 2) + J.col * 256 + (lane & 7) * 16;
          uint4 cg = lds128(ac + (swap >> 5)), cu = lds128(ac + 256 - (swap >> 5)), g4[NG], u4[NG];
          uint2 st[NG];
          auto load = [&] {
#pragma unroll
            for (int i = 0; i < NG; i++) { st[i] = lds64v(as + i * 32); g4[i] = lds128v(ag[i]); u4[i] = lds128v(au[i]); }
          };
#pragma unroll
          for (int i = 0; i < NG; i++) {
            const uint32_t a = (sm.slot(0) + (w * NG + i) * 512 + (lane >> 3) * 128 + (((lane & 7) ^ (lane >> 3)) << 4)) ^ (((w * NG + i) & 1) << 6);
            ag[i] = a + swap; au[i] = a + (swap ^ 8192);
          }
          mbar_wait(sm.filled(0), na & 1);
          mbar_wait(sm.filled(1), na & 1);
          load();
          if (w == 2 && elect()) red_relaxed(counter(C_RD + J.inst() * 16 + b, 0), 1);
          TRI(threadIdx.x == 11 * 32, ji, 3);
#pragma unroll 1
          for (uint32_t g = w; g < 4 * PER; g += 3) {
            float hinv[NG], hinv2[NG];
            uint4 gc[NG], uc[NG];
            const bool turn = ((g + 3) ^ g) & PER, half = ((g + 3) ^ g) & (2 * PER);
#pragma unroll
            for (int i = 0; i < NG; i++) {
              hinv[i] = 0.5f * __uint_as_float(st[i].x);
              hinv2[i] = hinv[i] * __uint_as_float(st[i].x);
              asm volatile("" : "+f"(hinv[i]), "+f"(hinv2[i]));
              gc[i] = fma8(dup_hi(st[i].y), cg, g4[i]);
              uc[i] = fma8(dup_hi(st[i].y), cu, u4[i]);
              ag[i] = (ag[i] + NG * 1536) ^ ((NG & 1) << 6);
              au[i] = (au[i] + NG * 1536) ^ ((NG & 1) << 6);
            }
            as += NG * 96;
            if (turn) {
              mbar_arrive_warp(sm.vacant((g / PER) ^ 2));
              if (half) {
                cg = lds128(ac + (swap >> 5) + 128); cu = lds128(ac + 384 - (swap >> 5));
                as -= 1024;
              }
#pragma unroll
              for (int i = 0; i < NG; i++) { ag[i] += half ? -3 * 8192 : 8192; au[i] += half ? -3 * 8192 : 8192; }
              TRX(threadIdx.x == 11 * 32 && g < 3 * PER, ji, 25, 25 + g / PER * 2, "%%clock");
              if (g < 3 * PER) mbar_wait(sm.filled(g / PER + 1), (g < PER ? na : nb) & 1);
              TRX(threadIdx.x == 11 * 32 && g < 3 * PER, ji, 25, 26 + g / PER * 2, "%%clock");
            }
            load();
            if (g == never) mbar_wait(sm.boot(), 0);
            bf16* out = SCR(sm, h, ho);
#pragma unroll
            for (int i = 0; i < NG; i++)
              stg128(out + i * 4 * F, make_uint4(swiglu2(gc[i].x, uc[i].x, hinv[i], hinv2[i]), swiglu2(gc[i].y, uc[i].y, hinv[i], hinv2[i]),
                                                 swiglu2(gc[i].z, uc[i].z, hinv[i], hinv2[i]), swiglu2(gc[i].w, uc[i].w, hinv[i], hinv2[i])));
            ho += NG * 12 * F * 2 - (half ? 128 * F * 2 - 128 : 0);
          }
          bar_sync<2, 96>();
          TRI(threadIdx.x == 11 * 32, ji, 4);
          if (w == 2 && elect()) red_release(counter(C_H + J.layer * 16 + b, J.col), 1);
          TRI(threadIdx.x == 11 * 32, ji, 5);
        } else if (J.type == T_Q) {
          const bool late = J.R > 0 && !(jw & JOB_EARLY);
          if (w == 0) {
            __syncwarp();
            if (ji != 0 && elect()) mbar_arrive_n(sm.aux_full(), 3);
#pragma unroll 1
            for (int phase = 0; phase < 2; phase++) {
              if (J.R > 0 && phase == late) import_halo(sm, SCR(sm, halo, (((J.layer * 16 + b - 2) * 16 + J.col) * 256 + lane) * 16), e1, lane);
              if (phase == 0) {
                mbar_arrive_warp(sm.kv_ready(-1));
                TRI(lane == 0, ji, 11);
#pragma unroll 1
                for (int h = 0; h < 2; h++) {
                  mbar_wait(sm.filled(h), na & 1);
                  TRI(lane == 0, ji, 3);
                  fence_proxy_async_smem();
                  bulk_wait_read<0>();
                  if (elect()) {
                    tma3d_store(&P.ow, J.col * 64, J.R * 128 + h * 64, rank, sm.slot(1) + h * 8192);
                    bulk_commit();
                  }
                }
                if (J.layer && elect()) red_relaxed(counter(C_RD + 32 + b, 0), 1);
              }
            }
            bulk_wait();
          }
          if (late && w < 2) {
            bar_sync<7, 64>();
            boundary_rows(sm, w, lane, rank * O_PLANE + J.R * 128 * (D * 2) + J.col * 128);
            bar_sync<7, 64>();
          }
          TRI(threadIdx.x == 256, ji, 4);
          if (w == 0 && elect()) {
            mbar_arrive_n(sm.vacant(0), 3);
            mbar_arrive_n(sm.vacant(1), 3);
            red_release(counter(C_O + J.layer * 16 + b, J.col), 1);
          }
          TRI(threadIdx.x == 256, ji, 5);
        } else if (w == 0) {
          wait_count(counter(C_RD + J.inst() * 16 + b, 0), e1 * (J.type == T_D ? 28 : 16));
          fence_proxy_async();
          const bool last = Job(jobs[ji + 1]).nk == 0, split = last && J.nk >= SPLIT_MIN;
#pragma unroll 1
          for (uint32_t v = 0; v < 4; v++) {
            const uint32_t u = last ? (v >> 1) + (v & 1) * 2 : v;
            mbar_wait(sm.filled(u), (u & 2 ? nb : na) & 1);
            TRI(u == 0 && lane == 0, ji, 3);
            fence_proxy_async_smem();
            const uint32_t src = (last && (u & 2) ? sm.stage(stages) : sm.slot(0)) + (u & 1) * SLOT;
#pragma unroll 1
            for (uint32_t p = 0; p < 16384 / PIECE; p++) {
              if (elect()) {
                tma3d_reduce_add(&P.xr, J.col * 256 + (split ? (u & 2) * 64 + p * PIECE / 8192 * 64 : (u & 2) * 32 + p * PIECE / 8192 * 128), J.R * 128 + (u & 1) * 64 + p * PIECE % 8192 / 128, rank, src + p * PIECE);
                bulk_commit();
              }
              if (!last) bulk_wait_read<DEPTH - 1>();
            }
            if (!last) {
              bulk_wait();
              if (elect()) mbar_arrive_n(sm.vacant(u ^ 2), 3);
            }
            if (u == 1 && J.inst() != 3) bar_arrive<8, 64>();
          }
          bulk_wait();
        }
        if ((J.type & 1) && J.inst() != 3 && w < 2) {
          if (w == 1) bar_sync<8, 64>();
          TRX(lane == 0, ji, 4, w ? 12 : 4, "%%globaltimer_lo");
          if (elect()) red_release(counter(C_X + J.inst() * 16 + b, J.col * 2 + 1 - w), J.nk);
          TRX(lane == 0, ji, 5, w ? 13 : 5, "%%globaltimer_lo");
          if (w == 1) bar_arrive<10, 64>(); else bar_sync<10, 64>();
        }
        na++;
        nb += J.type != T_Q;
      }
      TRI(threadIdx.x == 8 * 32, JMAX - 1, 6);
      TRK(threadIdx.x == 8 * 32, JMAX - 1, 24);
      if (w == 0 && elect()) red_relaxed(counter(C_EP, blockIdx.x), 1);
      if (w == 2 && __float_as_uint(lds32f(sm.pair_id())) != pair) __trap();
    }
  }
  cluster_arrive();
  cluster_wait();
}

typedef CUresult (*EncodeFn)(CUtensorMap*, CUtensorMapDataType, cuuint32_t, void*, const cuuint64_t*, const cuuint64_t*, const cuuint32_t*,
                             const cuuint32_t*, CUtensorMapInterleave, CUtensorMapSwizzle, CUtensorMapL2promotion, CUtensorMapFloatOOBfill);
struct Dim { cuuint64_t size, stride; cuuint32_t box; };
template <int N> void encode(EncodeFn fn, CUtensorMap* m, const void* ptr, const Dim (&d)[N]) {
  cuuint64_t dims[N], strides[N];
  cuuint32_t box[N], es[N];
  for (int i = 0; i < N; i++) { dims[i] = d[i].size; strides[i] = d[i].stride; box[i] = d[i].box; es[i] = 1; }
  fn(m, CU_TENSOR_MAP_DATA_TYPE_BFLOAT16, N, const_cast<void*>(ptr), dims, strides + 1, box, es, CU_TENSOR_MAP_INTERLEAVE_NONE,
     CU_TENSOR_MAP_SWIZZLE_128B, CU_TENSOR_MAP_L2_PROMOTION_L2_128B, CU_TENSOR_MAP_FLOAT_OOB_FILL_NONE);
}

}

extern "C" void kernel_launch(void* const* d_in, const int* in_sizes, int n_in, void* d_out, int out_size) {
  (void)in_sizes; (void)n_in; (void)out_size;
  static EncodeFn fn = nullptr;
  static Scratch* scr;
  static int sms;
  if (!fn) {
    void* p = nullptr;
    cudaDriverEntryPointQueryResult q;
    cudaGetDriverEntryPoint("cuTensorMapEncodeTiled", &p, cudaEnableDefault, &q);
    fn = (EncodeFn)p;
    scr = scratch_base();
    int device = 0;
    cudaGetDevice(&device);
    cudaDeviceGetAttribute(&sms, cudaDevAttrMultiProcessorCount, device);
    cudaFuncSetAttribute(mega_kernel, cudaFuncAttributeMaxDynamicSharedMemorySize, SMEM_BYTES);
  }
  static Params P;
  const char *wg = (const char*)d_in[4], *wu = (const char*)d_in[5], *w0 = wg < wu ? wg : wu;
  const cuuint64_t plane = wg < wu ? wu - wg : wg - wu;
  P.swap = wg < wu ? 0 : 8192;
  encode(fn, &P.a[0], d_in[0], {{D, 2, 64}, {S / 2, D * 4, 128}, {2, D * 2, 1}});
  encode(fn, &P.a[1], scr->o, {{D, 2, 64}, {S / 2, D * 2, 128}, {2, O_PLANE, 1}});
  encode(fn, &P.ow, scr->o, {{D, 2, 64}, {S / 2, D * 2, 64}, {2, O_PLANE, 1}});
  encode(fn, &P.a[2], d_out, {{D, 2, 64}, {S / 2, D * 4, 128}, {2, D * 2, 1}});
  encode(fn, &P.a[3], scr->h, {{F, 2, 64}, {S / 2, F * 2, 128}, {2, (cuuint64_t)F * S, 1}});
  encode(fn, &P.a[4], w0, {{F, 2, 64}, {D, F * 2, 256}, {2, plane, 1}});
  encode(fn, &P.a[5], d_in[0], {{64, 2, 64}, {S, D * 2, 64}, {16, 128, 4}});
  encode(fn, &P.w[T_Q], d_in[1], {{64, 2, 64}, {D, 3 * D * 2, 32}, {16, 128, 1}, {3, D * 2, 3}});
  encode(fn, &P.w[T_O], d_in[2], {{64, 2, 64}, {D, D * 2, 32}, {16, 128, 4}, {1, (cuuint64_t)D * D * 2, 1}});
  encode(fn, &P.w[T_G], w0, {{64, 2, 64}, {D, F * 2, 32}, {F / 64, 128, 2}, {2, plane, 2}});
  encode(fn, &P.w[T_D], d_in[6], {{64, 2, 64}, {F, D * 2, 32}, {16, 128, 4}, {1, (cuuint64_t)F * D * 2, 1}});
  encode(fn, &P.xr, d_out, {{D, 2, 64}, {S / 2, D * 4, PIECE / 128}, {2, D * 2, 1}});
  memcpy(P.jobs, kJobs, sizeof(kJobs));
  memcpy(P.kseq, kSeq, sizeof(kSeq));
  P.x0 = (const bf16*)d_in[0];
  P.wqkv = (const bf16*)d_in[1];
  P.out = (bf16*)d_out;
  mega_kernel<<<2 * NPAIR, 384, SMEM_BYTES>>>((char*)scr, sms == 2 * NPAIR, P);
}
```

```cpp
#include <cuda_runtime.h>
#include <cuda_bf16.h>
#include <cuda.h>
#include <stddef.h>
#include <stdint.h>
#include <string.h>

namespace {

typedef __nv_bfloat16 bf16;
typedef unsigned long long u64;
constexpr int S = 2048, D = 1024, F = 3584;
constexpr int STAGE = 49152, NSTAGE = 4, SLOT = 16384;
constexpr int STG_OFF = NSTAGE * STAGE, BAR_OFF = STG_OFF + 2 * SLOT, AUX_OFF = BAR_OFF + 336;
constexpr int SMEM_BYTES = AUX_OFF + 2736;
constexpr int SMEM_BASE = 1024;
constexpr int NPAIR = 66, JMAX = 24, KMAX = 296;
constexpr int T_Q = 0, T_O = 1, T_G = 2, T_D = 3;
constexpr uint32_t JOB_C = 1u << 18;
constexpr uint32_t K_LAST_A = 64, K_LAST_B = 128;
constexpr uint32_t JOB_EARLY = 1u << 21;
constexpr uint32_t JOB_X = JOB_EARLY;
#define V_BOOTP 4
#define V_BOOTS 5
#define V_BOOTO 8
#define V_STS 9
constexpr int BOOT_PIECES = V_BOOTP, BOOT_OUT = V_BOOTO, BOOT_STEP = V_BOOTS, ST_STEP = V_STS;
constexpr int SPLIT_MIN = 6;
#define V_PREP 3
constexpr int PREP = V_PREP, LAST_LEAD = 3;
#define V_LOOK 2
#define V_MID 7
constexpr int LOOK = V_LOOK, MID = V_MID;
#define V_PIECE 8192
#define V_DEPTH 2
constexpr int NG = 2, PIECE = V_PIECE, DEPTH = V_DEPTH;
#define V_SL1 200
#define V_SL2 300
#define V_SL3 300
constexpr uint32_t SPIN_LIMIT = 1u << 21;

constexpr int C_X = 0;
constexpr int C_O = C_X + 48;
constexpr int C_H = C_O + 32;
constexpr int C_RD = C_H + 32;
constexpr int C_EP = C_RD + 64;
constexpr int C_LINES = C_EP + 5;

struct Scratch {
  bf16 h[S * F];
  uint32_t cnt[256 * 32];
  bf16 o[S / 2 * D];
  u64 stats[4 * S];
  bf16 o1[S / 2 * D];
  u64 cs[44 * 128];
  ulonglong2 halo[2 * 16 * 16 * 8 * 32];
};
constexpr uint32_t O_PLANE = offsetof(Scratch, o1) - offsetof(Scratch, o);
static_assert(C_LINES <= 256, "");
constexpr size_t PAGE = 2 << 20;
__device__ __align__(1024) char g_scratch[sizeof(Scratch) + PAGE];
Scratch* scratch_base() {
  char* p;
  cudaGetSymbolAddress((void**)&p, g_scratch);
  return (Scratch*)(p + (-(size_t)p & (PAGE - 1)));
}

uint32_t kJobs[NPAIR][JMAX] = {
  {0xe44200,0xc10020,0xc44040,0xc08009,0xc10082,0x4101001a,0xc10022,0xc1800b,0x184170b3,0x46610054,0x5b610034,0x7d41000e,0xc1001e,0xc10076,0xc10096,0xc14037,0xc40000,0xc40000,0xc40000,0xc40000,0xc40000,0xc40000,0xc40000,0x80c40000},
  {0xe44000,0xc10018,0xc44080,0xc08009,0xc10021,0x22010052,0xc10092,0xc100aa,0xc09013,0x16410004,0x2d61004c,0x3461002c,0x4e410086,0xc10056,0x618100ae,0xc100b6,0xc1b02f,0xc40000,0xc40000,0xc40000,0xc40000,0xc40000,0xc40000,0x82c40000},
  {0xc10000,0xc44140,0xc04001,0xc10042,0x3a01004a,0xc1006a,0xc100b2,0xc1201b,0x26413033,0x6440b00d,0x681001d,0x3281002d,0xd48100a6,0xc101be,0xc1e007,0xc40000,0xc40000,0xc40000,0xc40000,0xc40000,0xc40000,0xc40000,0xc40000,0x7fc40000},
  {0xc10010,0xc440c0,0xc04001,0xc10002,0x3b01008a,0xc1019a,0xc101aa,0xc0800b,0x1a40d01b,0xc10014,0x66410064,0x2810006,0xc1008e,0xc10066,0xc1007e,0xc0e087,0xc1003f,0xc40000,0xc40000,0xc40000,0xc40000,0xc40000,0xc40000,0x7fc40000},
  {0xc10048,0xe10058,0xe10070,0xc05039,0x21010012,0x7a01b003,0xc1003a,0x29410044,0x3561001c,0x4f61005c,0x5761003c,0x7e41004e,0x6081009e,0xc100be,0xc1c00f,0xc40000,0xc40000,0xc40000,0xc40000,0xc40000,0xc40000,0xc40000,0xc40000,0x7fc40000},
  {0xe44240,0xc443c0,0xe10158,0xc10130,0xc040e1,0x170101ca,0x620101da,0xc101f2,0x641905b,0xc07063,0x324100c5,0x7a61016c,0x12a1013c,0x288101d6,0xc101ee,0xc10236,0xc1a04f,0xc40000,0xc40000,0xc40000,0xc40000,0xc40000,0xc40000,0x84c40000},
  {0xe44280,0xc44780,0xc10228,0x1f044840,0xe10270,0xc103ca,0x5e01039a,0xc103b2,0xc1042a,0xc103ba,0x6d4180bb,0x8810506,0xc100b5,0xd2810426,0xc103be,0xc1f097,0xc40000,0xc40000,0xc40000,0xc40000,0xc40000,0xc40000,0xc40000,0x86c40000},
  {0xe44380,0xc102d0,0xc040c1,0xc10091,0x1101044a,0x67010452,0xc1046a,0xc104f2,0x2c4170ab,0x5240e0bb,0x5810486,0xc104ce,0xc10466,0xc1047e,0xc1f09f,0xc40000,0xc40000,0xc40000,0xc40000,0xc40000,0xc40000,0xc40000,0xc40000,0x88c40000},
  {0xe442c0,0xc10320,0xc040c1,0x1d210338,0xc1054a,0x610105e2,0x7301e0cb,0xc10344,0xc1030c,0xc040bb,0x6041036c,0x1ca1033c,0x29810596,0x6c8105a6,0xc106f6,0xc1d0df,0xc40000,0xc40000,0xc40000,0xc40000,0xc40000,0xc40000,0xc40000,0x8ac40000},
  {0xe443c0,0xc10390,0xc44d80,0xc100d1,0x1501060a,0x64010612,0x720180c3,0x24106ba,0xc1038c,0x404103dc,0xc103f4,0x2c80c0e5,0x4d810656,0xc1066e,0xc1069e,0xc1a0ef,0xc40000,0xc40000,0xc40000,0xc40000,0xc40000,0xc40000,0xc40000,0x8cc40000},
  {0xc10088,0xe100e0,0xc10011,0x270100ca,0x6c01015a,0x7c01800b,0xc0d023,0x2140f0b3,0x516100dc,0xc10106,0xc1010e,0xc10166,0xc1013e,0xc1f017,0xc40000,0xc40000,0xc40000,0xc40000,0xc40000,0xc40000,0xc40000,0xc40000,0xc40000,0xec40000},
  {0xc10198,0xc101b0,0x1b0445c0,0xc44600,0xc446c0,0xc1030a,0x5d010322,0xc102f2,0xc0e04b,0xc101c4,0xc1707b,0x79410055,0xc07065,0xb0810075,0xd0810326,0xc10336,0xc1d05f,0xc40000,0xc40000,0xc40000,0xc40000,0xc40000,0xc40000,0xfc40000},
  {0xc10050,0xc10060,0xc10038,0x29210078,0x3e010062,0xc10032,0x441901b,0x2461000c,0x36610024,0x5d410074,0x228100ad,0x5b810026,0xc1006e,0xc1005e,0xc1203f,0xc40000,0xc40000,0xc40000,0xc40000,0xc40000,0xc40000,0xc40000,0xc40000,0x10c40000},
  {0xe44040,0xc444c0,0xc10168,0xc10049,0x1601024a,0x63010252,0xc10262,0xc1027a,0xc18073,0x55410045,0x48101c6,0xc1034e,0xc1035e,0xc1023e,0xc1e04f,0xc40000,0xc40000,0xc40000,0xc40000,0xc40000,0xc40000,0xc40000,0xc40000,0x91c40000},
  {0xe44080,0xc44700,0xe10220,0xc09089,0xc103c2,0x5a010412,0xc10512,0xc103f2,0x1e41c0a3,0x4961021c,0x58410234,0x36a1027c,0x4881041e,0x7281051e,0xc10436,0xc1909f,0xc40000,0xc40000,0xc40000,0xc40000,0xc40000,0xc40000,0xc40000,0x93c40000},
  {0xe44180,0xc44880,0xe102a0,0xc04081,0x1c2102f8,0xc104ca,0x66010462,0xc104ea,0xc104ba,0xc104fa,0xc102d4,0xc102ac,0x1d8104c6,0xc104d6,0x6d8104a6,0xc1053e,0xc0f087,0xc0c0b7,0xc40000,0xc40000,0xc40000,0xc40000,0xc40000,0x95c40000},
  {0xe440c0,0xc44ac0,0xc10328,0xc07041,0xc080c9,0xc0c0e1,0xb2010592,0xc105aa,0xc106e2,0x1d4130db,0xc090e3,0x484100fb,0xc810546,0x3f81054e,0x5d810566,0xc1057e,0xc200c7,0xc40000,0xc40000,0xc40000,0xc40000,0xc40000,0xc40000,0x97c40000},
  {0xe441c0,0xc44c40,0xc10398,0xc44d40,0xe103f0,0xc100f1,0xd0010692,0xc10632,0xc10672,0xc1067a,0x6f6103cc,0x736103a4,0x13810606,0xc1064e,0xc10626,0xc1067e,0xc0f0e7,0xc0e0ff,0xc40000,0xc40000,0xc40000,0xc40000,0xc40000,0x99c40000},
  {0xe44300,0xc100a0,0xc04001,0xc100c2,0x3c010112,0x7b01d003,0x741013a,0x234100c4,0x374100d4,0xc100ac,0x39a100fc,0xc10156,0x6981012e,0xc1019e,0xc1b01f,0xc40000,0xc40000,0xc40000,0xc40000,0xc40000,0xc40000,0xc40000,0xc40000,0x9bc40000},
  {0xe44340,0xc101d8,0xc09041,0xc10051,0x24010352,0xc1032a,0xc1b053,0x12410073,0xe101dc,0xe101ac,0xc10286,0x40810296,0x758102a6,0xc102e6,0xc19057,0xc40000,0xc40000,0xc40000,0xc40000,0xc40000,0xc40000,0xc40000,0xc40000,0x9dc40000},
  {0xc10008,0xc44000,0xc44100,0xe10068,0xc10029,0x3601009a,0xc1002a,0xc100a2,0xc1007a,0x3041803b,0xc0b095,0x10810046,0x41810016,0x7881002e,0xc1003e,0xc19037,0xc40000,0xc40000,0xc40000,0xc40000,0xc40000,0xc40000,0xc40000,0x1fc40000},
  {0xc10110,0xc44440,0xe10160,0xc101c2,0x4201021a,0xc10222,0xc10272,0xc101fa,0x3f410104,0x5e610114,0xc100dd,0x2081024e,0x5c8101e6,0xc101fe,0xc10047,0xc1007f,0xc40000,0xc40000,0xc40000,0xc40000,0xc40000,0xc40000,0xc40000,0x20c40000},
  {0xc10200,0xc44a00,0xc10260,0x3010402,0x4301050a,0xc10422,0xc0808b,0xc10432,0xc10244,0xe10214,0xc0b08d,0x7810386,0xc1050e,0x5f8103e6,0xc103fe,0xc1f0a7,0xc40000,0xc40000,0xc40000,0xc40000,0xc40000,0xc40000,0xc40000,0x7fc40000},
  {0xc102c0,0xc44900,0xc102b0,0x40449c0,0x120100b1,0x3801045a,0xc10472,0xa41a093,0x3d8102c4,0x4fa10294,0xe102e4,0xe102bc,0xc10516,0xc104e6,0xc104fe,0xc1b08f,0xc40000,0xc40000,0xc40000,0xc40000,0xc40000,0xc40000,0xc40000,0x7fc40000},
  {0xc10308,0xe10350,0xc44b00,0xe10378,0xc070f9,0x3f01059a,0xc105f2,0xc105ba,0x134105fa,0xe1034c,0xe10364,0xc106c6,0xc10556,0xc1055e,0xc105f6,0xc1e0ef,0xc40000,0xc40000,0xc40000,0xc40000,0xc40000,0xc40000,0xc40000,0x21c40000},
  {0xc10388,0xe103e0,0xc44d00,0xc10682,0x5801065a,0xc106aa,0xc41b0d3,0xc110eb,0x4a4130fb,0x3810686,0xc106ce,0xc106ee,0xc106a6,0xc1e0d7,0xc40000,0xc40000,0xc40000,0xc40000,0xc40000,0xc40000,0xc40000,0xc40000,0xc40000,0x22c40000},
  {0xe44100,0xc44180,0xe100d8,0xc44280,0xc10019,0x1001010a,0xc0b039,0xc10172,0xc1016a,0x1441a02b,0x4241009c,0xb8100f4,0x24810146,0x5981003d,0xf08100f6,0xc19017,0xc0c03f,0xc40000,0xc40000,0xc40000,0xc40000,0xc40000,0xc40000,0xa3c40000},
  {0xe44140,0xc101a0,0xc44640,0xc10059,0x1301028a,0x6501029a,0xc08079,0x71014053,0xc180e3,0xc0e07b,0xc101b4,0x37a101bc,0x4981007d,0x668102b6,0xc1033e,0xc1806f,0xc40000,0xc40000,0xc40000,0xc40000,0xc40000,0xc40000,0xc40000,0xa5c40000},
  {0x2e010040,0xe10028,0xe10030,0xc1000a,0x6801005a,0xc10072,0x40f013,0x104100ba,0x56410005,0x7161006c,0x14a1007c,0x2a810035,0x68810036,0xc1018e,0xc18027,0xc40000,0xc40000,0xc40000,0xc40000,0xc40000,0xc40000,0xc40000,0xc40000,0x7fc40000},
  {0xc10150,0xe10118,0xc44680,0xc10069,0x2f0101d2,0x7701c043,0x541023a,0x2241006b,0x4741011c,0xc10174,0x2f81020e,0xc1025e,0x7a8101f6,0xc10256,0xc0c05f,0xc0a077,0xc40000,0xc40000,0xc40000,0xc40000,0xc40000,0xc40000,0xc40000,0x27c40000},
  {0xc10208,0xc44740,0xc447c0,0xc04081,0xc07089,0x100a9,0xb00103da,0x7501d083,0x34103fa,0xe1020c,0xe10254,0xe1022c,0xc1038e,0xc1039e,0x768103b6,0xc1d08f,0xc0a0bf,0xc40000,0xc40000,0xc40000,0xc40000,0xc40000,0xc40000,0x28c40000},
  {0xc10290,0xc44940,0xc102f0,0x5010099,0x200080b9,0xd201049a,0xc104a2,0xc1047a,0xc0e09b,0x3e6102cc,0x5f40707b,0xc102f4,0x2b81048e,0xc1049e,0x7b8104b6,0xc104de,0xc160b7,0xc40000,0xc40000,0xc40000,0xc40000,0xc40000,0xc40000,0x29c40000},
  {0xc10318,0xc10358,0xc44b80,0xc10542,0x59010552,0xc1056a,0xc10572,0xc1c0eb,0x4b610314,0x59610374,0x7f61037c,0x158100fd,0x648105ae,0xc105e6,0xc180c7,0xc40000,0xc40000,0xc40000,0xc40000,0xc40000,0xc40000,0xc40000,0xc40000,0x2ac40000},
  {0xc103c0,0xc44c00,0xc103e8,0x6010602,0x4401061a,0xc090f9,0x7401a0cb,0xc170e3,0xc0d0fb,0xc103ec,0xc040e5,0x2e81068e,0xc1065e,0x7e8106b6,0xc1b0df,0xc0a0ff,0xc40000,0xc40000,0xc40000,0xc40000,0xc40000,0xc40000,0xc40000,0x7fc40000},
  {0xc100c8,0xc44240,0xc100b0,0x7010102,0x450100da,0xc1012a,0xc100f2,0xc100fa,0xe1008c,0xe10094,0xc0500d,0x1810186,0xc10196,0x6781016e,0xc100fe,0xc1d02f,0xc40000,0xc40000,0xc40000,0xc40000,0xc40000,0xc40000,0xc40000,0x2bc40000},
  {0xc101d0,0xe101e0,0xc100a1,0x250102ca,0x6e01031a,0x7e0102b2,0xc102ba,0xc0a06b,0x3161018c,0x676101ec,0x744102c6,0xc102d6,0x6f8102ae,0xc1032e,0xc1b067,0xc40000,0xc40000,0xc40000,0xc40000,0xc40000,0xc40000,0xc40000,0xc40000,0x2cc40000},
  {0xc10108,0xe10170,0xe10138,0xc08079,0x3701025a,0xc10232,0xc1404b,0x1b410144,0x2e610154,0x38610164,0x68410206,0xc101ce,0xc10226,0xc1037e,0xc1d067,0xc40000,0xc40000,0xc40000,0xc40000,0xc40000,0xc40000,0xc40000,0xc40000,0x2dc40000},
  {0xc10218,0xc10258,0xc10278,0x2a01040a,0xc080b9,0xc103ea,0xc1308b,0x1f41053a,0xc10085,0x7c61026c,0x16810406,0x478103d6,0x738103ae,0xc1042e,0xc19097,0xc40000,0xc40000,0xc40000,0xc40000,0xc40000,0xc40000,0xc40000,0xc40000,0x2ec40000},
  {0xc102c8,0xe102a8,0xc04081,0x1010482,0x5b010492,0x7601b083,0x941809b,0xe1028c,0xe102a4,0xc05095,0x11810446,0x42810496,0xc1046e,0xc104be,0xc190a7,0xc40000,0xc40000,0xc40000,0xc40000,0xc40000,0xc40000,0xc40000,0xc40000,0x2fc40000},
  {0xc10348,0xc44bc0,0xc10370,0x80105c2,0x4601058a,0x790200c3,0x14160db,0x3c410354,0x61610324,0x754105c6,0xc105d6,0x658106e6,0xc105fe,0xc1d0cf,0xc40000,0xc40000,0xc40000,0xc40000,0xc40000,0xc40000,0xc40000,0xc40000,0xc40000,0x30c40000},
  {0xc103d0,0xc103a8,0xc103f8,0x2b01064a,0x6901062a,0xc1069a,0xc106b2,0x27410384,0x394103d4,0x7b6103e4,0x17810646,0x448106d6,0xc106ae,0xc106be,0xc1a0e7,0xc40000,0xc40000,0xc40000,0xc40000,0xc40000,0xc40000,0xc40000,0xc40000,0x31c40000},
  {0xc100d0,0xe100a8,0xc100d9,0x2801018a,0x6d010132,0x7d010162,0xc1017a,0xc1102b,0x4140d03b,0xfa100ec,0x1b8100ce,0xc1015e,0x7d810136,0xc1a007,0xc0b037,0xc40000,0xc40000,0xc40000,0xc40000,0xc40000,0xc40000,0xc40000,0xc40000,0x32c40000},
  {0xc10190,0xc44580,0xc101f0,0x9010282,0x47010292,0xc102da,0xc102e2,0xc1033a,0xc10073,0x536101e4,0xc10306,0xc10356,0xc1029e,0xc102be,0xc1f057,0xc40000,0xc40000,0xc40000,0xc40000,0xc40000,0xc40000,0xc40000,0xc40000,0x33c40000},
  {0xc10148,0xc44400,0xc10128,0xa010202,0x4801020a,0xc101ea,0xc1604b,0x1c41037a,0x6e61010c,0x76610124,0x18810246,0xc10216,0x63810266,0xc1027e,0xc13047,0xc0a0bf,0xc40000,0xc40000,0xc40000,0xc40000,0xc40000,0xc40000,0xc40000,0x34c40000},
  {0xc10248,0xc44a40,0xc10268,0xb010382,0x490103d2,0xc103aa,0xc10532,0xc1043a,0xc120b3,0x50410264,0x8103c6,0xc10396,0xc103a6,0xc1043e,0xc1e0af,0xc40000,0xc40000,0xc40000,0xc40000,0xc40000,0xc40000,0xc40000,0xc40000,0x35c40000},
  {0xc10288,0x2c2102d8,0xe102b8,0xc1048a,0x6a0104d2,0xc104aa,0xc1052a,0x284150ab,0x5440e0bb,0xa81009d,0x34a102fc,0x4a81045e,0xc10476,0xc104ee,0xc110bf,0xc40000,0xc40000,0xc40000,0xc40000,0xc40000,0xc40000,0xc40000,0xc40000,0x36c40000},
  {0xc10340,0xc44a80,0xc10368,0xc010582,0x4a0106da,0xc105d2,0xc105ea,0xc106fa,0xc130f3,0x654100cd,0x1f810586,0xc105ce,0x6e8105ee,0xc105be,0xc0f0e7,0xc0c0f7,0xc40000,0xc40000,0xc40000,0xc40000,0xc40000,0xc40000,0xc40000,0x7fc40000},
  {0xc103d8,0xc44cc0,0xc040c1,0xc103b8,0x140106ca,0x5f010662,0xc106a2,0xc106ea,0xc1d0f3,0xc080fb,0xe8100d5,0x2381060e,0x5881061e,0xc10636,0xc106fe,0xc120ff,0xc40000,0xc40000,0xc40000,0xc40000,0xc40000,0xc40000,0xc40000,0x37c40000},
  {0xc10080,0xc441c0,0xc04001,0xc10142,0x3d0100d2,0xc101a2,0xc101ba,0xc12023,0x2540d02b,0x4340c03b,0x72410015,0x2681014e,0xc1011e,0xc100ee,0xc101a6,0xc0a027,0xc0a03f,0xc40000,0xc40000,0xc40000,0xc40000,0xc40000,0xc40000,0x7fc40000},
  {0xc10180,0xc44500,0xc101f8,0xd010302,0x4b0102d2,0x7801c043,0x8420063,0xc080f3,0x6241004d,0x1e809065,0x218100f5,0xd6810366,0xc102f6,0xc2006f,0xc40000,0xc40000,0xc40000,0xc40000,0xc40000,0xc40000,0xc40000,0xc40000,0xc40000,0x7fc40000},
  {0xc10140,0xc44380,0xc10120,0xe010342,0x4c01035a,0xc1022a,0xc1026a,0xc1e06b,0x4540c07b,0xc10134,0x3581006d,0x458101de,0x7c810276,0xc10376,0xc15077,0xc40000,0xc40000,0xc40000,0xc40000,0xc40000,0xc40000,0xc40000,0xc40000,0x7fc40000},
  {0xc10240,0xc44800,0xe10230,0xc10502,0x4d010392,0xc1041a,0xc103a2,0xc1209b,0x2040c0ab,0x4441025c,0xd810274,0x2581040e,0xc103de,0x7f8103f6,0xc10526,0xc130bf,0xc40000,0xc40000,0xc40000,0xc40000,0xc40000,0xc40000,0xc40000,0x7fc40000},
  {0xc10298,0xc448c0,0xc102e8,0xf010442,0x4e0104da,0xc10522,0xc104b2,0xc1c0a3,0x4c41029c,0x706102b4,0x1981044e,0x5a8100bd,0x6a810536,0xc1052e,0xc160b7,0xc40000,0xc40000,0xc40000,0xc40000,0xc40000,0xc40000,0xc40000,0xc40000,0x38c40000},
  {0xc10300,0xe10330,0xc44dc0,0xc100e9,0xb401055a,0xc105a2,0xc105b2,0xc106f2,0xc0b0eb,0x4d61035c,0x5a61032c,0xc1058e,0xc1059e,0x7781056e,0xc105de,0xc170f7,0xc40000,0xc40000,0xc40000,0xc40000,0xc40000,0xc40000,0xc40000,0x7fc40000},
  {0xc103c8,0xe103a0,0xc04081,0x2010642,0x5c010652,0xc10622,0xb41d0d3,0x3c8103c4,0x4ba1039c,0xe103b4,0xe103bc,0xc10616,0xc1062e,0xc1063e,0xc1a0d7,0xc40000,0xc40000,0xc40000,0xc40000,0xc40000,0xc40000,0xc40000,0xc40000,0x39c40000},
  {0xc100c0,0xc442c0,0xc100b8,0x192100f8,0x2301014a,0xc100e2,0xc100ea,0xc19023,0x336100cc,0x694100e4,0x3aa100bc,0xc10116,0xc101ae,0xc1017e,0xc1d01f,0xc40000,0xc40000,0xc40000,0xc40000,0xc40000,0xc40000,0xc40000,0xc40000,0x7fc40000},
  {0xc10188,0xe101a8,0xc080c9,0x18010071,0x400102a2,0xc102ea,0xc10332,0x11410184,0x2f6101d4,0x3a6101a4,0x6a410346,0xc102ce,0xc102de,0xc1036e,0xc15047,0xc0a07f,0xc40000,0xc40000,0xc40000,0xc40000,0xc40000,0xc40000,0xc40000,0x3ac40000},
  {0xc10100,0xc44480,0xc10178,0xc10242,0x4f010212,0xc101e2,0xe41f05b,0x2b61014c,0x3b61015c,0x6b61012c,0x7761017c,0x1a81021e,0x7481022e,0xc1026e,0xc19077,0xc40000,0xc40000,0xc40000,0xc40000,0xc40000,0xc40000,0xc40000,0xc40000,0x7fc40000},
  {0xc10210,0x2d210250,0xe10238,0xc1038a,0x6b0103e2,0x7001d08b,0x19410204,0xe1024c,0xe10224,0xe1023c,0xc040a5,0x4e8103ce,0xc103ee,0xc10416,0xc1a0af,0xc40000,0xc40000,0xc40000,0xc40000,0xc40000,0xc40000,0xc40000,0xc40000,0x3bc40000},
  {0xc10280,0xc44980,0xc102e0,0xc104c2,0x5401051a,0xc104e2,0xd41e093,0xc10284,0xc102dc,0xc102ec,0xc0c0a5,0x3e810456,0x6b8104ae,0xc104f6,0xc1b087,0xc40000,0xc40000,0xc40000,0xc40000,0xc40000,0xc40000,0xc40000,0xc40000,0x7fc40000},
  {0xc10310,0xc44b40,0xc10360,0xc106c2,0x550105ca,0xc10562,0xc105da,0xc1057a,0xc10304,0xc1031c,0xc10334,0x278100ed,0x438106de,0xc10576,0xc105b6,0xc150f7,0xc40000,0xc40000,0xc40000,0xc40000,0xc40000,0xc40000,0xc40000,0x3cc40000},
  {0xc10380,0xc44c80,0xc040c1,0x1e2103b0,0xc1068a,0x600106d2,0xc1066a,0xc1063a,0xc0f0db,0x3d610394,0x6c4103ac,0x3ba103fc,0xc10696,0xc10666,0xc10676,0xc0f0cf,0xc0e0ff,0xc40000,0xc40000,0xc40000,0xc40000,0xc40000,0xc40000,0x7fc40000},
  {0xc10090,0xc44200,0xc100e8,0x1a044340,0xc10031,0x39010152,0xc10122,0xc101b2,0x17410084,0xc11033,0x5c40703b,0xc100b4,0x2d810025,0x468100de,0x79810176,0xc101b6,0xc16027,0xc40000,0xc40000,0xc40000,0xc40000,0xc40000,0xc40000,0x3dc40000},
  {0xc101c8,0xc101e8,0xc10061,0x2601034a,0x6f0102aa,0x7f01036a,0xc102fa,0xe101cc,0xc1019c,0xc101f4,0x38a101fc,0x4c810316,0xc102ee,0xc1030e,0xc0c0cf,0xc0e07f,0xc40000,0xc40000,0xc40000,0xc40000,0xc40000,0xc40000,0xc40000,0x3ec40000},
  {0xc10098,0xc44300,0xc100f0,0xc10182,0x56010192,0xc1011a,0xf420013,0x2a414033,0x636100a4,0x784100c6,0xc100d6,0x628100e6,0xc10126,0xc1c00f,0xc40000,0xc40000,0xc40000,0xc40000,0xc40000,0xc40000,0xc40000,0xc40000,0xc40000,0x3fc40000},
  {0xc101c0,0xc44540,0xc101b8,0xc102c2,0x57010312,0xc10362,0xc10372,0xc09053,0x15411063,0xc10194,0xc0508d,0x981005d,0x3381028e,0x5e81031e,0xc102fe,0xc0f05f,0xc1007f,0xc40000,0xc40000,0xc40000,0xc40000,0xc40000,0xc40000,0x7fc40000},
};
uint8_t kSeq[NPAIR][KMAX] = {
  {0,1,2,3,0,1,2,3,4,5,6,7,8,9,10,11,12,13,14,15,0,1,2,3,64,67,72,78,76,70,66,74,64,66,76,78,65,67,77,79,68,70,69,71,72,74,73,75,4,6,0,2,5,7,1,3,12,14,8,10,13,15,9,11,4,6,8,10,0,2,5,7,9,11,12,14,1,3,13,15,88,89,94,95,116,117,118,119,106,107,78,79,82,83,112,113,84,85,102,103,98,99,72,73,72,73,80,81,98,99,74,75,110,111,112,113,86,87,92,93,78,79,64,65,66,67,84,68,70,69,71,76,78,72,74,64,66,77,79,73,75,65,67,68,70,72,74,69,71,64,66,76,78,73,75,65,67,77,79,8,10,0,2,9,11,12,14,1,3,4,6,13,15,5,7,12,14,8,10,4,6,0,2,13,15,9,11,5,7,1,3,12,14,8,10,13,15,4,6,9,11,5,7,0,2,1,3,200,202,73,75,196,198,192,194,204,206,197,199,193,195,205,207,71,66,67,112,113,98,99,86,87,110,111,114,115,88,89,118,119,196,197,230,0,0,0,0,0,0,0,0,0,0,0,0,0,0,0,0,0,0,0,0,0,0,0,0,0,0,0,0,0,0,0,0,0,0,0,0,0,0,0,0,0,0,0,0,0,0,0,0,0,0,0,0,0},
  {0,1,2,3,0,1,2,3,4,5,6,7,8,9,10,11,12,13,14,15,0,1,2,3,77,69,73,79,65,68,75,71,70,64,76,66,74,72,79,71,78,67,69,65,75,77,68,73,12,14,8,10,13,15,9,11,0,2,4,6,1,3,5,7,76,78,72,74,77,79,73,75,64,66,68,70,65,67,69,71,4,6,12,14,8,10,0,2,5,7,13,15,9,11,1,3,114,115,100,101,74,75,116,117,118,0,2,4,6,8,10,1,3,5,7,12,14,9,11,13,15,76,78,68,70,77,79,64,66,72,74,69,71,65,67,73,75,12,14,4,6,0,2,13,15,5,7,8,10,1,3,9,11,8,10,12,14,0,2,9,11,13,15,1,3,4,6,5,7,8,10,9,11,4,6,0,2,12,14,5,7,1,3,13,15,4,6,12,14,8,10,5,7,13,15,9,11,0,2,1,3,12,14,8,10,13,15,4,6,9,11,5,7,128,130,1,3,99,64,65,80,81,92,93,108,109,106,107,70,71,66,67,90,91,88,89,82,83,224,225,232,233,230,231,0,0,0,0,0,0,0,0,0,0,0,0,0,0,0,0,0,0,0,0,0,0,0,0,0,0,0,0,0,0,0,0,0,0,0,0,0,0,0,0,0,0,0,0,0,0,0,0,0,0,0,0},
  {64,65,66,67,68,69,70,71,72,73,74,75,76,77,78,79,0,1,2,3,79,75,77,73,0,2,12,14,1,3,13,15,4,6,5,7,8,10,9,11,64,66,72,74,65,67,73,75,76,78,68,70,77,79,69,71,4,6,12,14,8,10,0,2,5,7,13,15,9,11,1,3,0,2,8,10,4,6,12,14,1,3,9,11,5,7,13,15,83,98,99,108,109,92,93,78,79,84,85,100,101,66,67,74,75,88,66,67,84,85,68,69,90,91,104,105,70,71,210,211,228,229,106,107,222,71,72,69,66,64,78,74,77,76,75,73,64,71,78,77,69,72,75,70,74,79,76,73,68,67,66,65,64,71,78,74,77,70,73,69,66,72,76,79,68,65,67,75,4,6,5,7,8,10,12,14,9,11,13,15,0,2,1,3,4,6,12,14,8,10,5,7,13,15,0,2,9,11,1,3,106,107,104,105,92,93,88,89,72,73,90,91,100,101,78,79,116,117,64,65,118,119,208,209,94,95,76,77,240,241,0,0,0,0,0,0,0,0,0,0,0,0,0,0,0,0,0,0,0,0,0,0,0,0,0,0,0,0,0,0,0,0,0,0,0,0,0,0,0,0,0,0,0,0,0,0,0,0,0,0,0,0,0,0,0,0,0,0,0,0,0,0,0,0,0,0},
  {0,1,2,3,4,5,6,7,8,9,10,11,12,13,14,15,0,1,2,3,66,74,68,64,0,2,12,14,1,3,13,15,4,6,5,7,8,10,9,11,64,66,72,74,65,67,73,75,76,78,68,70,77,79,69,71,4,6,0,2,5,7,1,3,12,14,8,10,13,15,9,11,4,6,12,14,8,10,128,130,5,7,13,15,9,11,129,131,92,93,64,65,100,101,96,97,89,76,77,96,97,86,87,72,73,116,117,110,111,4,6,5,7,12,14,8,10,0,2,13,15,9,11,1,3,0,2,1,3,4,6,8,10,12,14,5,7,9,11,13,15,8,10,12,14,0,2,9,11,13,15,1,3,4,6,5,7,8,10,0,2,9,11,12,14,1,3,4,6,13,15,5,7,4,6,5,7,8,10,12,14,9,11,13,15,0,2,1,3,4,6,12,14,8,10,5,7,13,15,0,2,9,11,1,3,77,112,113,110,111,82,83,70,71,68,69,102,103,108,80,81,66,67,90,91,96,97,242,243,202,203,70,199,238,239,0,0,0,0,0,0,0,0,0,0,0,0,0,0,0,0,0,0,0,0,0,0,0,0,0,0,0,0,0,0,0,0,0,0,0,0,0,0,0,0,0,0,0,0,0,0,0,0,0,0,0,0,0,0,0,0,0,0,0,0,0},
  {64,65,66,67,68,69,70,71,72,73,74,75,76,77,78,79,64,65,66,67,68,69,70,71,72,73,74,75,76,77,78,79,64,65,66,67,68,69,70,71,72,73,74,75,76,77,78,79,198,69,194,199,204,12,14,8,10,13,15,9,11,0,2,4,6,1,3,5,7,70,71,64,65,98,99,92,93,78,79,112,113,94,95,72,73,80,81,84,85,114,115,116,117,106,107,66,136,138,128,130,137,139,129,131,140,142,141,143,132,134,133,135,0,2,4,6,8,10,1,3,5,7,12,14,9,11,13,15,4,6,5,7,0,2,8,10,12,14,1,3,9,11,13,15,68,70,69,71,64,66,72,74,76,78,65,67,73,75,77,79,132,134,128,130,133,135,129,131,136,138,140,142,137,139,141,143,8,10,0,2,9,11,12,14,1,3,4,6,13,15,5,7,12,14,8,10,4,6,0,2,13,15,9,11,5,7,1,3,4,6,12,14,8,10,5,7,13,15,0,2,137,139,1,3,92,93,108,109,98,99,80,81,100,101,70,71,116,117,96,97,74,75,64,65,112,113,82,83,234,235,212,213,0,0,0,0,0,0,0,0,0,0,0,0,0,0,0,0,0,0,0,0,0,0,0,0,0,0,0,0,0,0,0,0,0,0,0,0,0,0,0,0,0,0,0,0},
  {0,1,2,3,0,1,2,3,0,1,2,3,4,5,6,7,8,9,10,11,12,13,14,15,0,1,2,3,4,5,6,7,8,9,10,11,12,13,14,15,70,64,76,66,0,2,8,10,1,3,9,11,12,14,4,6,13,15,5,7,4,6,0,2,5,7,1,3,12,14,8,10,13,15,9,11,0,2,8,10,4,6,12,14,1,3,9,11,5,7,13,15,93,78,79,84,85,100,101,66,67,74,75,88,89,76,77,96,97,86,87,72,73,116,117,110,111,84,85,88,89,114,115,110,66,71,70,77,69,73,72,64,65,78,67,75,79,74,76,68,12,14,4,6,0,2,13,15,5,7,8,10,1,3,9,11,132,134,128,130,133,135,129,131,136,138,140,142,137,139,141,143,8,10,9,11,4,6,0,2,12,14,5,7,1,3,13,15,4,6,12,14,8,10,5,7,13,15,9,11,0,2,1,3,140,142,136,138,141,143,132,134,137,139,133,135,128,130,129,131,72,73,86,87,102,103,90,91,118,119,68,69,206,207,114,115,66,67,110,111,94,95,88,217,204,205,0,0,0,0,0,0,0,0,0,0,0,0,0,0,0,0,0,0,0,0,0,0,0,0,0,0,0,0,0,0,0,0,0,0,0,0,0,0,0,0,0,0,0,0,0,0,0,0,0,0},
  {0,1,2,3,0,1,2,3,0,1,2,3,4,5,6,7,8,9,10,11,12,13,14,15,0,1,2,3,0,1,2,3,4,5,6,7,8,9,10,11,12,13,14,15,0,2,8,10,1,3,9,11,12,14,4,6,13,15,5,7,4,6,0,2,5,7,1,3,12,14,8,10,13,15,9,11,0,2,8,10,4,6,12,14,1,3,9,11,5,7,13,15,4,6,12,14,8,10,0,2,5,7,13,15,137,11,1,3,136,138,128,130,137,139,129,131,140,142,141,143,132,134,133,135,204,205,236,237,240,241,210,211,226,227,228,229,192,193,200,201,208,209,202,203,212,213,214,215,8,10,12,14,0,2,9,11,13,15,1,3,4,6,5,7,78,74,77,71,70,64,66,69,79,200,75,68,204,73,195,65,4,6,5,7,8,10,12,14,9,11,13,15,0,2,1,3,132,134,140,142,136,138,133,135,141,143,128,130,137,139,129,131,99,102,103,86,87,104,105,78,79,118,119,114,115,88,89,112,113,100,101,64,65,84,85,94,95,224,225,82,83,196,197,0,0,0,0,0,0,0,0,0,0,0,0,0,0,0,0,0,0,0,0,0,0,0,0,0,0,0,0,0,0,0,0,0,0,0,0,0,0,0,0,0,0,0,0,0,0,0,0,0,0,0,0,0},
  {0,1,2,3,0,1,2,3,4,5,6,7,8,9,10,11,12,13,14,15,66,74,68,64,64,74,76,66,68,70,65,72,79,67,69,71,78,75,77,73,0,2,8,10,1,3,9,11,12,14,4,6,13,15,5,7,12,14,8,10,13,15,9,11,0,2,4,6,1,3,5,7,4,6,12,14,8,10,0,2,5,7,13,15,9,11,1,3,0,2,8,10,4,6,12,14,1,3,9,11,5,7,13,15,99,100,101,90,91,70,71,76,77,68,69,110,111,82,83,74,75,96,97,118,119,104,105,238,239,242,243,232,233,218,219,220,221,230,231,196,197,8,10,12,14,0,2,9,11,13,15,1,3,4,6,5,7,8,10,0,2,9,11,12,14,1,3,4,6,13,15,5,7,4,6,5,7,8,10,12,14,9,11,13,15,0,2,1,3,4,6,140,142,136,138,133,135,141,143,128,130,137,139,129,131,80,81,96,97,92,93,108,109,70,71,82,83,100,101,78,79,74,75,114,115,94,95,118,119,200,201,192,193,240,241,226,0,0,0,0,0,0,0,0,0,0,0,0,0,0,0,0,0,0,0,0,0,0,0,0,0,0,0,0,0,0,0,0,0,0,0,0,0,0,0,0,0,0,0,0,0,0,0,0,0,0,0,0,0,0,0,0,0,0,0,0},
  {0,1,2,3,0,1,2,3,4,5,6,7,8,9,10,11,12,13,14,15,69,76,67,65,0,1,2,3,4,5,6,7,8,9,10,11,12,13,14,15,0,2,8,10,1,3,9,11,12,14,4,6,13,15,5,7,4,6,8,10,0,2,5,7,9,11,12,14,1,3,13,15,88,89,94,95,116,117,118,119,106,107,78,79,82,83,112,113,84,85,102,103,98,99,72,73,92,93,64,65,100,101,0,2,4,6,8,10,1,3,5,7,12,14,9,11,13,15,12,14,4,6,13,15,0,2,8,10,5,7,1,3,9,11,222,223,244,245,12,14,4,6,0,2,13,15,5,7,8,10,1,3,9,11,132,134,128,130,133,135,129,131,136,138,140,142,137,139,141,143,8,10,9,11,4,6,0,2,12,14,5,7,1,3,13,15,4,6,5,7,8,10,12,14,9,11,13,15,0,2,1,3,12,14,8,10,13,15,4,6,9,11,5,7,0,2,1,3,65,112,113,98,99,88,89,86,87,84,85,90,91,106,235,68,69,104,105,76,77,116,117,110,111,102,103,194,195,0,0,0,0,0,0,0,0,0,0,0,0,0,0,0,0,0,0,0,0,0,0,0,0,0,0,0,0,0,0,0,0,0,0,0,0,0,0,0,0,0,0,0,0,0,0,0,0,0},
  {0,1,2,3,0,1,2,3,4,5,6,7,8,9,10,11,12,13,14,15,0,1,2,3,64,74,76,66,68,70,65,72,79,67,69,71,78,75,77,73,0,2,8,10,1,3,9,11,12,14,4,6,13,15,5,7,12,14,8,10,13,15,9,11,0,2,4,6,1,3,5,7,96,97,82,83,74,75,110,111,76,77,88,89,118,119,68,69,100,101,104,105,102,103,90,91,136,138,128,130,9,11,129,131,140,142,141,143,132,134,133,135,12,14,4,6,13,15,0,2,8,10,5,7,1,3,9,11,4,6,5,7,0,2,8,10,12,14,1,3,9,11,13,15,4,6,8,10,5,7,0,2,12,14,9,11,1,3,13,15,77,69,78,72,76,68,66,73,79,67,75,65,8,10,9,11,4,6,0,2,12,14,5,7,1,3,13,15,4,6,12,14,8,10,5,7,13,15,9,11,0,2,1,3,12,14,8,10,132,134,0,2,141,143,9,11,133,135,129,131,64,65,80,81,92,93,108,109,106,107,70,71,66,67,90,91,88,89,82,83,96,97,232,233,230,231,0,0,0,0,0,0,0,0,0,0,0,0,0,0,0,0,0,0,0,0,0,0,0,0,0,0,0,0,0,0,0,0,0,0,0,0,0,0,0,0,0,0,0,0,0,0,0,0,0,0},
  {64,65,66,67,68,69,70,71,72,73,74,75,76,77,78,79,0,1,2,3,4,5,6,7,8,9,10,11,12,13,14,15,64,74,76,66,68,70,65,72,79,67,69,71,78,75,77,73,0,2,8,10,1,3,9,11,12,14,4,6,13,15,5,7,4,6,0,2,5,7,1,3,12,14,8,10,13,15,9,11,114,115,76,77,70,71,86,87,90,91,74,75,66,67,68,69,80,81,108,109,110,111,104,105,84,85,88,89,114,115,110,111,98,99,66,67,94,85,68,69,90,91,104,105,70,71,210,211,100,101,234,235,4,6,5,7,0,2,8,10,12,14,1,3,9,11,13,15,8,10,12,14,0,2,9,11,13,15,1,3,4,6,5,7,8,10,0,2,9,11,12,14,1,3,4,6,13,15,5,7,4,6,5,7,8,10,12,14,9,11,13,15,0,2,1,3,4,6,12,14,8,10,133,135,13,15,0,2,137,139,1,3,99,102,103,86,87,104,105,78,79,118,119,114,115,88,89,112,113,100,101,64,65,84,85,94,95,224,225,210,211,196,197,0,0,0,0,0,0,0,0,0,0,0,0,0,0,0,0,0,0,0,0,0,0,0,0,0,0,0,0,0,0,0,0,0,0,0,0,0,0,0,0,0,0,0,0,0,0,0,0,0,0,0,0,0},
  {0,1,2,3,4,5,6,7,8,9,10,11,12,13,14,15,0,1,2,3,4,5,6,7,8,9,10,11,12,13,14,15,0,1,2,3,0,1,2,3,0,1,2,3,0,2,8,10,1,3,9,11,12,14,4,6,13,15,5,7,4,6,8,10,0,2,5,7,9,11,12,14,1,3,13,15,0,2,8,10,4,6,12,14,1,3,9,11,5,7,13,15,72,73,92,93,64,65,100,101,96,97,114,115,76,77,0,2,4,6,8,10,1,3,5,7,12,14,9,11,13,15,204,205,108,109,112,113,210,211,226,227,228,229,192,193,200,201,208,209,202,203,212,213,214,71,69,72,78,64,77,75,74,79,73,67,76,70,68,66,65,68,66,73,79,67,75,65,78,74,77,71,70,64,194,69,207,200,75,196,204,73,195,65,4,6,5,7,8,10,12,14,9,11,13,15,0,2,1,3,12,14,8,10,13,15,4,6,9,11,5,7,0,2,1,3,65,112,113,98,99,88,89,86,87,84,85,90,91,106,107,68,69,104,105,76,77,116,117,238,239,102,103,194,195,0,0,0,0,0,0,0,0,0,0,0,0,0,0,0,0,0,0,0,0,0,0,0,0,0,0,0,0,0,0,0,0,0,0,0,0,0,0,0,0,0,0,0,0,0,0,0,0,0,0,0},
  {0,1,2,3,4,5,6,7,8,9,10,11,12,13,14,15,0,1,2,3,4,5,6,7,8,9,10,11,12,13,14,15,0,1,2,3,4,5,6,7,8,9,10,11,12,13,14,15,64,65,66,67,68,69,70,71,72,73,74,75,76,77,78,79,4,6,8,10,0,2,5,7,9,11,12,14,1,3,13,15,0,2,8,10,4,6,12,14,1,3,9,11,5,7,13,15,64,65,70,71,80,81,112,113,90,91,102,103,118,119,104,105,114,115,106,107,94,95,68,69,82,12,14,4,6,13,15,0,2,8,10,5,7,1,3,9,11,0,2,1,3,4,6,8,10,12,14,5,7,9,11,13,15,68,70,72,74,69,71,64,66,76,78,73,75,65,67,77,79,64,71,78,74,77,70,73,69,66,72,76,79,68,65,67,75,4,6,5,7,8,10,12,14,9,11,13,15,0,2,1,3,4,6,12,14,8,10,5,7,13,15,9,11,0,2,1,3,204,206,200,202,196,198,192,194,205,207,201,203,197,199,193,195,78,79,106,107,86,87,94,95,76,77,220,221,72,73,98,227,212,213,0,0,0,0,0,0,0,0,0,0,0,0,0,0,0,0,0,0,0,0,0,0,0,0,0,0,0,0,0,0,0,0,0,0,0,0,0,0,0,0,0,0,0,0,0},
  {0,1,2,3,0,1,2,3,0,1,2,3,4,5,6,7,8,9,10,11,12,13,14,15,64,67,72,77,69,73,78,76,70,66,74,79,65,68,75,71,0,2,8,10,1,3,9,11,12,14,4,6,13,15,5,7,12,14,8,10,13,15,9,11,0,2,4,6,1,3,5,7,4,6,8,10,0,2,5,7,9,11,12,14,1,3,13,15,136,138,128,130,137,139,129,131,140,142,141,143,132,134,133,135,78,79,64,65,66,67,84,85,68,69,90,91,104,105,70,71,210,211,100,101,106,107,222,223,66,71,70,77,69,73,72,64,65,78,67,75,79,74,76,68,8,10,12,14,0,2,9,11,13,15,1,3,4,6,5,7,8,10,0,2,9,11,12,14,1,3,4,6,13,15,5,7,12,14,8,10,4,6,0,2,13,15,9,11,5,7,1,3,4,6,12,14,8,10,5,7,141,143,0,2,137,139,1,3,92,93,108,109,98,99,80,81,100,101,70,71,116,117,96,97,74,75,64,65,112,113,82,83,106,107,212,213,232,233,0,0,0,0,0,0,0,0,0,0,0,0,0,0,0,0,0,0,0,0,0,0,0,0,0,0,0,0,0,0,0,0,0,0,0,0,0,0,0,0,0,0,0,0,0,0,0,0,0,0,0,0,0,0,0,0,0,0},
  {0,1,2,3,0,1,2,3,0,1,2,3,4,5,6,7,8,9,10,11,12,13,14,15,64,67,72,77,69,73,78,76,70,64,66,76,78,65,67,77,79,68,70,69,71,72,74,73,75,12,14,8,10,13,15,9,11,0,2,4,6,1,3,5,7,76,78,72,74,77,79,73,75,64,66,68,70,65,67,69,71,0,2,8,10,4,6,12,14,1,3,9,11,5,7,13,15,84,85,88,89,114,115,110,111,98,99,66,67,94,95,70,71,76,77,106,107,96,97,64,65,78,79,90,91,4,6,5,7,0,2,8,10,12,14,1,3,9,11,13,15,4,6,8,10,5,7,0,2,12,14,9,11,1,3,13,15,132,134,128,130,133,135,129,131,136,138,140,142,137,139,141,143,12,14,8,10,4,6,0,2,13,15,9,11,5,7,1,3,12,14,8,10,4,6,0,2,13,15,9,11,5,7,1,3,12,14,8,10,13,15,132,134,9,11,133,135,128,130,129,131,99,88,89,86,87,84,85,90,91,234,235,68,69,104,105,76,77,116,117,110,111,102,103,194,195,0,0,0,0,0,0,0,0,0,0,0,0,0,0,0,0,0,0,0,0,0,0,0,0,0,0,0,0,0,0,0,0,0,0,0,0,0,0,0,0,0,0,0,0,0,0,0,0,0,0},
  {0,1,2,3,0,1,2,3,0,1,2,3,4,5,6,7,8,9,10,11,12,13,14,15,79,75,77,73,0,1,2,3,4,5,6,7,8,9,10,11,12,13,14,15,0,2,8,10,1,3,9,11,12,14,4,6,13,15,5,7,4,6,8,10,0,2,5,7,9,11,12,14,1,3,13,15,4,6,12,14,8,10,0,2,5,7,13,15,9,11,1,3,136,138,128,130,137,139,129,131,140,142,141,143,132,134,133,135,136,138,128,130,137,139,129,131,140,142,141,143,132,134,133,135,4,6,5,7,12,14,8,10,0,2,13,15,9,11,1,3,12,14,4,6,0,2,13,15,5,7,8,10,1,3,9,11,8,10,12,14,0,2,9,11,13,15,1,3,4,6,5,7,8,10,9,11,4,6,0,2,12,14,5,7,1,3,13,15,4,6,5,7,8,10,12,14,9,11,13,15,0,2,1,3,4,6,12,14,8,10,5,7,13,15,0,2,9,11,1,3,109,86,87,114,115,98,99,66,67,84,85,96,97,74,75,102,103,80,81,96,97,76,77,218,219,236,237,0,0,0,0,0,0,0,0,0,0,0,0,0,0,0,0,0,0,0,0,0,0,0,0,0,0,0,0,0,0,0,0,0,0,0,0,0,0,0,0,0,0,0,0,0,0,0,0,0},
  {0,1,2,3,0,1,2,3,0,1,2,3,4,5,6,7,8,9,10,11,12,13,14,15,72,78,70,71,66,74,68,70,66,74,79,65,68,75,71,74,72,79,71,78,67,69,65,75,77,68,73,12,14,8,10,13,15,9,11,0,2,4,6,1,3,5,7,4,6,12,14,8,10,0,2,5,7,13,15,9,11,1,3,4,6,8,10,0,2,5,7,9,11,12,14,1,3,13,15,68,69,82,83,98,99,108,109,92,93,78,79,84,85,100,101,66,67,74,75,86,87,92,93,118,119,68,69,216,217,198,199,206,207,246,247,194,195,238,239,242,243,232,233,8,10,12,14,0,2,9,11,13,15,1,3,4,6,5,7,8,10,0,2,9,11,12,14,1,3,4,6,13,15,5,7,4,6,5,7,8,10,12,14,9,11,13,15,0,2,1,3,132,134,140,142,136,138,133,135,141,143,128,130,137,139,129,131,106,107,104,105,92,93,88,89,72,73,90,91,100,101,78,79,116,117,64,65,118,119,208,209,94,95,76,77,240,241,238,239,0,0,0,0,0,0,0,0,0,0,0,0,0,0,0,0,0,0,0,0,0,0,0,0,0,0,0,0,0,0,0,0,0,0,0,0,0,0,0,0,0,0,0,0,0,0,0,0,0,0,0,0,0,0,0,0,0},
  {0,1,2,3,0,1,2,3,0,1,2,3,4,5,6,7,8,9,10,11,12,13,14,15,0,1,2,3,0,1,2,3,4,5,6,7,8,9,10,11,12,13,14,15,76,69,70,72,74,66,71,75,67,77,68,73,79,206,64,65,12,14,8,10,13,15,9,11,0,2,4,6,1,3,5,7,0,2,8,10,4,6,12,14,1,3,9,11,5,7,13,15,0,2,8,10,4,6,12,14,1,3,9,11,5,7,13,15,136,138,128,130,137,139,129,131,140,142,141,143,132,134,133,135,12,14,4,6,13,15,0,2,8,10,5,7,1,3,9,11,0,2,1,3,4,6,8,10,12,14,5,7,9,11,13,15,8,10,12,14,0,2,9,11,13,15,1,3,4,6,5,7,8,10,0,2,9,11,12,14,1,3,4,6,13,15,5,7,4,6,5,7,8,10,12,14,9,11,13,15,0,2,1,3,4,6,140,142,136,138,5,7,141,143,0,2,137,139,129,131,75,98,99,66,67,80,81,92,93,114,115,112,113,88,89,110,111,82,83,68,69,104,105,108,109,102,103,244,245,0,0,0,0,0,0,0,0,0,0,0,0,0,0,0,0,0,0,0,0,0,0,0,0,0,0,0,0,0,0,0,0,0,0,0,0,0,0,0,0,0,0,0,0,0,0,0},
  {0,1,2,3,0,1,2,3,4,5,6,7,8,9,10,11,12,13,14,15,69,76,67,65,0,2,12,14,1,3,13,15,4,6,5,7,8,10,9,11,12,14,8,10,13,15,9,11,0,2,4,6,1,3,5,7,67,108,109,86,87,96,97,82,83,74,75,110,111,76,77,88,89,118,119,68,69,100,101,104,105,102,103,90,91,136,138,128,130,137,139,129,131,140,142,141,143,132,134,133,135,0,2,4,6,8,10,1,3,5,7,12,14,9,11,13,15,4,6,5,7,12,14,8,10,0,2,13,15,9,11,1,3,12,14,4,6,0,2,13,15,5,7,8,10,1,3,9,11,132,134,128,130,133,135,129,131,136,138,140,142,137,139,141,143,8,10,9,11,4,6,0,2,12,14,5,7,1,3,13,15,4,6,12,14,8,10,5,7,13,15,9,11,0,2,1,3,12,14,8,10,4,6,0,2,13,15,9,11,5,7,1,3,80,81,96,97,92,93,108,109,70,71,82,83,100,101,206,207,74,75,114,115,94,95,118,119,200,201,192,0,0,0,0,0,0,0,0,0,0,0,0,0,0,0,0,0,0,0,0,0,0,0,0,0,0,0,0,0,0,0,0,0,0,0,0,0,0,0,0,0,0,0,0,0,0,0,0,0,0,0,0,0,0,0,0},
  {0,1,2,3,0,1,2,3,4,5,6,7,8,9,10,11,12,13,14,15,64,79,75,77,73,69,76,67,65,64,74,76,66,68,70,65,72,79,67,69,71,78,75,77,73,12,14,8,10,13,15,9,11,0,2,4,6,1,3,5,7,4,6,12,14,8,10,0,2,5,7,13,15,9,11,1,3,76,77,88,89,106,107,78,79,96,97,108,109,114,115,100,101,74,75,116,117,118,119,82,83,112,113,98,72,73,80,81,98,99,74,75,110,111,112,113,86,87,92,93,4,6,5,7,0,2,8,10,12,14,1,3,9,11,13,15,12,14,4,6,0,2,13,15,5,7,8,10,1,3,9,11,8,10,12,14,0,2,9,11,13,15,1,3,4,6,5,7,8,10,9,11,4,6,0,2,12,14,5,7,1,3,13,15,4,6,5,7,8,10,12,14,9,11,13,15,0,2,1,3,132,134,133,135,136,138,140,142,137,139,141,143,128,130,129,131,90,91,106,107,92,93,116,117,72,73,76,77,108,109,110,111,208,209,70,71,66,67,202,203,226,0,0,0,0,0,0,0,0,0,0,0,0,0,0,0,0,0,0,0,0,0,0,0,0,0,0,0,0,0,0,0,0,0,0,0,0,0,0,0,0,0,0,0,0,0,0,0,0,0,0,0,0,0,0,0},
  {64,65,66,67,68,69,70,71,72,73,74,75,76,77,78,79,0,1,2,3,0,1,2,3,64,65,66,67,68,69,70,71,72,73,74,75,76,77,78,79,72,76,64,70,66,74,71,78,67,79,65,197,75,68,73,77,4,6,0,2,5,7,1,3,12,14,8,10,13,15,9,11,4,6,12,14,8,10,0,2,5,7,13,15,9,11,1,3,68,70,72,74,64,66,69,71,73,75,76,78,65,67,77,79,136,138,128,130,137,139,129,131,140,142,141,143,132,134,133,135,76,77,108,109,112,113,82,83,226,227,100,101,64,65,200,201,208,209,202,203,212,213,214,215,71,69,72,78,64,77,75,74,79,73,67,8,10,12,14,0,2,9,11,13,15,1,3,4,6,5,7,8,10,9,11,4,6,0,2,12,14,5,7,1,3,13,15,4,6,12,14,8,10,5,7,13,15,9,11,0,2,1,3,132,134,140,142,136,138,133,135,141,143,128,130,137,139,129,131,64,65,84,85,92,93,104,105,74,75,78,79,100,101,82,83,72,73,116,117,222,223,234,235,198,0,0,0,0,0,0,0,0,0,0,0,0,0,0,0,0,0,0,0,0,0,0,0,0,0,0,0,0,0,0,0,0,0,0,0,0,0,0,0,0,0,0,0,0,0,0,0,0,0,0,0,0},
  {0,1,2,3,4,5,6,7,8,9,10,11,12,13,14,15,0,1,2,3,64,65,66,67,68,69,70,71,72,73,74,75,76,77,78,79,64,66,76,78,65,67,77,79,68,70,69,71,72,74,73,75,4,6,0,2,5,7,1,3,12,14,8,10,13,15,9,11,4,6,8,10,0,2,5,7,9,11,12,14,1,3,13,15,0,2,8,10,4,6,12,14,1,3,9,11,5,7,13,15,136,138,128,130,137,139,129,131,140,142,141,143,132,134,133,135,64,66,68,70,72,74,65,67,69,71,76,78,73,75,77,79,68,70,69,71,76,78,72,74,64,66,77,79,73,75,65,67,64,71,78,77,69,72,75,70,74,79,76,73,68,67,66,65,8,10,0,2,9,11,12,14,1,3,4,6,13,15,5,7,4,6,5,7,8,10,12,14,9,11,13,15,0,2,1,3,132,134,140,142,136,138,133,135,141,143,128,130,137,139,129,131,106,107,104,105,92,93,88,89,72,73,90,91,100,101,78,79,84,85,80,81,66,67,90,91,96,97,242,243,202,203,198,199,0,0,0,0,0,0,0,0,0,0,0,0,0,0,0,0,0,0,0,0,0,0,0,0,0,0,0,0,0,0,0,0,0,0,0,0,0,0,0,0,0,0,0,0,0,0,0,0,0,0,0,0},
  {64,65,66,67,68,69,70,71,72,73,74,75,76,77,78,79,0,1,2,3,64,65,66,67,68,69,70,71,72,73,74,75,76,77,78,79,64,66,76,78,65,67,77,79,68,70,69,71,72,74,73,75,64,66,72,74,65,67,73,75,76,78,68,70,77,79,69,71,4,6,8,10,0,2,5,7,9,11,12,14,1,3,13,15,80,81,108,109,110,111,104,105,0,2,8,10,4,6,12,14,1,3,9,11,5,7,13,15,0,2,4,6,8,10,1,3,5,7,12,14,9,11,13,15,4,6,5,7,12,14,8,10,0,2,13,15,9,11,1,3,71,72,69,66,64,78,74,77,76,75,73,8,10,12,14,0,2,9,11,13,15,1,3,4,6,5,7,8,10,0,2,9,11,12,14,1,3,4,6,13,15,5,7,4,6,5,7,8,10,12,14,9,11,13,15,0,2,1,3,132,134,140,142,136,138,133,135,141,143,128,130,137,139,129,131,64,65,78,79,90,91,106,107,94,95,68,69,96,97,74,75,98,99,66,67,80,81,220,221,242,243,112,113,216,217,236,0,0,0,0,0,0,0,0,0,0,0,0,0,0,0,0,0,0,0,0,0,0,0,0,0,0,0,0,0,0,0,0,0,0,0,0,0,0,0,0,0,0,0,0,0,0,0,0,0,0},
  {64,65,66,67,68,69,70,71,72,73,74,75,76,77,78,79,0,1,2,3,0,1,2,3,4,5,6,7,8,9,10,11,12,13,14,15,0,1,2,3,76,69,70,72,74,66,71,75,67,77,68,73,79,78,64,65,4,6,0,2,5,7,1,3,12,14,8,10,13,15,9,11,0,2,8,10,4,6,12,14,1,3,9,11,5,7,13,15,108,109,114,115,100,101,74,75,116,117,118,119,82,83,112,113,98,99,102,103,68,69,110,111,104,105,0,2,4,6,8,10,1,3,5,7,12,14,9,11,13,15,4,6,5,7,12,14,8,10,0,2,13,15,9,11,1,3,64,66,65,67,68,70,72,74,76,78,69,71,73,75,77,79,132,134,128,130,133,135,129,131,136,138,140,142,137,139,141,143,8,10,9,11,4,6,0,2,12,14,5,7,1,3,13,15,4,6,5,7,8,10,12,14,9,11,13,15,0,2,1,3,4,6,12,14,8,10,5,7,13,15,0,2,9,11,1,3,105,72,73,86,87,102,103,90,91,118,119,68,69,78,79,114,115,66,67,110,111,94,95,216,217,204,205,0,0,0,0,0,0,0,0,0,0,0,0,0,0,0,0,0,0,0,0,0,0,0,0,0,0,0,0,0,0,0,0,0,0,0,0,0,0,0,0,0,0,0},
  {64,65,66,67,68,69,70,71,72,73,74,75,76,77,78,79,64,65,66,67,68,69,70,71,72,73,74,75,76,77,78,79,0,1,2,3,0,1,2,3,4,5,6,7,8,9,10,11,12,13,14,15,198,197,194,199,204,203,206,4,6,0,2,5,7,1,3,12,14,8,10,13,15,9,11,0,2,8,10,4,6,12,14,1,3,9,11,5,7,13,15,136,138,128,130,9,11,129,131,140,142,141,143,132,134,133,135,136,138,128,130,137,139,129,131,140,142,141,143,132,134,133,135,12,14,4,6,13,15,0,2,8,10,5,7,1,3,9,11,0,2,1,3,4,6,8,10,12,14,5,7,9,11,13,15,8,10,12,14,0,2,9,11,13,15,1,3,4,6,5,7,8,10,9,11,4,6,0,2,12,14,5,7,1,3,13,15,12,14,8,10,4,6,0,2,13,15,9,11,5,7,1,3,12,14,8,10,13,15,4,6,9,11,5,7,0,2,1,3,118,119,76,77,74,75,68,69,72,73,100,101,110,111,84,85,206,207,116,117,94,95,242,243,86,87,240,241,226,227,0,0,0,0,0,0,0,0,0,0,0,0,0,0,0,0,0,0,0,0,0,0,0,0,0,0,0,0,0,0,0,0,0,0,0,0,0,0,0,0,0,0,0,0,0,0,0},
  {64,65,66,67,68,69,70,71,72,73,74,75,76,77,78,79,0,1,2,3,4,5,6,7,8,9,10,11,12,13,14,15,0,1,2,3,64,66,76,78,65,67,77,79,68,70,69,71,72,74,73,75,4,6,0,2,5,7,1,3,12,14,8,10,13,15,9,11,4,6,12,14,8,10,0,2,5,7,13,15,9,11,1,3,97,108,109,114,115,100,101,74,75,116,117,118,119,82,83,112,113,98,99,102,103,68,69,110,111,104,105,114,115,102,103,98,99,100,101,90,91,70,71,76,77,68,69,110,193,200,201,208,209,202,203,212,213,214,215,222,223,244,245,234,235,224,225,8,10,12,14,0,2,9,11,13,15,1,3,4,6,5,7,8,10,0,2,9,11,12,14,1,3,4,6,13,15,5,7,4,6,12,14,8,10,5,7,13,15,9,11,0,2,1,3,4,6,5,7,8,10,140,142,9,11,13,15,0,2,1,3,90,91,106,107,92,93,116,117,72,73,76,77,108,109,110,111,80,81,70,71,66,67,74,75,98,99,102,103,214,215,0,0,0,0,0,0,0,0,0,0,0,0,0,0,0,0,0,0,0,0,0,0,0,0,0,0,0,0,0,0,0,0,0,0,0,0,0,0,0,0,0,0,0,0,0,0,0,0,0,0,0,0,0,0,0},
  {0,1,2,3,0,1,2,3,0,1,2,3,4,5,6,7,8,9,10,11,12,13,14,15,0,1,2,3,74,66,76,79,70,72,64,67,71,69,78,68,75,65,77,73,0,2,8,10,1,3,9,11,12,14,4,6,13,15,5,7,203,206,200,202,196,201,207,205,195,192,193,0,2,8,10,4,6,12,14,1,3,9,11,5,7,13,15,4,6,12,14,8,10,0,2,5,7,13,15,137,139,129,131,112,113,84,85,88,89,66,67,78,79,92,93,72,73,80,81,106,107,116,117,236,237,64,65,94,95,4,6,5,7,0,2,8,10,12,14,1,3,9,11,13,15,4,6,8,10,5,7,0,2,12,14,9,11,1,3,13,15,72,74,76,78,64,66,73,75,77,79,65,67,68,70,69,71,72,79,194,76,192,67,202,196,199,206,198,197,205,201,193,203,12,14,8,10,13,15,4,6,9,11,5,7,0,2,1,3,90,91,106,107,92,93,116,117,72,73,76,77,108,109,110,111,80,81,70,71,66,67,74,75,98,82,83,68,69,104,105,108,109,102,103,244,245,0,0,0,0,0,0,0,0,0,0,0,0,0,0,0,0,0,0,0,0,0,0,0,0,0,0,0,0,0,0,0,0,0,0,0,0,0,0,0,0,0,0,0,0,0,0,0,0,0,0},
  {0,1,2,3,0,1,2,3,4,5,6,7,8,9,10,11,12,13,14,15,0,1,2,3,74,66,76,79,70,72,64,67,71,69,78,68,75,65,77,73,0,2,8,10,1,3,9,11,12,14,4,6,13,15,5,7,4,6,0,2,5,7,1,3,12,14,8,10,13,15,9,11,202,196,201,207,205,195,192,193,90,91,70,71,72,73,66,67,64,65,84,85,92,93,80,81,86,87,94,95,84,85,88,89,114,115,110,111,98,99,66,67,94,95,70,71,76,77,106,107,96,97,64,65,215,222,223,244,245,234,235,224,225,216,217,198,199,206,4,6,8,10,5,7,0,2,12,14,9,11,1,3,13,15,132,134,128,130,133,135,129,131,136,138,140,142,137,139,141,143,72,79,194,76,192,67,202,196,199,206,198,197,205,201,193,203,12,14,8,10,13,15,4,6,9,11,5,7,0,2,1,3,4,6,12,14,136,138,5,7,13,15,128,130,137,139,129,131,80,81,92,93,108,109,106,107,70,71,66,67,90,91,88,89,82,83,224,225,232,233,230,231,0,0,0,0,0,0,0,0,0,0,0,0,0,0,0,0,0,0,0,0,0,0,0,0,0,0,0,0,0,0,0,0,0,0,0,0,0,0,0,0,0,0,0,0,0,0,0,0,0,0,0,0,0,0},
  {64,65,66,67,68,69,70,71,72,73,74,75,76,77,78,79,0,1,2,3,4,5,6,7,8,9,10,11,12,13,14,15,64,65,66,67,68,69,70,71,72,73,74,75,76,77,78,79,0,2,8,10,1,3,9,11,12,14,4,6,13,15,5,7,4,6,0,2,5,7,1,3,12,14,8,10,13,15,9,11,0,2,8,10,4,6,12,14,1,3,9,11,5,7,13,15,119,82,83,112,113,98,99,102,103,68,69,110,111,104,105,200,202,192,194,201,203,193,195,204,206,205,207,196,198,197,199,66,71,70,77,69,73,72,64,65,78,67,75,79,74,76,68,76,78,68,70,64,66,77,79,69,71,72,74,65,67,73,75,132,134,128,130,133,135,129,131,136,138,140,142,137,139,141,143,78,74,77,71,70,64,194,69,207,200,75,196,204,73,195,65,12,14,8,10,13,15,4,6,9,11,5,7,0,2,1,3,72,74,64,66,73,75,76,78,65,67,196,198,77,79,197,199,68,69,96,97,74,75,98,99,66,67,80,81,92,93,114,115,112,113,88,89,108,109,246,247,0,0,0,0,0,0,0,0,0,0,0,0,0,0,0,0,0,0,0,0,0,0,0,0,0,0,0,0,0,0,0,0,0,0,0,0,0,0,0,0,0,0,0,0,0,0,0,0,0},
  {0,1,2,3,4,5,6,7,8,9,10,11,12,13,14,15,64,65,66,67,68,69,70,71,72,73,74,75,76,77,78,79,0,1,2,3,72,76,64,70,66,74,71,78,67,79,65,197,75,68,73,77,12,14,8,10,13,15,9,11,0,2,4,6,1,3,5,7,108,109,86,87,96,97,82,83,74,75,110,111,76,77,88,89,118,119,68,69,100,101,104,105,102,103,90,91,136,138,128,130,137,139,129,131,140,142,141,143,132,134,133,135,76,77,68,69,110,111,82,83,74,75,96,97,118,119,104,105,4,6,5,7,0,2,8,10,12,14,1,3,9,11,13,15,4,6,8,10,5,7,0,2,12,14,9,11,1,3,13,15,8,10,0,2,9,11,12,14,1,3,4,6,13,15,5,7,12,14,8,10,4,6,0,2,13,15,9,11,5,7,1,3,12,14,8,10,13,15,132,134,9,11,5,7,0,2,1,3,136,138,9,11,132,134,0,2,140,142,133,135,129,131,141,143,79,74,75,114,115,94,95,118,119,72,73,64,208,209,96,97,76,77,218,219,236,237,0,0,0,0,0,0,0,0,0,0,0,0,0,0,0,0,0,0,0,0,0,0,0,0,0,0,0,0,0,0,0,0,0,0,0,0,0,0,0,0,0,0,0,0,0,0,0,0,0,0},
  {64,65,66,67,68,69,70,71,72,73,74,75,76,77,78,79,0,1,2,3,0,1,2,3,66,74,68,64,66,74,79,65,68,75,71,72,76,64,70,66,74,71,78,67,79,65,69,75,68,73,77,4,6,0,2,5,7,1,3,12,14,8,10,13,15,9,11,70,71,64,65,98,99,92,93,78,79,112,113,94,95,72,73,80,81,84,85,114,115,116,117,106,107,66,67,108,136,138,128,130,137,139,129,131,140,142,141,143,132,134,133,135,12,14,4,6,13,15,0,2,8,10,5,7,1,3,9,11,4,6,5,7,12,14,8,10,0,2,13,15,9,11,1,3,76,78,4,6,0,2,13,15,5,7,8,10,1,3,9,11,8,10,0,2,9,11,12,14,1,3,4,6,13,15,5,7,12,14,8,10,4,6,0,2,13,15,9,11,5,7,1,3,12,14,8,10,13,15,4,6,9,11,5,7,0,2,1,3,92,93,108,109,98,99,80,81,100,101,70,71,116,117,96,97,74,75,64,65,112,113,82,83,234,235,84,85,104,112,113,228,229,192,193,216,217,246,247,0,0,0,0,0,0,0,0,0,0,0,0,0,0,0,0,0,0,0,0,0,0,0,0,0,0,0,0,0,0,0,0,0,0,0,0,0,0,0,0,0,0,0,0,0,0,0,0,0},
  {0,1,2,3,4,5,6,7,8,9,10,11,12,13,14,15,0,1,2,3,0,1,2,3,4,5,6,7,8,9,10,11,12,13,14,15,74,66,76,79,70,72,64,67,71,69,78,68,75,65,77,73,198,194,204,206,200,202,196,192,4,6,0,2,5,7,1,3,12,14,8,10,13,15,9,11,4,6,8,10,0,2,5,7,9,11,12,14,1,3,13,15,136,138,128,130,137,139,129,131,140,142,141,143,132,134,133,135,88,89,76,77,96,97,86,87,72,73,116,117,110,111,12,14,4,6,13,15,0,2,8,10,5,7,1,3,9,11,219,220,221,230,231,196,197,4,6,8,10,5,7,0,2,12,14,9,11,1,3,13,15,8,10,0,2,9,11,12,14,1,3,4,6,13,15,5,7,12,14,8,10,4,6,0,2,13,15,9,11,5,7,1,3,12,14,8,10,13,15,4,6,9,11,5,7,0,2,1,3,12,14,8,10,132,134,0,2,13,15,9,11,133,135,1,3,64,65,84,85,92,93,104,105,74,75,206,207,100,101,82,83,200,201,116,117,222,223,0,0,0,0,0,0,0,0,0,0,0,0,0,0,0,0,0,0,0,0,0,0,0,0,0,0,0,0,0,0,0,0,0,0,0,0,0,0,0,0,0,0,0,0,0,0,0,0,0},
  {0,1,2,3,4,5,6,7,8,9,10,11,12,13,14,15,64,65,66,67,68,69,70,71,72,73,74,75,76,77,78,79,0,1,2,3,64,66,76,78,65,67,77,79,68,70,69,71,72,74,73,75,12,14,8,10,13,15,9,11,0,2,4,6,1,3,5,7,4,6,12,14,8,10,0,2,5,7,13,15,9,11,1,3,0,2,8,10,4,6,12,14,1,3,9,11,5,7,13,15,112,113,84,85,88,89,66,67,78,79,92,93,72,73,80,81,106,107,116,117,108,109,64,65,94,95,86,87,4,6,5,7,12,14,8,10,0,2,13,15,9,11,1,3,4,6,8,10,5,7,0,2,12,14,9,11,1,3,13,15,132,134,128,130,133,135,129,131,136,138,140,142,137,139,141,143,200,207,194,204,192,195,202,196,199,206,198,197,205,201,193,203,4,6,12,14,8,10,5,7,13,15,9,11,0,2,1,3,4,6,5,7,136,138,140,142,9,11,141,143,128,130,129,131,82,83,70,71,68,69,102,103,108,109,86,87,114,115,98,99,66,67,84,85,224,225,202,203,0,0,0,0,0,0,0,0,0,0,0,0,0,0,0,0,0,0,0,0,0,0,0,0,0,0,0,0,0,0,0,0,0,0,0,0,0,0,0,0,0,0,0,0,0,0,0,0},
  {64,65,66,67,68,69,70,71,72,73,74,75,76,77,78,79,0,1,2,3,0,1,2,3,4,5,6,7,8,9,10,11,12,13,14,15,64,66,76,78,65,67,77,79,68,70,69,71,72,74,73,75,4,6,0,2,5,7,1,3,12,14,8,10,13,15,9,11,200,202,196,201,207,205,195,192,193,96,97,114,115,76,77,70,71,86,87,90,91,74,75,66,67,68,69,80,81,108,109,110,111,104,105,78,79,90,91,80,81,102,103,104,105,108,109,112,113,72,73,116,117,82,83,100,101,74,204,205,236,237,240,241,210,211,226,227,228,229,192,12,14,4,6,0,2,13,15,5,7,8,10,1,3,9,11,64,71,70,74,8,10,0,2,9,11,12,14,1,3,4,6,13,15,5,7,12,14,8,10,4,6,0,2,13,15,9,11,5,7,1,3,12,14,8,10,13,15,4,6,9,11,5,7,0,2,1,3,80,81,96,97,92,93,108,109,70,71,82,83,100,101,78,79,74,75,114,115,94,95,118,119,72,73,64,112,113,228,229,192,193,216,217,246,247,0,0,0,0,0,0,0,0,0,0,0,0,0,0,0,0,0,0,0,0,0,0,0,0,0,0,0,0,0,0,0,0,0,0,0,0,0,0,0,0,0,0,0,0,0,0,0,0,0,0,0,0},
  {64,65,66,67,68,69,70,71,72,73,74,75,76,77,78,79,0,1,2,3,0,1,2,3,4,5,6,7,8,9,10,11,12,13,14,15,64,66,76,78,65,67,77,79,68,70,69,71,72,74,73,75,4,6,0,2,5,7,1,3,12,14,8,10,13,15,9,11,4,6,12,14,8,10,0,2,5,7,13,15,9,11,1,3,0,2,8,10,4,6,12,14,1,3,9,11,5,7,13,15,136,138,128,130,137,139,129,131,140,142,141,143,132,134,133,135,12,14,4,6,13,15,0,2,8,10,5,7,1,3,9,11,68,70,69,71,76,78,72,74,64,66,77,79,73,75,65,67,79,68,65,67,70,8,10,12,14,0,2,9,11,13,15,1,3,4,6,5,7,8,10,9,11,4,6,0,2,12,14,5,7,1,3,13,15,4,6,12,14,8,10,5,7,13,15,9,11,0,2,1,3,132,134,140,142,136,138,133,135,141,143,128,130,137,139,129,131,118,119,76,77,74,75,68,69,72,73,100,101,110,111,84,85,206,207,116,117,94,95,242,243,214,215,240,241,226,0,0,0,0,0,0,0,0,0,0,0,0,0,0,0,0,0,0,0,0,0,0,0,0,0,0,0,0,0,0,0,0,0,0,0,0,0,0,0,0,0,0,0,0,0,0,0,0,0,0},
  {0,1,2,3,4,5,6,7,8,9,10,11,12,13,14,15,0,1,2,3,4,5,6,7,8,9,10,11,12,13,14,15,70,64,76,66,74,72,79,71,78,67,69,65,75,77,68,73,0,2,8,10,1,3,9,11,12,14,4,6,13,15,5,7,4,6,0,2,5,7,1,3,12,14,8,10,13,15,9,11,0,2,8,10,4,6,12,14,1,3,9,11,5,7,13,15,136,138,128,130,137,139,129,131,140,142,141,143,132,134,133,135,112,113,84,85,88,89,66,67,78,79,76,78,68,70,77,79,64,66,72,74,69,71,65,67,73,75,12,14,4,6,0,2,13,15,5,7,8,10,1,3,9,11,8,10,12,14,0,2,9,11,13,15,1,3,4,6,5,7,8,10,9,11,4,6,0,2,12,14,5,7,1,3,13,15,4,6,12,14,8,10,5,7,13,15,9,11,0,2,1,3,4,6,12,14,8,10,5,7,13,15,9,11,128,130,1,3,89,108,109,118,119,82,83,70,71,100,101,102,103,84,85,116,117,72,73,214,215,238,239,232,233,204,205,0,0,0,0,0,0,0,0,0,0,0,0,0,0,0,0,0,0,0,0,0,0,0,0,0,0,0,0,0,0,0,0,0,0,0,0,0,0,0,0,0,0,0,0,0,0,0,0,0,0,0},
  {64,65,66,67,68,69,70,71,72,73,74,75,76,77,78,79,0,1,2,3,4,5,6,7,8,9,10,11,12,13,14,15,0,1,2,3,4,5,6,7,8,9,10,11,12,13,14,15,198,197,194,199,204,203,206,200,4,6,0,2,5,7,1,3,12,14,8,10,13,15,9,11,0,2,8,10,4,6,12,14,1,3,9,11,5,7,13,15,70,71,86,87,90,91,74,75,66,67,68,69,80,81,108,109,110,111,104,105,0,2,4,6,8,10,1,3,5,7,12,14,9,11,13,15,4,6,5,7,12,14,8,10,0,2,13,15,9,11,1,3,0,2,1,3,4,6,8,10,12,14,5,7,9,11,13,15,8,10,12,14,0,2,9,11,13,15,1,3,4,6,5,7,8,10,0,2,9,11,12,14,1,3,4,6,13,15,5,7,4,6,5,7,8,10,12,14,9,11,13,15,0,2,1,3,4,6,12,14,8,10,5,7,13,15,0,2,9,11,1,3,64,65,78,79,90,91,106,107,94,95,68,69,96,97,74,75,98,99,66,67,208,209,92,93,242,243,240,241,216,0,0,0,0,0,0,0,0,0,0,0,0,0,0,0,0,0,0,0,0,0,0,0,0,0,0,0,0,0,0,0,0,0,0,0,0,0,0,0,0,0,0,0,0,0,0,0},
  {0,1,2,3,4,5,6,7,8,9,10,11,12,13,14,15,64,65,66,67,68,69,70,71,72,73,74,75,76,77,78,79,0,1,2,3,4,5,6,7,8,9,10,11,12,13,14,15,0,2,8,10,1,3,9,11,12,14,4,6,13,15,5,7,197,199,203,201,207,205,195,193,4,6,12,14,8,10,0,2,5,7,13,15,9,11,1,3,88,89,94,95,116,117,118,119,106,107,78,79,82,83,112,113,84,85,102,136,138,128,130,137,139,129,131,140,142,141,143,132,134,133,135,66,71,70,77,69,73,72,64,65,78,67,75,79,74,76,68,12,14,4,6,0,2,13,15,5,7,8,10,1,3,9,11,8,10,12,14,0,2,9,11,13,15,1,3,4,6,5,7,8,10,9,11,4,6,0,2,12,14,5,7,1,3,13,15,4,6,12,14,8,10,5,7,13,15,9,11,0,2,1,3,4,6,12,14,136,138,5,7,13,15,137,139,128,130,129,131,90,91,106,107,92,93,116,117,72,73,76,77,108,109,110,111,80,81,198,199,66,67,202,203,226,0,0,0,0,0,0,0,0,0,0,0,0,0,0,0,0,0,0,0,0,0,0,0,0,0,0,0,0,0,0,0,0,0,0,0,0,0,0,0,0,0,0,0,0,0,0,0,0,0,0,0,0},
  {64,65,66,67,68,69,70,71,72,73,74,75,76,77,78,79,0,1,2,3,4,5,6,7,8,9,10,11,12,13,14,15,72,78,70,71,64,66,76,78,65,67,77,79,68,70,69,71,72,74,73,75,12,14,8,10,13,15,9,11,0,2,4,6,1,3,5,7,109,86,87,96,97,82,83,74,75,110,111,76,77,88,89,118,119,68,69,100,101,104,105,102,103,90,91,64,65,70,71,80,81,112,113,90,91,102,103,118,119,104,105,114,115,106,107,94,95,68,69,12,14,4,6,13,15,0,2,8,10,5,7,1,3,9,11,0,2,1,3,4,6,8,10,12,14,5,7,9,11,13,15,76,70,68,66,65,8,10,12,14,0,2,9,11,13,15,1,3,4,6,5,7,8,10,9,11,4,6,0,2,12,14,5,7,1,3,13,15,4,6,12,14,8,10,5,7,13,15,9,11,0,2,1,3,132,134,140,142,136,138,133,135,141,143,128,130,137,139,129,131,109,118,119,82,83,70,71,100,101,102,103,84,85,116,117,72,73,86,87,110,111,232,233,204,205,0,0,0,0,0,0,0,0,0,0,0,0,0,0,0,0,0,0,0,0,0,0,0,0,0,0,0,0,0,0,0,0,0,0,0,0,0,0,0,0,0,0,0,0,0,0,0,0,0,0,0},
  {64,65,66,67,68,69,70,71,72,73,74,75,76,77,78,79,0,1,2,3,0,1,2,3,4,5,6,7,8,9,10,11,12,13,14,15,64,66,76,78,65,67,77,79,68,70,69,71,72,74,73,75,64,66,72,74,65,67,73,75,76,78,68,70,77,79,69,71,70,71,64,65,98,99,92,93,78,79,112,113,94,95,72,73,80,81,84,85,114,115,116,117,106,107,66,67,108,109,86,87,64,65,70,71,80,81,112,113,90,91,102,103,118,119,104,105,114,115,106,107,94,95,4,6,5,7,12,14,8,10,0,2,13,15,9,11,1,3,0,2,1,3,4,6,8,10,12,14,5,7,9,11,13,15,8,10,12,14,0,2,9,11,13,15,1,3,4,6,5,7,8,10,9,11,4,6,0,2,12,14,5,7,1,3,13,15,4,6,5,7,8,10,12,14,9,11,13,15,0,2,1,3,4,6,12,14,8,10,5,7,13,15,0,2,9,11,1,3,85,104,105,72,73,86,87,102,103,90,91,118,119,68,69,206,207,114,115,66,67,110,111,94,95,216,217,204,205,0,0,0,0,0,0,0,0,0,0,0,0,0,0,0,0,0,0,0,0,0,0,0,0,0,0,0,0,0,0,0,0,0,0,0,0,0,0,0,0,0,0,0,0,0,0,0,0,0},
  {0,1,2,3,4,5,6,7,8,9,10,11,12,13,14,15,0,1,2,3,4,5,6,7,8,9,10,11,12,13,14,15,0,1,2,3,4,5,6,7,8,9,10,11,12,13,14,15,0,2,8,10,1,3,9,11,12,14,4,6,13,15,5,7,4,6,12,14,8,10,0,2,5,7,13,15,9,11,1,3,4,6,0,2,5,7,1,3,12,14,8,10,13,15,9,11,0,2,8,10,4,6,12,14,1,3,137,139,5,7,141,143,0,2,4,6,8,10,1,3,5,7,12,14,9,11,13,15,4,6,5,7,12,14,8,10,0,2,13,15,9,11,1,3,0,2,1,3,4,6,8,10,12,14,5,7,9,11,13,15,8,10,12,14,0,2,9,11,13,15,1,3,4,6,5,7,8,10,9,11,4,6,0,2,12,14,5,7,1,3,13,15,4,6,12,14,8,10,5,7,13,15,9,11,0,2,1,3,4,6,140,142,136,138,5,7,141,143,128,130,137,139,129,131,108,109,118,119,82,83,70,71,100,101,102,103,84,85,116,117,72,73,86,87,110,111,232,233,204,205,0,0,0,0,0,0,0,0,0,0,0,0,0,0,0,0,0,0,0,0,0,0,0,0,0,0,0,0,0,0,0,0,0,0,0,0,0,0,0,0,0,0,0,0,0,0},
  {0,1,2,3,4,5,6,7,8,9,10,11,12,13,14,15,0,1,2,3,4,5,6,7,8,9,10,11,12,13,14,15,74,66,76,79,70,72,64,67,71,69,78,68,75,65,77,73,0,2,8,10,1,3,9,11,12,14,4,6,13,15,5,7,0,2,8,10,4,6,12,14,1,3,9,11,5,7,13,15,4,6,8,10,0,2,5,7,9,11,12,14,1,3,13,15,136,138,128,130,137,139,129,131,140,142,141,143,132,134,133,135,86,87,114,115,102,103,98,99,100,101,90,91,70,71,204,205,68,206,207,246,247,194,195,238,239,242,243,232,233,218,76,78,68,70,64,66,77,79,69,71,72,74,65,67,73,75,8,10,0,2,9,11,12,14,1,3,4,6,13,15,5,7,12,14,8,10,4,6,0,2,13,15,9,11,5,7,1,3,12,14,8,10,13,15,4,6,9,11,5,7,0,2,1,3,110,111,82,83,70,71,68,69,102,103,108,109,86,87,114,115,98,99,66,67,84,85,96,97,74,75,103,208,209,96,97,76,77,218,219,236,237,0,0,0,0,0,0,0,0,0,0,0,0,0,0,0,0,0,0,0,0,0,0,0,0,0,0,0,0,0,0,0,0,0,0,0,0,0,0,0,0,0,0,0,0,0,0,0,0,0,0,0,0,0},
  {0,1,2,3,4,5,6,7,8,9,10,11,12,13,14,15,0,1,2,3,0,1,2,3,4,5,6,7,8,9,10,11,12,13,14,15,64,66,76,78,65,67,77,79,68,70,69,71,72,74,73,75,12,14,8,10,13,15,9,11,0,2,4,6,1,3,5,7,4,6,0,2,5,7,1,3,12,14,8,10,13,15,9,11,4,6,8,10,0,2,5,7,9,11,12,14,1,3,13,15,136,138,128,130,137,139,129,131,140,142,141,143,132,134,133,135,108,109,204,205,88,89,114,115,96,97,102,103,116,117,246,247,0,2,1,3,4,6,8,10,12,14,5,7,9,11,13,15,8,10,12,14,0,2,9,11,13,15,1,3,4,6,5,7,8,10,9,11,4,6,0,2,12,14,5,7,1,3,13,15,12,14,8,10,4,6,0,2,13,15,9,11,5,7,1,3,132,134,140,142,136,138,133,135,141,143,128,130,137,139,129,131,99,102,103,86,87,104,105,78,79,118,119,114,115,88,89,112,113,100,101,64,65,84,85,94,95,224,225,210,211,196,197,0,0,0,0,0,0,0,0,0,0,0,0,0,0,0,0,0,0,0,0,0,0,0,0,0,0,0,0,0,0,0,0,0,0,0,0,0,0,0,0,0,0,0,0,0,0,0,0,0,0,0,0,0},
  {64,65,66,67,68,69,70,71,72,73,74,75,76,77,78,79,0,1,2,3,0,1,2,3,4,5,6,7,8,9,10,11,12,13,14,15,64,66,76,78,65,67,77,79,68,70,69,71,72,74,73,75,64,66,72,74,65,67,73,75,76,78,68,70,77,79,69,71,4,6,12,14,8,10,0,2,5,7,13,15,9,11,1,3,88,89,94,95,116,117,118,119,106,107,78,79,82,83,112,113,84,85,102,103,98,99,136,138,128,130,137,139,129,131,140,142,141,143,132,134,133,135,12,14,4,6,13,15,0,2,8,10,5,7,1,3,9,11,0,2,1,3,4,6,8,10,12,14,5,7,9,11,13,15,8,10,12,14,0,2,9,11,13,15,1,3,4,6,5,7,8,10,9,11,4,6,0,2,12,14,5,7,1,3,13,15,4,6,5,7,8,10,12,14,9,11,13,15,0,2,1,3,4,6,12,14,8,10,5,7,13,15,0,2,9,11,1,3,69,102,103,108,109,86,87,114,115,98,99,66,67,84,85,96,97,74,75,68,69,104,105,108,109,102,103,244,245,0,0,0,0,0,0,0,0,0,0,0,0,0,0,0,0,0,0,0,0,0,0,0,0,0,0,0,0,0,0,0,0,0,0,0,0,0,0,0,0,0,0,0,0,0,0,0,0,0},
  {64,65,66,67,68,69,70,71,72,73,74,75,76,77,78,79,0,1,2,3,0,1,2,3,4,5,6,7,8,9,10,11,12,13,14,15,64,66,76,78,65,67,77,79,68,70,69,71,72,74,73,75,12,14,8,10,13,15,9,11,0,2,4,6,1,3,5,7,4,6,12,14,8,10,0,2,5,7,13,15,9,11,1,3,0,2,8,10,4,6,12,14,1,3,9,11,5,7,13,15,136,138,128,130,137,139,129,131,140,142,141,143,132,134,133,135,94,95,108,109,76,77,88,89,114,115,96,97,102,103,116,117,118,119,0,2,1,3,4,6,8,10,12,14,5,7,9,11,13,15,8,10,12,14,0,2,9,11,13,15,1,3,4,6,5,7,8,10,9,11,4,6,0,2,12,14,5,7,1,3,13,15,4,6,5,7,8,10,12,14,9,11,13,15,0,2,1,3,4,6,12,14,8,10,5,7,13,15,0,2,9,11,1,3,118,119,76,77,74,75,68,69,72,73,100,101,110,111,84,85,78,79,116,117,94,95,242,243,214,215,240,241,226,227,0,0,0,0,0,0,0,0,0,0,0,0,0,0,0,0,0,0,0,0,0,0,0,0,0,0,0,0,0,0,0,0,0,0,0,0,0,0,0,0,0,0,0,0,0,0,0,0,0,0,0,0},
  {64,65,66,67,68,69,70,71,72,73,74,75,76,77,78,79,64,65,66,67,68,69,70,71,72,73,74,75,76,77,78,79,0,1,2,3,4,5,6,7,8,9,10,11,12,13,14,15,0,2,8,10,1,3,9,11,12,14,4,6,13,15,5,7,12,14,8,10,13,15,9,11,0,2,4,6,1,3,5,7,4,6,12,14,8,10,0,2,5,7,13,15,9,11,1,3,68,70,76,78,72,74,64,66,69,71,77,79,73,75,65,67,72,73,80,81,106,107,116,117,108,109,64,65,94,95,86,87,114,115,102,103,226,234,235,224,225,216,217,198,199,206,207,246,247,194,195,64,71,78,77,69,72,75,70,74,79,76,73,68,67,66,65,196,198,192,194,197,199,193,195,200,202,204,206,201,203,205,207,12,14,8,10,4,6,0,2,13,15,9,11,5,7,1,3,12,14,8,10,13,15,132,134,9,11,133,135,128,130,1,3,196,198,204,206,200,202,69,71,205,207,201,203,192,194,193,195,81,66,67,90,91,96,97,114,115,74,75,198,199,238,239,210,211,0,0,0,0,0,0,0,0,0,0,0,0,0,0,0,0,0,0,0,0,0,0,0,0,0,0,0,0,0,0,0,0,0,0,0,0,0,0,0,0,0,0,0,0,0,0,0,0,0,0,0,0},
  {64,65,66,67,68,69,70,71,72,73,74,75,76,77,78,79,0,1,2,3,0,1,2,3,4,5,6,7,8,9,10,11,12,13,14,15,64,66,76,78,65,67,77,79,68,70,69,71,72,74,73,75,4,6,0,2,5,7,1,3,12,14,8,10,13,15,9,11,76,78,72,74,77,79,73,75,64,66,68,70,65,67,69,71,4,6,12,14,8,10,0,2,5,7,13,15,9,11,1,3,8,10,128,130,9,11,1,3,140,142,13,15,132,134,133,135,107,94,95,108,109,76,77,88,89,114,115,96,97,102,103,116,117,118,119,71,72,69,66,64,78,74,77,76,75,73,79,68,65,67,70,8,10,12,14,0,2,9,11,13,15,1,3,4,6,5,7,8,10,0,2,9,11,12,14,1,3,4,6,13,15,5,7,4,6,12,14,8,10,5,7,13,15,9,11,0,2,1,3,4,6,12,14,8,10,5,7,13,15,0,2,9,11,1,3,64,65,78,79,90,91,106,107,94,95,68,69,96,97,74,102,103,208,209,96,97,76,77,218,219,236,237,0,0,0,0,0,0,0,0,0,0,0,0,0,0,0,0,0,0,0,0,0,0,0,0,0,0,0,0,0,0,0,0,0,0,0,0,0,0,0,0,0,0,0,0,0,0,0,0,0,0,0,0,0,0},
  {0,1,2,3,4,5,6,7,8,9,10,11,12,13,14,15,0,1,2,3,79,75,77,73,0,1,2,3,4,5,6,7,8,9,10,11,12,13,14,15,0,2,8,10,1,3,9,11,12,14,4,6,13,15,5,7,4,6,8,10,0,2,5,7,9,11,12,14,1,3,13,15,4,6,8,10,0,2,5,7,9,11,12,14,1,3,13,15,4,6,12,14,8,10,0,2,5,7,13,15,9,11,1,3,72,73,80,81,98,99,74,75,110,111,112,113,86,87,92,93,78,79,64,65,66,67,84,85,68,69,90,91,104,218,219,220,221,230,231,196,197,71,69,72,78,64,77,75,74,79,73,67,76,70,68,66,65,8,10,0,2,9,11,12,14,1,3,4,6,13,15,5,7,12,14,8,10,4,6,0,2,13,15,9,11,5,7,1,3,12,14,8,10,13,15,4,6,9,11,5,7,0,2,1,3,196,198,204,206,200,202,197,199,205,207,192,194,201,203,193,195,78,79,106,235,86,87,94,95,76,77,220,221,200,201,98,99,212,213,0,0,0,0,0,0,0,0,0,0,0,0,0,0,0,0,0,0,0,0,0,0,0,0,0,0,0,0,0,0,0,0,0,0,0,0,0,0,0,0,0,0,0,0,0,0,0,0,0,0,0,0,0,0,0,0,0},
  {64,65,66,67,68,69,70,71,72,73,74,75,76,77,78,79,0,1,2,3,72,78,70,71,0,2,12,14,1,3,13,15,4,6,5,7,8,10,9,11,12,14,8,10,13,15,9,11,0,2,4,6,1,3,5,7,4,6,8,10,0,2,5,7,9,11,12,14,1,3,13,15,8,10,0,2,9,11,1,3,12,14,13,15,132,134,5,7,95,70,71,76,77,106,107,96,97,64,65,78,79,90,91,80,81,102,69,110,111,82,83,74,75,96,97,118,119,104,105,94,223,244,245,234,235,224,225,216,217,198,199,71,69,72,78,64,77,75,74,79,73,67,76,70,68,66,65,8,10,0,2,9,11,12,14,1,3,4,6,13,15,5,7,12,14,8,10,4,6,0,2,13,15,9,11,5,7,1,3,4,6,12,14,8,10,5,7,13,15,9,11,0,2,1,3,68,70,69,71,200,202,204,206,201,203,205,207,192,194,193,195,64,65,78,79,90,91,106,107,94,95,112,113,228,229,64,193,216,217,246,247,0,0,0,0,0,0,0,0,0,0,0,0,0,0,0,0,0,0,0,0,0,0,0,0,0,0,0,0,0,0,0,0,0,0,0,0,0,0,0,0,0,0,0,0,0,0,0,0,0,0,0,0,0,0,0,0,0,0,0,0,0,0,0,0,0},
  {64,65,66,67,68,69,70,71,72,73,74,75,76,77,78,79,0,1,2,3,0,1,2,3,4,5,6,7,8,9,10,11,12,13,14,15,64,66,76,78,65,67,77,79,68,70,69,71,72,74,73,75,12,14,8,10,13,15,9,11,0,2,4,6,1,3,5,7,70,71,64,65,98,99,92,93,78,79,112,113,94,95,72,73,80,81,84,85,114,115,116,117,106,107,66,67,111,98,99,66,67,94,95,70,71,76,77,106,107,96,97,64,65,78,79,90,91,80,81,102,103,104,105,236,237,240,241,72,105,70,71,210,211,100,101,106,71,72,69,66,64,78,74,77,76,75,73,79,68,65,67,70,64,71,70,74,77,69,78,72,76,78,74,77,71,70,64,66,69,207,200,75,68,204,73,195,65,4,6,5,7,8,10,12,14,9,11,13,15,0,2,1,3,12,14,8,10,13,15,132,134,9,11,133,135,0,2,1,3,118,119,76,77,74,75,68,69,72,73,100,101,110,111,84,85,206,207,116,117,94,95,114,115,214,215,112,113,98,99,192,193,0,0,0,0,0,0,0,0,0,0,0,0,0,0,0,0,0,0,0,0,0,0,0,0,0,0,0,0,0,0,0,0,0,0,0,0,0,0,0,0,0,0,0,0,0,0,0,0,0,0,0,0,0,0,0},
  {64,65,66,67,68,69,70,71,72,73,74,75,76,77,78,79,0,1,2,3,64,65,66,67,68,69,70,71,72,73,74,75,76,77,78,79,64,66,76,78,65,67,77,79,68,70,69,71,72,74,73,75,4,6,0,2,5,7,1,3,12,14,8,10,13,15,9,11,4,6,12,14,8,10,0,2,5,7,13,15,9,11,1,3,4,6,12,14,8,10,0,2,5,7,13,15,137,139,129,131,92,93,72,73,80,81,106,107,116,117,108,109,64,65,94,95,86,87,114,115,102,103,98,99,100,101,90,91,70,71,207,246,247,194,195,238,239,242,243,232,233,218,4,6,8,10,5,7,0,2,12,14,9,11,1,3,13,15,64,71,78,74,77,70,73,69,66,72,76,79,68,65,67,75,12,14,8,10,4,6,0,2,13,15,9,11,5,7,1,3,12,14,8,10,13,15,4,6,9,11,5,7,0,2,1,3,204,206,200,202,205,207,196,198,201,203,197,199,192,194,193,195,71,66,67,112,113,98,99,86,87,110,111,114,115,88,89,118,119,68,69,230,231,0,0,0,0,0,0,0,0,0,0,0,0,0,0,0,0,0,0,0,0,0,0,0,0,0,0,0,0,0,0,0,0,0,0,0,0,0,0,0,0,0,0,0,0,0,0,0,0,0,0,0,0,0},
  {64,65,66,67,68,69,70,71,72,73,74,75,76,77,78,79,0,1,2,3,0,1,2,3,4,5,6,7,8,9,10,11,12,13,14,15,64,66,76,78,65,67,77,79,68,70,69,71,72,74,73,75,12,14,8,10,13,15,9,11,0,2,4,6,1,3,5,7,4,6,0,2,5,7,1,3,12,14,8,10,13,15,9,11,4,6,8,10,0,2,5,7,9,11,12,14,1,3,13,15,82,83,98,99,108,109,92,93,78,79,84,85,100,101,66,67,74,75,112,113,84,85,88,89,66,67,78,79,92,93,4,6,5,7,0,2,8,10,12,14,1,3,9,11,13,15,4,6,8,10,5,7,0,2,12,14,9,11,1,3,13,15,8,10,0,2,9,11,12,14,1,3,4,6,13,15,5,7,12,14,8,10,4,6,0,2,13,15,9,11,5,7,1,3,12,14,8,10,13,15,132,134,9,11,5,7,0,2,1,3,196,198,69,71,200,202,204,206,201,203,205,207,192,194,193,195,78,79,106,107,86,87,94,95,76,77,220,221,200,201,98,99,212,213,208,0,0,0,0,0,0,0,0,0,0,0,0,0,0,0,0,0,0,0,0,0,0,0,0,0,0,0,0,0,0,0,0,0,0,0,0,0,0,0,0,0,0,0,0,0,0,0,0,0,0,0},
  {0,1,2,3,4,5,6,7,8,9,10,11,12,13,14,15,0,1,2,3,0,1,2,3,4,5,6,7,8,9,10,11,12,13,14,15,64,66,76,78,65,67,77,79,68,70,69,71,72,74,73,75,4,6,0,2,5,7,1,3,12,14,8,10,13,15,9,11,4,6,8,10,0,2,5,7,9,11,12,14,1,3,13,15,0,2,8,10,4,6,12,14,1,3,137,139,5,7,13,15,80,81,102,103,104,105,108,109,112,113,72,73,116,117,82,83,100,101,74,75,86,87,92,93,118,119,68,69,4,6,5,7,0,2,8,10,12,14,1,3,9,11,13,15,4,6,8,10,5,7,0,2,12,14,9,11,1,3,13,15,8,10,0,2,9,11,12,14,1,3,4,6,13,15,5,7,200,207,194,204,192,195,202,196,199,206,198,197,205,201,193,203,12,14,8,10,13,15,4,6,9,11,5,7,0,2,1,3,132,134,12,14,136,138,133,135,13,15,137,139,128,130,129,131,106,107,70,71,66,67,112,113,98,99,86,87,110,111,242,243,88,89,118,119,196,197,0,0,0,0,0,0,0,0,0,0,0,0,0,0,0,0,0,0,0,0,0,0,0,0,0,0,0,0,0,0,0,0,0,0,0,0,0,0,0,0,0,0,0,0,0,0,0,0,0,0},
  {64,65,66,67,68,69,70,71,72,73,74,75,76,77,78,79,0,1,2,3,4,5,6,7,8,9,10,11,12,13,14,15,0,1,2,3,72,76,64,70,66,74,71,78,67,79,65,69,75,68,73,77,4,6,0,2,5,7,1,3,12,14,8,10,13,15,9,11,4,6,8,10,0,2,5,7,9,11,12,14,1,3,13,15,0,2,8,10,4,6,12,14,1,3,137,139,5,7,141,143,192,194,200,202,68,70,204,206,193,195,201,203,197,199,205,207,111,82,83,74,75,96,97,118,119,104,105,4,6,5,7,0,2,8,10,12,14,1,3,9,11,13,15,76,78,68,70,0,2,13,15,5,7,8,10,1,3,9,11,8,10,0,2,9,11,12,14,1,3,4,6,13,15,5,7,12,14,8,10,4,6,0,2,13,15,9,11,5,7,1,3,4,6,12,14,8,10,5,7,13,15,9,11,0,2,1,3,12,14,136,138,132,134,0,2,141,143,137,139,133,135,129,131,64,65,84,85,92,93,104,105,74,75,206,207,100,101,82,83,200,201,116,117,222,223,234,0,0,0,0,0,0,0,0,0,0,0,0,0,0,0,0,0,0,0,0,0,0,0,0,0,0,0,0,0,0,0,0,0,0,0,0,0,0,0,0,0,0,0,0,0,0,0,0,0,0},
  {64,65,66,67,68,69,70,71,72,73,74,75,76,77,78,79,0,1,2,3,4,5,6,7,8,9,10,11,12,13,14,15,69,76,67,65,64,66,76,78,65,67,77,79,68,70,69,71,72,74,73,75,12,14,8,10,13,15,9,11,0,2,4,6,1,3,5,7,4,6,8,10,0,2,5,7,9,11,12,14,1,3,13,15,90,91,70,71,72,73,66,67,64,65,84,85,92,93,80,81,86,87,94,95,76,77,88,89,106,107,78,79,96,0,2,4,6,8,10,1,3,5,7,12,14,9,11,13,15,4,6,5,7,0,2,8,10,12,14,1,3,9,11,13,15,4,6,8,10,5,7,0,2,12,14,9,11,1,3,13,15,132,134,128,130,133,135,129,131,136,138,140,142,137,139,141,143,8,10,9,11,4,6,0,2,12,14,5,7,1,3,13,15,4,6,12,14,8,10,5,7,13,15,9,11,0,2,1,3,132,134,140,142,136,138,133,135,141,143,128,130,137,139,129,131,104,105,78,79,118,119,114,115,88,89,112,113,100,101,64,65,84,85,94,95,96,97,210,211,196,197,0,0,0,0,0,0,0,0,0,0,0,0,0,0,0,0,0,0,0,0,0,0,0,0,0,0,0,0,0,0,0,0,0,0,0,0,0,0,0,0,0,0,0,0,0},
  {64,65,66,67,68,69,70,71,72,73,74,75,76,77,78,79,0,1,2,3,0,1,2,3,4,5,6,7,8,9,10,11,12,13,14,15,0,1,2,3,4,5,6,7,8,9,10,11,12,13,14,15,0,2,8,10,1,3,9,11,12,14,4,6,13,15,5,7,4,6,8,10,0,2,5,7,9,11,12,14,1,3,13,15,4,6,12,14,8,10,0,2,5,7,13,15,9,11,1,3,103,104,105,108,109,112,113,72,73,116,117,82,83,100,101,74,75,86,87,92,93,118,119,68,69,76,78,68,70,77,79,64,66,72,74,69,71,65,67,73,75,0,2,1,3,4,6,8,10,12,14,5,7,9,11,13,15,132,134,128,130,133,135,129,131,136,138,140,142,137,139,141,143,8,10,9,11,4,6,0,2,12,14,5,7,1,3,13,15,4,6,12,14,8,10,5,7,13,15,9,11,0,2,1,3,132,134,140,142,136,138,133,135,141,143,128,130,137,139,129,131,65,112,113,98,99,88,89,86,87,84,85,90,91,106,107,68,69,104,105,76,77,116,117,110,111,102,103,194,195,0,0,0,0,0,0,0,0,0,0,0,0,0,0,0,0,0,0,0,0,0,0,0,0,0,0,0,0,0,0,0,0,0,0,0,0,0,0,0,0,0,0,0,0,0,0},
  {64,65,66,67,68,69,70,71,72,73,74,75,76,77,78,79,0,1,2,3,4,5,6,7,8,9,10,11,12,13,14,15,64,67,72,77,69,73,78,76,76,69,70,72,74,66,71,75,67,77,68,73,79,206,64,65,4,6,8,10,0,2,5,7,9,11,12,14,1,3,13,15,4,6,12,14,8,10,0,2,5,7,13,15,9,11,1,3,0,2,8,10,4,6,12,14,1,3,9,11,5,7,13,15,0,2,4,6,8,10,1,3,5,7,12,14,9,11,13,15,4,6,5,7,12,14,8,10,0,2,13,15,9,11,1,3,0,2,1,3,4,6,8,10,12,14,5,7,9,11,13,15,8,10,12,14,0,2,9,11,13,15,1,3,4,6,5,7,8,10,0,2,9,11,12,14,1,3,4,6,13,15,5,7,12,14,8,10,4,6,0,2,13,15,9,11,5,7,1,3,4,6,12,14,8,10,5,7,13,15,9,11,0,2,1,3,116,117,64,65,118,119,80,81,94,95,76,77,112,113,110,111,82,83,70,71,68,112,113,228,229,64,65,88,217,246,247,0,0,0,0,0,0,0,0,0,0,0,0,0,0,0,0,0,0,0,0,0,0,0,0,0,0,0,0,0,0,0,0,0,0,0,0,0,0,0,0,0,0,0,0,0,0,0,0,0},
  {64,65,66,67,68,69,70,71,72,73,74,75,76,77,78,79,0,1,2,3,0,1,2,3,4,5,6,7,8,9,10,11,12,13,14,15,64,66,76,78,65,67,77,79,68,70,69,71,72,74,73,75,12,14,8,10,13,15,9,11,0,2,4,6,1,3,5,7,4,6,8,10,0,2,5,7,9,11,12,14,1,3,13,15,64,65,70,71,80,81,112,113,90,91,102,103,118,119,104,105,114,115,106,107,94,95,68,69,82,83,98,99,108,109,92,12,14,4,6,13,15,0,2,8,10,5,7,1,3,9,11,4,6,5,7,0,2,8,10,12,14,1,3,9,11,13,15,76,78,68,70,64,66,77,79,69,71,72,74,65,67,73,75,132,134,128,130,133,135,129,131,136,138,140,142,137,139,141,143,12,14,8,10,4,6,0,2,13,15,9,11,5,7,1,3,4,6,12,14,8,10,5,7,13,15,9,11,0,2,1,3,4,6,12,14,136,138,5,7,13,15,137,139,128,130,129,131,64,65,84,85,92,93,104,105,74,75,206,207,100,101,82,83,72,73,116,117,222,223,234,235,198,0,0,0,0,0,0,0,0,0,0,0,0,0,0,0,0,0,0,0,0,0,0,0,0,0,0,0,0,0,0,0,0,0,0,0,0,0,0,0,0,0,0,0,0},
  {0,1,2,3,4,5,6,7,8,9,10,11,12,13,14,15,64,65,66,67,68,69,70,71,72,73,74,75,76,77,78,79,0,1,2,3,4,5,6,7,8,9,10,11,12,13,14,15,0,2,8,10,1,3,9,11,12,14,4,6,13,15,5,7,4,6,8,10,0,2,5,7,9,11,12,14,1,3,13,15,103,98,99,72,73,92,93,64,65,100,101,96,97,114,115,76,77,70,71,86,87,90,91,74,75,66,67,68,69,0,2,4,6,8,10,1,3,5,7,12,14,9,11,13,15,12,14,4,6,13,15,0,2,8,10,5,7,1,3,9,11,0,2,1,3,4,6,8,10,12,14,5,7,9,11,13,15,132,134,128,130,133,135,129,131,136,138,140,142,137,139,141,143,79,67,75,65,8,10,0,2,9,11,12,14,1,3,4,6,13,15,5,7,4,6,12,14,8,10,5,7,13,15,9,11,0,2,1,3,8,10,9,11,4,6,0,2,140,142,133,135,1,3,141,143,64,65,80,81,92,93,108,109,106,107,70,71,66,67,90,91,88,89,82,83,224,225,232,233,230,231,0,0,0,0,0,0,0,0,0,0,0,0,0,0,0,0,0,0,0,0,0,0,0,0,0,0,0,0,0,0,0,0,0,0,0,0,0,0,0,0,0,0,0,0,0},
  {64,65,66,67,68,69,70,71,72,73,74,75,76,77,78,79,0,1,2,3,64,65,66,67,68,69,70,71,72,73,74,75,76,77,78,79,64,66,76,78,65,67,77,79,68,70,69,71,72,74,73,75,4,6,0,2,5,7,1,3,12,14,8,10,13,15,9,11,4,6,8,10,0,2,5,7,9,11,12,14,1,3,13,15,90,91,70,71,72,73,66,67,64,65,84,85,92,93,80,81,86,87,94,95,76,77,88,89,106,107,78,79,96,97,0,2,4,6,8,10,1,3,5,7,12,14,9,11,13,15,4,6,5,7,0,2,8,10,12,14,1,3,9,11,13,15,12,14,4,6,0,2,13,15,5,7,8,10,1,3,9,11,64,71,70,74,77,69,78,72,76,68,66,73,8,10,9,11,4,6,0,2,12,14,5,7,1,3,13,15,4,6,12,14,8,10,5,7,13,15,9,11,0,2,1,3,12,14,8,10,13,15,4,6,9,11,5,7,0,2,1,3,106,107,104,105,92,93,88,89,72,73,90,91,100,101,206,207,116,117,64,65,118,119,80,209,222,223,204,0,0,0,0,0,0,0,0,0,0,0,0,0,0,0,0,0,0,0,0,0,0,0,0,0,0,0,0,0,0,0,0,0,0,0,0,0,0,0,0,0,0,0,0,0,0,0},
  {0,1,2,3,4,5,6,7,8,9,10,11,12,13,14,15,0,1,2,3,64,65,66,67,68,69,70,71,72,73,74,75,76,77,78,79,64,66,76,78,65,67,77,79,68,70,69,71,72,74,73,75,64,66,72,74,65,67,73,75,76,78,68,70,77,79,69,71,4,6,8,10,0,2,5,7,9,11,12,14,1,3,13,15,68,70,64,66,69,71,65,67,76,78,72,74,77,79,73,75,136,138,128,130,137,139,129,131,140,142,141,143,132,134,133,135,64,66,68,70,72,74,65,67,69,71,76,78,73,75,77,79,4,6,5,7,0,2,8,10,12,14,1,3,9,11,13,15,4,6,8,10,5,7,0,2,12,14,9,11,1,3,13,15,64,71,78,74,77,70,73,69,66,72,76,79,68,65,67,75,12,14,8,10,4,6,0,2,13,15,9,11,5,7,1,3,12,14,8,10,13,15,132,134,9,11,133,135,0,2,1,3,204,206,200,202,205,207,196,198,201,203,197,199,192,194,193,195,107,70,71,66,67,112,113,98,99,86,87,110,111,242,243,88,89,118,119,196,197,0,0,0,0,0,0,0,0,0,0,0,0,0,0,0,0,0,0,0,0,0,0,0,0,0,0,0,0,0,0,0,0,0,0,0,0,0,0,0,0,0,0,0,0,0,0,0},
  {64,65,66,67,68,69,70,71,72,73,74,75,76,77,78,79,0,1,2,3,72,78,70,71,0,1,2,3,4,5,6,7,8,9,10,11,12,13,14,15,0,2,8,10,1,3,9,11,12,14,4,6,13,15,5,7,12,14,8,10,13,15,9,11,0,2,4,6,1,3,5,7,4,6,12,14,8,10,0,2,5,7,13,15,9,11,1,3,136,138,128,130,137,139,129,131,140,142,141,143,132,134,133,135,75,88,89,76,77,96,97,86,87,72,73,116,117,110,111,4,6,5,7,12,14,8,10,0,2,13,15,9,11,1,3,12,14,4,6,0,2,13,15,5,7,8,10,1,3,9,11,132,134,128,130,133,135,129,131,136,138,140,142,137,139,141,143,8,10,9,11,4,6,0,2,12,14,5,7,1,3,13,15,4,6,5,7,8,10,12,14,9,11,13,15,0,2,1,3,12,14,8,10,13,15,132,134,9,11,133,135,128,130,129,131,116,117,96,97,74,75,64,65,112,113,82,83,106,107,84,80,81,66,67,90,91,96,97,242,243,74,75,198,199,0,0,0,0,0,0,0,0,0,0,0,0,0,0,0,0,0,0,0,0,0,0,0,0,0,0,0,0,0,0,0,0,0,0,0,0,0,0,0,0,0,0,0,0,0,0,0,0,0,0,0,0},
  {0,1,2,3,4,5,6,7,8,9,10,11,12,13,14,15,0,1,2,3,0,1,2,3,4,5,6,7,8,9,10,11,12,13,14,15,0,1,2,3,76,69,70,72,74,66,71,75,67,77,68,73,79,78,64,65,12,14,8,10,13,15,9,11,0,2,4,6,1,3,5,7,4,6,8,10,0,2,5,7,9,11,12,14,1,3,13,15,128,130,136,138,4,6,140,142,129,131,137,139,133,135,141,143,0,2,4,6,8,10,1,3,5,7,12,14,9,11,13,15,95,108,109,76,77,88,89,114,115,96,97,102,103,244,245,246,247,219,220,221,230,231,196,197,4,6,8,10,5,7,0,2,12,14,9,11,1,3,13,15,64,71,70,74,77,69,78,72,76,68,66,73,79,67,75,65,12,14,8,10,4,6,0,2,13,15,9,11,5,7,1,3,12,14,8,10,13,15,4,6,9,11,5,7,0,2,1,3,76,78,72,74,77,79,68,70,73,75,69,71,64,66,65,67,82,83,70,71,100,101,102,103,84,85,116,117,72,73,86,87,110,111,232,233,204,205,0,0,0,0,0,0,0,0,0,0,0,0,0,0,0,0,0,0,0,0,0,0,0,0,0,0,0,0,0,0,0,0,0,0,0,0,0,0,0,0,0,0,0,0,0,0,0,0,0,0},
  {64,65,66,67,68,69,70,71,72,73,74,75,76,77,78,79,0,1,2,3,4,5,6,7,8,9,10,11,12,13,14,15,70,64,76,66,74,72,79,71,78,67,69,65,75,77,68,73,0,2,8,10,1,3,9,11,12,14,4,6,13,15,5,7,4,6,12,14,8,10,0,2,5,7,13,15,9,11,1,3,4,6,12,14,8,10,0,2,5,7,13,15,9,11,1,3,136,138,128,130,137,139,129,131,140,142,141,143,132,134,133,135,12,14,4,6,13,15,0,2,8,10,5,7,1,3,9,11,4,6,5,7,0,2,8,10,12,14,1,3,9,11,13,15,4,6,8,10,5,7,0,2,12,14,9,11,1,3,13,15,132,134,128,130,133,135,129,131,136,138,140,142,137,139,141,143,8,10,9,11,4,6,0,2,12,14,5,7,1,3,13,15,4,6,12,14,8,10,5,7,13,15,9,11,0,2,1,3,8,10,0,2,9,11,140,142,1,3,132,134,141,143,133,135,92,93,108,109,98,99,80,81,100,101,70,71,110,111,82,83,68,69,104,105,108,109,102,103,244,245,0,0,0,0,0,0,0,0,0,0,0,0,0,0,0,0,0,0,0,0,0,0,0,0,0,0,0,0,0,0,0,0,0,0,0,0,0,0,0,0,0,0,0,0,0,0},
  {0,1,2,3,4,5,6,7,8,9,10,11,12,13,14,15,0,1,2,3,0,1,2,3,4,5,6,7,8,9,10,11,12,13,14,15,64,66,76,78,65,67,77,79,68,70,69,71,72,74,73,75,12,14,8,10,13,15,9,11,0,2,4,6,1,3,5,7,4,6,0,2,5,7,1,3,12,14,8,10,13,15,9,11,90,91,70,71,72,73,66,67,64,65,84,85,92,93,80,81,86,87,94,95,76,77,88,89,106,107,78,79,96,97,108,109,72,73,80,81,98,99,74,75,110,111,240,241,86,87,92,93,206,207,192,193,0,2,1,3,4,6,8,10,12,14,5,7,9,11,13,15,8,10,12,14,0,2,9,11,13,15,1,3,4,6,5,7,8,10,9,11,4,6,0,2,12,14,5,7,1,3,13,15,4,6,5,7,8,10,12,14,9,11,13,15,0,2,1,3,132,134,5,7,136,138,140,142,9,11,141,143,128,130,129,131,104,105,72,73,86,87,102,103,90,91,118,119,68,69,206,207,114,115,66,67,110,111,222,223,216,217,204,205,0,0,0,0,0,0,0,0,0,0,0,0,0,0,0,0,0,0,0,0,0,0,0,0,0,0,0,0,0,0,0,0,0,0,0,0,0,0,0,0,0,0,0,0,0,0,0,0,0,0,0,0},
  {64,65,66,67,68,69,70,71,72,73,74,75,76,77,78,79,0,1,2,3,0,1,2,3,4,5,6,7,8,9,10,11,12,13,14,15,64,66,76,78,65,67,77,79,68,70,69,71,72,74,73,75,12,14,8,10,13,15,9,11,0,2,4,6,1,3,5,7,4,6,8,10,0,2,5,7,9,11,12,14,1,3,13,15,0,2,8,10,4,6,12,14,1,3,9,11,5,7,13,15,99,102,103,68,69,110,111,104,105,73,116,117,82,83,100,101,74,75,86,87,92,93,118,119,68,69,4,6,5,7,12,14,8,10,0,2,13,15,9,11,1,3,79,68,65,67,70,64,71,78,77,69,72,75,70,74,79,76,73,68,67,66,65,8,10,0,2,9,11,12,14,1,3,4,6,13,15,5,7,12,14,8,10,4,6,0,2,13,15,9,11,5,7,1,3,4,6,12,14,8,10,5,7,13,15,0,2,9,11,1,3,80,81,96,97,92,93,108,109,70,71,82,83,100,101,78,206,207,106,107,86,87,94,95,76,77,220,221,200,201,226,227,0,0,0,0,0,0,0,0,0,0,0,0,0,0,0,0,0,0,0,0,0,0,0,0,0,0,0,0,0,0,0,0,0,0,0,0,0,0,0,0,0,0,0,0,0,0,0,0,0,0,0,0,0,0},
};

struct alignas(64) Params {
  CUtensorMap a[6];
  CUtensorMap w[4];
  CUtensorMap ow;
  CUtensorMap xr;
  const bf16 *x0, *wqkv;
  bf16* out;
  uint32_t swap;
  uint32_t jobs[NPAIR][JMAX];
  uint8_t kseq[NPAIR][KMAX];
};

template <class T> __device__ __forceinline__ T* at(T* base, uint32_t bytes) {
  T* r;
  asm("{\n.reg .u32 lo, hi;\nmov.b64 {lo, hi}, %1;\nadd.cc.u32 lo, lo, %2;\naddc.u32 hi, hi, 0;\nmov.b64 %0, {lo, hi};\n}" : "=l"(r) : "l"(base), "r"(bytes));
  return r;
}
#define SCR(sm, member, bytes) reinterpret_cast<decltype(&scratch_base()->member[0])>(at((sm).scratch, offsetof(Scratch, member) + (bytes)))
#define counter(line, word) SCR(sm, cnt, (line) * 128 + (word) * 4)
#define TRS(st, slot) do {} while (0)
#define TRX(cond, job, bit, slot, reg) do {} while (0)
#define TR(job, slot) do {} while (0)
#define TRI(cond, job, slot) do {} while (0)
#define TRK(cond, job, slot) do {} while (0)
#define TRC(job, slot) do {} while (0)

__device__ __forceinline__ uint32_t smem_u32(const void* p) { return (uint32_t)__cvta_generic_to_shared(p); }
__device__ __forceinline__ void mbar_init(uint32_t bar, uint32_t cnt) { asm volatile("mbarrier.init.shared::cta.b64 [%0], %1;" ::"r"(bar), "r"(cnt) : "memory"); }
__device__ __forceinline__ void mbar_expect_tx(uint32_t bar, uint32_t bytes) { asm volatile("mbarrier.arrive.expect_tx.shared::cta.b64 _, [%0], %1;" ::"r"(bar), "r"(bytes) : "memory"); }
__device__ __forceinline__ void mbar_arrive_n(uint32_t bar, uint32_t cnt) { asm volatile("mbarrier.arrive.shared::cta.b64 _, [%0], %1;" ::"r"(bar), "r"(cnt) : "memory"); }
__device__ __forceinline__ void mbar_arrive_cl_if(uint32_t cond, uint32_t bar) {
  asm volatile("{\n.reg .pred p;\nsetp.ne.u32 p, %1, 0;\n@p mbarrier.arrive.shared::cluster.b64 _, [%0];\n}" ::"r"(bar), "r"(cond) : "memory");
}
__device__ __forceinline__ void mbar_arrive_warp(uint32_t bar) {
  asm volatile("{\n.reg .pred p;\nbar.warp.sync -1;\nelect.sync _|p, -1;\n@p mbarrier.arrive.shared::cta.b64 _, [%0];\n}" ::"r"(bar) : "memory");
}
__device__ __forceinline__ uint32_t mapa(uint32_t addr, uint32_t cta) { uint32_t r; asm("mapa.shared::cluster.u32 %0, %1, %2;" : "=r"(r) : "r"(addr), "r"(cta)); return r; }
__device__ __forceinline__ bool mbar_test(uint32_t bar, uint32_t parity) {
  uint32_t ok;
  asm volatile("{\n.reg .pred p;\nmbarrier.test_wait.parity.shared::cta.b64 p, [%1], %2;\nselp.u32 %0, 1, 0, p;\n}\n" : "=r"(ok) : "r"(bar), "r"(parity) : "memory");
  return ok;
}
__device__ __forceinline__ void mbar_wait(uint32_t bar, uint32_t parity) {
  asm volatile(
      "{\n.reg .pred p;\n.reg .u32 n;\nmov.u32 n, 0;\n"
      "WAIT:\nmbarrier.try_wait.parity.shared::cta.b64 p, [%0], %1;\n@p bra DONE;\n"
      "add.u32 n, n, 1;\nsetp.lt.u32 p, n, %2;\n@p bra WAIT;\ntrap;\nDONE:\n}\n" ::"r"(bar), "r"(parity), "n"(SPIN_LIMIT) : "memory");
}
template <int ID, int N> __device__ __forceinline__ void bar_sync() { asm volatile("bar.sync %0, %1;" ::"n"(ID), "n"(N) : "memory"); }
template <int ID, int N> __device__ __forceinline__ void bar_arrive() { asm volatile("bar.arrive %0, %1;" ::"n"(ID), "n"(N) : "memory"); }
__device__ __forceinline__ uint32_t ld_relaxed(const uint32_t* p) { uint32_t v; asm volatile("ld.relaxed.gpu.global.u32 %0, [%1];" : "=r"(v) : "l"(p) : "memory"); return v; }
__device__ __forceinline__ void red_relaxed(uint32_t* p, uint32_t v) { asm volatile("red.relaxed.gpu.global.add.u32 [%0], %1;" ::"l"(p), "r"(v) : "memory"); }
__device__ __forceinline__ void red_release(uint32_t* p, uint32_t v) {
  asm volatile("fence.release.gpu;\nred.relaxed.gpu.global.add.u32 [%0], %1;" ::"l"(p), "r"(v) : "memory");
}
__device__ __forceinline__ bool elect() {
  uint32_t p;
  asm volatile("{\n.reg .pred P;\nelect.sync _|P, 0xffffffff;\nselp.u32 %0, 1, 0, P;\n}\n" : "=r"(p));
  return p;
}
__device__ __forceinline__ void fence_acquire() { asm volatile("fence.acquire.gpu;" ::: "memory"); }
__device__ __forceinline__ void wait_count(const uint32_t* p, uint32_t target) {
  for (uint32_t n = 0; !__all_sync(~0u, (int)(ld_relaxed(p) - target) >= 0); n++) {
    __nanosleep(V_SL1);
    if (n > SPIN_LIMIT) __trap();
  }
  fence_acquire();
}
__device__ __forceinline__ void fence_proxy_async() { asm volatile("fence.proxy.async.global;" ::: "memory"); }
__device__ __forceinline__ void fence_proxy_async_smem() { asm volatile("fence.proxy.async.shared::cta;" ::: "memory"); }
__device__ __forceinline__ void tma4d_mc(uint32_t dst, const CUtensorMap* tm, int c1, int c2, uint32_t bar, uint64_t pol) {
  asm volatile("cp.async.bulk.tensor.4d.shared::cluster.global.mbarrier::complete_tx::bytes.multicast::cluster.L2::cache_hint [%0], [%1, {%3, %4, %5, %3}], [%2], %6, %7;"
               ::"r"(dst), "l"(tm), "r"(bar), "r"(0), "r"(c1), "r"(c2), "h"((uint16_t)3), "l"(pol) : "memory");
}
__device__ __forceinline__ void tma3d(uint32_t dst, const CUtensorMap* tm, int c0, int c1, int c2, uint32_t bar, uint64_t pol) {
  asm volatile("cp.async.bulk.tensor.3d.shared::cluster.global.mbarrier::complete_tx::bytes.L2::cache_hint [%0], [%1, {%3, %4, %5}], [%2], %6;"
               ::"r"(dst), "l"(tm), "r"(bar), "r"(c0), "r"(c1), "r"(c2), "l"(pol) : "memory");
}
__device__ __forceinline__ void tma3d_reduce_add(const CUtensorMap* tm, int c0, int c1, int c2, uint32_t src) {
  asm volatile("cp.reduce.async.bulk.tensor.3d.global.shared::cta.add.tile.bulk_group [%0, {%2, %3, %4}], [%1];"
               ::"l"(tm), "r"(src), "r"(c0), "r"(c1), "r"(c2) : "memory");
}
__device__ __forceinline__ void tma3d_store(const CUtensorMap* tm, int c0, int c1, int c2, uint32_t src) {
  asm volatile("cp.async.bulk.tensor.3d.global.shared::cta.tile.bulk_group [%0, {%2, %3, %4}], [%1];"
               ::"l"(tm), "r"(src), "r"(c0), "r"(c1), "r"(c2) : "memory");
}
__device__ __forceinline__ void bulk_commit() { asm volatile("cp.async.bulk.commit_group;" ::: "memory"); }
template <int N> __device__ __forceinline__ void bulk_wait_read() { asm volatile("cp.async.bulk.wait_group.read %0;" ::"n"(N) : "memory"); }
__device__ __forceinline__ void bulk_wait() { asm volatile("cp.async.bulk.wait_group 0;" ::: "memory"); }
__device__ __forceinline__ uint2 lds64(uint32_t a) { uint2 v; asm volatile("ld.shared.v2.u32 {%0,%1}, [%2];" : "=r"(v.x), "=r"(v.y) : "r"(a) : "memory"); return v; }
__device__ __forceinline__ float lds32f(uint32_t a) { float v; asm volatile("ld.shared.f32 %0, [%1];" : "=f"(v) : "r"(a) : "memory"); return v; }
__device__ __forceinline__ uint4 lds128(uint32_t a) { uint4 v; asm volatile("ld.shared.v4.u32 {%0,%1,%2,%3}, [%4];" : "=r"(v.x), "=r"(v.y), "=r"(v.z), "=r"(v.w) : "r"(a) : "memory"); return v; }
__device__ __forceinline__ uint2 lds64v(uint32_t a) { uint2 v; asm volatile("ld.volatile.shared.v2.u32 {%0,%1}, [%2];" : "=r"(v.x), "=r"(v.y) : "r"(a) : "memory"); return v; }
__device__ __forceinline__ uint4 lds128v(uint32_t a) { uint4 v; asm volatile("ld.volatile.shared.v4.u32 {%0,%1,%2,%3}, [%4];" : "=r"(v.x), "=r"(v.y), "=r"(v.z), "=r"(v.w) : "r"(a) : "memory"); return v; }
__device__ __forceinline__ void sts32(uint32_t a, uint32_t v) { asm volatile("st.shared.u32 [%0], %1;" ::"r"(a), "r"(v) : "memory"); }
__device__ __forceinline__ void sts64(uint32_t a, uint2 v) { asm volatile("st.shared.v2.u32 [%0], {%1,%2};" ::"r"(a), "r"(v.x), "r"(v.y) : "memory"); }
__device__ __forceinline__ void stg128(void* p, uint4 v) { asm volatile("st.global.L1::no_allocate.v4.u32 [%0], {%1,%2,%3,%4};" ::"l"(p), "r"(v.x), "r"(v.y), "r"(v.z), "r"(v.w) : "memory"); }
__device__ __forceinline__ uint4 ldg128(const void* p) { uint4 v; asm volatile("ld.relaxed.gpu.global.v4.u32 {%0,%1,%2,%3}, [%4];" : "=r"(v.x), "=r"(v.y), "=r"(v.z), "=r"(v.w) : "l"(p) : "memory"); return v; }
__device__ __forceinline__ void prefetch_tm(const CUtensorMap* tm) { asm volatile("prefetch.tensormap [%0];" ::"l"(tm) : "memory"); }
template <int N> __device__ __forceinline__ void wg_wait() { asm volatile("wgmma.wait_group.sync.aligned %0;" ::"n"(N) : "memory"); }
__device__ __forceinline__ void cluster_arrive() { asm volatile("barrier.cluster.arrive.relaxed.aligned;" ::: "memory"); }
__device__ __forceinline__ void cluster_wait() { asm volatile("barrier.cluster.wait.acquire.aligned;" ::: "memory"); }
__device__ __forceinline__ uint32_t pack_bf16(float lo, float hi) { uint32_t r; asm("cvt.rn.bf16x2.f32 %0, %1, %2;" : "=r"(r) : "f"(hi), "f"(lo)); return r; }
__device__ __forceinline__ float bf_lo(uint32_t v) { return __uint_as_float(v << 16); }
__device__ __forceinline__ float bf_hi(uint32_t v) { return __uint_as_float(v & 0xffff0000u); }
__device__ __forceinline__ uint32_t dup_hi(uint32_t v) { return __byte_perm(v, 0, 0x3232); }
__device__ __forceinline__ float bf_round(float x) { return __bfloat162float(__float2bfloat16_rn(x)); }
__device__ __forceinline__ uint32_t bf2_add(uint32_t a, uint32_t b) { uint32_t r; asm("add.rn.bf16x2 %0, %1, %2;" : "=r"(r) : "r"(a), "r"(b)); return r; }
__device__ __forceinline__ uint32_t bf2_mul(uint32_t a, uint32_t b) { uint32_t r; asm("mul.rn.bf16x2 %0, %1, %2;" : "=r"(r) : "r"(a), "r"(b)); return r; }
__device__ __forceinline__ uint32_t bf2_fma(uint32_t a, uint32_t b, uint32_t c) { uint32_t r; asm("fma.rn.bf16x2 %0, %1, %2, %3;" : "=r"(r) : "r"(a), "r"(b), "r"(c)); return r; }
__device__ __forceinline__ uint4 add8(uint4 a, uint4 b) { return make_uint4(bf2_add(a.x, b.x), bf2_add(a.y, b.y), bf2_add(a.z, b.z), bf2_add(a.w, b.w)); }
__device__ __forceinline__ uint4 fma8(uint32_t a, uint4 b, uint4 c) { return make_uint4(bf2_fma(a, b.x, c.x), bf2_fma(a, b.y, c.y), bf2_fma(a, b.z, c.z), bf2_fma(a, b.w, c.w)); }
__device__ __forceinline__ void stsm4(uint32_t a, uint32_t r0, uint32_t r1, uint32_t r2, uint32_t r3) {
  asm volatile("stmatrix.sync.aligned.m8n8.x4.shared.b16 [%0], {%1,%2,%3,%4};" ::"r"(a), "r"(r0), "r"(r1), "r"(r2), "r"(r3) : "memory");
}
__device__ __forceinline__ void ldsm4(uint32_t a, uint32_t (&r)[4]) {
  asm volatile("ldmatrix.sync.aligned.m8n8.x4.shared.b16 {%0,%1,%2,%3}, [%4];" : "=r"(r[0]), "=r"(r[1]), "=r"(r[2]), "=r"(r[3]) : "r"(a) : "memory");
}
__device__ __forceinline__ void ldsm4t(uint32_t a, uint32_t (&r)[4]) {
  asm volatile("ldmatrix.sync.aligned.m8n8.x4.trans.shared.b16 {%0,%1,%2,%3}, [%4];" : "=r"(r[0]), "=r"(r[1]), "=r"(r[2]), "=r"(r[3]) : "r"(a) : "memory");
}
__device__ __forceinline__ void mma16816(float (&c)[4], uint32_t a0, uint32_t a1, uint32_t a2, uint32_t a3, uint32_t b0, uint32_t b1) {
  asm volatile("mma.sync.aligned.m16n8k16.row.col.f32.bf16.bf16.f32 {%0,%1,%2,%3}, {%4,%5,%6,%7}, {%8,%9}, {%0,%1,%2,%3};"
               : "+f"(c[0]), "+f"(c[1]), "+f"(c[2]), "+f"(c[3]) : "r"(a0), "r"(a1), "r"(a2), "r"(a3), "r"(b0), "r"(b1));
}
__device__ __forceinline__ void mma1688(float (&c)[4], uint32_t a0, uint32_t a1, uint32_t b0) {
  asm volatile("mma.sync.aligned.m16n8k8.row.col.f32.bf16.bf16.f32 {%0,%1,%2,%3}, {%4,%5}, {%6}, {%0,%1,%2,%3};"
               : "+f"(c[0]), "+f"(c[1]), "+f"(c[2]), "+f"(c[3]) : "r"(a0), "r"(a1), "r"(b0));
}
__device__ __forceinline__ float ex2(float x) { float y; asm("ex2.approx.ftz.f32 %0, %1;" : "=f"(y) : "f"(x)); return y; }
__device__ __forceinline__ float sqrt_fast(float x) { float y; asm("sqrt.approx.f32 %0, %1;" : "=f"(y) : "f"(x)); return y; }
__device__ __forceinline__ float tanh_fast(float x) { float y; asm("tanh.approx.f32 %0, %1;" : "=f"(y) : "f"(x)); return y; }
__device__ __forceinline__ float rcp(float x) { float y; asm("rcp.approx.ftz.f32 %0, %1;" : "=f"(y) : "f"(x)); return y; }
__device__ __forceinline__ uint32_t opaque_zero() { uint32_t z; asm volatile("mov.u32 %0, %%ctaid.y;" : "=r"(z)); return z; }
__device__ __forceinline__ int fresh_tid() { int t; asm volatile("mov.u32 %0, %%tid.x;" : "=r"(t)); return t; }

__device__ __forceinline__ void first_kstep(float (&d)[128], uint32_t a, uint32_t b) {
  asm volatile("{\n.reg .u32 t;\n.reg .u64 da, db;\nwgmma.fence.sync.aligned;\n"
    "add.u32 t, %128, 0;\nmov.b64 da, {t, %130};\nadd.u32 t, %129, 0;\nmov.b64 db, {t, %130};\n"
    "wgmma.mma_async.sync.aligned.m64n256k16.f32.bf16.bf16 {%0, %1, %2, %3, %4, %5, %6, %7, %8, %9, %10, %11, %12, %13, %14, %15, %16, %17, %18, %19, %20, %21, %22, %23, %24, %25, %26, %27, %28, %29, %30, %31, %32, %33, %34, %35, %36, %37, %38, %39, %40, %41, %42, %43, %44, %45, %46, %47, %48, %49, %50, %51, %52, %53, %54, %55, %56, %57, %58, %59, %60, %61, %62, %63, %64, %65, %66, %67, %68, %69, %70, %71, %72, %73, %74, %75, %76, %77, %78, %79, %80, %81, %82, %83, %84, %85, %86, %87, %88, %89, %90, %91, %92, %93, %94, %95, %96, %97, %98, %99, %100, %101, %102, %103, %104, %105, %106, %107, %108, %109, %110, %111, %112, %113, %114, %115, %116, %117, %118, %119, %120, %121, %122, %123, %124, %125, %126, %127}, da, db, 0, 1, 1, 0, 1;\nwgmma.commit_group.sync.aligned;\n"
    "add.u32 t, %128, 2;\nmov.b64 da, {t, %130};\nadd.u32 t, %129, 128;\nmov.b64 db, {t, %130};\n"
    "wgmma.mma_async.sync.aligned.m64n256k16.f32.bf16.bf16 {%0, %1, %2, %3, %4, %5, %6, %7, %8, %9, %10, %11, %12, %13, %14, %15, %16, %17, %18, %19, %20, %21, %22, %23, %24, %25, %26, %27, %28, %29, %30, %31, %32, %33, %34, %35, %36, %37, %38, %39, %40, %41, %42, %43, %44, %45, %46, %47, %48, %49, %50, %51, %52, %53, %54, %55, %56, %57, %58, %59, %60, %61, %62, %63, %64, %65, %66, %67, %68, %69, %70, %71, %72, %73, %74, %75, %76, %77, %78, %79, %80, %81, %82, %83, %84, %85, %86, %87, %88, %89, %90, %91, %92, %93, %94, %95, %96, %97, %98, %99, %100, %101, %102, %103, %104, %105, %106, %107, %108, %109, %110, %111, %112, %113, %114, %115, %116, %117, %118, %119, %120, %121, %122, %123, %124, %125, %126, %127}, da, db, 1, 1, 1, 0, 1;\n"
    "add.u32 t, %128, 4;\nmov.b64 da, {t, %130};\nadd.u32 t, %129, 1024;\nmov.b64 db, {t, %130};\n"
    "wgmma.mma_async.sync.aligned.m64n256k16.f32.bf16.bf16 {%0, %1, %2, %3, %4, %5, %6, %7, %8, %9, %10, %11, %12, %13, %14, %15, %16, %17, %18, %19, %20, %21, %22, %23, %24, %25, %26, %27, %28, %29, %30, %31, %32, %33, %34, %35, %36, %37, %38, %39, %40, %41, %42, %43, %44, %45, %46, %47, %48, %49, %50, %51, %52, %53, %54, %55, %56, %57, %58, %59, %60, %61, %62, %63, %64, %65, %66, %67, %68, %69, %70, %71, %72, %73, %74, %75, %76, %77, %78, %79, %80, %81, %82, %83, %84, %85, %86, %87, %88, %89, %90, %91, %92, %93, %94, %95, %96, %97, %98, %99, %100, %101, %102, %103, %104, %105, %106, %107, %108, %109, %110, %111, %112, %113, %114, %115, %116, %117, %118, %119, %120, %121, %122, %123, %124, %125, %126, %127}, da, db, 1, 1, 1, 0, 1;\n"
    "add.u32 t, %128, 6;\nmov.b64 da, {t, %130};\nadd.u32 t, %129, 1152;\nmov.b64 db, {t, %130};\n"
    "wgmma.mma_async.sync.aligned.m64n256k16.f32.bf16.bf16 {%0, %1, %2, %3, %4, %5, %6, %7, %8, %9, %10, %11, %12, %13, %14, %15, %16, %17, %18, %19, %20, %21, %22, %23, %24, %25, %26, %27, %28, %29, %30, %31, %32, %33, %34, %35, %36, %37, %38, %39, %40, %41, %42, %43, %44, %45, %46, %47, %48, %49, %50, %51, %52, %53, %54, %55, %56, %57, %58, %59, %60, %61, %62, %63, %64, %65, %66, %67, %68, %69, %70, %71, %72, %73, %74, %75, %76, %77, %78, %79, %80, %81, %82, %83, %84, %85, %86, %87, %88, %89, %90, %91, %92, %93, %94, %95, %96, %97, %98, %99, %100, %101, %102, %103, %104, %105, %106, %107, %108, %109, %110, %111, %112, %113, %114, %115, %116, %117, %118, %119, %120, %121, %122, %123, %124, %125, %126, %127}, da, db, 1, 1, 1, 0, 1;\nwgmma.commit_group.sync.aligned;\n"
    "}\n"
    : "=f"(d[0]), "=f"(d[1]), "=f"(d[2]), "=f"(d[3]), "=f"(d[4]), "=f"(d[5]), "=f"(d[6]), "=f"(d[7]), "=f"(d[8]), "=f"(d[9]), "=f"(d[10]), "=f"(d[11]), "=f"(d[12]), "=f"(d[13]), "=f"(d[14]), "=f"(d[15]), "=f"(d[16]), "=f"(d[17]), "=f"(d[18]), "=f"(d[19]), "=f"(d[20]), "=f"(d[21]), "=f"(d[22]), "=f"(d[23]), "=f"(d[24]), "=f"(d[25]), "=f"(d[26]), "=f"(d[27]), "=f"(d[28]), "=f"(d[29]), "=f"(d[30]), "=f"(d[31]), "=f"(d[32]), "=f"(d[33]), "=f"(d[34]), "=f"(d[35]), "=f"(d[36]), "=f"(d[37]), "=f"(d[38]), "=f"(d[39]), "=f"(d[40]), "=f"(d[41]), "=f"(d[42]), "=f"(d[43]), "=f"(d[44]), "=f"(d[45]), "=f"(d[46]), "=f"(d[47]), "=f"(d[48]), "=f"(d[49]), "=f"(d[50]), "=f"(d[51]), "=f"(d[52]), "=f"(d[53]), "=f"(d[54]), "=f"(d[55]), "=f"(d[56]), "=f"(d[57]), "=f"(d[58]), "=f"(d[59]), "=f"(d[60]), "=f"(d[61]), "=f"(d[62]), "=f"(d[63]), "=f"(d[64]), "=f"(d[65]), "=f"(d[66]), "=f"(d[67]), "=f"(d[68]), "=f"(d[69]), "=f"(d[70]), "=f"(d[71]), "=f"(d[72]), "=f"(d[73]), "=f"(d[74]), "=f"(d[75]), "=f"(d[76]), "=f"(d[77]), "=f"(d[78]), "=f"(d[79]), "=f"(d[80]), "=f"(d[81]), "=f"(d[82]), "=f"(d[83]), "=f"(d[84]), "=f"(d[85]), "=f"(d[86]), "=f"(d[87]), "=f"(d[88]), "=f"(d[89]), "=f"(d[90]), "=f"(d[91]), "=f"(d[92]), "=f"(d[93]), "=f"(d[94]), "=f"(d[95]), "=f"(d[96]), "=f"(d[97]), "=f"(d[98]), "=f"(d[99]), "=f"(d[100]), "=f"(d[101]), "=f"(d[102]), "=f"(d[103]), "=f"(d[104]), "=f"(d[105]), "=f"(d[106]), "=f"(d[107]), "=f"(d[108]), "=f"(d[109]), "=f"(d[110]), "=f"(d[111]), "=f"(d[112]), "=f"(d[113]), "=f"(d[114]), "=f"(d[115]), "=f"(d[116]), "=f"(d[117]), "=f"(d[118]), "=f"(d[119]), "=f"(d[120]), "=f"(d[121]), "=f"(d[122]), "=f"(d[123]), "=f"(d[124]), "=f"(d[125]), "=f"(d[126]), "=f"(d[127])
    : "r"(a), "r"(b), "n"(0x40000040) : "memory");
}
__device__ __forceinline__ void kstep(float (&d)[128], uint32_t a, uint32_t b) {
  asm volatile("{\n.reg .u32 t;\n.reg .u64 da, db;\nwgmma.fence.sync.aligned;\n"
    "add.u32 t, %128, 0;\nmov.b64 da, {t, %130};\nadd.u32 t, %129, 0;\nmov.b64 db, {t, %130};\n"
    "wgmma.mma_async.sync.aligned.m64n256k16.f32.bf16.bf16 {%0, %1, %2, %3, %4, %5, %6, %7, %8, %9, %10, %11, %12, %13, %14, %15, %16, %17, %18, %19, %20, %21, %22, %23, %24, %25, %26, %27, %28, %29, %30, %31, %32, %33, %34, %35, %36, %37, %38, %39, %40, %41, %42, %43, %44, %45, %46, %47, %48, %49, %50, %51, %52, %53, %54, %55, %56, %57, %58, %59, %60, %61, %62, %63, %64, %65, %66, %67, %68, %69, %70, %71, %72, %73, %74, %75, %76, %77, %78, %79, %80, %81, %82, %83, %84, %85, %86, %87, %88, %89, %90, %91, %92, %93, %94, %95, %96, %97, %98, %99, %100, %101, %102, %103, %104, %105, %106, %107, %108, %109, %110, %111, %112, %113, %114, %115, %116, %117, %118, %119, %120, %121, %122, %123, %124, %125, %126, %127}, da, db, 1, 1, 1, 0, 1;\nwgmma.commit_group.sync.aligned;\n"
    "add.u32 t, %128, 2;\nmov.b64 da, {t, %130};\nadd.u32 t, %129, 128;\nmov.b64 db, {t, %130};\n"
    "wgmma.mma_async.sync.aligned.m64n256k16.f32.bf16.bf16 {%0, %1, %2, %3, %4, %5, %6, %7, %8, %9, %10, %11, %12, %13, %14, %15, %16, %17, %18, %19, %20, %21, %22, %23, %24, %25, %26, %27, %28, %29, %30, %31, %32, %33, %34, %35, %36, %37, %38, %39, %40, %41, %42, %43, %44, %45, %46, %47, %48, %49, %50, %51, %52, %53, %54, %55, %56, %57, %58, %59, %60, %61, %62, %63, %64, %65, %66, %67, %68, %69, %70, %71, %72, %73, %74, %75, %76, %77, %78, %79, %80, %81, %82, %83, %84, %85, %86, %87, %88, %89, %90, %91, %92, %93, %94, %95, %96, %97, %98, %99, %100, %101, %102, %103, %104, %105, %106, %107, %108, %109, %110, %111, %112, %113, %114, %115, %116, %117, %118, %119, %120, %121, %122, %123, %124, %125, %126, %127}, da, db, 1, 1, 1, 0, 1;\n"
    "add.u32 t, %128, 4;\nmov.b64 da, {t, %130};\nadd.u32 t, %129, 1024;\nmov.b64 db, {t, %130};\n"
    "wgmma.mma_async.sync.aligned.m64n256k16.f32.bf16.bf16 {%0, %1, %2, %3, %4, %5, %6, %7, %8, %9, %10, %11, %12, %13, %14, %15, %16, %17, %18, %19, %20, %21, %22, %23, %24, %25, %26, %27, %28, %29, %30, %31, %32, %33, %34, %35, %36, %37, %38, %39, %40, %41, %42, %43, %44, %45, %46, %47, %48, %49, %50, %51, %52, %53, %54, %55, %56, %57, %58, %59, %60, %61, %62, %63, %64, %65, %66, %67, %68, %69, %70, %71, %72, %73, %74, %75, %76, %77, %78, %79, %80, %81, %82, %83, %84, %85, %86, %87, %88, %89, %90, %91, %92, %93, %94, %95, %96, %97, %98, %99, %100, %101, %102, %103, %104, %105, %106, %107, %108, %109, %110, %111, %112, %113, %114, %115, %116, %117, %118, %119, %120, %121, %122, %123, %124, %125, %126, %127}, da, db, 1, 1, 1, 0, 1;\n"
    "add.u32 t, %128, 6;\nmov.b64 da, {t, %130};\nadd.u32 t, %129, 1152;\nmov.b64 db, {t, %130};\n"
    "wgmma.mma_async.sync.aligned.m64n256k16.f32.bf16.bf16 {%0, %1, %2, %3, %4, %5, %6, %7, %8, %9, %10, %11, %12, %13, %14, %15, %16, %17, %18, %19, %20, %21, %22, %23, %24, %25, %26, %27, %28, %29, %30, %31, %32, %33, %34, %35, %36, %37, %38, %39, %40, %41, %42, %43, %44, %45, %46, %47, %48, %49, %50, %51, %52, %53, %54, %55, %56, %57, %58, %59, %60, %61, %62, %63, %64, %65, %66, %67, %68, %69, %70, %71, %72, %73, %74, %75, %76, %77, %78, %79, %80, %81, %82, %83, %84, %85, %86, %87, %88, %89, %90, %91, %92, %93, %94, %95, %96, %97, %98, %99, %100, %101, %102, %103, %104, %105, %106, %107, %108, %109, %110, %111, %112, %113, %114, %115, %116, %117, %118, %119, %120, %121, %122, %123, %124, %125, %126, %127}, da, db, 1, 1, 1, 0, 1;\nwgmma.commit_group.sync.aligned;\n"
    "}\n"
    : "+f"(d[0]), "+f"(d[1]), "+f"(d[2]), "+f"(d[3]), "+f"(d[4]), "+f"(d[5]), "+f"(d[6]), "+f"(d[7]), "+f"(d[8]), "+f"(d[9]), "+f"(d[10]), "+f"(d[11]), "+f"(d[12]), "+f"(d[13]), "+f"(d[14]), "+f"(d[15]), "+f"(d[16]), "+f"(d[17]), "+f"(d[18]), "+f"(d[19]), "+f"(d[20]), "+f"(d[21]), "+f"(d[22]), "+f"(d[23]), "+f"(d[24]), "+f"(d[25]), "+f"(d[26]), "+f"(d[27]), "+f"(d[28]), "+f"(d[29]), "+f"(d[30]), "+f"(d[31]), "+f"(d[32]), "+f"(d[33]), "+f"(d[34]), "+f"(d[35]), "+f"(d[36]), "+f"(d[37]), "+f"(d[38]), "+f"(d[39]), "+f"(d[40]), "+f"(d[41]), "+f"(d[42]), "+f"(d[43]), "+f"(d[44]), "+f"(d[45]), "+f"(d[46]), "+f"(d[47]), "+f"(d[48]), "+f"(d[49]), "+f"(d[50]), "+f"(d[51]), "+f"(d[52]), "+f"(d[53]), "+f"(d[54]), "+f"(d[55]), "+f"(d[56]), "+f"(d[57]), "+f"(d[58]), "+f"(d[59]), "+f"(d[60]), "+f"(d[61]), "+f"(d[62]), "+f"(d[63]), "+f"(d[64]), "+f"(d[65]), "+f"(d[66]), "+f"(d[67]), "+f"(d[68]), "+f"(d[69]), "+f"(d[70]), "+f"(d[71]), "+f"(d[72]), "+f"(d[73]), "+f"(d[74]), "+f"(d[75]), "+f"(d[76]), "+f"(d[77]), "+f"(d[78]), "+f"(d[79]), "+f"(d[80]), "+f"(d[81]), "+f"(d[82]), "+f"(d[83]), "+f"(d[84]), "+f"(d[85]), "+f"(d[86]), "+f"(d[87]), "+f"(d[88]), "+f"(d[89]), "+f"(d[90]), "+f"(d[91]), "+f"(d[92]), "+f"(d[93]), "+f"(d[94]), "+f"(d[95]), "+f"(d[96]), "+f"(d[97]), "+f"(d[98]), "+f"(d[99]), "+f"(d[100]), "+f"(d[101]), "+f"(d[102]), "+f"(d[103]), "+f"(d[104]), "+f"(d[105]), "+f"(d[106]), "+f"(d[107]), "+f"(d[108]), "+f"(d[109]), "+f"(d[110]), "+f"(d[111]), "+f"(d[112]), "+f"(d[113]), "+f"(d[114]), "+f"(d[115]), "+f"(d[116]), "+f"(d[117]), "+f"(d[118]), "+f"(d[119]), "+f"(d[120]), "+f"(d[121]), "+f"(d[122]), "+f"(d[123]), "+f"(d[124]), "+f"(d[125]), "+f"(d[126]), "+f"(d[127])
    : "r"(a), "r"(b), "n"(0x40000040) : "memory");
}
__device__ __forceinline__ void first_kstep(float (&d)[96], uint32_t a, uint32_t b) {
  asm volatile("{\n.reg .u32 t;\n.reg .u64 da, db;\nwgmma.fence.sync.aligned;\n"
    "add.u32 t, %96, 0;\nmov.b64 da, {t, %98};\nadd.u32 t, %97, 0;\nmov.b64 db, {t, %98};\n"
    "wgmma.mma_async.sync.aligned.m64n192k16.f32.bf16.bf16 {%0, %1, %2, %3, %4, %5, %6, %7, %8, %9, %10, %11, %12, %13, %14, %15, %16, %17, %18, %19, %20, %21, %22, %23, %24, %25, %26, %27, %28, %29, %30, %31, %32, %33, %34, %35, %36, %37, %38, %39, %40, %41, %42, %43, %44, %45, %46, %47, %48, %49, %50, %51, %52, %53, %54, %55, %56, %57, %58, %59, %60, %61, %62, %63, %64, %65, %66, %67, %68, %69, %70, %71, %72, %73, %74, %75, %76, %77, %78, %79, %80, %81, %82, %83, %84, %85, %86, %87, %88, %89, %90, %91, %92, %93, %94, %95}, da, db, 0, 1, 1, 0, 1;\nwgmma.commit_group.sync.aligned;\n"
    "add.u32 t, %96, 2;\nmov.b64 da, {t, %98};\nadd.u32 t, %97, 128;\nmov.b64 db, {t, %98};\n"
    "wgmma.mma_async.sync.aligned.m64n192k16.f32.bf16.bf16 {%0, %1, %2, %3, %4, %5, %6, %7, %8, %9, %10, %11, %12, %13, %14, %15, %16, %17, %18, %19, %20, %21, %22, %23, %24, %25, %26, %27, %28, %29, %30, %31, %32, %33, %34, %35, %36, %37, %38, %39, %40, %41, %42, %43, %44, %45, %46, %47, %48, %49, %50, %51, %52, %53, %54, %55, %56, %57, %58, %59, %60, %61, %62, %63, %64, %65, %66, %67, %68, %69, %70, %71, %72, %73, %74, %75, %76, %77, %78, %79, %80, %81, %82, %83, %84, %85, %86, %87, %88, %89, %90, %91, %92, %93, %94, %95}, da, db, 1, 1, 1, 0, 1;\n"
    "add.u32 t, %96, 4;\nmov.b64 da, {t, %98};\nadd.u32 t, %97, 1024;\nmov.b64 db, {t, %98};\n"
    "wgmma.mma_async.sync.aligned.m64n192k16.f32.bf16.bf16 {%0, %1, %2, %3, %4, %5, %6, %7, %8, %9, %10, %11, %12, %13, %14, %15, %16, %17, %18, %19, %20, %21, %22, %23, %24, %25, %26, %27, %28, %29, %30, %31, %32, %33, %34, %35, %36, %37, %38, %39, %40, %41, %42, %43, %44, %45, %46, %47, %48, %49, %50, %51, %52, %53, %54, %55, %56, %57, %58, %59, %60, %61, %62, %63, %64, %65, %66, %67, %68, %69, %70, %71, %72, %73, %74, %75, %76, %77, %78, %79, %80, %81, %82, %83, %84, %85, %86, %87, %88, %89, %90, %91, %92, %93, %94, %95}, da, db, 1, 1, 1, 0, 1;\n"
    "add.u32 t, %96, 6;\nmov.b64 da, {t, %98};\nadd.u32 t, %97, 1152;\nmov.b64 db, {t, %98};\n"
    "wgmma.mma_async.sync.aligned.m64n192k16.f32.bf16.bf16 {%0, %1, %2, %3, %4, %5, %6, %7, %8, %9, %10, %11, %12, %13, %14, %15, %16, %17, %18, %19, %20, %21, %22, %23, %24, %25, %26, %27, %28, %29, %30, %31, %32, %33, %34, %35, %36, %37, %38, %39, %40, %41, %42, %43, %44, %45, %46, %47, %48, %49, %50, %51, %52, %53, %54, %55, %56, %57, %58, %59, %60, %61, %62, %63, %64, %65, %66, %67, %68, %69, %70, %71, %72, %73, %74, %75, %76, %77, %78, %79, %80, %81, %82, %83, %84, %85, %86, %87, %88, %89, %90, %91, %92, %93, %94, %95}, da, db, 1, 1, 1, 0, 1;\nwgmma.commit_group.sync.aligned;\n"
    "}\n"
    : "=f"(d[0]), "=f"(d[1]), "=f"(d[2]), "=f"(d[3]), "=f"(d[4]), "=f"(d[5]), "=f"(d[6]), "=f"(d[7]), "=f"(d[8]), "=f"(d[9]), "=f"(d[10]), "=f"(d[11]), "=f"(d[12]), "=f"(d[13]), "=f"(d[14]), "=f"(d[15]), "=f"(d[16]), "=f"(d[17]), "=f"(d[18]), "=f"(d[19]), "=f"(d[20]), "=f"(d[21]), "=f"(d[22]), "=f"(d[23]), "=f"(d[24]), "=f"(d[25]), "=f"(d[26]), "=f"(d[27]), "=f"(d[28]), "=f"(d[29]), "=f"(d[30]), "=f"(d[31]), "=f"(d[32]), "=f"(d[33]), "=f"(d[34]), "=f"(d[35]), "=f"(d[36]), "=f"(d[37]), "=f"(d[38]), "=f"(d[39]), "=f"(d[40]), "=f"(d[41]), "=f"(d[42]), "=f"(d[43]), "=f"(d[44]), "=f"(d[45]), "=f"(d[46]), "=f"(d[47]), "=f"(d[48]), "=f"(d[49]), "=f"(d[50]), "=f"(d[51]), "=f"(d[52]), "=f"(d[53]), "=f"(d[54]), "=f"(d[55]), "=f"(d[56]), "=f"(d[57]), "=f"(d[58]), "=f"(d[59]), "=f"(d[60]), "=f"(d[61]), "=f"(d[62]), "=f"(d[63]), "=f"(d[64]), "=f"(d[65]), "=f"(d[66]), "=f"(d[67]), "=f"(d[68]), "=f"(d[69]), "=f"(d[70]), "=f"(d[71]), "=f"(d[72]), "=f"(d[73]), "=f"(d[74]), "=f"(d[75]), "=f"(d[76]), "=f"(d[77]), "=f"(d[78]), "=f"(d[79]), "=f"(d[80]), "=f"(d[81]), "=f"(d[82]), "=f"(d[83]), "=f"(d[84]), "=f"(d[85]), "=f"(d[86]), "=f"(d[87]), "=f"(d[88]), "=f"(d[89]), "=f"(d[90]), "=f"(d[91]), "=f"(d[92]), "=f"(d[93]), "=f"(d[94]), "=f"(d[95])
    : "r"(a), "r"(b), "n"(0x40000040) : "memory");
}
__device__ __forceinline__ void kstep(float (&d)[96], uint32_t a, uint32_t b) {
  asm volatile("{\n.reg .u32 t;\n.reg .u64 da, db;\nwgmma.fence.sync.aligned;\n"
    "add.u32 t, %96, 0;\nmov.b64 da, {t, %98};\nadd.u32 t, %97, 0;\nmov.b64 db, {t, %98};\n"
    "wgmma.mma_async.sync.aligned.m64n192k16.f32.bf16.bf16 {%0, %1, %2, %3, %4, %5, %6, %7, %8, %9, %10, %11, %12, %13, %14, %15, %16, %17, %18, %19, %20, %21, %22, %23, %24, %25, %26, %27, %28, %29, %30, %31, %32, %33, %34, %35, %36, %37, %38, %39, %40, %41, %42, %43, %44, %45, %46, %47, %48, %49, %50, %51, %52, %53, %54, %55, %56, %57, %58, %59, %60, %61, %62, %63, %64, %65, %66, %67, %68, %69, %70, %71, %72, %73, %74, %75, %76, %77, %78, %79, %80, %81, %82, %83, %84, %85, %86, %87, %88, %89, %90, %91, %92, %93, %94, %95}, da, db, 1, 1, 1, 0, 1;\nwgmma.commit_group.sync.aligned;\n"
    "add.u32 t, %96, 2;\nmov.b64 da, {t, %98};\nadd.u32 t, %97, 128;\nmov.b64 db, {t, %98};\n"
    "wgmma.mma_async.sync.aligned.m64n192k16.f32.bf16.bf16 {%0, %1, %2, %3, %4, %5, %6, %7, %8, %9, %10, %11, %12, %13, %14, %15, %16, %17, %18, %19, %20, %21, %22, %23, %24, %25, %26, %27, %28, %29, %30, %31, %32, %33, %34, %35, %36, %37, %38, %39, %40, %41, %42, %43, %44, %45, %46, %47, %48, %49, %50, %51, %52, %53, %54, %55, %56, %57, %58, %59, %60, %61, %62, %63, %64, %65, %66, %67, %68, %69, %70, %71, %72, %73, %74, %75, %76, %77, %78, %79, %80, %81, %82, %83, %84, %85, %86, %87, %88, %89, %90, %91, %92, %93, %94, %95}, da, db, 1, 1, 1, 0, 1;\n"
    "add.u32 t, %96, 4;\nmov.b64 da, {t, %98};\nadd.u32 t, %97, 1024;\nmov.b64 db, {t, %98};\n"
    "wgmma.mma_async.sync.aligned.m64n192k16.f32.bf16.bf16 {%0, %1, %2, %3, %4, %5, %6, %7, %8, %9, %10, %11, %12, %13, %14, %15, %16, %17, %18, %19, %20, %21, %22, %23, %24, %25, %26, %27, %28, %29, %30, %31, %32, %33, %34, %35, %36, %37, %38, %39, %40, %41, %42, %43, %44, %45, %46, %47, %48, %49, %50, %51, %52, %53, %54, %55, %56, %57, %58, %59, %60, %61, %62, %63, %64, %65, %66, %67, %68, %69, %70, %71, %72, %73, %74, %75, %76, %77, %78, %79, %80, %81, %82, %83, %84, %85, %86, %87, %88, %89, %90, %91, %92, %93, %94, %95}, da, db, 1, 1, 1, 0, 1;\n"
    "add.u32 t, %96, 6;\nmov.b64 da, {t, %98};\nadd.u32 t, %97, 1152;\nmov.b64 db, {t, %98};\n"
    "wgmma.mma_async.sync.aligned.m64n192k16.f32.bf16.bf16 {%0, %1, %2, %3, %4, %5, %6, %7, %8, %9, %10, %11, %12, %13, %14, %15, %16, %17, %18, %19, %20, %21, %22, %23, %24, %25, %26, %27, %28, %29, %30, %31, %32, %33, %34, %35, %36, %37, %38, %39, %40, %41, %42, %43, %44, %45, %46, %47, %48, %49, %50, %51, %52, %53, %54, %55, %56, %57, %58, %59, %60, %61, %62, %63, %64, %65, %66, %67, %68, %69, %70, %71, %72, %73, %74, %75, %76, %77, %78, %79, %80, %81, %82, %83, %84, %85, %86, %87, %88, %89, %90, %91, %92, %93, %94, %95}, da, db, 1, 1, 1, 0, 1;\nwgmma.commit_group.sync.aligned;\n"
    "}\n"
    : "+f"(d[0]), "+f"(d[1]), "+f"(d[2]), "+f"(d[3]), "+f"(d[4]), "+f"(d[5]), "+f"(d[6]), "+f"(d[7]), "+f"(d[8]), "+f"(d[9]), "+f"(d[10]), "+f"(d[11]), "+f"(d[12]), "+f"(d[13]), "+f"(d[14]), "+f"(d[15]), "+f"(d[16]), "+f"(d[17]), "+f"(d[18]), "+f"(d[19]), "+f"(d[20]), "+f"(d[21]), "+f"(d[22]), "+f"(d[23]), "+f"(d[24]), "+f"(d[25]), "+f"(d[26]), "+f"(d[27]), "+f"(d[28]), "+f"(d[29]), "+f"(d[30]), "+f"(d[31]), "+f"(d[32]), "+f"(d[33]), "+f"(d[34]), "+f"(d[35]), "+f"(d[36]), "+f"(d[37]), "+f"(d[38]), "+f"(d[39]), "+f"(d[40]), "+f"(d[41]), "+f"(d[42]), "+f"(d[43]), "+f"(d[44]), "+f"(d[45]), "+f"(d[46]), "+f"(d[47]), "+f"(d[48]), "+f"(d[49]), "+f"(d[50]), "+f"(d[51]), "+f"(d[52]), "+f"(d[53]), "+f"(d[54]), "+f"(d[55]), "+f"(d[56]), "+f"(d[57]), "+f"(d[58]), "+f"(d[59]), "+f"(d[60]), "+f"(d[61]), "+f"(d[62]), "+f"(d[63]), "+f"(d[64]), "+f"(d[65]), "+f"(d[66]), "+f"(d[67]), "+f"(d[68]), "+f"(d[69]), "+f"(d[70]), "+f"(d[71]), "+f"(d[72]), "+f"(d[73]), "+f"(d[74]), "+f"(d[75]), "+f"(d[76]), "+f"(d[77]), "+f"(d[78]), "+f"(d[79]), "+f"(d[80]), "+f"(d[81]), "+f"(d[82]), "+f"(d[83]), "+f"(d[84]), "+f"(d[85]), "+f"(d[86]), "+f"(d[87]), "+f"(d[88]), "+f"(d[89]), "+f"(d[90]), "+f"(d[91]), "+f"(d[92]), "+f"(d[93]), "+f"(d[94]), "+f"(d[95])
    : "r"(a), "r"(b), "n"(0x40000040) : "memory");
}
__device__ __forceinline__ void half_kstep0(float (&d)[64], uint32_t a, uint32_t b) {
  asm volatile("{\n.reg .u32 t;\n.reg .u64 da, db;\nwgmma.fence.sync.aligned;\n"
    "add.u32 t, %64, 0;\nmov.b64 da, {t, %66};\nadd.u32 t, %65, 0;\nmov.b64 db, {t, %66};\n"
    "wgmma.mma_async.sync.aligned.m64n128k16.f32.bf16.bf16 {%0, %1, %2, %3, %4, %5, %6, %7, %8, %9, %10, %11, %12, %13, %14, %15, %16, %17, %18, %19, %20, %21, %22, %23, %24, %25, %26, %27, %28, %29, %30, %31, %32, %33, %34, %35, %36, %37, %38, %39, %40, %41, %42, %43, %44, %45, %46, %47, %48, %49, %50, %51, %52, %53, %54, %55, %56, %57, %58, %59, %60, %61, %62, %63}, da, db, 1, 1, 1, 0, 1;\n"
    "add.u32 t, %64, 2;\nmov.b64 da, {t, %66};\nadd.u32 t, %65, 128;\nmov.b64 db, {t, %66};\n"
    "wgmma.mma_async.sync.aligned.m64n128k16.f32.bf16.bf16 {%0, %1, %2, %3, %4, %5, %6, %7, %8, %9, %10, %11, %12, %13, %14, %15, %16, %17, %18, %19, %20, %21, %22, %23, %24, %25, %26, %27, %28, %29, %30, %31, %32, %33, %34, %35, %36, %37, %38, %39, %40, %41, %42, %43, %44, %45, %46, %47, %48, %49, %50, %51, %52, %53, %54, %55, %56, %57, %58, %59, %60, %61, %62, %63}, da, db, 1, 1, 1, 0, 1;\n"
    "add.u32 t, %64, 4;\nmov.b64 da, {t, %66};\nadd.u32 t, %65, 1024;\nmov.b64 db, {t, %66};\n"
    "wgmma.mma_async.sync.aligned.m64n128k16.f32.bf16.bf16 {%0, %1, %2, %3, %4, %5, %6, %7, %8, %9, %10, %11, %12, %13, %14, %15, %16, %17, %18, %19, %20, %21, %22, %23, %24, %25, %26, %27, %28, %29, %30, %31, %32, %33, %34, %35, %36, %37, %38, %39, %40, %41, %42, %43, %44, %45, %46, %47, %48, %49, %50, %51, %52, %53, %54, %55, %56, %57, %58, %59, %60, %61, %62, %63}, da, db, 1, 1, 1, 0, 1;\n"
    "add.u32 t, %64, 6;\nmov.b64 da, {t, %66};\nadd.u32 t, %65, 1152;\nmov.b64 db, {t, %66};\n"
    "wgmma.mma_async.sync.aligned.m64n128k16.f32.bf16.bf16 {%0, %1, %2, %3, %4, %5, %6, %7, %8, %9, %10, %11, %12, %13, %14, %15, %16, %17, %18, %19, %20, %21, %22, %23, %24, %25, %26, %27, %28, %29, %30, %31, %32, %33, %34, %35, %36, %37, %38, %39, %40, %41, %42, %43, %44, %45, %46, %47, %48, %49, %50, %51, %52, %53, %54, %55, %56, %57, %58, %59, %60, %61, %62, %63}, da, db, 1, 1, 1, 0, 1;\n"
    "wgmma.commit_group.sync.aligned;\n}\n"
    : "+f"(d[0]), "+f"(d[1]), "+f"(d[2]), "+f"(d[3]), "+f"(d[4]), "+f"(d[5]), "+f"(d[6]), "+f"(d[7]), "+f"(d[8]), "+f"(d[9]), "+f"(d[10]), "+f"(d[11]), "+f"(d[12]), "+f"(d[13]), "+f"(d[14]), "+f"(d[15]), "+f"(d[16]), "+f"(d[17]), "+f"(d[18]), "+f"(d[19]), "+f"(d[20]), "+f"(d[21]), "+f"(d[22]), "+f"(d[23]), "+f"(d[24]), "+f"(d[25]), "+f"(d[26]), "+f"(d[27]), "+f"(d[28]), "+f"(d[29]), "+f"(d[30]), "+f"(d[31]), "+f"(d[32]), "+f"(d[33]), "+f"(d[34]), "+f"(d[35]), "+f"(d[36]), "+f"(d[37]), "+f"(d[38]), "+f"(d[39]), "+f"(d[40]), "+f"(d[41]), "+f"(d[42]), "+f"(d[43]), "+f"(d[44]), "+f"(d[45]), "+f"(d[46]), "+f"(d[47]), "+f"(d[48]), "+f"(d[49]), "+f"(d[50]), "+f"(d[51]), "+f"(d[52]), "+f"(d[53]), "+f"(d[54]), "+f"(d[55]), "+f"(d[56]), "+f"(d[57]), "+f"(d[58]), "+f"(d[59]), "+f"(d[60]), "+f"(d[61]), "+f"(d[62]), "+f"(d[63])
    : "r"(a), "r"(b), "n"(0x40000040) : "memory");
}
__device__ __forceinline__ void half_kstep1(float (&d)[64], uint32_t a, uint32_t b) {
  asm volatile("{\n.reg .u32 t;\n.reg .u64 da, db;\nwgmma.fence.sync.aligned;\n"
    "add.u32 t, %64, 0;\nmov.b64 da, {t, %66};\nadd.u32 t, %65, 512;\nmov.b64 db, {t, %66};\n"
    "wgmma.mma_async.sync.aligned.m64n128k16.f32.bf16.bf16 {%0, %1, %2, %3, %4, %5, %6, %7, %8, %9, %10, %11, %12, %13, %14, %15, %16, %17, %18, %19, %20, %21, %22, %23, %24, %25, %26, %27, %28, %29, %30, %31, %32, %33, %34, %35, %36, %37, %38, %39, %40, %41, %42, %43, %44, %45, %46, %47, %48, %49, %50, %51, %52, %53, %54, %55, %56, %57, %58, %59, %60, %61, %62, %63}, da, db, 1, 1, 1, 0, 1;\n"
    "add.u32 t, %64, 2;\nmov.b64 da, {t, %66};\nadd.u32 t, %65, 640;\nmov.b64 db, {t, %66};\n"
    "wgmma.mma_async.sync.aligned.m64n128k16.f32.bf16.bf16 {%0, %1, %2, %3, %4, %5, %6, %7, %8, %9, %10, %11, %12, %13, %14, %15, %16, %17, %18, %19, %20, %21, %22, %23, %24, %25, %26, %27, %28, %29, %30, %31, %32, %33, %34, %35, %36, %37, %38, %39, %40, %41, %42, %43, %44, %45, %46, %47, %48, %49, %50, %51, %52, %53, %54, %55, %56, %57, %58, %59, %60, %61, %62, %63}, da, db, 1, 1, 1, 0, 1;\n"
    "add.u32 t, %64, 4;\nmov.b64 da, {t, %66};\nadd.u32 t, %65, 1536;\nmov.b64 db, {t, %66};\n"
    "wgmma.mma_async.sync.aligned.m64n128k16.f32.bf16.bf16 {%0, %1, %2, %3, %4, %5, %6, %7, %8, %9, %10, %11, %12, %13, %14, %15, %16, %17, %18, %19, %20, %21, %22, %23, %24, %25, %26, %27, %28, %29, %30, %31, %32, %33, %34, %35, %36, %37, %38, %39, %40, %41, %42, %43, %44, %45, %46, %47, %48, %49, %50, %51, %52, %53, %54, %55, %56, %57, %58, %59, %60, %61, %62, %63}, da, db, 1, 1, 1, 0, 1;\n"
    "add.u32 t, %64, 6;\nmov.b64 da, {t, %66};\nadd.u32 t, %65, 1664;\nmov.b64 db, {t, %66};\n"
    "wgmma.mma_async.sync.aligned.m64n128k16.f32.bf16.bf16 {%0, %1, %2, %3, %4, %5, %6, %7, %8, %9, %10, %11, %12, %13, %14, %15, %16, %17, %18, %19, %20, %21, %22, %23, %24, %25, %26, %27, %28, %29, %30, %31, %32, %33, %34, %35, %36, %37, %38, %39, %40, %41, %42, %43, %44, %45, %46, %47, %48, %49, %50, %51, %52, %53, %54, %55, %56, %57, %58, %59, %60, %61, %62, %63}, da, db, 1, 1, 1, 0, 1;\n"
    "wgmma.commit_group.sync.aligned;\n}\n"
    : "+f"(d[0]), "+f"(d[1]), "+f"(d[2]), "+f"(d[3]), "+f"(d[4]), "+f"(d[5]), "+f"(d[6]), "+f"(d[7]), "+f"(d[8]), "+f"(d[9]), "+f"(d[10]), "+f"(d[11]), "+f"(d[12]), "+f"(d[13]), "+f"(d[14]), "+f"(d[15]), "+f"(d[16]), "+f"(d[17]), "+f"(d[18]), "+f"(d[19]), "+f"(d[20]), "+f"(d[21]), "+f"(d[22]), "+f"(d[23]), "+f"(d[24]), "+f"(d[25]), "+f"(d[26]), "+f"(d[27]), "+f"(d[28]), "+f"(d[29]), "+f"(d[30]), "+f"(d[31]), "+f"(d[32]), "+f"(d[33]), "+f"(d[34]), "+f"(d[35]), "+f"(d[36]), "+f"(d[37]), "+f"(d[38]), "+f"(d[39]), "+f"(d[40]), "+f"(d[41]), "+f"(d[42]), "+f"(d[43]), "+f"(d[44]), "+f"(d[45]), "+f"(d[46]), "+f"(d[47]), "+f"(d[48]), "+f"(d[49]), "+f"(d[50]), "+f"(d[51]), "+f"(d[52]), "+f"(d[53]), "+f"(d[54]), "+f"(d[55]), "+f"(d[56]), "+f"(d[57]), "+f"(d[58]), "+f"(d[59]), "+f"(d[60]), "+f"(d[61]), "+f"(d[62]), "+f"(d[63])
    : "r"(a), "r"(b), "n"(0x40000040) : "memory");
}

__device__ __forceinline__ void sum_columns(float (&d)[4], uint32_t a, uint32_t b) {
  asm volatile("{\n.reg .u32 t;\n.reg .u64 da, db;\nmov.b64 db, {%5, 0};\nwgmma.fence.sync.aligned;\n"
               "add.u32 t, %4, 0;\nmov.b64 da, {t, %6};\nwgmma.mma_async.sync.aligned.m64n8k16.f32.bf16.bf16 {%0, %1, %2, %3}, da, db, 1, 1, 1, 1, 0;\n"
               "add.u32 t, %4, 128;\nmov.b64 da, {t, %6};\nwgmma.mma_async.sync.aligned.m64n8k16.f32.bf16.bf16 {%0, %1, %2, %3}, da, db, 1, 1, 1, 1, 0;\n"
               "add.u32 t, %4, 256;\nmov.b64 da, {t, %6};\nwgmma.mma_async.sync.aligned.m64n8k16.f32.bf16.bf16 {%0, %1, %2, %3}, da, db, 1, 1, 1, 1, 0;\n"
               "add.u32 t, %4, 384;\nmov.b64 da, {t, %6};\nwgmma.mma_async.sync.aligned.m64n8k16.f32.bf16.bf16 {%0, %1, %2, %3}, da, db, 1, 1, 1, 1, 0;\n"
               "add.u32 t, %4, 512;\nmov.b64 da, {t, %6};\nwgmma.mma_async.sync.aligned.m64n8k16.f32.bf16.bf16 {%0, %1, %2, %3}, da, db, 1, 1, 1, 1, 0;\n"
               "add.u32 t, %4, 640;\nmov.b64 da, {t, %6};\nwgmma.mma_async.sync.aligned.m64n8k16.f32.bf16.bf16 {%0, %1, %2, %3}, da, db, 1, 1, 1, 1, 0;\n"
               "add.u32 t, %4, 768;\nmov.b64 da, {t, %6};\nwgmma.mma_async.sync.aligned.m64n8k16.f32.bf16.bf16 {%0, %1, %2, %3}, da, db, 1, 1, 1, 1, 0;\n"
               "add.u32 t, %4, 896;\nmov.b64 da, {t, %6};\nwgmma.mma_async.sync.aligned.m64n8k16.f32.bf16.bf16 {%0, %1, %2, %3}, da, db, 1, 1, 1, 1, 0;\n"
               "add.u32 t, %4, 1024;\nmov.b64 da, {t, %6};\nwgmma.mma_async.sync.aligned.m64n8k16.f32.bf16.bf16 {%0, %1, %2, %3}, da, db, 1, 1, 1, 1, 0;\n"
               "add.u32 t, %4, 1152;\nmov.b64 da, {t, %6};\nwgmma.mma_async.sync.aligned.m64n8k16.f32.bf16.bf16 {%0, %1, %2, %3}, da, db, 1, 1, 1, 1, 0;\n"
               "add.u32 t, %4, 1280;\nmov.b64 da, {t, %6};\nwgmma.mma_async.sync.aligned.m64n8k16.f32.bf16.bf16 {%0, %1, %2, %3}, da, db, 1, 1, 1, 1, 0;\n"
               "add.u32 t, %4, 1408;\nmov.b64 da, {t, %6};\nwgmma.mma_async.sync.aligned.m64n8k16.f32.bf16.bf16 {%0, %1, %2, %3}, da, db, 1, 1, 1, 1, 0;\n"
               "add.u32 t, %4, 1536;\nmov.b64 da, {t, %6};\nwgmma.mma_async.sync.aligned.m64n8k16.f32.bf16.bf16 {%0, %1, %2, %3}, da, db, 1, 1, 1, 1, 0;\n"
               "add.u32 t, %4, 1664;\nmov.b64 da, {t, %6};\nwgmma.mma_async.sync.aligned.m64n8k16.f32.bf16.bf16 {%0, %1, %2, %3}, da, db, 1, 1, 1, 1, 0;\n"
               "add.u32 t, %4, 1792;\nmov.b64 da, {t, %6};\nwgmma.mma_async.sync.aligned.m64n8k16.f32.bf16.bf16 {%0, %1, %2, %3}, da, db, 1, 1, 1, 1, 0;\n"
               "add.u32 t, %4, 1920;\nmov.b64 da, {t, %6};\nwgmma.mma_async.sync.aligned.m64n8k16.f32.bf16.bf16 {%0, %1, %2, %3}, da, db, 1, 1, 1, 1, 0;\n"
               "wgmma.commit_group.sync.aligned;\nwgmma.wait_group.sync.aligned 0;\n}"
               : "+f"(d[0]), "+f"(d[1]), "+f"(d[2]), "+f"(d[3]) : "r"(a), "r"(b), "n"(0x40000040) : "memory");
}
struct Job {
  uint32_t type, layer, R, col, nk;
  __device__ __forceinline__ explicit Job(uint32_t j) : type(j & 3), layer((j >> 2) & 1), R((j >> 3) & 7), col((j >> 6) & 63), nk((j >> 12) & 63) {}
  __device__ __forceinline__ uint32_t inst() const { return layer * 2 + (type >> 1); }
};
struct Smem {
  char* scratch;
  uint32_t base;
  __device__ __forceinline__ uint32_t stage(uint32_t s) const { return base + (s & (NSTAGE - 1)) * STAGE; }
  __device__ __forceinline__ uint32_t slot(uint32_t c) const { return base + STG_OFF + c * SLOT; }
  __device__ __forceinline__ uint32_t full(uint32_t s) const { return base + BAR_OFF + (s & (NSTAGE - 1)) * 8; }
  __device__ __forceinline__ uint32_t empty(uint32_t s) const { return base + BAR_OFF + 32 + (s & (NSTAGE - 1)) * 8; }
  __device__ __forceinline__ uint32_t filled(uint32_t u) const { return base + BAR_OFF + 64 + u * 8; }
  __device__ __forceinline__ uint32_t vacant(uint32_t u) const { return base + BAR_OFF + 96 + u * 8; }
  __device__ __forceinline__ uint32_t summed(uint32_t s) const { return base + BAR_OFF + 128 + (s & (NSTAGE - 1)) * 8; }
  __device__ __forceinline__ uint32_t aux_full() const { return base + BAR_OFF + 160; }
  __device__ __forceinline__ uint32_t boot() const { return base + BAR_OFF + 168; }
  __device__ __forceinline__ uint32_t xchg_full() const { return base + BAR_OFF + 176; }
  __device__ __forceinline__ uint32_t wgmma_done() const { return base + BAR_OFF + 184; }
  __device__ __forceinline__ uint32_t mma_done() const { return base + BAR_OFF + 192; }
  __device__ __forceinline__ uint32_t kv_ready(int w) const { return base + BAR_OFF + 208 + w * 8; }
  __device__ __forceinline__ uint32_t pair_id() const { return base + BAR_OFF + 280; }
  __device__ __forceinline__ uint32_t stats() const { return base + AUX_OFF; }
  __device__ __forceinline__ uint32_t sums() const { return base + AUX_OFF + 1088; }
  __device__ __forceinline__ uint32_t xchg() const { return base + AUX_OFF + 1600; }
};
__device__ __forceinline__ uint32_t par(uint32_t s) { return (s / NSTAGE) & 1; }

__device__ __forceinline__ void st_word(u64* p, uint32_t lo, uint32_t hi) {
  asm volatile("st.relaxed.gpu.global.u64 [%0], %1;" ::"l"(p), "l"(((u64)hi << 32) | lo) : "memory");
}
__device__ __forceinline__ uint2 ld_word(const u64* p) {
  u64 v;
  asm volatile("ld.relaxed.gpu.global.u64 %0, [%1];" : "=l"(v) : "l"(p) : "memory");
  return make_uint2((uint32_t)v, (uint32_t)(v >> 32));
}
__device__ __forceinline__ void add_moments(uint4 v, float (&m)[4]) {
  const uint32_t w[4] = {v.x, v.y, v.z, v.w};
#pragma unroll
  for (int c = 0; c < 4; c++) {
    const float lo = bf_lo(w[c]), hi = bf_hi(w[c]);
    m[0] += lo; m[1] += hi; m[2] = fmaf(lo, lo, m[2]); m[3] = fmaf(hi, hi, m[3]);
  }
}
__device__ __forceinline__ void publish_stats(const Smem& sm, float s, float q, uint32_t idx, bool valid, uint32_t e1) {
  const float mean = s * (1.f / D), var = fmaxf(q * (1.f / D) - mean * mean, 0.f);
  const u64 word = ((u64)((__float_as_uint(-bf_round(mean)) & 0xffff0000u) | (e1 & 0xffff)) << 32) | __float_as_uint(rcp(bf_round(sqrt_fast(bf_round(bf_round(var) + 1e-5f)))));
  asm volatile("{\n.reg .pred p;\nsetp.ne.u32 p, %2, 0;\n@p st.relaxed.gpu.global.u64 [%0], %1;\n}" ::"l"(SCR(sm, stats, idx * 8)), "l"(word), "r"((uint32_t)valid) : "memory");
}
__device__ __forceinline__ void stats_task(const Smem& sm, uint32_t jw, int rank, int w, uint32_t e1, const bf16* x) {
  const uint32_t inst = (jw >> 22) & 3, lane = fresh_tid() & 31, steps = (jw >> 31) * 2 + 2;
  uint32_t row = ((jw >> 24) & 127) * 8 + (w - 1) * 4 + (lane >> 3);
  wait_count(counter(C_X + inst * 16 + (row >> 7) * 2 + rank, lane & 7), e1 * (inst & 1 ? 56 : 16));
  const uint4* p = at(reinterpret_cast<const uint4*>(x), (row * 2 + rank) * (D * 2) + (lane & 7) * 16);
  uint4 v[8];
  float m[4] = {0.f, 0.f, 0.f, 0.f};
#pragma unroll
  for (int i = 0; i < 8; i++) v[i] = ldg128(p + i * 8);
#pragma unroll 1
  for (uint32_t it = 1; it <= steps; it++) {
    p = at(p, it & 1 ? 1024 : 8 * D * 4 - 1024);
#pragma unroll
    for (int i = 0; i < 8; i++) {
      add_moments(v[i], m);
      if (it < steps) v[i] = ldg128(p + i * 8);
    }
    if (!(it & 1)) {
      m[0] += m[1]; m[2] += m[3];
#pragma unroll
      for (int o = 1; o <= 4; o <<= 1) { m[0] += __shfl_xor_sync(~0u, m[0], o); m[2] += __shfl_xor_sync(~0u, m[2], o); }
      publish_stats(sm, m[0], m[2], (inst + 1) * S + rank * (S / 2) + row, (lane & 7) == 0, e1);
      m[0] = m[1] = m[2] = m[3] = 0.f;
      row += 8;
    }
  }
}
struct Stager {
  uint2 st[5], cs[4];
  __device__ __forceinline__ void load(const Smem& sm, const Job& J, int rank, int lane, bool sums) {
#pragma unroll
    for (int i = 0; i < 5; i++) st[i] = ld_word(SCR(sm, stats, (J.inst() * S + rank * (S / 2) + J.R * 128 + min(max(lane - 8 + 32 * i, J.R && J.type == T_Q ? -8 : 0), 127)) * 8));
#pragma unroll
    for (int i = 0; i < 4; i++)
      if (sums && (i < 3 || J.type == T_G)) cs[i] = ld_word(SCR(sm, cs, ((J.col + J.type * 8) * 128 + lane) * 8) + i * 32);
  }
  __device__ __forceinline__ void store(const Smem& sm, const Job& J, int rank, int lane, bool sums, uint32_t e1) {
    for (uint32_t n = 0;; n++) {
      uint32_t bad = (st[1].y ^ e1) | (st[2].y ^ e1) | (st[3].y ^ e1);
      bad |= (st[0].y ^ e1) | (st[4].y ^ e1);
      if (sums) bad |= (cs[0].y ^ e1) | (cs[1].y ^ e1) | (cs[2].y ^ e1);
      if (J.type == T_G) bad |= cs[3].y ^ e1;
      if (__all_sync(~0u, (bad & 0xffff) == 0)) break;
      __nanosleep(V_SL2);
      if (n > SPIN_LIMIT) __trap();
      load(sm, J, rank, lane, sums);
    }
#pragma unroll
    for (int i = 0; i < 5; i++) {
      if (i < 4 || lane < 8) sts64(sm.stats() + (lane + 32 * i) * 8, st[i]);
      if (i < 4 && sums && (i < 3 || J.type == T_G)) sts32(sm.sums() + (lane + 32 * i) * 4, cs[i].x);
    }
  }
};
__device__ __forceinline__ void add_cols(float (&a)[8], uint4 x, uint4 y) {
  const uint4 t = add8(x, y);
  a[0] += bf_lo(t.x); a[1] += bf_hi(t.x); a[2] += bf_lo(t.y); a[3] += bf_hi(t.y);
  a[4] += bf_lo(t.z); a[5] += bf_hi(t.z); a[6] += bf_lo(t.w); a[7] += bf_hi(t.w);
}
__device__ __forceinline__ void reduce_cols(float (&a)[8], int lane) {
#pragma unroll
  for (int i = 0; i < 4; i++) { const bool up = lane & 16; const float o = __shfl_xor_sync(~0u, up ? a[i] : a[i + 4], 16); a[i] = (up ? a[i + 4] : a[i]) + o; }
#pragma unroll
  for (int i = 0; i < 2; i++) { const bool up = lane & 8; const float o = __shfl_xor_sync(~0u, up ? a[i] : a[i + 2], 8); a[i] = (up ? a[i + 2] : a[i]) + o; }
}
template <class Fn>
__device__ __forceinline__ uint32_t qkv_col_sums(const Smem& sm, int rank, int w, int lane, Fn between) {
  float a[8] = {0.f, 0.f, 0.f, 0.f, 0.f, 0.f, 0.f, 0.f};
#pragma unroll 1
  for (int s = 0; s < D / 64; s++) {
    between(s);
    const uint32_t p = sm.stage(s) + SLOT + rank * SLOT + w * 4096 + (lane >> 3) * 128 + (((lane & 7) ^ (lane >> 3)) << 4);
    uint4 v[8];
    mbar_wait(sm.full(s), par(s));
#pragma unroll
    for (int j = 0; j < 8; j++) v[j] = lds128((p ^ ((j & 1) * 64)) + j * 512);
    __syncwarp();
    mbar_arrive_cl_if(lane < 2, mapa(sm.summed(s), lane & 1));
    add_cols(a, add8(v[0], v[1]), add8(v[2], v[3]));
    add_cols(a, add8(v[4], v[5]), add8(v[6], v[7]));
  }
  reduce_cols(a, lane);
  const uint32_t slot = sm.xchg() + (w * 32 + lane) * 8;
  asm volatile("st.async.weak.shared::cluster.mbarrier::complete_tx::bytes.v2.b32 [%0], {%1, %2}, [%3];"
               ::"r"(mapa(slot, rank ^ 1)), "r"(__float_as_uint(a[0])), "r"(__float_as_uint(a[1])), "r"(mapa(sm.xchg_full(), rank ^ 1)) : "memory");
  mbar_wait(sm.xchg_full(), 0);
  const uint2 o = lds64(slot);
  return pack_bf16(a[0] + __uint_as_float(o.x), a[1] + __uint_as_float(o.y));
}

constexpr float LOGIT_SCALE = 0.17677669529663687f * 1.4426950408889634f;
constexpr float MASKED = -1e30f;
enum { A_CS = 16, A_NM = 40, A_KT = 42, A_KU = 44, A_CT = 46, A_CU = 48, A_BIAS = 50, A_MASK = 52, A_ZERO = 53 };
__device__ __forceinline__ void attention_prepare(uint32_t (&r)[64], const Smem& sm, int W, int lane, bool first) {
  const int i = lane >> 2, c = (lane & 3) * 2;
  r[A_ZERO] = opaque_zero();
  r[A_MASK] = (c > i ? 0xffffu : 0u) | (c + 1 > i ? 0xffff0000u : 0u);
  const uint32_t a = sm.stats() + W * 128;
  const uint2 r0 = lds64(a + 64 + i * 8), r1 = lds64(a + 128 + i * 8);
#pragma unroll
  for (int y = 0; y < 2; y++) {
    const uint32_t k = a + (c + y + (c + y > i ? 0 : 8)) * 8;
    const float kt = lds32f(k), ku = lds32f(k + 64);
    r[A_KT + y] = __float_as_uint(kt); r[A_CT + y] = __float_as_uint(__uint_as_float(r0.x) * LOGIT_SCALE * kt);
    r[A_KU + y] = __float_as_uint(ku); r[A_CU + y] = __float_as_uint(__uint_as_float(r1.x) * LOGIT_SCALE * ku);
    r[A_BIAS + y] = __float_as_uint(first && W == 0 && c + y > i ? MASKED : 0.f);
  }
#pragma unroll
  for (int j = 0; j < 6; j++) {
    const uint4 v = lds128(sm.sums() + c * 48 + j * 16);
    r[A_CS + 4 * j] = v.x; r[A_CS + 4 * j + 1] = v.y; r[A_CS + 4 * j + 2] = v.z; r[A_CS + 4 * j + 3] = v.w;
  }
  r[A_NM] = dup_hi(r0.y); r[A_NM + 1] = dup_hi(r1.y);
}
__device__ __forceinline__ bool attention(const float (&acc)[96], uint32_t (&r)[64], const Smem& sm, int W, int lane, uint32_t t8, uint32_t t16,
                                          bool halo, uint32_t block, uint32_t tag, uint32_t parity, uint32_t next_bar, uint32_t next_parity, int ji) {
#define TRW W
  const uint32_t own = (W >> 2) * SLOT;
  const uint32_t pk = W == 0 ? (halo ? 4096 : 1024) : W == 4 ? 7168 : own - 1024;
  const uint32_t pv = W == 0 && halo ? 6144 : pk + 8192;
  uint32_t x[48];
  auto pack = [&](int j0, int step, int count) {
#pragma unroll
    for (int j = j0; j < j0 + step * count; j += step) x[j] = bf2_fma(r[A_NM + j % 2], r[A_CS + j / 2], pack_bf16(acc[2 * j], acc[2 * j + 1]));
  };
  auto put8 = [&](uint32_t a, int j) {
    stsm4(t8 + a, x[j], x[j + 2], x[j + 4], x[j + 6]);
    stsm4((t8 ^ 64) + a, x[j + 8], x[j + 10], x[j + 12], x[j + 14]);
  };
  uint32_t k0[2][4], v0[2][4], v12[4][4];
  pack(17, 2, 8);
  put8(own + 1024, 17);
  pack(32, 1, 16);
#pragma unroll
  for (int j = 0; j < 4; j++) stsm4((t16 ^ (j << 5)) + (own + 8192), x[32 + 4 * j], x[33 + 4 * j], x[34 + 4 * j], x[35 + 4 * j]);
  mbar_arrive_warp(sm.kv_ready(W));
  pack(16, 2, 8);
  pack(0, 1, 16);
  if (W == 0) {
    put8(0, 16);
#pragma unroll
    for (int j = 0; j < 4; j++) stsm4(lane & 8 ? sm.xchg() : (t16 ^ (j << 5)) + 2048, x[4 * j], x[4 * j + 1], x[4 * j + 2], x[4 * j + 3]);
  }
  mbar_wait(sm.kv_ready(W - 1), parity);
#pragma unroll
  for (int h = 0; h < 2; h++) ldsm4((t8 ^ (h * 64)) + pk, k0[h]);
#pragma unroll
  for (int j = 0; j < 4; j++) ldsm4t((t16 ^ (j << 5)) + (own + 8192), v12[j]);
#pragma unroll
  for (int h = 0; h < 2; h++) ldsm4t((t8 ^ (h * 64)) + pv, v0[h]);
  if (W < 4) mbar_wait(sm.wgmma_done(), parity);
  const bool next_full = mbar_test(next_bar, next_parity);
  TRC(ji, 20);
  float s0[2][4], s1[2][4], s2[2][4];
#pragma unroll
  for (int h = 0; h < 2; h++) {
#pragma unroll
    for (int y = 0; y < 4; y++) s0[h][y] = s1[h][y] = s2[h][y] = 0.f;
  }
#pragma unroll
  for (int ks = 0; ks < 2; ks++)
#pragma unroll
    for (int h = 0; h < 2; h++) {
      const int n = 8 * h + 4 * ks;
      mma16816(s1[h], x[n], x[n + 1], x[n + 2], x[n + 3], x[16 + n], x[18 + n]);
      mma16816(s2[h], x[n], x[n + 1], x[n + 2], x[n + 3], x[17 + n], x[19 + n]);
      mma16816(s0[h], x[n], x[n + 1], x[n + 2], x[n + 3], k0[h][2 * ks], k0[h][2 * ks + 1]);
    }
  const uint32_t mask = r[A_MASK];
  const bool after[2] = {(mask & 1) != 0, (int)mask < 0};
  float lt[2][2], lu[2][2], mt[2], mu[2];
#pragma unroll
  for (int h = 0; h < 2; h++) {
#pragma unroll
    for (int y = 0; y < 2; y++) {
      lt[h][y] = fmaf(after[y] ? s0[h][y] : s1[h][y], __uint_as_float(r[A_CT + y]), __uint_as_float(r[A_BIAS + y]));
      lu[h][y] = (after[y] ? s1[h][2 + y] : s2[h][2 + y]) * __uint_as_float(r[A_CU + y]);
    }
    mt[h] = fmaxf(lt[h][0], lt[h][1]);
    mu[h] = fmaxf(lu[h][0], lu[h][1]);
  }
#pragma unroll
  for (int d = 1; d <= 2; d++)
#pragma unroll
    for (int h = 0; h < 2; h++) {
      mt[h] = fmaxf(mt[h], __shfl_xor_sync(~0u, mt[h], d));
      mu[h] = fmaxf(mu[h], __shfl_xor_sync(~0u, mu[h], d));
    }
  float o[2][4][4];
#pragma unroll
  for (int h = 0; h < 2; h++) {
#pragma unroll
    for (int y = 0; y < 2; y++) { lt[h][y] = ex2(lt[h][y] - mt[h]); lu[h][y] = ex2(lu[h][y] - mu[h]); }
    const uint32_t pt = pack_bf16(lt[h][0] * __uint_as_float(r[A_KT]), lt[h][1] * __uint_as_float(r[A_KT + 1]));
    const uint32_t pu = pack_bf16(lu[h][0] * __uint_as_float(r[A_KU]), lu[h][1] * __uint_as_float(r[A_KU + 1]));
#pragma unroll
    for (int n = 0; n < 4; n++) {
      o[h][n][0] = o[h][n][1] = o[h][n][2] = o[h][n][3] = 0.f;
      mma16816(o[h][n], pt & ~mask, pu & mask, 0u, pu & ~mask, v12[2 * h + n / 2][n % 2 * 2], v12[2 * h + n / 2][n % 2 * 2 + 1]);
    }
#pragma unroll
    for (int n = 0; n < 4; n++) mma1688(o[h][n], pt & mask, 0u, v0[h][n]);
    mt[h] = lt[h][0] + lt[h][1];
    mu[h] = lu[h][0] + lu[h][1];
  }
#pragma unroll
  for (int d = 1; d <= 2; d++)
#pragma unroll
    for (int h = 0; h < 2; h++) {
      mt[h] += __shfl_xor_sync(~0u, mt[h], d);
      mu[h] += __shfl_xor_sync(~0u, mu[h], d);
    }
  uint32_t dep = 0;
#pragma unroll
  for (int n = 0; n < 3; n++) dep |= __float_as_uint(o[n % 2][n / 2][0]);
  mbar_arrive_warp(sm.mma_done() + (dep & r[A_ZERO]));
  TRC(ji, 22);
  if (W == 7) {
    ulonglong2* exp = SCR(sm, halo, (block * 256 + lane) * 16);
#pragma unroll
    for (int m = 0; m < 8; m++)
      asm volatile("st.relaxed.gpu.global.v2.u64 [%0], {%1,%2};" ::"l"(exp + m * 32), "l"(((u64)tag << 32) | x[17 + 4 * m]), "l"(((u64)tag << 32) | x[19 + 4 * m]) : "memory");
  }
#pragma unroll
  for (int h = 0; h < 2; h++) {
    const float rt = rcp(mt[h]), ru = rcp(mu[h]);
#pragma unroll
    for (int n = 0; n < 4; n++) {
      r[8 * h + 2 * n] = pack_bf16(o[h][n][0] * rt, o[h][n][1] * rt);
      r[8 * h + 2 * n + 1] = pack_bf16(o[h][n][2] * ru, o[h][n][3] * ru);
    }
  }
  return next_full;
}
__device__ __forceinline__ void import_halo(const Smem& sm, const ulonglong2* halo, uint32_t tag, int lane) {
  u64 x[16];
  for (uint32_t n = 0;; n++) {
#pragma unroll
    for (int m = 0; m < 8; m++)
      asm volatile("ld.relaxed.gpu.global.v2.u64 {%0,%1}, [%2];" : "=l"(x[2 * m]), "=l"(x[2 * m + 1]) : "l"(halo + m * 32) : "memory");
    uint32_t bad = 0;
#pragma unroll
    for (int m = 0; m < 16; m++) bad |= (uint32_t)(x[m] >> 32) ^ tag;
    if (__all_sync(~0u, bad == 0)) break;
    __nanosleep(V_SL3);
    if (n > SPIN_LIMIT) __trap();
  }
  const uint32_t a = sm.slot(0) + 4096 + (lane & 7) * 128 + (((lane >> 3) ^ (lane & 7)) << 4);
#pragma unroll
  for (int m = 0; m < 4; m++) stsm4((a ^ ((m & 1) * 64)) + (m >> 1) * 2048, (uint32_t)x[4 * m], (uint32_t)x[4 * m + 1], (uint32_t)x[4 * m + 2], (uint32_t)x[4 * m + 3]);
}
__device__ __forceinline__ void unpack8(uint4 v, float* f) {
  f[0] = bf_lo(v.x); f[1] = bf_hi(v.x); f[2] = bf_lo(v.y); f[3] = bf_hi(v.y);
  f[4] = bf_lo(v.z); f[5] = bf_hi(v.z); f[6] = bf_lo(v.w); f[7] = bf_hi(v.w);
}
__device__ __forceinline__ void boundary_rows(const Smem& sm, int h, int lane, uint32_t out) {
  const int i = lane >> 2, u = h * 4 + (lane & 3);
  uint4 r[8];
  float x[8], l[8], ik[8];
  unpack8(lds128(sm.slot(0) + 2048 + i * 128 + ((u ^ i) << 4)), x);
#pragma unroll
  for (int j = 0; j < 8; j++) {
    r[j] = lds128(sm.slot(0) + j * 128 + (j > i ? 4096 : 0) + ((u ^ j) << 4));
    ik[j] = lds32f(sm.stats() + j * 8 + (j > i ? 0 : 64));
  }
  const float cq = lds32f(sm.stats() + 64 + i * 8) * LOGIT_SCALE;
#pragma unroll
  for (int j = 0; j < 8; j++) {
    float kf[8];
    unpack8(r[j], kf);
    r[j] = lds128(sm.slot(0) + j * 128 + (j > i ? 6144 : 8192) + ((u ^ j) << 4));
    l[j] = 0.f;
#pragma unroll
    for (int d = 0; d < 8; d++) l[j] = fmaf(x[d], kf[d], l[j]);
  }
#pragma unroll
  for (int d = 1; d <= 2; d++)
#pragma unroll
    for (int j = 0; j < 8; j++) l[j] += __shfl_xor_sync(~0u, l[j], d);
  float m = MASKED, sum = 0.f;
#pragma unroll
  for (int j = 0; j < 8; j++) { l[j] *= cq * ik[j]; m = fmaxf(m, l[j]); }
#pragma unroll
  for (int j = 0; j < 8; j++) { l[j] = ex2(l[j] - m); sum += l[j]; }
  const float rs = rcp(sum);
#pragma unroll
  for (int d = 0; d < 8; d++) x[d] = 0.f;
#pragma unroll
  for (int j = 0; j < 8; j++) {
    const float pw = l[j] * ik[j] * rs;
    float vf[8];
    unpack8(r[j], vf);
#pragma unroll
    for (int d = 0; d < 8; d++) x[d] = fmaf(pw, vf[d], x[d]);
  }
  stg128(SCR(sm, o, out + i * (2 * D) + u * 16), make_uint4(pack_bf16(x[0], x[1]), pack_bf16(x[2], x[3]), pack_bf16(x[4], x[5]), pack_bf16(x[6], x[7])));
}
__device__ __forceinline__ uint32_t swiglu2(uint32_t g, uint32_t u, float hinv, float hinv2) {
  const float a = bf_lo(g) * hinv, b = bf_hi(g) * hinv, a2 = bf_lo(g) * hinv2, b2 = bf_hi(g) * hinv2;
  return bf2_mul(pack_bf16(fmaf(a2, tanh_fast(a), a2), fmaf(b2, tanh_fast(b), b2)), u);
}

__device__ __forceinline__ const uint32_t* dep_counter(const Smem& sm, uint32_t jw, int rank, uint32_t k) {
  const Job J(jw);
  const uint32_t b = J.R * 2 + rank;
  const uint32_t line = J.type == T_O ? C_O + J.layer * 16 + b : J.type == T_D ? C_H + J.layer * 16 + b : C_X + max((int)J.inst() - 1, 0) * 16 + b;
  return counter(line, J.type & 1 ? k >> (J.type >> 1) : (k >> 2) * 2 + (k & 1));
}
__device__ __forceinline__ void producer(const Params& P, const Smem& sm, const uint32_t* jobs, const uint8_t* kseq, int rank, int lane, uint32_t launches) {
  const uint32_t e1 = __shfl_sync(~0u, launches, 0) + 1;
  uint32_t s = (jobs[0] & JOB_C) ? 0 : NSTAGE;
  uint32_t end = 0, poll = 0;
  uint64_t keep, stream;
  asm("createpolicy.fractional.L2::evict_unchanged.b64 %0, 1.0;" : "=l"(keep));
  asm("createpolicy.fractional.L2::evict_first.b64 %0, 1.0;" : "=l"(stream));
  const uint32_t* dep = counter(0, 0);
  const uint32_t summed_end = (jobs[0] & JOB_C) ? 0 : D / 64 + NSTAGE;
  for (int ji = 0;; ji++) {
    const uint32_t jw = jobs[ji];
    const Job J(jw);
    if (J.nk == 0) break;
    const bool isC = jw & JOB_C, isX = isC && (jw & JOB_X);
    const uint32_t target = (jw & 7) == 0 ? 0 : e1 * (J.type == T_Q ? 56 : J.type == T_G ? 16 : 1);
    const uint32_t g = J.col * 2 + rank;
    const CUtensorMap* tmA = &P.a[isC ? 4 + isX : (jw & 7) == 4 ? 2 : J.type];
    const CUtensorMap* tmB = &P.w[J.type];
    const uint32_t bytes = isC ? 32768 : J.type == T_Q ? 40960 : STAGE, bcol = J.col << (J.type == T_Q ? 0 : J.type == T_G ? 1 : 2);
    const uint32_t a0 = isX ? 0 : (g >> 2) * 128 + (g & 1) * 64, a1 = isX ? g * 64 : J.R * 128, ak = isX ? 0 : 256, a2 = isC ? (g >> 1) & 1 : rank;
    end += J.nk;
    uint32_t sa = s, spins = 0;
    auto issue_a = [&](uint32_t k) { TRS(sa, 1); tma3d(sm.stage(sa), tmA, isC ? a0 : (k & 63) * 64, isC ? a1 + k * ak : a1, isX ? k * 4 : a2, sm.full(sa), (k & K_LAST_A) ? stream : keep); };
    auto issue_b = [&](uint32_t k) {
      mbar_expect_tx(sm.full(s), bytes);
      TRS(s, 0);
      if (!isC) tma4d_mc(sm.stage(s) + SLOT + rank * SLOT, tmB, (k & 63) * 64 + rank * 32, bcol, sm.full(s), (k & K_LAST_B) ? stream : keep);
    };
    TRI(lane == 0, ji, 6);
    TRK(lane == 0, ji, 24);
    while (true) {
      const uint32_t missing = __ballot_sync(~0u, (int)(poll - target) < 0 && lane < J.nk);
      uint32_t lim = end;
      if (missing) lim += __ffs(missing) - 1 - J.nk;
      if (lim > sa) {
        fence_acquire();
        fence_proxy_async();
        TRI(sa == end - J.nk && lane == 0, ji, 7);
#pragma unroll 1
        for (; sa < min(lim, s); sa++) {
          const uint32_t k = kseq[sa];
          if (elect()) issue_a(k);
        }
#pragma unroll 1
        for (int phase = 0;; phase++) {
          const uint32_t upto = phase == 2 ? lim : phase == 1 ? lim - LOOK : min((int)lim - LOOK, (int)sa + MID);
#pragma unroll 1
          for (; (int)sa < (int)upto; sa++, s++) {
            const uint32_t k = kseq[s];
            uint32_t stage = sm.stage(s), bar = sm.full(s), c0 = isC ? a0 : (k & 63) * 64, c1 = isC ? a1 + k * ak : a1, kb = (k & 63) * 64 + rank * 32, c2 = isX ? k * 4 : a2;
            uint64_t pa = (k & K_LAST_A) ? stream : keep, pb = (k & K_LAST_B) ? stream : keep;
            asm volatile("" : "+r"(stage), "+r"(bar), "+r"(c0), "+r"(c1), "+r"(kb), "+r"(c2), "+l"(pa), "+l"(pb));
            if (s < summed_end) mbar_wait(sm.summed(s), par(s) ^ 1);
            mbar_wait(bar + 32, par(s) ^ 1);
            TRS(s, 0);
            asm volatile("{\n.reg .pred p, q;\nelect.sync _|p, -1;\nsetp.eq.and.u32 q, %14, 0, p;\n"
                         "@q cp.async.bulk.tensor.4d.shared::cluster.global.mbarrier::complete_tx::bytes.multicast::cluster.L2::cache_hint [%3], [%4, {%5, %6, %7, %5}], [%0], %8, %9;\n"
                         "@p cp.async.bulk.tensor.3d.shared::cluster.global.mbarrier::complete_tx::bytes.L2::cache_hint [%2], [%10, {%11, %12, %13}], [%0], %15;\n"
                         "@p mbarrier.arrive.expect_tx.shared::cta.b64 _, [%0], %1;\n}"
                         ::"r"(bar), "r"(bytes), "r"(stage), "r"(stage + SLOT + rank * SLOT), "l"(tmB), "r"(0), "r"(kb), "r"(bcol), "h"((uint16_t)3), "l"(pb),
                           "l"(tmA), "r"(c0), "r"(c1), "r"(c2), "r"((uint32_t)isC), "l"(pa) : "memory");
            TRS(s, 1);
          }
          if (phase == 2) break;
          if (phase == 1) poll = ld_relaxed(dep);
          else if (lim == end) dep = dep_counter(sm, jobs[ji + 1], rank, (reinterpret_cast<const uint32_t*>(kseq)[(end + lane) >> 2] >> ((end + lane) % 4 * 8)) & 63);
        }
        if (lim == end) break;
      } else {
        if (s < min(end, sa + NSTAGE) && __all_sync(~0u, mbar_test(sm.empty(s), par(s) ^ 1))) {
          const uint32_t k = kseq[s];
          if (s < summed_end) mbar_wait(sm.summed(s), par(s) ^ 1);
          if (elect()) issue_b(k);
          s++;
        }
        poll = ld_relaxed(dep);
        if (++spins > SPIN_LIMIT) __trap();
      }
    }
    TRI(lane == 0, ji, 8);
  }
}

__global__ void __cluster_dims__(2, 1, 1) __launch_bounds__(384, 1) mega_kernel(char* scratch, uint32_t by_place, const __grid_constant__ Params P) {
#undef TRW
#define TRW warp
  extern __shared__ __align__(1024) uint8_t smem_raw[];
  TRX(threadIdx.x == 320, JMAX - 1, 0, 1, "%%globaltimer_lo");
  TRX(threadIdx.x == 320, JMAX - 1, 0, 25, "%%clock");
  TRX(threadIdx.x == 320, JMAX - 1, 0, 28, "%%smid");
  Smem sm;
  sm.scratch = scratch;
  sm.base = smem_u32(smem_raw);
  if ((sm.base & 0x3FFFF) != SMEM_BASE) __trap();
  const int warp = __shfl_sync(~0u, threadIdx.x >> 5, 0);
  const int rank = blockIdx.x & 1;
  uint32_t smid;
  asm("mov.u32 %0, %%smid;" : "=r"(smid));
  const uint32_t pair = !by_place ? blockIdx.x >> 1 : smid < 2 * NPAIR - 8 ? (smid >> 1) + 4 : (smid >> 1) + 4 - NPAIR;
  const uint32_t* jobs = P.jobs[pair];
  const uint32_t launches = ld_relaxed(counter(C_EP, blockIdx.x + threadIdx.y));
  if (warp == 10) {
    if (elect()) {
      for (int i = 0; i < NSTAGE; i++) mbar_init(sm.full(i), 1);
      mbar_init(sm.boot(), 1);
      asm volatile("fence.mbarrier_init.release.cluster;" ::: "memory");
    }
    cluster_arrive();
    const uint32_t first = jobs[0];
    const bool isC = first & JOB_C;
    if (elect()) {
      prefetch_tm(&P.a[0]);
      prefetch_tm(&P.w[0]);
    }
    uint64_t keep;
    asm("createpolicy.fractional.L2::evict_unchanged.b64 %0, 1.0;" : "=l"(keep));
    const Job J(first);
    if (!isC) {
      if (elect()) {
        mbar_expect_tx(sm.full(0), 40960);
        tma3d(sm.stage(0), &P.a[0], 0, J.R * 128, rank, sm.full(0), keep);
        TRS(0, 1);
      }
      TRX(threadIdx.x == 320, JMAX - 1, 0, 26, "%%clock");
      cluster_wait();
      TRX(threadIdx.x == 320, JMAX - 1, 0, 27, "%%clock");
      if (elect()) {
        tma4d_mc(sm.stage(0) + SLOT + rank * SLOT, &P.w[0], rank * 32, J.col, sm.full(0), keep);
        TRS(0, 0);
      }
#pragma unroll 1
      for (int k = 1; k < NSTAGE; k++) {
        if (elect()) {
          tma4d_mc(sm.stage(k) + SLOT + rank * SLOT, &P.w[0], k * 64 + rank * 32, J.col, sm.full(k), keep);
          TRS(k, 0);
          mbar_expect_tx(sm.full(k), 40960);
          tma3d(sm.stage(k), &P.a[0], k * 64, J.R * 128, rank, sm.full(k), keep);
          TRS(k, 1);
        }
      }
    } else {
      cluster_wait();
      if (!(first & JOB_X)) mbar_wait(sm.boot(), 0);
    }
  } else {
    if (warp < 8 && elect()) {
      mbar_init(sm.kv_ready(warp), 1);
      if (warp == 3) {
        mbar_init(sm.aux_full(), 3); mbar_init(sm.wgmma_done(), 4); mbar_init(sm.mma_done(), 8); mbar_init(sm.xchg_full(), 1); mbar_init(sm.kv_ready(-1), 1);
        mbar_expect_tx(sm.xchg_full(), 768);
      } else if (warp > 3) {
        mbar_init(sm.empty(warp), 4); mbar_init(sm.summed(warp), 6); mbar_init(sm.filled(warp - 4), 4); mbar_init(sm.vacant(warp - 4), 3);
      }
      asm volatile("fence.mbarrier_init.release.cluster;" ::: "memory");
    }
    cluster_arrive();
  }
  TRI(threadIdx.x == 0, JMAX - 1, 0);

  if (warp < 8) {
    asm volatile("setmaxnreg.inc.sync.aligned.u32 208;");
    const uint32_t e1 = launches + 1;
    cluster_wait();
    const uint32_t wg = warp >> 2;
    uint32_t rel = (threadIdx.x & 95) == 0 ? mapa(sm.empty(0), (threadIdx.x & 32) ? rank ^ 1 : rank) : 0;
    uint32_t dst = sm.slot(0) + (warp & 3) * 2048 + (threadIdx.x & 15) * 128 + ((((threadIdx.x >> 4) & 1) ^ (threadIdx.x & 7)) << 4);
    uint32_t t8 = sm.slot(0) + (warp & 3) * 2048 + (threadIdx.x & 7) * 128 + ((((threadIdx.x >> 3) & 3) ^ (threadIdx.x & 7)) << 4);
    rel = __shfl_sync(~0u, rel, threadIdx.x);
    dst = __shfl_sync(~0u, dst, threadIdx.x);
    t8 = __shfl_sync(~0u, t8, threadIdx.x);
    const uint32_t da0 = ((SMEM_BASE >> 4) | (1 << 16)) + wg * 512, dba = (255 << 16) + 1024 - wg * 512;
    uint32_t pend[64], todo = 0, pbar = 0, vbar = sm.vacant(0), ppar = 0, poff = 0, direct = 0;
    uint32_t s = 0, na = 0, nb = 0, ready = 0;
    auto release = [&](uint32_t st) { mbar_arrive_cl_if(rel, rel + (st & (NSTAGE - 1)) * 8); };
    auto flush = [&](bool vacant) {
      if (__all_sync(~0u, vacant)) {
        const uint32_t a = dst + poff;
        if (todo & 2) {
#pragma unroll
          for (int j = 0; j < 4; j++) stsm4(a ^ (j << 5), pend[4 * j], pend[4 * j + 1], pend[4 * j + 2], pend[4 * j + 3]);
          if (todo == 2) {
#pragma unroll
            for (int j = 0; j < 4; j++) stsm4((a ^ (j << 5)) + 8192, pend[16 + 4 * j], pend[17 + 4 * j], pend[18 + 4 * j], pend[19 + 4 * j]);
          }
        } else {
#pragma unroll
          for (int j = 0; j < 8; j++) stsm4((a ^ ((j & 3) << 5)) + (j >> 2) * 8192, pend[32 + 4 * j], pend[33 + 4 * j], pend[34 + 4 * j], pend[35 + 4 * j]);
        }
        mbar_arrive_warp(pbar);
        pbar += 16; vbar += 16; ppar = ~nb & 1;
        todo = todo == 2;
      }
    };
    uint32_t jw = jobs[0];
#pragma unroll
    for (int i = 0; i < 64; i++) pend[i] = 0;
    for (int ji = 0;; ji++) {
      const uint32_t cur = jw, nk = (jw >> 12) & 63, isQ = (jw & 3) == T_Q;
      jw = jobs[ji + 1];
      if (__builtin_expect((cur & JOB_C) || !ready, 0)) {
        for (uint32_t spins = 0; todo && ((cur & JOB_C) || !ready);) {
          if (direct && todo == 1) {
            vbar = sm.empty(s); ppar = par(s) ^ 1; poff = sm.stage(s) - sm.slot(0) + wg * SLOT;
          }
          flush(mbar_test(vbar, ppar));
          ready = __all_sync(~0u, mbar_test(sm.full(s), par(s)));
          if (++spins > SPIN_LIMIT) __trap();
        }
        if (cur & JOB_C) {
          if (nk == 0) break;
          TRC(ji, 16);
          constexpr uint32_t ONES = 0x3f803f80;
          const uint32_t lane = fresh_tid() & 31, g = ((cur >> 6) & 63) * 2 + rank;
          if (!(cur & JOB_X)) {
            float d[4] = {0.f, 0.f, 0.f, 0.f};
            sts32(sm.xchg() + 128 + lane * 4, ONES);
            fence_proxy_async_smem();
            bar_sync<9, 256>();
#pragma unroll 1
            for (int i = 0; i < 4; i++, s++) {
              mbar_wait(sm.full(s), par(s));
              if (!wg) sum_columns(d, da0 + (s & (NSTAGE - 1)) * (STAGE / 16), (SMEM_BASE + AUX_OFF + 1600 + 128) >> 4);
              release(s);
            }
            const float c = lane & 1 ? d[2] : d[0], c1 = __shfl_down_sync(~0u, c, 4);
            asm volatile("{\n.reg .pred p;\nsetp.eq.u32 p, %2, 0;\n@p st.relaxed.gpu.global.u64 [%0], %1;\n}"
                         ::"l"(SCR(sm, cs, (16 * 128 + g * 32 + (warp & 3) * 8 + (lane & 1) * 4 + (lane >> 3)) * 8)), "l"(((u64)e1 << 32) | pack_bf16(c, c1)), "r"((lane & 6) | wg) : "memory");
          } else {
            float a[6][4];
#pragma unroll
            for (int n = 0; n < 24; n++) pend[n] = 0;
#pragma unroll 1
            for (int i = 0;; i++) {
              const uint32_t p = dst - sm.slot(0) + sm.stage(s) + wg * SLOT;
              mbar_wait(sm.full(s), par(s));
              uint32_t v[8][4];
#pragma unroll
              for (int n = 0; n < 24; n++) a[n / 4][n % 4] = __uint_as_float(pend[n]);
#pragma unroll
              for (int j = 0; j < 8; j++) ldsm4((p ^ ((j & 3) << 5)) + (j >> 2) * 8192, v[j]);
#pragma unroll
              for (int j = 0; j < 8; j++) {
                mma16816(a[4 + (j & 1)], v[j][0], v[j][1], v[j][2], v[j][3], ONES, ONES);
#pragma unroll
                for (int n = 0; n < 4; n++) mma1688(a[n], v[j][n & 2], v[j][(n & 2) + 1], v[j][n]);
              }
#pragma unroll
              for (int n = 0; n < 24; n++) pend[n] = __float_as_uint(a[n / 4][n % 4]);
              if (i == 3) break;
              bar_sync<9, 256>();
              release(s++);
            }
            const uint32_t part = sm.stage(s) + 2 * SLOT + lane * 8, row = g * 64 + (warp & 3) * 16 + wg * 8 + (lane >> 2);
            const bool odd = lane & 4;
            const float s0 = a[4][0] + a[5][0], q0 = odd ? a[0][1] + a[2][1] : a[0][0] + a[2][0];
            const float s1 = a[4][2] + a[5][2], q1 = odd ? a[1][3] + a[3][3] : a[1][2] + a[3][2];
            sts64(part + warp * 256, make_uint2(__float_as_uint(wg ? s0 : s1), __float_as_uint(wg ? q0 : q1)));
            bar_sync<9, 256>();
            const uint2 o = lds64(part + (warp ^ 4) * 256);
            fence_proxy_async_smem();
            bar_sync<9, 256>();
            release(s++);
            publish_stats(sm, (wg ? s1 : s0) + __uint_as_float(o.x), (wg ? q1 : q0) + __uint_as_float(o.y), (row & 1) * (S / 2) + (row >> 1), (lane & 3) == lane >> 3, e1);
          }
          ready = 0;
          TRC(ji, 18);
          continue;
        }
        if (!ready) mbar_wait(sm.full(s), par(s));
      }
      auto mainloop = [&](auto& acc, uint32_t nk, uint32_t last_lead, auto near_end) {
        const uint32_t lead = (jw >> 12) % 64 == 0 ? min(last_lead, nk - 2) : 2, turn = wg ? lead : nk - 2, hurry = nk - lead - wg;
        uint32_t owed = 0;
        uint32_t da = da0 + (s & (NSTAGE - 1)) * (STAGE / 16);
        if (todo == 3) mbar_wait(vbar, ppar);
        if (wg) bar_sync<13, 256>();
        TRC(ji, 16);
        first_kstep(acc, da, da + dba);
        if (!wg) bar_arrive<13, 256>();
        constexpr uint32_t CLEAR = sizeof(acc) == 96 * 4 ? PREP + 2 : 3;
        for (uint32_t left = nk - 1;; left--) {
          for (uint32_t spins = 0;; spins++) {
            const bool vacant = mbar_test(vbar, ppar), next_full = mbar_test(sm.full(s + 1), par(s + 1));
            wg_wait<2>();
            mbar_arrive_cl_if(owed, owed + ((s - 1) & (NSTAGE - 1)) * 8);
            owed = 0;
            ready = __all_sync(~0u, next_full);
            if (!todo) {
              near_end(left, vacant);
              break;
            }
            const bool go = ready && left >= max(CLEAR, lead + 1);
            if (!(go && spins)) flush(vacant);
            if (go) break;
            if (spins > SPIN_LIMIT) __trap();
          }
          if (left == 0) break;
          if (!ready) mbar_wait(sm.full(s + 1), par(s + 1));
          owed = rel;
          if (left == turn) {
            wg_wait<0>();
            release(s);
            owed = 0;
            if (wg) bar_sync<1, 256>();
          }
          if (left - lead < hurry) wg_wait<1>();
          s++;
          da = da0 + (s & (NSTAGE - 1)) * (STAGE / 16);
          kstep(acc, da, da + dba);
          if (left == 1 + wg * 64) bar_arrive<1, 256>();
        }
      };
      if (isQ) {
        float acc[96];
        const uint32_t lane = (((dst - SMEM_BASE) >> 7) & 15) | ((dst ^ (dst >> 3)) & 16), qpar = (na ^ nb) & 1;
        uint32_t prepare_at = PREP;
        mainloop(acc, nk, LAST_LEAD, [&](uint32_t left, bool aux_full) {
          if (left == PREP + 1) {
            vbar = sm.aux_full(); ppar = qpar;
          } else if (left == prepare_at) {
            if (left == 0) mbar_wait(vbar, ppar);
            if (left == 0 || __all_sync(~0u, aux_full)) attention_prepare(pend, sm, warp, lane, !(cur & 0x38));
            else prepare_at--;
          }
        });
        wg_wait<0>();
        release(s);
        u64 token = 0;
        asm volatile("{\n.reg .pred p;\nsetp.eq.u32 p, %2, 0;\n@p mbarrier.arrive.shared::cta.b64 %0, [%1];\n}" : "+l"(token) : "r"(sm.wgmma_done()), "r"(lane + 1 - wg) : "memory");
        pend[A_NM + 1] |= (uint32_t)token & pend[A_ZERO];
        TRC(ji, 18);
        ready = __all_sync(~0u, attention(acc, pend, sm, warp, lane, t8, dst, cur & JOB_EARLY, (((cur >> 2) & 1) * 16 + ((cur >> 3) & 7) * 2 + rank) * 16 + ((cur >> 6) & 15), e1, qpar,
                                          sm.full(s + 1), par(s + 1), ji));
        todo = 3; pbar = sm.filled(wg); vbar = sm.mma_done(); ppar = qpar; poff = SLOT + wg * 8192;
      } else {
        float acc[128];
        direct = (cur & 1) && (jw >> 12) % 64 == 0;
        const bool split = direct && nk >= SPLIT_MIN;
        mainloop(acc, split ? nk - 3 : nk, split ? 0 : LAST_LEAD, [](uint32_t, bool) {});
        pbar = sm.filled(wg); vbar = pbar + 32; ppar = na & 1; poff = wg * SLOT;
        nb++;
        todo = 2;
        if (__builtin_expect(split, 0)) {
          const uint32_t s0 = s;
          uint32_t d[3];
#pragma unroll
          for (int i = 0; i < 3; i++) d[i] = da0 + ((s0 + 1 + i) & (NSTAGE - 1)) * (STAGE / 16);
          wg_wait<0>();
          release(s0);
          float lo[64], hi[64];
#pragma unroll
          for (int i = 0; i < 64; i++) {
            asm volatile("mov.b32 %0, %1;" : "=f"(lo[i]) : "f"(acc[i]));
            asm volatile("mov.b32 %0, %1;" : "=f"(hi[i]) : "f"(acc[64 + i]));
          }
          if (wg) {
            bar_sync<1, 256>();
            bar_sync<3, 256>();
          }
          mbar_wait(sm.full(s0 + 1), par(s0 + 1));
          half_kstep0(lo, d[0], d[0] + dba);
          mbar_wait(sm.full(s0 + 2), par(s0 + 2));
          half_kstep0(lo, d[1], d[1] + dba);
          half_kstep1(hi, d[0], d[0] + dba);
          mbar_wait(sm.full(s0 + 3), par(s0 + 3));
          half_kstep0(lo, d[2], d[2] + dba);
          half_kstep1(hi, d[1], d[1] + dba);
          half_kstep1(hi, d[2], d[2] + dba);
          if (!wg) bar_arrive<3, 256>();
          s += 3;
          wg_wait<2>();
#pragma unroll
          for (int i = 0; i < 32; i++) pend[i] = pack_bf16(lo[2 * i], lo[2 * i + 1]);
          mbar_wait(vbar, ppar);
          flush(true);
          wg_wait<0>();
          TRC(ji, 18);
#pragma unroll
          for (int i = 0; i < 32; i++) pend[32 + i] = pack_bf16(hi[2 * i], hi[2 * i + 1]);
        } else {
          wg_wait<0>();
          release(s);
          const bool next_full = mbar_test(sm.full(s + 1), par(s + 1));
          TRC(ji, 18);
#pragma unroll
          for (int i = 0; i < 64; i++) {
            const int j = (i & 15) + (i & 16) * 2 + (i >> 5) * 16;
            pend[i] = pack_bf16(acc[2 * j], acc[2 * j + 1]);
          }
          ready = __all_sync(~0u, next_full);
        }
      }
      na++;
      s++;
    }
  } else {
    asm volatile("setmaxnreg.dec.sync.aligned.u32 88;");
    if (warp == 10) {
      producer(P, sm, jobs, P.kseq[pair], rank, threadIdx.x & 31, launches);
    } else {
      const uint32_t e1 = __shfl_sync(~0u, launches, 0) + 1;
      const int w = min(warp - 8, 2);
      cluster_wait();
      if (w == 1) asm volatile("st.shared::cluster.u32 [%0], %1;" ::"r"(mapa(sm.pair_id(), rank ^ 1)), "r"(pair) : "memory");
      const uint32_t boot = jobs[JMAX - 1] >> 24, pieces = (boot & 127) == 127 ? 0 : 1 + (boot >> 7), piece0 = (boot & 127) * 2 + rank * pieces;
      auto copy_rows = [&](uint32_t step, uint32_t n) {
        constexpr int IN = 2 * SLOT / BOOT_PIECES, OUT = 2 * SLOT / BOOT_OUT;
        const uint32_t rows = (piece0 + n) * 32768;
        if (step == BOOT_STEP) mbar_wait(sm.boot(), n & 1);
        if (elect()) {
          if (step == 0) mbar_expect_tx(sm.boot(), pieces ? 2 * SLOT : 0);
          if (step < BOOT_PIECES && pieces)
            asm volatile("cp.async.bulk.shared::cluster.global.mbarrier::complete_tx::bytes [%0], [%1], %2, [%3];"
                         ::"r"(sm.slot(0) + step * IN), "l"(at(P.x0, rows + step * IN)), "n"(IN), "r"(sm.boot()) : "memory");
          if (step - BOOT_STEP < BOOT_OUT && pieces) {
            asm volatile("cp.async.bulk.global.shared::cta.bulk_group [%0], [%1], %2;"
                         ::"l"(at(P.out, rows + (step - BOOT_STEP) * OUT)), "r"(sm.slot(0) + (step - BOOT_STEP) * OUT), "n"(OUT) : "memory");
            bulk_commit();
          }
        }
        if (step == BOOT_STEP + BOOT_OUT) {
          bulk_wait();
          if (n + 1 >= pieces && elect()) {
            mbar_arrive_n(sm.vacant(0), 3);
            mbar_arrive_n(sm.vacant(1), 3);
          }
        }
      };
      if (jobs[0] & JOB_C) {
        if (w == 2) {
          if (jobs[0] & JOB_X) mbar_wait(sm.full(3), 0);
#pragma unroll 1
          for (uint32_t n = 0; n == 0 || n < pieces; n++) {
#pragma unroll 1
            for (int i = 0; i <= BOOT_STEP + BOOT_OUT; i++) {
              copy_rows(i, n);
              bulk_wait_read<0>();
            }
          }
        }
      } else {
        const int lane = threadIdx.x & 31, word = (lane >> 3) * 24 + w * 8 + (lane & 7);
        Stager st;
        const uint32_t cs = qkv_col_sums(sm, rank, w, lane, [&](int s) {
          if (w == 2) copy_rows(s - 1, 0);
          if (w == 0 && s == ST_STEP) st.load(sm, Job(jobs[0]), rank, lane, false);
          if (w == 0 && s == ST_STEP + 2) st.store(sm, Job(jobs[0]), rank, lane, false, e1);
        });
        sts32(sm.sums() + word * 4, cs);
        mbar_arrive_warp(sm.aux_full());
        if ((jobs[0] & 0x38) == 0 && rank == 0) st_word(SCR(sm, cs, (((jobs[0] >> 6) & 15) * 128 + word) * 8), cs, e1);
      }
      bar_sync<2, 96>();
      if (w == 2 && pieces && elect()) {
        red_release(counter(C_RD + (piece0 >> 4) * 2, 0), pieces);
        red_relaxed(counter(C_RD + (piece0 >> 4) * 2 + 1, 0), pieces);
      }
      uint32_t na = 0, nb = 0, stages = 0;
      for (int ji = 0;; ji++) {
        const uint32_t jw = jobs[ji];
        const Job J(jw);
        if (J.nk == 0) break;
        stages += J.nk;
        if (w != 0 && ((jw >> 22) & 3) != 3) {
          stats_task(sm, jw, rank, w, e1, P.out);
          TRI(threadIdx.x == 11 * 32, ji, 10);
        }
        if (jw & JOB_C) continue;
        const int lane = fresh_tid() & 31;
        const uint32_t b = J.R * 2 + rank;
        if (w == 0 && !(J.type & 1) && ji != 0) {
          Stager st;
          st.load(sm, J, rank, lane, true);
          st.store(sm, J, rank, lane, true, e1);
          TRI(lane == 0, ji, 9);
        }
        if (J.type == T_G) {
          bar_sync<2, 96>();
          constexpr int PER = 16 / NG;
          const uint32_t swap = P.swap, never = jw, ac = sm.sums() + (lane & 7) * 16;
          uint32_t ag[NG], au[NG], as = sm.stats() + 64 + w * NG * 32 + (lane >> 3) * 8;
          uint32_t ho = (rank * (S / 2) + J.R * 128 + w * NG * 4 + (lane >> 3)) * (F * 2) + J.col * 256 + (lane & 7) * 16;
          uint4 cg = lds128(ac + (swap >> 5)), cu = lds128(ac + 256 - (swap >> 5)), g4[NG], u4[NG];
          uint2 st[NG];
          auto load = [&] {
#pragma unroll
            for (int i = 0; i < NG; i++) { st[i] = lds64v(as + i * 32); g4[i] = lds128v(ag[i]); u4[i] = lds128v(au[i]); }
          };
#pragma unroll
          for (int i = 0; i < NG; i++) {
            const uint32_t a = (sm.slot(0) + (w * NG + i) * 512 + (lane >> 3) * 128 + (((lane & 7) ^ (lane >> 3)) << 4)) ^ (((w * NG + i) & 1) << 6);
            ag[i] = a + swap; au[i] = a + (swap ^ 8192);
          }
          mbar_wait(sm.filled(0), na & 1);
          mbar_wait(sm.filled(1), na & 1);
          load();
          if (w == 2 && elect()) red_relaxed(counter(C_RD + J.inst() * 16 + b, 0), 1);
          TRI(threadIdx.x == 11 * 32, ji, 3);
#pragma unroll 1
          for (uint32_t g = w; g < 4 * PER; g += 3) {
            float hinv[NG], hinv2[NG];
            uint4 gc[NG], uc[NG];
            const bool turn = ((g + 3) ^ g) & PER, half = ((g + 3) ^ g) & (2 * PER);
#pragma unroll
            for (int i = 0; i < NG; i++) {
              hinv[i] = 0.5f * __uint_as_float(st[i].x);
              hinv2[i] = hinv[i] * __uint_as_float(st[i].x);
              asm volatile("" : "+f"(hinv[i]), "+f"(hinv2[i]));
              gc[i] = fma8(dup_hi(st[i].y), cg, g4[i]);
              uc[i] = fma8(dup_hi(st[i].y), cu, u4[i]);
              ag[i] = (ag[i] + NG * 1536) ^ ((NG & 1) << 6);
              au[i] = (au[i] + NG * 1536) ^ ((NG & 1) << 6);
            }
            as += NG * 96;
            if (turn) {
              mbar_arrive_warp(sm.vacant((g / PER) ^ 2));
              if (half) {
                cg = lds128(ac + (swap >> 5) + 128); cu = lds128(ac + 384 - (swap >> 5));
                as -= 1024;
              }
#pragma unroll
              for (int i = 0; i < NG; i++) { ag[i] += half ? -3 * 8192 : 8192; au[i] += half ? -3 * 8192 : 8192; }
              TRX(threadIdx.x == 11 * 32 && g < 3 * PER, ji, 25, 25 + g / PER * 2, "%%clock");
              if (g < 3 * PER) mbar_wait(sm.filled(g / PER + 1), (g < PER ? na : nb) & 1);
              TRX(threadIdx.x == 11 * 32 && g < 3 * PER, ji, 25, 26 + g / PER * 2, "%%clock");
            }
            load();
            if (g == never) mbar_wait(sm.boot(), 0);
            bf16* out = SCR(sm, h, ho);
#pragma unroll
            for (int i = 0; i < NG; i++)
              stg128(out + i * 4 * F, make_uint4(swiglu2(gc[i].x, uc[i].x, hinv[i], hinv2[i]), swiglu2(gc[i].y, uc[i].y, hinv[i], hinv2[i]),
                                                 swiglu2(gc[i].z, uc[i].z, hinv[i], hinv2[i]), swiglu2(gc[i].w, uc[i].w, hinv[i], hinv2[i])));
            ho += NG * 12 * F * 2 - (half ? 128 * F * 2 - 128 : 0);
          }
          bar_sync<2, 96>();
          TRI(threadIdx.x == 11 * 32, ji, 4);
          if (w == 2 && elect()) red_release(counter(C_H + J.layer * 16 + b, J.col), 1);
          TRI(threadIdx.x == 11 * 32, ji, 5);
        } else if (J.type == T_Q) {
          const bool late = J.R > 0 && !(jw & JOB_EARLY);
          if (w == 0) {
            __syncwarp();
            if (ji != 0 && elect()) mbar_arrive_n(sm.aux_full(), 3);
#pragma unroll 1
            for (int phase = 0; phase < 2; phase++) {
              if (J.R > 0 && phase == late) import_halo(sm, SCR(sm, halo, (((J.layer * 16 + b - 2) * 16 + J.col) * 256 + lane) * 16), e1, lane);
              if (phase == 0) {
                mbar_arrive_warp(sm.kv_ready(-1));
                TRI(lane == 0, ji, 11);
#pragma unroll 1
                for (int h = 0; h < 2; h++) {
                  mbar_wait(sm.filled(h), na & 1);
                  TRI(lane == 0, ji, 3);
                  fence_proxy_async_smem();
                  bulk_wait_read<0>();
                  if (elect()) {
                    tma3d_store(&P.ow, J.col * 64, J.R * 128 + h * 64, rank, sm.slot(1) + h * 8192);
                    bulk_commit();
                  }
                }
                if (J.layer && elect()) red_relaxed(counter(C_RD + 32 + b, 0), 1);
              }
            }
            bulk_wait();
          }
          if (late && w < 2) {
            bar_sync<7, 64>();
            boundary_rows(sm, w, lane, rank * O_PLANE + J.R * 128 * (D * 2) + J.col * 128);
            bar_sync<7, 64>();
          }
          TRI(threadIdx.x == 256, ji, 4);
          if (w == 0 && elect()) {
            mbar_arrive_n(sm.vacant(0), 3);
            mbar_arrive_n(sm.vacant(1), 3);
            red_release(counter(C_O + J.layer * 16 + b, J.col), 1);
          }
          TRI(threadIdx.x == 256, ji, 5);
        } else if (w == 0) {
          wait_count(counter(C_RD + J.inst() * 16 + b, 0), e1 * (J.type == T_D ? 28 : 16));
          fence_proxy_async();
          const bool last = Job(jobs[ji + 1]).nk == 0, split = last && J.nk >= SPLIT_MIN;
#pragma unroll 1
          for (uint32_t v = 0; v < 4; v++) {
            const uint32_t u = last ? (v >> 1) + (v & 1) * 2 : v;
            mbar_wait(sm.filled(u), (u & 2 ? nb : na) & 1);
            TRI(u == 0 && lane == 0, ji, 3);
            fence_proxy_async_smem();
            const uint32_t src = (last && (u & 2) ? sm.stage(stages) : sm.slot(0)) + (u & 1) * SLOT;
#pragma unroll 1
            for (uint32_t p = 0; p < 16384 / PIECE; p++) {
              if (elect()) {
                tma3d_reduce_add(&P.xr, J.col * 256 + (split ? (u & 2) * 64 + p * PIECE / 8192 * 64 : (u & 2) * 32 + p * PIECE / 8192 * 128), J.R * 128 + (u & 1) * 64 + p * PIECE % 8192 / 128, rank, src + p * PIECE);
                bulk_commit();
              }
              if (!last) bulk_wait_read<DEPTH - 1>();
            }
            if (!last) {
              bulk_wait();
              if (elect()) mbar_arrive_n(sm.vacant(u ^ 2), 3);
            }
            if (u == 1 && J.inst() != 3) bar_arrive<8, 64>();
          }
          bulk_wait();
        }
        if ((J.type & 1) && J.inst() != 3 && w < 2) {
          if (w == 1) bar_sync<8, 64>();
          TRX(lane == 0, ji, 4, w ? 12 : 4, "%%globaltimer_lo");
          if (elect()) red_release(counter(C_X + J.inst() * 16 + b, J.col * 2 + 1 - w), J.nk);
          TRX(lane == 0, ji, 5, w ? 13 : 5, "%%globaltimer_lo");
          if (w == 1) bar_arrive<10, 64>(); else bar_sync<10, 64>();
        }
        na++;
        nb += J.type != T_Q;
      }
      TRI(threadIdx.x == 8 * 32, JMAX - 1, 6);
      TRK(threadIdx.x == 8 * 32, JMAX - 1, 24);
      if (w == 0 && elect()) red_relaxed(counter(C_EP, blockIdx.x), 1);
      if (w == 2 && __float_as_uint(lds32f(sm.pair_id())) != pair) __trap();
    }
  }
  cluster_arrive();
  cluster_wait();
}

typedef CUresult (*EncodeFn)(CUtensorMap*, CUtensorMapDataType, cuuint32_t, void*, const cuuint64_t*, const cuuint64_t*, const cuuint32_t*,
                             const cuuint32_t*, CUtensorMapInterleave, CUtensorMapSwizzle, CUtensorMapL2promotion, CUtensorMapFloatOOBfill);
struct Dim { cuuint64_t size, stride; cuuint32_t box; };
template <int N> void encode(EncodeFn fn, CUtensorMap* m, const void* ptr, const Dim (&d)[N]) {
  cuuint64_t dims[N], strides[N];
  cuuint32_t box[N], es[N];
  for (int i = 0; i < N; i++) { dims[i] = d[i].size; strides[i] = d[i].stride; box[i] = d[i].box; es[i] = 1; }
  fn(m, CU_TENSOR_MAP_DATA_TYPE_BFLOAT16, N, const_cast<void*>(ptr), dims, strides + 1, box, es, CU_TENSOR_MAP_INTERLEAVE_NONE,
     CU_TENSOR_MAP_SWIZZLE_128B, CU_TENSOR_MAP_L2_PROMOTION_L2_128B, CU_TENSOR_MAP_FLOAT_OOB_FILL_NONE);
}

}

extern "C" void kernel_launch(void* const* d_in, const int* in_sizes, int n_in, void* d_out, int out_size) {
  (void)in_sizes; (void)n_in; (void)out_size;
  static EncodeFn fn = nullptr;
  static Scratch* scr;
  static int sms;
  if (!fn) {
    void* p = nullptr;
    cudaDriverEntryPointQueryResult q;
    cudaGetDriverEntryPoint("cuTensorMapEncodeTiled", &p, cudaEnableDefault, &q);
    fn = (EncodeFn)p;
    scr = scratch_base();
    int device = 0;
    cudaGetDevice(&device);
    cudaDeviceGetAttribute(&sms, cudaDevAttrMultiProcessorCount, device);
    cudaFuncSetAttribute(mega_kernel, cudaFuncAttributeMaxDynamicSharedMemorySize, SMEM_BYTES);
  }
  static Params P;
  const char *wg = (const char*)d_in[4], *wu = (const char*)d_in[5], *w0 = wg < wu ? wg : wu;
  const cuuint64_t plane = wg < wu ? wu - wg : wg - wu;
  P.swap = wg < wu ? 0 : 8192;
  encode(fn, &P.a[0], d_in[0], {{D, 2, 64}, {S / 2, D * 4, 128}, {2, D * 2, 1}});
  encode(fn, &P.a[1], scr->o, {{D, 2, 64}, {S / 2, D * 2, 128}, {2, O_PLANE, 1}});
  encode(fn, &P.ow, scr->o, {{D, 2, 64}, {S / 2, D * 2, 64}, {2, O_PLANE, 1}});
  encode(fn, &P.a[2], d_out, {{D, 2, 64}, {S / 2, D * 4, 128}, {2, D * 2, 1}});
  encode(fn, &P.a[3], scr->h, {{F, 2, 64}, {S / 2, F * 2, 128}, {2, (cuuint64_t)F * S, 1}});
  encode(fn, &P.a[4], w0, {{F, 2, 64}, {D, F * 2, 256}, {2, plane, 1}});
  encode(fn, &P.a[5], d_in[0], {{64, 2, 64}, {S, D * 2, 64}, {16, 128, 4}});
  encode(fn, &P.w[T_Q], d_in[1], {{64, 2, 64}, {D, 3 * D * 2, 32}, {16, 128, 1}, {3, D * 2, 3}});
  encode(fn, &P.w[T_O], d_in[2], {{64, 2, 64}, {D, D * 2, 32}, {16, 128, 4}, {1, (cuuint64_t)D * D * 2, 1}});
  encode(fn, &P.w[T_G], w0, {{64, 2, 64}, {D, F * 2, 32}, {F / 64, 128, 2}, {2, plane, 2}});
  encode(fn, &P.w[T_D], d_in[6], {{64, 2, 64}, {F, D * 2, 32}, {16, 128, 4}, {1, (cuuint64_t)F * D * 2, 1}});
  encode(fn, &P.xr, d_out, {{D, 2, 64}, {S / 2, D * 4, PIECE / 128}, {2, D * 2, 1}});
  memcpy(P.jobs, kJobs, sizeof(kJobs));
  memcpy(P.kseq, kSeq, sizeof(kSeq));
  P.x0 = (const bf16*)d_in[0];
  P.wqkv = (const bf16*)d_in[1];
  P.out = (bf16*)d_out;
  mega_kernel<<<2 * NPAIR, 384, SMEM_BYTES>>>((char*)scr, sms == 2 * NPAIR, P);
}
```

```cpp
#include <cuda_runtime.h>
#include <cuda_bf16.h>
#include <cuda.h>
#include <stddef.h>
#include <stdint.h>
#include <string.h>

namespace {

typedef __nv_bfloat16 bf16;
typedef unsigned long long u64;
constexpr int S = 2048, D = 1024, F = 3584;
constexpr int STAGE = 49152, NSTAGE = 4, SLOT = 16384;
constexpr int STG_OFF = NSTAGE * STAGE, BAR_OFF = STG_OFF + 2 * SLOT, AUX_OFF = BAR_OFF + 336;
constexpr int SMEM_BYTES = AUX_OFF + 2736;
constexpr int SMEM_BASE = 1024;
constexpr int NPAIR = 66, JMAX = 24, KMAX = 296;
constexpr int T_Q = 0, T_O = 1, T_G = 2, T_D = 3;
constexpr uint32_t JOB_C = 1u << 18;
constexpr uint32_t K_LAST_A = 64, K_LAST_B = 128;
constexpr uint32_t JOB_EARLY = 1u << 21;
constexpr uint32_t JOB_X = JOB_EARLY;
constexpr int BOOT_PIECES = 4, BOOT_OUT = 8, BOOT_STEP = 5, ST_STEP = 9;
constexpr int SPLIT_MIN = 6;
constexpr int PREP = 3, LAST_LEAD = 3;
constexpr int LOOK = 2, MID = 7;
constexpr int NG = 2, PIECE = 8192, DEPTH = 2;
constexpr uint32_t SPIN_LIMIT = 1u << 21;

constexpr int C_X = 0;
constexpr int C_O = C_X + 48;
constexpr int C_H = C_O + 32;
constexpr int C_RD = C_H + 32;
constexpr int C_EP = C_RD + 64;
constexpr int C_LINES = C_EP + 5;

struct Scratch {
  bf16 h[S * F];
  uint32_t cnt[256 * 32];
  bf16 o[S / 2 * D];
  u64 stats[4 * S];
  bf16 o1[S / 2 * D];
  u64 cs[44 * 128];
  ulonglong2 halo[2 * 16 * 16 * 8 * 32];
};
constexpr uint32_t O_PLANE = offsetof(Scratch, o1) - offsetof(Scratch, o);
static_assert(C_LINES <= 256, "");
constexpr size_t PAGE = 2 << 20;
__device__ __align__(1024) char g_scratch[sizeof(Scratch) + PAGE];
Scratch* scratch_base() {
  char* p;
  cudaGetSymbolAddress((void**)&p, g_scratch);
  return (Scratch*)(p + (-(size_t)p & (PAGE - 1)));
}

uint32_t kJobs[NPAIR][JMAX] = {
  {0xe44200,0xc10020,0xc44040,0xc08009,0xc10082,0x4101001a,0xc10022,0xc1800b,0x184170b3,0x46610054,0x5b610034,0x7d41000e,0xc1001e,0xc10076,0xc10096,0xc14037,0xc40000,0xc40000,0xc40000,0xc40000,0xc40000,0xc40000,0xc40000,0x80c40000},
  {0xe44000,0xc10018,0xc44080,0xc08009,0xc10021,0x22010052,0xc10092,0xc100aa,0xc09013,0x16410004,0x2d61004c,0x3461002c,0x4e410086,0xc10056,0x618100ae,0xc100b6,0xc1b02f,0xc40000,0xc40000,0xc40000,0xc40000,0xc40000,0xc40000,0x82c40000},
  {0xc10000,0xc44140,0xc04001,0xc10042,0x3a01004a,0xc1006a,0xc100b2,0xc1201b,0x26413033,0x6440b00d,0x681001d,0x3281002d,0xd48100a6,0xc101be,0xc1e007,0xc40000,0xc40000,0xc40000,0xc40000,0xc40000,0xc40000,0xc40000,0xc40000,0x7fc40000},
  {0xc10010,0xc440c0,0xc04001,0xc10002,0x3b01008a,0xc1019a,0xc101aa,0xc0800b,0x1a40d01b,0xc10014,0x66410064,0x2810006,0xc1008e,0xc10066,0xc1007e,0xc0e087,0xc1003f,0xc40000,0xc40000,0xc40000,0xc40000,0xc40000,0xc40000,0x7fc40000},
  {0xc10048,0xe10058,0xe10070,0xc05039,0x21010012,0x7a01b003,0xc1003a,0x29410044,0x3561001c,0x4f61005c,0x5761003c,0x7e41004e,0x6081009e,0xc100be,0xc1c00f,0xc40000,0xc40000,0xc40000,0xc40000,0xc40000,0xc40000,0xc40000,0xc40000,0x7fc40000},
  {0xe44240,0xc443c0,0xe10158,0xc10130,0xc040e1,0x170101ca,0x620101da,0xc101f2,0x641905b,0xc07063,0x324100c5,0x7a61016c,0x12a1013c,0x288101d6,0xc101ee,0xc10236,0xc1a04f,0xc40000,0xc40000,0xc40000,0xc40000,0xc40000,0xc40000,0x84c40000},
  {0xe44280,0xc44780,0xc10228,0x1f044840,0xe10270,0xc103ca,0x5e01039a,0xc103b2,0xc1042a,0xc103ba,0x6d4180bb,0x8810506,0xc100b5,0xd2810426,0xc103be,0xc1f097,0xc40000,0xc40000,0xc40000,0xc40000,0xc40000,0xc40000,0xc40000,0x86c40000},
  {0xe44380,0xc102d0,0xc040c1,0xc10091,0x1101044a,0x67010452,0xc1046a,0xc104f2,0x2c4170ab,0x5240e0bb,0x5810486,0xc104ce,0xc10466,0xc1047e,0xc1f09f,0xc40000,0xc40000,0xc40000,0xc40000,0xc40000,0xc40000,0xc40000,0xc40000,0x88c40000},
  {0xe442c0,0xc10320,0xc040c1,0x1d210338,0xc1054a,0x610105e2,0x7301e0cb,0xc10344,0xc1030c,0xc040bb,0x6041036c,0x1ca1033c,0x29810596,0x6c8105a6,0xc106f6,0xc1d0df,0xc40000,0xc40000,0xc40000,0xc40000,0xc40000,0xc40000,0xc40000,0x8ac40000},
  {0xe443c0,0xc10390,0xc44d80,0xc100d1,0x1501060a,0x64010612,0x720180c3,0x24106ba,0xc1038c,0x404103dc,0xc103f4,0x2c80c0e5,0x4d810656,0xc1066e,0xc1069e,0xc1a0ef,0xc40000,0xc40000,0xc40000,0xc40000,0xc40000,0xc40000,0xc40000,0x8cc40000},
  {0xc10088,0xe100e0,0xc10011,0x270100ca,0x6c01015a,0x7c01800b,0xc0d023,0x2140f0b3,0x516100dc,0xc10106,0xc1010e,0xc10166,0xc1013e,0xc1f017,0xc40000,0xc40000,0xc40000,0xc40000,0xc40000,0xc40000,0xc40000,0xc40000,0xc40000,0xec40000},
  {0xc10198,0xc101b0,0x1b0445c0,0xc44600,0xc446c0,0xc1030a,0x5d010322,0xc102f2,0xc0e04b,0xc101c4,0xc1707b,0x79410055,0xc07065,0xb0810075,0xd0810326,0xc10336,0xc1d05f,0xc40000,0xc40000,0xc40000,0xc40000,0xc40000,0xc40000,0xfc40000},
  {0xc10050,0xc10060,0xc10038,0x29210078,0x3e010062,0xc10032,0x441901b,0x2461000c,0x36610024,0x5d410074,0x228100ad,0x5b810026,0xc1006e,0xc1005e,0xc1203f,0xc40000,0xc40000,0xc40000,0xc40000,0xc40000,0xc40000,0xc40000,0xc40000,0x10c40000},
  {0xe44040,0xc444c0,0xc10168,0xc10049,0x1601024a,0x63010252,0xc10262,0xc1027a,0xc18073,0x55410045,0x48101c6,0xc1034e,0xc1035e,0xc1023e,0xc1e04f,0xc40000,0xc40000,0xc40000,0xc40000,0xc40000,0xc40000,0xc40000,0xc40000,0x91c40000},
  {0xe44080,0xc44700,0xe10220,0xc09089,0xc103c2,0x5a010412,0xc10512,0xc103f2,0x1e41c0a3,0x4961021c,0x58410234,0x36a1027c,0x4881041e,0x7281051e,0xc10436,0xc1909f,0xc40000,0xc40000,0xc40000,0xc40000,0xc40000,0xc40000,0xc40000,0x93c40000},
  {0xe44180,0xc44880,0xe102a0,0xc04081,0x1c2102f8,0xc104ca,0x66010462,0xc104ea,0xc104ba,0xc104fa,0xc102d4,0xc102ac,0x1d8104c6,0xc104d6,0x6d8104a6,0xc1053e,0xc0f087,0xc0c0b7,0xc40000,0xc40000,0xc40000,0xc40000,0xc40000,0x95c40000},
  {0xe440c0,0xc44ac0,0xc10328,0xc07041,0xc080c9,0xc0c0e1,0xb2010592,0xc105aa,0xc106e2,0x1d4130db,0xc090e3,0x484100fb,0xc810546,0x3f81054e,0x5d810566,0xc1057e,0xc200c7,0xc40000,0xc40000,0xc40000,0xc40000,0xc40000,0xc40000,0x97c40000},
  {0xe441c0,0xc44c40,0xc10398,0xc44d40,0xe103f0,0xc100f1,0xd0010692,0xc10632,0xc10672,0xc1067a,0x6f6103cc,0x736103a4,0x13810606,0xc1064e,0xc10626,0xc1067e,0xc0f0e7,0xc0e0ff,0xc40000,0xc40000,0xc40000,0xc40000,0xc40000,0x99c40000},
  {0xe44300,0xc100a0,0xc04001,0xc100c2,0x3c010112,0x7b01d003,0x741013a,0x234100c4,0x374100d4,0xc100ac,0x39a100fc,0xc10156,0x6981012e,0xc1019e,0xc1b01f,0xc40000,0xc40000,0xc40000,0xc40000,0xc40000,0xc40000,0xc40000,0xc40000,0x9bc40000},
  {0xe44340,0xc101d8,0xc09041,0xc10051,0x24010352,0xc1032a,0xc1b053,0x12410073,0xe101dc,0xe101ac,0xc10286,0x40810296,0x758102a6,0xc102e6,0xc19057,0xc40000,0xc40000,0xc40000,0xc40000,0xc40000,0xc40000,0xc40000,0xc40000,0x9dc40000},
  {0xc10008,0xc44000,0xc44100,0xe10068,0xc10029,0x3601009a,0xc1002a,0xc100a2,0xc1007a,0x3041803b,0xc0b095,0x10810046,0x41810016,0x7881002e,0xc1003e,0xc19037,0xc40000,0xc40000,0xc40000,0xc40000,0xc40000,0xc40000,0xc40000,0x1fc40000},
  {0xc10110,0xc44440,0xe10160,0xc101c2,0x4201021a,0xc10222,0xc10272,0xc101fa,0x3f410104,0x5e610114,0xc100dd,0x2081024e,0x5c8101e6,0xc101fe,0xc10047,0xc1007f,0xc40000,0xc40000,0xc40000,0xc40000,0xc40000,0xc40000,0xc40000,0x20c40000},
  {0xc10200,0xc44a00,0xc10260,0x3010402,0x4301050a,0xc10422,0xc0808b,0xc10432,0xc10244,0xe10214,0xc0b08d,0x7810386,0xc1050e,0x5f8103e6,0xc103fe,0xc1f0a7,0xc40000,0xc40000,0xc40000,0xc40000,0xc40000,0xc40000,0xc40000,0x7fc40000},
  {0xc102c0,0xc44900,0xc102b0,0x40449c0,0x120100b1,0x3801045a,0xc10472,0xa41a093,0x3d8102c4,0x4fa10294,0xe102e4,0xe102bc,0xc10516,0xc104e6,0xc104fe,0xc1b08f,0xc40000,0xc40000,0xc40000,0xc40000,0xc40000,0xc40000,0xc40000,0x7fc40000},
  {0xc10308,0xe10350,0xc44b00,0xe10378,0xc070f9,0x3f01059a,0xc105f2,0xc105ba,0x134105fa,0xe1034c,0xe10364,0xc106c6,0xc10556,0xc1055e,0xc105f6,0xc1e0ef,0xc40000,0xc40000,0xc40000,0xc40000,0xc40000,0xc40000,0xc40000,0x21c40000},
  {0xc10388,0xe103e0,0xc44d00,0xc10682,0x5801065a,0xc106aa,0xc41b0d3,0xc110eb,0x4a4130fb,0x3810686,0xc106ce,0xc106ee,0xc106a6,0xc1e0d7,0xc40000,0xc40000,0xc40000,0xc40000,0xc40000,0xc40000,0xc40000,0xc40000,0xc40000,0x22c40000},
  {0xe44100,0xc44180,0xe100d8,0xc44280,0xc10019,0x1001010a,0xc0b039,0xc10172,0xc1016a,0x1441a02b,0x4241009c,0xb8100f4,0x24810146,0x5981003d,0xf08100f6,0xc19017,0xc0c03f,0xc40000,0xc40000,0xc40000,0xc40000,0xc40000,0xc40000,0xa3c40000},
  {0xe44140,0xc101a0,0xc44640,0xc10059,0x1301028a,0x6501029a,0xc08079,0x71014053,0xc180e3,0xc0e07b,0xc101b4,0x37a101bc,0x4981007d,0x668102b6,0xc1033e,0xc1806f,0xc40000,0xc40000,0xc40000,0xc40000,0xc40000,0xc40000,0xc40000,0xa5c40000},
  {0x2e010040,0xe10028,0xe10030,0xc1000a,0x6801005a,0xc10072,0x40f013,0x104100ba,0x56410005,0x7161006c,0x14a1007c,0x2a810035,0x68810036,0xc1018e,0xc18027,0xc40000,0xc40000,0xc40000,0xc40000,0xc40000,0xc40000,0xc40000,0xc40000,0x7fc40000},
  {0xc10150,0xe10118,0xc44680,0xc10069,0x2f0101d2,0x7701c043,0x541023a,0x2241006b,0x4741011c,0xc10174,0x2f81020e,0xc1025e,0x7a8101f6,0xc10256,0xc0c05f,0xc0a077,0xc40000,0xc40000,0xc40000,0xc40000,0xc40000,0xc40000,0xc40000,0x27c40000},
  {0xc10208,0xc44740,0xc447c0,0xc04081,0xc07089,0x100a9,0xb00103da,0x7501d083,0x34103fa,0xe1020c,0xe10254,0xe1022c,0xc1038e,0xc1039e,0x768103b6,0xc1d08f,0xc0a0bf,0xc40000,0xc40000,0xc40000,0xc40000,0xc40000,0xc40000,0x28c40000},
  {0xc10290,0xc44940,0xc102f0,0x5010099,0x200080b9,0xd201049a,0xc104a2,0xc1047a,0xc0e09b,0x3e6102cc,0x5f40707b,0xc102f4,0x2b81048e,0xc1049e,0x7b8104b6,0xc104de,0xc160b7,0xc40000,0xc40000,0xc40000,0xc40000,0xc40000,0xc40000,0x29c40000},
  {0xc10318,0xc10358,0xc44b80,0xc10542,0x59010552,0xc1056a,0xc10572,0xc1c0eb,0x4b610314,0x59610374,0x7f61037c,0x158100fd,0x648105ae,0xc105e6,0xc180c7,0xc40000,0xc40000,0xc40000,0xc40000,0xc40000,0xc40000,0xc40000,0xc40000,0x2ac40000},
  {0xc103c0,0xc44c00,0xc103e8,0x6010602,0x4401061a,0xc090f9,0x7401a0cb,0xc170e3,0xc0d0fb,0xc103ec,0xc040e5,0x2e81068e,0xc1065e,0x7e8106b6,0xc1b0df,0xc0a0ff,0xc40000,0xc40000,0xc40000,0xc40000,0xc40000,0xc40000,0xc40000,0x7fc40000},
  {0xc100c8,0xc44240,0xc100b0,0x7010102,0x450100da,0xc1012a,0xc100f2,0xc100fa,0xe1008c,0xe10094,0xc0500d,0x1810186,0xc10196,0x6781016e,0xc100fe,0xc1d02f,0xc40000,0xc40000,0xc40000,0xc40000,0xc40000,0xc40000,0xc40000,0x2bc40000},
  {0xc101d0,0xe101e0,0xc100a1,0x250102ca,0x6e01031a,0x7e0102b2,0xc102ba,0xc0a06b,0x3161018c,0x676101ec,0x744102c6,0xc102d6,0x6f8102ae,0xc1032e,0xc1b067,0xc40000,0xc40000,0xc40000,0xc40000,0xc40000,0xc40000,0xc40000,0xc40000,0x2cc40000},
  {0xc10108,0xe10170,0xe10138,0xc08079,0x3701025a,0xc10232,0xc1404b,0x1b410144,0x2e610154,0x38610164,0x68410206,0xc101ce,0xc10226,0xc1037e,0xc1d067,0xc40000,0xc40000,0xc40000,0xc40000,0xc40000,0xc40000,0xc40000,0xc40000,0x2dc40000},
  {0xc10218,0xc10258,0xc10278,0x2a01040a,0xc080b9,0xc103ea,0xc1308b,0x1f41053a,0xc10085,0x7c61026c,0x16810406,0x478103d6,0x738103ae,0xc1042e,0xc19097,0xc40000,0xc40000,0xc40000,0xc40000,0xc40000,0xc40000,0xc40000,0xc40000,0x2ec40000},
  {0xc102c8,0xe102a8,0xc04081,0x1010482,0x5b010492,0x7601b083,0x941809b,0xe1028c,0xe102a4,0xc05095,0x11810446,0x42810496,0xc1046e,0xc104be,0xc190a7,0xc40000,0xc40000,0xc40000,0xc40000,0xc40000,0xc40000,0xc40000,0xc40000,0x2fc40000},
  {0xc10348,0xc44bc0,0xc10370,0x80105c2,0x4601058a,0x790200c3,0x14160db,0x3c410354,0x61610324,0x754105c6,0xc105d6,0x658106e6,0xc105fe,0xc1d0cf,0xc40000,0xc40000,0xc40000,0xc40000,0xc40000,0xc40000,0xc40000,0xc40000,0xc40000,0x30c40000},
  {0xc103d0,0xc103a8,0xc103f8,0x2b01064a,0x6901062a,0xc1069a,0xc106b2,0x27410384,0x394103d4,0x7b6103e4,0x17810646,0x448106d6,0xc106ae,0xc106be,0xc1a0e7,0xc40000,0xc40000,0xc40000,0xc40000,0xc40000,0xc40000,0xc40000,0xc40000,0x31c40000},
  {0xc100d0,0xe100a8,0xc100d9,0x2801018a,0x6d010132,0x7d010162,0xc1017a,0xc1102b,0x4140d03b,0xfa100ec,0x1b8100ce,0xc1015e,0x7d810136,0xc1a007,0xc0b037,0xc40000,0xc40000,0xc40000,0xc40000,0xc40000,0xc40000,0xc40000,0xc40000,0x32c40000},
  {0xc10190,0xc44580,0xc101f0,0x9010282,0x47010292,0xc102da,0xc102e2,0xc1033a,0xc10073,0x536101e4,0xc10306,0xc10356,0xc1029e,0xc102be,0xc1f057,0xc40000,0xc40000,0xc40000,0xc40000,0xc40000,0xc40000,0xc40000,0xc40000,0x33c40000},
  {0xc10148,0xc44400,0xc10128,0xa010202,0x4801020a,0xc101ea,0xc1604b,0x1c41037a,0x6e61010c,0x76610124,0x18810246,0xc10216,0x63810266,0xc1027e,0xc13047,0xc0a0bf,0xc40000,0xc40000,0xc40000,0xc40000,0xc40000,0xc40000,0xc40000,0x34c40000},
  {0xc10248,0xc44a40,0xc10268,0xb010382,0x490103d2,0xc103aa,0xc10532,0xc1043a,0xc120b3,0x50410264,0x8103c6,0xc10396,0xc103a6,0xc1043e,0xc1e0af,0xc40000,0xc40000,0xc40000,0xc40000,0xc40000,0xc40000,0xc40000,0xc40000,0x35c40000},
  {0xc10288,0x2c2102d8,0xe102b8,0xc1048a,0x6a0104d2,0xc104aa,0xc1052a,0x284150ab,0x5440e0bb,0xa81009d,0x34a102fc,0x4a81045e,0xc10476,0xc104ee,0xc110bf,0xc40000,0xc40000,0xc40000,0xc40000,0xc40000,0xc40000,0xc40000,0xc40000,0x36c40000},
  {0xc10340,0xc44a80,0xc10368,0xc010582,0x4a0106da,0xc105d2,0xc105ea,0xc106fa,0xc130f3,0x654100cd,0x1f810586,0xc105ce,0x6e8105ee,0xc105be,0xc0f0e7,0xc0c0f7,0xc40000,0xc40000,0xc40000,0xc40000,0xc40000,0xc40000,0xc40000,0x7fc40000},
  {0xc103d8,0xc44cc0,0xc040c1,0xc103b8,0x140106ca,0x5f010662,0xc106a2,0xc106ea,0xc1d0f3,0xc080fb,0xe8100d5,0x2381060e,0x5881061e,0xc10636,0xc106fe,0xc120ff,0xc40000,0xc40000,0xc40000,0xc40000,0xc40000,0xc40000,0xc40000,0x37c40000},
  {0xc10080,0xc441c0,0xc04001,0xc10142,0x3d0100d2,0xc101a2,0xc101ba,0xc12023,0x2540d02b,0x4340c03b,0x72410015,0x2681014e,0xc1011e,0xc100ee,0xc101a6,0xc0a027,0xc0a03f,0xc40000,0xc40000,0xc40000,0xc40000,0xc40000,0xc40000,0x7fc40000},
  {0xc10180,0xc44500,0xc101f8,0xd010302,0x4b0102d2,0x7801c043,0x8420063,0xc080f3,0x6241004d,0x1e809065,0x218100f5,0xd6810366,0xc102f6,0xc2006f,0xc40000,0xc40000,0xc40000,0xc40000,0xc40000,0xc40000,0xc40000,0xc40000,0xc40000,0x7fc40000},
  {0xc10140,0xc44380,0xc10120,0xe010342,0x4c01035a,0xc1022a,0xc1026a,0xc1e06b,0x4540c07b,0xc10134,0x3581006d,0x458101de,0x7c810276,0xc10376,0xc15077,0xc40000,0xc40000,0xc40000,0xc40000,0xc40000,0xc40000,0xc40000,0xc40000,0x7fc40000},
  {0xc10240,0xc44800,0xe10230,0xc10502,0x4d010392,0xc1041a,0xc103a2,0xc1209b,0x2040c0ab,0x4441025c,0xd810274,0x2581040e,0xc103de,0x7f8103f6,0xc10526,0xc130bf,0xc40000,0xc40000,0xc40000,0xc40000,0xc40000,0xc40000,0xc40000,0x7fc40000},
  {0xc10298,0xc448c0,0xc102e8,0xf010442,0x4e0104da,0xc10522,0xc104b2,0xc1c0a3,0x4c41029c,0x706102b4,0x1981044e,0x5a8100bd,0x6a810536,0xc1052e,0xc160b7,0xc40000,0xc40000,0xc40000,0xc40000,0xc40000,0xc40000,0xc40000,0xc40000,0x38c40000},
  {0xc10300,0xe10330,0xc44dc0,0xc100e9,0xb401055a,0xc105a2,0xc105b2,0xc106f2,0xc0b0eb,0x4d61035c,0x5a61032c,0xc1058e,0xc1059e,0x7781056e,0xc105de,0xc170f7,0xc40000,0xc40000,0xc40000,0xc40000,0xc40000,0xc40000,0xc40000,0x7fc40000},
  {0xc103c8,0xe103a0,0xc04081,0x2010642,0x5c010652,0xc10622,0xb41d0d3,0x3c8103c4,0x4ba1039c,0xe103b4,0xe103bc,0xc10616,0xc1062e,0xc1063e,0xc1a0d7,0xc40000,0xc40000,0xc40000,0xc40000,0xc40000,0xc40000,0xc40000,0xc40000,0x39c40000},
  {0xc100c0,0xc442c0,0xc100b8,0x192100f8,0x2301014a,0xc100e2,0xc100ea,0xc19023,0x336100cc,0x694100e4,0x3aa100bc,0xc10116,0xc101ae,0xc1017e,0xc1d01f,0xc40000,0xc40000,0xc40000,0xc40000,0xc40000,0xc40000,0xc40000,0xc40000,0x7fc40000},
  {0xc10188,0xe101a8,0xc080c9,0x18010071,0x400102a2,0xc102ea,0xc10332,0x11410184,0x2f6101d4,0x3a6101a4,0x6a410346,0xc102ce,0xc102de,0xc1036e,0xc15047,0xc0a07f,0xc40000,0xc40000,0xc40000,0xc40000,0xc40000,0xc40000,0xc40000,0x3ac40000},
  {0xc10100,0xc44480,0xc10178,0xc10242,0x4f010212,0xc101e2,0xe41f05b,0x2b61014c,0x3b61015c,0x6b61012c,0x7761017c,0x1a81021e,0x7481022e,0xc1026e,0xc19077,0xc40000,0xc40000,0xc40000,0xc40000,0xc40000,0xc40000,0xc40000,0xc40000,0x7fc40000},
  {0xc10210,0x2d210250,0xe10238,0xc1038a,0x6b0103e2,0x7001d08b,0x19410204,0xe1024c,0xe10224,0xe1023c,0xc040a5,0x4e8103ce,0xc103ee,0xc10416,0xc1a0af,0xc40000,0xc40000,0xc40000,0xc40000,0xc40000,0xc40000,0xc40000,0xc40000,0x3bc40000},
  {0xc10280,0xc44980,0xc102e0,0xc104c2,0x5401051a,0xc104e2,0xd41e093,0xc10284,0xc102dc,0xc102ec,0xc0c0a5,0x3e810456,0x6b8104ae,0xc104f6,0xc1b087,0xc40000,0xc40000,0xc40000,0xc40000,0xc40000,0xc40000,0xc40000,0xc40000,0x7fc40000},
  {0xc10310,0xc44b40,0xc10360,0xc106c2,0x550105ca,0xc10562,0xc105da,0xc1057a,0xc10304,0xc1031c,0xc10334,0x278100ed,0x438106de,0xc10576,0xc105b6,0xc150f7,0xc40000,0xc40000,0xc40000,0xc40000,0xc40000,0xc40000,0xc40000,0x3cc40000},
  {0xc10380,0xc44c80,0xc040c1,0x1e2103b0,0xc1068a,0x600106d2,0xc1066a,0xc1063a,0xc0f0db,0x3d610394,0x6c4103ac,0x3ba103fc,0xc10696,0xc10666,0xc10676,0xc0f0cf,0xc0e0ff,0xc40000,0xc40000,0xc40000,0xc40000,0xc40000,0xc40000,0x7fc40000},
  {0xc10090,0xc44200,0xc100e8,0x1a044340,0xc10031,0x39010152,0xc10122,0xc101b2,0x17410084,0xc11033,0x5c40703b,0xc100b4,0x2d810025,0x468100de,0x79810176,0xc101b6,0xc16027,0xc40000,0xc40000,0xc40000,0xc40000,0xc40000,0xc40000,0x3dc40000},
  {0xc101c8,0xc101e8,0xc10061,0x2601034a,0x6f0102aa,0x7f01036a,0xc102fa,0xe101cc,0xc1019c,0xc101f4,0x38a101fc,0x4c810316,0xc102ee,0xc1030e,0xc0c0cf,0xc0e07f,0xc40000,0xc40000,0xc40000,0xc40000,0xc40000,0xc40000,0xc40000,0x3ec40000},
  {0xc10098,0xc44300,0xc100f0,0xc10182,0x56010192,0xc1011a,0xf420013,0x2a414033,0x636100a4,0x784100c6,0xc100d6,0x628100e6,0xc10126,0xc1c00f,0xc40000,0xc40000,0xc40000,0xc40000,0xc40000,0xc40000,0xc40000,0xc40000,0xc40000,0x3fc40000},
  {0xc101c0,0xc44540,0xc101b8,0xc102c2,0x57010312,0xc10362,0xc10372,0xc09053,0x15411063,0xc10194,0xc0508d,0x981005d,0x3381028e,0x5e81031e,0xc102fe,0xc0f05f,0xc1007f,0xc40000,0xc40000,0xc40000,0xc40000,0xc40000,0xc40000,0x7fc40000},
};
uint8_t kSeq[NPAIR][KMAX] = {
  {0,1,2,3,0,1,2,3,4,5,6,7,8,9,10,11,12,13,14,15,0,1,2,3,64,67,72,78,76,70,66,74,64,66,76,78,65,67,77,79,68,70,69,71,72,74,73,75,4,6,0,2,5,7,1,3,12,14,8,10,13,15,9,11,4,6,8,10,0,2,5,7,9,11,12,14,1,3,13,15,88,89,94,95,116,117,118,119,106,107,78,79,82,83,112,113,84,85,102,103,98,99,72,73,72,73,80,81,98,99,74,75,110,111,112,113,86,87,92,93,78,79,64,65,66,67,84,68,70,69,71,76,78,72,74,64,66,77,79,73,75,65,67,68,70,72,74,69,71,64,66,76,78,73,75,65,67,77,79,8,10,0,2,9,11,12,14,1,3,4,6,13,15,5,7,12,14,8,10,4,6,0,2,13,15,9,11,5,7,1,3,12,14,8,10,13,15,4,6,9,11,5,7,0,2,1,3,200,202,73,75,196,198,192,194,204,206,197,199,193,195,205,207,71,66,67,112,113,98,99,86,87,110,111,114,115,88,89,118,119,196,197,230,0,0,0,0,0,0,0,0,0,0,0,0,0,0,0,0,0,0,0,0,0,0,0,0,0,0,0,0,0,0,0,0,0,0,0,0,0,0,0,0,0,0,0,0,0,0,0,0,0,0,0,0,0},
  {0,1,2,3,0,1,2,3,4,5,6,7,8,9,10,11,12,13,14,15,0,1,2,3,77,69,73,79,65,68,75,71,70,64,76,66,74,72,79,71,78,67,69,65,75,77,68,73,12,14,8,10,13,15,9,11,0,2,4,6,1,3,5,7,76,78,72,74,77,79,73,75,64,66,68,70,65,67,69,71,4,6,12,14,8,10,0,2,5,7,13,15,9,11,1,3,114,115,100,101,74,75,116,117,118,0,2,4,6,8,10,1,3,5,7,12,14,9,11,13,15,76,78,68,70,77,79,64,66,72,74,69,71,65,67,73,75,12,14,4,6,0,2,13,15,5,7,8,10,1,3,9,11,8,10,12,14,0,2,9,11,13,15,1,3,4,6,5,7,8,10,9,11,4,6,0,2,12,14,5,7,1,3,13,15,4,6,12,14,8,10,5,7,13,15,9,11,0,2,1,3,12,14,8,10,13,15,4,6,9,11,5,7,128,130,1,3,99,64,65,80,81,92,93,108,109,106,107,70,71,66,67,90,91,88,89,82,83,224,225,232,233,230,231,0,0,0,0,0,0,0,0,0,0,0,0,0,0,0,0,0,0,0,0,0,0,0,0,0,0,0,0,0,0,0,0,0,0,0,0,0,0,0,0,0,0,0,0,0,0,0,0,0,0,0,0},
  {64,65,66,67,68,69,70,71,72,73,74,75,76,77,78,79,0,1,2,3,79,75,77,73,0,2,12,14,1,3,13,15,4,6,5,7,8,10,9,11,64,66,72,74,65,67,73,75,76,78,68,70,77,79,69,71,4,6,12,14,8,10,0,2,5,7,13,15,9,11,1,3,0,2,8,10,4,6,12,14,1,3,9,11,5,7,13,15,83,98,99,108,109,92,93,78,79,84,85,100,101,66,67,74,75,88,66,67,84,85,68,69,90,91,104,105,70,71,210,211,228,229,106,107,222,71,72,69,66,64,78,74,77,76,75,73,64,71,78,77,69,72,75,70,74,79,76,73,68,67,66,65,64,71,78,74,77,70,73,69,66,72,76,79,68,65,67,75,4,6,5,7,8,10,12,14,9,11,13,15,0,2,1,3,4,6,12,14,8,10,5,7,13,15,0,2,9,11,1,3,106,107,104,105,92,93,88,89,72,73,90,91,100,101,78,79,116,117,64,65,118,119,208,209,94,95,76,77,240,241,0,0,0,0,0,0,0,0,0,0,0,0,0,0,0,0,0,0,0,0,0,0,0,0,0,0,0,0,0,0,0,0,0,0,0,0,0,0,0,0,0,0,0,0,0,0,0,0,0,0,0,0,0,0,0,0,0,0,0,0,0,0,0,0,0,0},
  {0,1,2,3,4,5,6,7,8,9,10,11,12,13,14,15,0,1,2,3,66,74,68,64,0,2,12,14,1,3,13,15,4,6,5,7,8,10,9,11,64,66,72,74,65,67,73,75,76,78,68,70,77,79,69,71,4,6,0,2,5,7,1,3,12,14,8,10,13,15,9,11,4,6,12,14,8,10,128,130,5,7,13,15,9,11,129,131,92,93,64,65,100,101,96,97,89,76,77,96,97,86,87,72,73,116,117,110,111,4,6,5,7,12,14,8,10,0,2,13,15,9,11,1,3,0,2,1,3,4,6,8,10,12,14,5,7,9,11,13,15,8,10,12,14,0,2,9,11,13,15,1,3,4,6,5,7,8,10,0,2,9,11,12,14,1,3,4,6,13,15,5,7,4,6,5,7,8,10,12,14,9,11,13,15,0,2,1,3,4,6,12,14,8,10,5,7,13,15,0,2,9,11,1,3,77,112,113,110,111,82,83,70,71,68,69,102,103,108,80,81,66,67,90,91,96,97,242,243,202,203,70,199,238,239,0,0,0,0,0,0,0,0,0,0,0,0,0,0,0,0,0,0,0,0,0,0,0,0,0,0,0,0,0,0,0,0,0,0,0,0,0,0,0,0,0,0,0,0,0,0,0,0,0,0,0,0,0,0,0,0,0,0,0,0,0},
  {64,65,66,67,68,69,70,71,72,73,74,75,76,77,78,79,64,65,66,67,68,69,70,71,72,73,74,75,76,77,78,79,64,65,66,67,68,69,70,71,72,73,74,75,76,77,78,79,198,69,194,199,204,12,14,8,10,13,15,9,11,0,2,4,6,1,3,5,7,70,71,64,65,98,99,92,93,78,79,112,113,94,95,72,73,80,81,84,85,114,115,116,117,106,107,66,136,138,128,130,137,139,129,131,140,142,141,143,132,134,133,135,0,2,4,6,8,10,1,3,5,7,12,14,9,11,13,15,4,6,5,7,0,2,8,10,12,14,1,3,9,11,13,15,68,70,69,71,64,66,72,74,76,78,65,67,73,75,77,79,132,134,128,130,133,135,129,131,136,138,140,142,137,139,141,143,8,10,0,2,9,11,12,14,1,3,4,6,13,15,5,7,12,14,8,10,4,6,0,2,13,15,9,11,5,7,1,3,4,6,12,14,8,10,5,7,13,15,0,2,137,139,1,3,92,93,108,109,98,99,80,81,100,101,70,71,116,117,96,97,74,75,64,65,112,113,82,83,234,235,212,213,0,0,0,0,0,0,0,0,0,0,0,0,0,0,0,0,0,0,0,0,0,0,0,0,0,0,0,0,0,0,0,0,0,0,0,0,0,0,0,0,0,0,0,0},
  {0,1,2,3,0,1,2,3,0,1,2,3,4,5,6,7,8,9,10,11,12,13,14,15,0,1,2,3,4,5,6,7,8,9,10,11,12,13,14,15,70,64,76,66,0,2,8,10,1,3,9,11,12,14,4,6,13,15,5,7,4,6,0,2,5,7,1,3,12,14,8,10,13,15,9,11,0,2,8,10,4,6,12,14,1,3,9,11,5,7,13,15,93,78,79,84,85,100,101,66,67,74,75,88,89,76,77,96,97,86,87,72,73,116,117,110,111,84,85,88,89,114,115,110,66,71,70,77,69,73,72,64,65,78,67,75,79,74,76,68,12,14,4,6,0,2,13,15,5,7,8,10,1,3,9,11,132,134,128,130,133,135,129,131,136,138,140,142,137,139,141,143,8,10,9,11,4,6,0,2,12,14,5,7,1,3,13,15,4,6,12,14,8,10,5,7,13,15,9,11,0,2,1,3,140,142,136,138,141,143,132,134,137,139,133,135,128,130,129,131,72,73,86,87,102,103,90,91,118,119,68,69,206,207,114,115,66,67,110,111,94,95,88,217,204,205,0,0,0,0,0,0,0,0,0,0,0,0,0,0,0,0,0,0,0,0,0,0,0,0,0,0,0,0,0,0,0,0,0,0,0,0,0,0,0,0,0,0,0,0,0,0,0,0,0,0},
  {0,1,2,3,0,1,2,3,0,1,2,3,4,5,6,7,8,9,10,11,12,13,14,15,0,1,2,3,0,1,2,3,4,5,6,7,8,9,10,11,12,13,14,15,0,2,8,10,1,3,9,11,12,14,4,6,13,15,5,7,4,6,0,2,5,7,1,3,12,14,8,10,13,15,9,11,0,2,8,10,4,6,12,14,1,3,9,11,5,7,13,15,4,6,12,14,8,10,0,2,5,7,13,15,137,11,1,3,136,138,128,130,137,139,129,131,140,142,141,143,132,134,133,135,204,205,236,237,240,241,210,211,226,227,228,229,192,193,200,201,208,209,202,203,212,213,214,215,8,10,12,14,0,2,9,11,13,15,1,3,4,6,5,7,78,74,77,71,70,64,66,69,79,200,75,68,204,73,195,65,4,6,5,7,8,10,12,14,9,11,13,15,0,2,1,3,132,134,140,142,136,138,133,135,141,143,128,130,137,139,129,131,99,102,103,86,87,104,105,78,79,118,119,114,115,88,89,112,113,100,101,64,65,84,85,94,95,224,225,82,83,196,197,0,0,0,0,0,0,0,0,0,0,0,0,0,0,0,0,0,0,0,0,0,0,0,0,0,0,0,0,0,0,0,0,0,0,0,0,0,0,0,0,0,0,0,0,0,0,0,0,0,0,0,0,0},
  {0,1,2,3,0,1,2,3,4,5,6,7,8,9,10,11,12,13,14,15,66,74,68,64,64,74,76,66,68,70,65,72,79,67,69,71,78,75,77,73,0,2,8,10,1,3,9,11,12,14,4,6,13,15,5,7,12,14,8,10,13,15,9,11,0,2,4,6,1,3,5,7,4,6,12,14,8,10,0,2,5,7,13,15,9,11,1,3,0,2,8,10,4,6,12,14,1,3,9,11,5,7,13,15,99,100,101,90,91,70,71,76,77,68,69,110,111,82,83,74,75,96,97,118,119,104,105,238,239,242,243,232,233,218,219,220,221,230,231,196,197,8,10,12,14,0,2,9,11,13,15,1,3,4,6,5,7,8,10,0,2,9,11,12,14,1,3,4,6,13,15,5,7,4,6,5,7,8,10,12,14,9,11,13,15,0,2,1,3,4,6,140,142,136,138,133,135,141,143,128,130,137,139,129,131,80,81,96,97,92,93,108,109,70,71,82,83,100,101,78,79,74,75,114,115,94,95,118,119,200,201,192,193,240,241,226,0,0,0,0,0,0,0,0,0,0,0,0,0,0,0,0,0,0,0,0,0,0,0,0,0,0,0,0,0,0,0,0,0,0,0,0,0,0,0,0,0,0,0,0,0,0,0,0,0,0,0,0,0,0,0,0,0,0,0,0},
  {0,1,2,3,0,1,2,3,4,5,6,7,8,9,10,11,12,13,14,15,69,76,67,65,0,1,2,3,4,5,6,7,8,9,10,11,12,13,14,15,0,2,8,10,1,3,9,11,12,14,4,6,13,15,5,7,4,6,8,10,0,2,5,7,9,11,12,14,1,3,13,15,88,89,94,95,116,117,118,119,106,107,78,79,82,83,112,113,84,85,102,103,98,99,72,73,92,93,64,65,100,101,0,2,4,6,8,10,1,3,5,7,12,14,9,11,13,15,12,14,4,6,13,15,0,2,8,10,5,7,1,3,9,11,222,223,244,245,12,14,4,6,0,2,13,15,5,7,8,10,1,3,9,11,132,134,128,130,133,135,129,131,136,138,140,142,137,139,141,143,8,10,9,11,4,6,0,2,12,14,5,7,1,3,13,15,4,6,5,7,8,10,12,14,9,11,13,15,0,2,1,3,12,14,8,10,13,15,4,6,9,11,5,7,0,2,1,3,65,112,113,98,99,88,89,86,87,84,85,90,91,106,235,68,69,104,105,76,77,116,117,110,111,102,103,194,195,0,0,0,0,0,0,0,0,0,0,0,0,0,0,0,0,0,0,0,0,0,0,0,0,0,0,0,0,0,0,0,0,0,0,0,0,0,0,0,0,0,0,0,0,0,0,0,0,0},
  {0,1,2,3,0,1,2,3,4,5,6,7,8,9,10,11,12,13,14,15,0,1,2,3,64,74,76,66,68,70,65,72,79,67,69,71,78,75,77,73,0,2,8,10,1,3,9,11,12,14,4,6,13,15,5,7,12,14,8,10,13,15,9,11,0,2,4,6,1,3,5,7,96,97,82,83,74,75,110,111,76,77,88,89,118,119,68,69,100,101,104,105,102,103,90,91,136,138,128,130,9,11,129,131,140,142,141,143,132,134,133,135,12,14,4,6,13,15,0,2,8,10,5,7,1,3,9,11,4,6,5,7,0,2,8,10,12,14,1,3,9,11,13,15,4,6,8,10,5,7,0,2,12,14,9,11,1,3,13,15,77,69,78,72,76,68,66,73,79,67,75,65,8,10,9,11,4,6,0,2,12,14,5,7,1,3,13,15,4,6,12,14,8,10,5,7,13,15,9,11,0,2,1,3,12,14,8,10,132,134,0,2,141,143,9,11,133,135,129,131,64,65,80,81,92,93,108,109,106,107,70,71,66,67,90,91,88,89,82,83,96,97,232,233,230,231,0,0,0,0,0,0,0,0,0,0,0,0,0,0,0,0,0,0,0,0,0,0,0,0,0,0,0,0,0,0,0,0,0,0,0,0,0,0,0,0,0,0,0,0,0,0,0,0,0,0},
  {64,65,66,67,68,69,70,71,72,73,74,75,76,77,78,79,0,1,2,3,4,5,6,7,8,9,10,11,12,13,14,15,64,74,76,66,68,70,65,72,79,67,69,71,78,75,77,73,0,2,8,10,1,3,9,11,12,14,4,6,13,15,5,7,4,6,0,2,5,7,1,3,12,14,8,10,13,15,9,11,114,115,76,77,70,71,86,87,90,91,74,75,66,67,68,69,80,81,108,109,110,111,104,105,84,85,88,89,114,115,110,111,98,99,66,67,94,85,68,69,90,91,104,105,70,71,210,211,100,101,234,235,4,6,5,7,0,2,8,10,12,14,1,3,9,11,13,15,8,10,12,14,0,2,9,11,13,15,1,3,4,6,5,7,8,10,0,2,9,11,12,14,1,3,4,6,13,15,5,7,4,6,5,7,8,10,12,14,9,11,13,15,0,2,1,3,4,6,12,14,8,10,133,135,13,15,0,2,137,139,1,3,99,102,103,86,87,104,105,78,79,118,119,114,115,88,89,112,113,100,101,64,65,84,85,94,95,224,225,210,211,196,197,0,0,0,0,0,0,0,0,0,0,0,0,0,0,0,0,0,0,0,0,0,0,0,0,0,0,0,0,0,0,0,0,0,0,0,0,0,0,0,0,0,0,0,0,0,0,0,0,0,0,0,0,0},
  {0,1,2,3,4,5,6,7,8,9,10,11,12,13,14,15,0,1,2,3,4,5,6,7,8,9,10,11,12,13,14,15,0,1,2,3,0,1,2,3,0,1,2,3,0,2,8,10,1,3,9,11,12,14,4,6,13,15,5,7,4,6,8,10,0,2,5,7,9,11,12,14,1,3,13,15,0,2,8,10,4,6,12,14,1,3,9,11,5,7,13,15,72,73,92,93,64,65,100,101,96,97,114,115,76,77,0,2,4,6,8,10,1,3,5,7,12,14,9,11,13,15,204,205,108,109,112,113,210,211,226,227,228,229,192,193,200,201,208,209,202,203,212,213,214,71,69,72,78,64,77,75,74,79,73,67,76,70,68,66,65,68,66,73,79,67,75,65,78,74,77,71,70,64,194,69,207,200,75,196,204,73,195,65,4,6,5,7,8,10,12,14,9,11,13,15,0,2,1,3,12,14,8,10,13,15,4,6,9,11,5,7,0,2,1,3,65,112,113,98,99,88,89,86,87,84,85,90,91,106,107,68,69,104,105,76,77,116,117,238,239,102,103,194,195,0,0,0,0,0,0,0,0,0,0,0,0,0,0,0,0,0,0,0,0,0,0,0,0,0,0,0,0,0,0,0,0,0,0,0,0,0,0,0,0,0,0,0,0,0,0,0,0,0,0,0},
  {0,1,2,3,4,5,6,7,8,9,10,11,12,13,14,15,0,1,2,3,4,5,6,7,8,9,10,11,12,13,14,15,0,1,2,3,4,5,6,7,8,9,10,11,12,13,14,15,64,65,66,67,68,69,70,71,72,73,74,75,76,77,78,79,4,6,8,10,0,2,5,7,9,11,12,14,1,3,13,15,0,2,8,10,4,6,12,14,1,3,9,11,5,7,13,15,64,65,70,71,80,81,112,113,90,91,102,103,118,119,104,105,114,115,106,107,94,95,68,69,82,12,14,4,6,13,15,0,2,8,10,5,7,1,3,9,11,0,2,1,3,4,6,8,10,12,14,5,7,9,11,13,15,68,70,72,74,69,71,64,66,76,78,73,75,65,67,77,79,64,71,78,74,77,70,73,69,66,72,76,79,68,65,67,75,4,6,5,7,8,10,12,14,9,11,13,15,0,2,1,3,4,6,12,14,8,10,5,7,13,15,9,11,0,2,1,3,204,206,200,202,196,198,192,194,205,207,201,203,197,199,193,195,78,79,106,107,86,87,94,95,76,77,220,221,72,73,98,227,212,213,0,0,0,0,0,0,0,0,0,0,0,0,0,0,0,0,0,0,0,0,0,0,0,0,0,0,0,0,0,0,0,0,0,0,0,0,0,0,0,0,0,0,0,0,0},
  {0,1,2,3,0,1,2,3,0,1,2,3,4,5,6,7,8,9,10,11,12,13,14,15,64,67,72,77,69,73,78,76,70,66,74,79,65,68,75,71,0,2,8,10,1,3,9,11,12,14,4,6,13,15,5,7,12,14,8,10,13,15,9,11,0,2,4,6,1,3,5,7,4,6,8,10,0,2,5,7,9,11,12,14,1,3,13,15,136,138,128,130,137,139,129,131,140,142,141,143,132,134,133,135,78,79,64,65,66,67,84,85,68,69,90,91,104,105,70,71,210,211,100,101,106,107,222,223,66,71,70,77,69,73,72,64,65,78,67,75,79,74,76,68,8,10,12,14,0,2,9,11,13,15,1,3,4,6,5,7,8,10,0,2,9,11,12,14,1,3,4,6,13,15,5,7,12,14,8,10,4,6,0,2,13,15,9,11,5,7,1,3,4,6,12,14,8,10,5,7,141,143,0,2,137,139,1,3,92,93,108,109,98,99,80,81,100,101,70,71,116,117,96,97,74,75,64,65,112,113,82,83,106,107,212,213,232,233,0,0,0,0,0,0,0,0,0,0,0,0,0,0,0,0,0,0,0,0,0,0,0,0,0,0,0,0,0,0,0,0,0,0,0,0,0,0,0,0,0,0,0,0,0,0,0,0,0,0,0,0,0,0,0,0,0,0},
  {0,1,2,3,0,1,2,3,0,1,2,3,4,5,6,7,8,9,10,11,12,13,14,15,64,67,72,77,69,73,78,76,70,64,66,76,78,65,67,77,79,68,70,69,71,72,74,73,75,12,14,8,10,13,15,9,11,0,2,4,6,1,3,5,7,76,78,72,74,77,79,73,75,64,66,68,70,65,67,69,71,0,2,8,10,4,6,12,14,1,3,9,11,5,7,13,15,84,85,88,89,114,115,110,111,98,99,66,67,94,95,70,71,76,77,106,107,96,97,64,65,78,79,90,91,4,6,5,7,0,2,8,10,12,14,1,3,9,11,13,15,4,6,8,10,5,7,0,2,12,14,9,11,1,3,13,15,132,134,128,130,133,135,129,131,136,138,140,142,137,139,141,143,12,14,8,10,4,6,0,2,13,15,9,11,5,7,1,3,12,14,8,10,4,6,0,2,13,15,9,11,5,7,1,3,12,14,8,10,13,15,132,134,9,11,133,135,128,130,129,131,99,88,89,86,87,84,85,90,91,234,235,68,69,104,105,76,77,116,117,110,111,102,103,194,195,0,0,0,0,0,0,0,0,0,0,0,0,0,0,0,0,0,0,0,0,0,0,0,0,0,0,0,0,0,0,0,0,0,0,0,0,0,0,0,0,0,0,0,0,0,0,0,0,0,0},
  {0,1,2,3,0,1,2,3,0,1,2,3,4,5,6,7,8,9,10,11,12,13,14,15,79,75,77,73,0,1,2,3,4,5,6,7,8,9,10,11,12,13,14,15,0,2,8,10,1,3,9,11,12,14,4,6,13,15,5,7,4,6,8,10,0,2,5,7,9,11,12,14,1,3,13,15,4,6,12,14,8,10,0,2,5,7,13,15,9,11,1,3,136,138,128,130,137,139,129,131,140,142,141,143,132,134,133,135,136,138,128,130,137,139,129,131,140,142,141,143,132,134,133,135,4,6,5,7,12,14,8,10,0,2,13,15,9,11,1,3,12,14,4,6,0,2,13,15,5,7,8,10,1,3,9,11,8,10,12,14,0,2,9,11,13,15,1,3,4,6,5,7,8,10,9,11,4,6,0,2,12,14,5,7,1,3,13,15,4,6,5,7,8,10,12,14,9,11,13,15,0,2,1,3,4,6,12,14,8,10,5,7,13,15,0,2,9,11,1,3,109,86,87,114,115,98,99,66,67,84,85,96,97,74,75,102,103,80,81,96,97,76,77,218,219,236,237,0,0,0,0,0,0,0,0,0,0,0,0,0,0,0,0,0,0,0,0,0,0,0,0,0,0,0,0,0,0,0,0,0,0,0,0,0,0,0,0,0,0,0,0,0,0,0,0,0},
  {0,1,2,3,0,1,2,3,0,1,2,3,4,5,6,7,8,9,10,11,12,13,14,15,72,78,70,71,66,74,68,70,66,74,79,65,68,75,71,74,72,79,71,78,67,69,65,75,77,68,73,12,14,8,10,13,15,9,11,0,2,4,6,1,3,5,7,4,6,12,14,8,10,0,2,5,7,13,15,9,11,1,3,4,6,8,10,0,2,5,7,9,11,12,14,1,3,13,15,68,69,82,83,98,99,108,109,92,93,78,79,84,85,100,101,66,67,74,75,86,87,92,93,118,119,68,69,216,217,198,199,206,207,246,247,194,195,238,239,242,243,232,233,8,10,12,14,0,2,9,11,13,15,1,3,4,6,5,7,8,10,0,2,9,11,12,14,1,3,4,6,13,15,5,7,4,6,5,7,8,10,12,14,9,11,13,15,0,2,1,3,132,134,140,142,136,138,133,135,141,143,128,130,137,139,129,131,106,107,104,105,92,93,88,89,72,73,90,91,100,101,78,79,116,117,64,65,118,119,208,209,94,95,76,77,240,241,238,239,0,0,0,0,0,0,0,0,0,0,0,0,0,0,0,0,0,0,0,0,0,0,0,0,0,0,0,0,0,0,0,0,0,0,0,0,0,0,0,0,0,0,0,0,0,0,0,0,0,0,0,0,0,0,0,0,0},
  {0,1,2,3,0,1,2,3,0,1,2,3,4,5,6,7,8,9,10,11,12,13,14,15,0,1,2,3,0,1,2,3,4,5,6,7,8,9,10,11,12,13,14,15,76,69,70,72,74,66,71,75,67,77,68,73,79,206,64,65,12,14,8,10,13,15,9,11,0,2,4,6,1,3,5,7,0,2,8,10,4,6,12,14,1,3,9,11,5,7,13,15,0,2,8,10,4,6,12,14,1,3,9,11,5,7,13,15,136,138,128,130,137,139,129,131,140,142,141,143,132,134,133,135,12,14,4,6,13,15,0,2,8,10,5,7,1,3,9,11,0,2,1,3,4,6,8,10,12,14,5,7,9,11,13,15,8,10,12,14,0,2,9,11,13,15,1,3,4,6,5,7,8,10,0,2,9,11,12,14,1,3,4,6,13,15,5,7,4,6,5,7,8,10,12,14,9,11,13,15,0,2,1,3,4,6,140,142,136,138,5,7,141,143,0,2,137,139,129,131,75,98,99,66,67,80,81,92,93,114,115,112,113,88,89,110,111,82,83,68,69,104,105,108,109,102,103,244,245,0,0,0,0,0,0,0,0,0,0,0,0,0,0,0,0,0,0,0,0,0,0,0,0,0,0,0,0,0,0,0,0,0,0,0,0,0,0,0,0,0,0,0,0,0,0,0},
  {0,1,2,3,0,1,2,3,4,5,6,7,8,9,10,11,12,13,14,15,69,76,67,65,0,2,12,14,1,3,13,15,4,6,5,7,8,10,9,11,12,14,8,10,13,15,9,11,0,2,4,6,1,3,5,7,67,108,109,86,87,96,97,82,83,74,75,110,111,76,77,88,89,118,119,68,69,100,101,104,105,102,103,90,91,136,138,128,130,137,139,129,131,140,142,141,143,132,134,133,135,0,2,4,6,8,10,1,3,5,7,12,14,9,11,13,15,4,6,5,7,12,14,8,10,0,2,13,15,9,11,1,3,12,14,4,6,0,2,13,15,5,7,8,10,1,3,9,11,132,134,128,130,133,135,129,131,136,138,140,142,137,139,141,143,8,10,9,11,4,6,0,2,12,14,5,7,1,3,13,15,4,6,12,14,8,10,5,7,13,15,9,11,0,2,1,3,12,14,8,10,4,6,0,2,13,15,9,11,5,7,1,3,80,81,96,97,92,93,108,109,70,71,82,83,100,101,206,207,74,75,114,115,94,95,118,119,200,201,192,0,0,0,0,0,0,0,0,0,0,0,0,0,0,0,0,0,0,0,0,0,0,0,0,0,0,0,0,0,0,0,0,0,0,0,0,0,0,0,0,0,0,0,0,0,0,0,0,0,0,0,0,0,0,0,0},
  {0,1,2,3,0,1,2,3,4,5,6,7,8,9,10,11,12,13,14,15,64,79,75,77,73,69,76,67,65,64,74,76,66,68,70,65,72,79,67,69,71,78,75,77,73,12,14,8,10,13,15,9,11,0,2,4,6,1,3,5,7,4,6,12,14,8,10,0,2,5,7,13,15,9,11,1,3,76,77,88,89,106,107,78,79,96,97,108,109,114,115,100,101,74,75,116,117,118,119,82,83,112,113,98,72,73,80,81,98,99,74,75,110,111,112,113,86,87,92,93,4,6,5,7,0,2,8,10,12,14,1,3,9,11,13,15,12,14,4,6,0,2,13,15,5,7,8,10,1,3,9,11,8,10,12,14,0,2,9,11,13,15,1,3,4,6,5,7,8,10,9,11,4,6,0,2,12,14,5,7,1,3,13,15,4,6,5,7,8,10,12,14,9,11,13,15,0,2,1,3,132,134,133,135,136,138,140,142,137,139,141,143,128,130,129,131,90,91,106,107,92,93,116,117,72,73,76,77,108,109,110,111,208,209,70,71,66,67,202,203,226,0,0,0,0,0,0,0,0,0,0,0,0,0,0,0,0,0,0,0,0,0,0,0,0,0,0,0,0,0,0,0,0,0,0,0,0,0,0,0,0,0,0,0,0,0,0,0,0,0,0,0,0,0,0,0},
  {64,65,66,67,68,69,70,71,72,73,74,75,76,77,78,79,0,1,2,3,0,1,2,3,64,65,66,67,68,69,70,71,72,73,74,75,76,77,78,79,72,76,64,70,66,74,71,78,67,79,65,197,75,68,73,77,4,6,0,2,5,7,1,3,12,14,8,10,13,15,9,11,4,6,12,14,8,10,0,2,5,7,13,15,9,11,1,3,68,70,72,74,64,66,69,71,73,75,76,78,65,67,77,79,136,138,128,130,137,139,129,131,140,142,141,143,132,134,133,135,76,77,108,109,112,113,82,83,226,227,100,101,64,65,200,201,208,209,202,203,212,213,214,215,71,69,72,78,64,77,75,74,79,73,67,8,10,12,14,0,2,9,11,13,15,1,3,4,6,5,7,8,10,9,11,4,6,0,2,12,14,5,7,1,3,13,15,4,6,12,14,8,10,5,7,13,15,9,11,0,2,1,3,132,134,140,142,136,138,133,135,141,143,128,130,137,139,129,131,64,65,84,85,92,93,104,105,74,75,78,79,100,101,82,83,72,73,116,117,222,223,234,235,198,0,0,0,0,0,0,0,0,0,0,0,0,0,0,0,0,0,0,0,0,0,0,0,0,0,0,0,0,0,0,0,0,0,0,0,0,0,0,0,0,0,0,0,0,0,0,0,0,0,0,0,0},
  {0,1,2,3,4,5,6,7,8,9,10,11,12,13,14,15,0,1,2,3,64,65,66,67,68,69,70,71,72,73,74,75,76,77,78,79,64,66,76,78,65,67,77,79,68,70,69,71,72,74,73,75,4,6,0,2,5,7,1,3,12,14,8,10,13,15,9,11,4,6,8,10,0,2,5,7,9,11,12,14,1,3,13,15,0,2,8,10,4,6,12,14,1,3,9,11,5,7,13,15,136,138,128,130,137,139,129,131,140,142,141,143,132,134,133,135,64,66,68,70,72,74,65,67,69,71,76,78,73,75,77,79,68,70,69,71,76,78,72,74,64,66,77,79,73,75,65,67,64,71,78,77,69,72,75,70,74,79,76,73,68,67,66,65,8,10,0,2,9,11,12,14,1,3,4,6,13,15,5,7,4,6,5,7,8,10,12,14,9,11,13,15,0,2,1,3,132,134,140,142,136,138,133,135,141,143,128,130,137,139,129,131,106,107,104,105,92,93,88,89,72,73,90,91,100,101,78,79,84,85,80,81,66,67,90,91,96,97,242,243,202,203,198,199,0,0,0,0,0,0,0,0,0,0,0,0,0,0,0,0,0,0,0,0,0,0,0,0,0,0,0,0,0,0,0,0,0,0,0,0,0,0,0,0,0,0,0,0,0,0,0,0,0,0,0,0},
  {64,65,66,67,68,69,70,71,72,73,74,75,76,77,78,79,0,1,2,3,64,65,66,67,68,69,70,71,72,73,74,75,76,77,78,79,64,66,76,78,65,67,77,79,68,70,69,71,72,74,73,75,64,66,72,74,65,67,73,75,76,78,68,70,77,79,69,71,4,6,8,10,0,2,5,7,9,11,12,14,1,3,13,15,80,81,108,109,110,111,104,105,0,2,8,10,4,6,12,14,1,3,9,11,5,7,13,15,0,2,4,6,8,10,1,3,5,7,12,14,9,11,13,15,4,6,5,7,12,14,8,10,0,2,13,15,9,11,1,3,71,72,69,66,64,78,74,77,76,75,73,8,10,12,14,0,2,9,11,13,15,1,3,4,6,5,7,8,10,0,2,9,11,12,14,1,3,4,6,13,15,5,7,4,6,5,7,8,10,12,14,9,11,13,15,0,2,1,3,132,134,140,142,136,138,133,135,141,143,128,130,137,139,129,131,64,65,78,79,90,91,106,107,94,95,68,69,96,97,74,75,98,99,66,67,80,81,220,221,242,243,112,113,216,217,236,0,0,0,0,0,0,0,0,0,0,0,0,0,0,0,0,0,0,0,0,0,0,0,0,0,0,0,0,0,0,0,0,0,0,0,0,0,0,0,0,0,0,0,0,0,0,0,0,0,0},
  {64,65,66,67,68,69,70,71,72,73,74,75,76,77,78,79,0,1,2,3,0,1,2,3,4,5,6,7,8,9,10,11,12,13,14,15,0,1,2,3,76,69,70,72,74,66,71,75,67,77,68,73,79,78,64,65,4,6,0,2,5,7,1,3,12,14,8,10,13,15,9,11,0,2,8,10,4,6,12,14,1,3,9,11,5,7,13,15,108,109,114,115,100,101,74,75,116,117,118,119,82,83,112,113,98,99,102,103,68,69,110,111,104,105,0,2,4,6,8,10,1,3,5,7,12,14,9,11,13,15,4,6,5,7,12,14,8,10,0,2,13,15,9,11,1,3,64,66,65,67,68,70,72,74,76,78,69,71,73,75,77,79,132,134,128,130,133,135,129,131,136,138,140,142,137,139,141,143,8,10,9,11,4,6,0,2,12,14,5,7,1,3,13,15,4,6,5,7,8,10,12,14,9,11,13,15,0,2,1,3,4,6,12,14,8,10,5,7,13,15,0,2,9,11,1,3,105,72,73,86,87,102,103,90,91,118,119,68,69,78,79,114,115,66,67,110,111,94,95,216,217,204,205,0,0,0,0,0,0,0,0,0,0,0,0,0,0,0,0,0,0,0,0,0,0,0,0,0,0,0,0,0,0,0,0,0,0,0,0,0,0,0,0,0,0,0},
  {64,65,66,67,68,69,70,71,72,73,74,75,76,77,78,79,64,65,66,67,68,69,70,71,72,73,74,75,76,77,78,79,0,1,2,3,0,1,2,3,4,5,6,7,8,9,10,11,12,13,14,15,198,197,194,199,204,203,206,4,6,0,2,5,7,1,3,12,14,8,10,13,15,9,11,0,2,8,10,4,6,12,14,1,3,9,11,5,7,13,15,136,138,128,130,9,11,129,131,140,142,141,143,132,134,133,135,136,138,128,130,137,139,129,131,140,142,141,143,132,134,133,135,12,14,4,6,13,15,0,2,8,10,5,7,1,3,9,11,0,2,1,3,4,6,8,10,12,14,5,7,9,11,13,15,8,10,12,14,0,2,9,11,13,15,1,3,4,6,5,7,8,10,9,11,4,6,0,2,12,14,5,7,1,3,13,15,12,14,8,10,4,6,0,2,13,15,9,11,5,7,1,3,12,14,8,10,13,15,4,6,9,11,5,7,0,2,1,3,118,119,76,77,74,75,68,69,72,73,100,101,110,111,84,85,206,207,116,117,94,95,242,243,86,87,240,241,226,227,0,0,0,0,0,0,0,0,0,0,0,0,0,0,0,0,0,0,0,0,0,0,0,0,0,0,0,0,0,0,0,0,0,0,0,0,0,0,0,0,0,0,0,0,0,0,0},
  {64,65,66,67,68,69,70,71,72,73,74,75,76,77,78,79,0,1,2,3,4,5,6,7,8,9,10,11,12,13,14,15,0,1,2,3,64,66,76,78,65,67,77,79,68,70,69,71,72,74,73,75,4,6,0,2,5,7,1,3,12,14,8,10,13,15,9,11,4,6,12,14,8,10,0,2,5,7,13,15,9,11,1,3,97,108,109,114,115,100,101,74,75,116,117,118,119,82,83,112,113,98,99,102,103,68,69,110,111,104,105,114,115,102,103,98,99,100,101,90,91,70,71,76,77,68,69,110,193,200,201,208,209,202,203,212,213,214,215,222,223,244,245,234,235,224,225,8,10,12,14,0,2,9,11,13,15,1,3,4,6,5,7,8,10,0,2,9,11,12,14,1,3,4,6,13,15,5,7,4,6,12,14,8,10,5,7,13,15,9,11,0,2,1,3,4,6,5,7,8,10,140,142,9,11,13,15,0,2,1,3,90,91,106,107,92,93,116,117,72,73,76,77,108,109,110,111,80,81,70,71,66,67,74,75,98,99,102,103,214,215,0,0,0,0,0,0,0,0,0,0,0,0,0,0,0,0,0,0,0,0,0,0,0,0,0,0,0,0,0,0,0,0,0,0,0,0,0,0,0,0,0,0,0,0,0,0,0,0,0,0,0,0,0,0,0},
  {0,1,2,3,0,1,2,3,0,1,2,3,4,5,6,7,8,9,10,11,12,13,14,15,0,1,2,3,74,66,76,79,70,72,64,67,71,69,78,68,75,65,77,73,0,2,8,10,1,3,9,11,12,14,4,6,13,15,5,7,203,206,200,202,196,201,207,205,195,192,193,0,2,8,10,4,6,12,14,1,3,9,11,5,7,13,15,4,6,12,14,8,10,0,2,5,7,13,15,137,139,129,131,112,113,84,85,88,89,66,67,78,79,92,93,72,73,80,81,106,107,116,117,236,237,64,65,94,95,4,6,5,7,0,2,8,10,12,14,1,3,9,11,13,15,4,6,8,10,5,7,0,2,12,14,9,11,1,3,13,15,72,74,76,78,64,66,73,75,77,79,65,67,68,70,69,71,72,79,194,76,192,67,202,196,199,206,198,197,205,201,193,203,12,14,8,10,13,15,4,6,9,11,5,7,0,2,1,3,90,91,106,107,92,93,116,117,72,73,76,77,108,109,110,111,80,81,70,71,66,67,74,75,98,82,83,68,69,104,105,108,109,102,103,244,245,0,0,0,0,0,0,0,0,0,0,0,0,0,0,0,0,0,0,0,0,0,0,0,0,0,0,0,0,0,0,0,0,0,0,0,0,0,0,0,0,0,0,0,0,0,0,0,0,0,0},
  {0,1,2,3,0,1,2,3,4,5,6,7,8,9,10,11,12,13,14,15,0,1,2,3,74,66,76,79,70,72,64,67,71,69,78,68,75,65,77,73,0,2,8,10,1,3,9,11,12,14,4,6,13,15,5,7,4,6,0,2,5,7,1,3,12,14,8,10,13,15,9,11,202,196,201,207,205,195,192,193,90,91,70,71,72,73,66,67,64,65,84,85,92,93,80,81,86,87,94,95,84,85,88,89,114,115,110,111,98,99,66,67,94,95,70,71,76,77,106,107,96,97,64,65,215,222,223,244,245,234,235,224,225,216,217,198,199,206,4,6,8,10,5,7,0,2,12,14,9,11,1,3,13,15,132,134,128,130,133,135,129,131,136,138,140,142,137,139,141,143,72,79,194,76,192,67,202,196,199,206,198,197,205,201,193,203,12,14,8,10,13,15,4,6,9,11,5,7,0,2,1,3,4,6,12,14,136,138,5,7,13,15,128,130,137,139,129,131,80,81,92,93,108,109,106,107,70,71,66,67,90,91,88,89,82,83,224,225,232,233,230,231,0,0,0,0,0,0,0,0,0,0,0,0,0,0,0,0,0,0,0,0,0,0,0,0,0,0,0,0,0,0,0,0,0,0,0,0,0,0,0,0,0,0,0,0,0,0,0,0,0,0,0,0,0,0},
  {64,65,66,67,68,69,70,71,72,73,74,75,76,77,78,79,0,1,2,3,4,5,6,7,8,9,10,11,12,13,14,15,64,65,66,67,68,69,70,71,72,73,74,75,76,77,78,79,0,2,8,10,1,3,9,11,12,14,4,6,13,15,5,7,4,6,0,2,5,7,1,3,12,14,8,10,13,15,9,11,0,2,8,10,4,6,12,14,1,3,9,11,5,7,13,15,119,82,83,112,113,98,99,102,103,68,69,110,111,104,105,200,202,192,194,201,203,193,195,204,206,205,207,196,198,197,199,66,71,70,77,69,73,72,64,65,78,67,75,79,74,76,68,76,78,68,70,64,66,77,79,69,71,72,74,65,67,73,75,132,134,128,130,133,135,129,131,136,138,140,142,137,139,141,143,78,74,77,71,70,64,194,69,207,200,75,196,204,73,195,65,12,14,8,10,13,15,4,6,9,11,5,7,0,2,1,3,72,74,64,66,73,75,76,78,65,67,196,198,77,79,197,199,68,69,96,97,74,75,98,99,66,67,80,81,92,93,114,115,112,113,88,89,108,109,246,247,0,0,0,0,0,0,0,0,0,0,0,0,0,0,0,0,0,0,0,0,0,0,0,0,0,0,0,0,0,0,0,0,0,0,0,0,0,0,0,0,0,0,0,0,0,0,0,0,0},
  {0,1,2,3,4,5,6,7,8,9,10,11,12,13,14,15,64,65,66,67,68,69,70,71,72,73,74,75,76,77,78,79,0,1,2,3,72,76,64,70,66,74,71,78,67,79,65,197,75,68,73,77,12,14,8,10,13,15,9,11,0,2,4,6,1,3,5,7,108,109,86,87,96,97,82,83,74,75,110,111,76,77,88,89,118,119,68,69,100,101,104,105,102,103,90,91,136,138,128,130,137,139,129,131,140,142,141,143,132,134,133,135,76,77,68,69,110,111,82,83,74,75,96,97,118,119,104,105,4,6,5,7,0,2,8,10,12,14,1,3,9,11,13,15,4,6,8,10,5,7,0,2,12,14,9,11,1,3,13,15,8,10,0,2,9,11,12,14,1,3,4,6,13,15,5,7,12,14,8,10,4,6,0,2,13,15,9,11,5,7,1,3,12,14,8,10,13,15,132,134,9,11,5,7,0,2,1,3,136,138,9,11,132,134,0,2,140,142,133,135,129,131,141,143,79,74,75,114,115,94,95,118,119,72,73,64,208,209,96,97,76,77,218,219,236,237,0,0,0,0,0,0,0,0,0,0,0,0,0,0,0,0,0,0,0,0,0,0,0,0,0,0,0,0,0,0,0,0,0,0,0,0,0,0,0,0,0,0,0,0,0,0,0,0,0,0},
  {64,65,66,67,68,69,70,71,72,73,74,75,76,77,78,79,0,1,2,3,0,1,2,3,66,74,68,64,66,74,79,65,68,75,71,72,76,64,70,66,74,71,78,67,79,65,69,75,68,73,77,4,6,0,2,5,7,1,3,12,14,8,10,13,15,9,11,70,71,64,65,98,99,92,93,78,79,112,113,94,95,72,73,80,81,84,85,114,115,116,117,106,107,66,67,108,136,138,128,130,137,139,129,131,140,142,141,143,132,134,133,135,12,14,4,6,13,15,0,2,8,10,5,7,1,3,9,11,4,6,5,7,12,14,8,10,0,2,13,15,9,11,1,3,76,78,4,6,0,2,13,15,5,7,8,10,1,3,9,11,8,10,0,2,9,11,12,14,1,3,4,6,13,15,5,7,12,14,8,10,4,6,0,2,13,15,9,11,5,7,1,3,12,14,8,10,13,15,4,6,9,11,5,7,0,2,1,3,92,93,108,109,98,99,80,81,100,101,70,71,116,117,96,97,74,75,64,65,112,113,82,83,234,235,84,85,104,112,113,228,229,192,193,216,217,246,247,0,0,0,0,0,0,0,0,0,0,0,0,0,0,0,0,0,0,0,0,0,0,0,0,0,0,0,0,0,0,0,0,0,0,0,0,0,0,0,0,0,0,0,0,0,0,0,0,0},
  {0,1,2,3,4,5,6,7,8,9,10,11,12,13,14,15,0,1,2,3,0,1,2,3,4,5,6,7,8,9,10,11,12,13,14,15,74,66,76,79,70,72,64,67,71,69,78,68,75,65,77,73,198,194,204,206,200,202,196,192,4,6,0,2,5,7,1,3,12,14,8,10,13,15,9,11,4,6,8,10,0,2,5,7,9,11,12,14,1,3,13,15,136,138,128,130,137,139,129,131,140,142,141,143,132,134,133,135,88,89,76,77,96,97,86,87,72,73,116,117,110,111,12,14,4,6,13,15,0,2,8,10,5,7,1,3,9,11,219,220,221,230,231,196,197,4,6,8,10,5,7,0,2,12,14,9,11,1,3,13,15,8,10,0,2,9,11,12,14,1,3,4,6,13,15,5,7,12,14,8,10,4,6,0,2,13,15,9,11,5,7,1,3,12,14,8,10,13,15,4,6,9,11,5,7,0,2,1,3,12,14,8,10,132,134,0,2,13,15,9,11,133,135,1,3,64,65,84,85,92,93,104,105,74,75,206,207,100,101,82,83,200,201,116,117,222,223,0,0,0,0,0,0,0,0,0,0,0,0,0,0,0,0,0,0,0,0,0,0,0,0,0,0,0,0,0,0,0,0,0,0,0,0,0,0,0,0,0,0,0,0,0,0,0,0,0},
  {0,1,2,3,4,5,6,7,8,9,10,11,12,13,14,15,64,65,66,67,68,69,70,71,72,73,74,75,76,77,78,79,0,1,2,3,64,66,76,78,65,67,77,79,68,70,69,71,72,74,73,75,12,14,8,10,13,15,9,11,0,2,4,6,1,3,5,7,4,6,12,14,8,10,0,2,5,7,13,15,9,11,1,3,0,2,8,10,4,6,12,14,1,3,9,11,5,7,13,15,112,113,84,85,88,89,66,67,78,79,92,93,72,73,80,81,106,107,116,117,108,109,64,65,94,95,86,87,4,6,5,7,12,14,8,10,0,2,13,15,9,11,1,3,4,6,8,10,5,7,0,2,12,14,9,11,1,3,13,15,132,134,128,130,133,135,129,131,136,138,140,142,137,139,141,143,200,207,194,204,192,195,202,196,199,206,198,197,205,201,193,203,4,6,12,14,8,10,5,7,13,15,9,11,0,2,1,3,4,6,5,7,136,138,140,142,9,11,141,143,128,130,129,131,82,83,70,71,68,69,102,103,108,109,86,87,114,115,98,99,66,67,84,85,224,225,202,203,0,0,0,0,0,0,0,0,0,0,0,0,0,0,0,0,0,0,0,0,0,0,0,0,0,0,0,0,0,0,0,0,0,0,0,0,0,0,0,0,0,0,0,0,0,0,0,0},
  {64,65,66,67,68,69,70,71,72,73,74,75,76,77,78,79,0,1,2,3,0,1,2,3,4,5,6,7,8,9,10,11,12,13,14,15,64,66,76,78,65,67,77,79,68,70,69,71,72,74,73,75,4,6,0,2,5,7,1,3,12,14,8,10,13,15,9,11,200,202,196,201,207,205,195,192,193,96,97,114,115,76,77,70,71,86,87,90,91,74,75,66,67,68,69,80,81,108,109,110,111,104,105,78,79,90,91,80,81,102,103,104,105,108,109,112,113,72,73,116,117,82,83,100,101,74,204,205,236,237,240,241,210,211,226,227,228,229,192,12,14,4,6,0,2,13,15,5,7,8,10,1,3,9,11,64,71,70,74,8,10,0,2,9,11,12,14,1,3,4,6,13,15,5,7,12,14,8,10,4,6,0,2,13,15,9,11,5,7,1,3,12,14,8,10,13,15,4,6,9,11,5,7,0,2,1,3,80,81,96,97,92,93,108,109,70,71,82,83,100,101,78,79,74,75,114,115,94,95,118,119,72,73,64,112,113,228,229,192,193,216,217,246,247,0,0,0,0,0,0,0,0,0,0,0,0,0,0,0,0,0,0,0,0,0,0,0,0,0,0,0,0,0,0,0,0,0,0,0,0,0,0,0,0,0,0,0,0,0,0,0,0,0,0,0,0},
  {64,65,66,67,68,69,70,71,72,73,74,75,76,77,78,79,0,1,2,3,0,1,2,3,4,5,6,7,8,9,10,11,12,13,14,15,64,66,76,78,65,67,77,79,68,70,69,71,72,74,73,75,4,6,0,2,5,7,1,3,12,14,8,10,13,15,9,11,4,6,12,14,8,10,0,2,5,7,13,15,9,11,1,3,0,2,8,10,4,6,12,14,1,3,9,11,5,7,13,15,136,138,128,130,137,139,129,131,140,142,141,143,132,134,133,135,12,14,4,6,13,15,0,2,8,10,5,7,1,3,9,11,68,70,69,71,76,78,72,74,64,66,77,79,73,75,65,67,79,68,65,67,70,8,10,12,14,0,2,9,11,13,15,1,3,4,6,5,7,8,10,9,11,4,6,0,2,12,14,5,7,1,3,13,15,4,6,12,14,8,10,5,7,13,15,9,11,0,2,1,3,132,134,140,142,136,138,133,135,141,143,128,130,137,139,129,131,118,119,76,77,74,75,68,69,72,73,100,101,110,111,84,85,206,207,116,117,94,95,242,243,214,215,240,241,226,0,0,0,0,0,0,0,0,0,0,0,0,0,0,0,0,0,0,0,0,0,0,0,0,0,0,0,0,0,0,0,0,0,0,0,0,0,0,0,0,0,0,0,0,0,0,0,0,0,0},
  {0,1,2,3,4,5,6,7,8,9,10,11,12,13,14,15,0,1,2,3,4,5,6,7,8,9,10,11,12,13,14,15,70,64,76,66,74,72,79,71,78,67,69,65,75,77,68,73,0,2,8,10,1,3,9,11,12,14,4,6,13,15,5,7,4,6,0,2,5,7,1,3,12,14,8,10,13,15,9,11,0,2,8,10,4,6,12,14,1,3,9,11,5,7,13,15,136,138,128,130,137,139,129,131,140,142,141,143,132,134,133,135,112,113,84,85,88,89,66,67,78,79,76,78,68,70,77,79,64,66,72,74,69,71,65,67,73,75,12,14,4,6,0,2,13,15,5,7,8,10,1,3,9,11,8,10,12,14,0,2,9,11,13,15,1,3,4,6,5,7,8,10,9,11,4,6,0,2,12,14,5,7,1,3,13,15,4,6,12,14,8,10,5,7,13,15,9,11,0,2,1,3,4,6,12,14,8,10,5,7,13,15,9,11,128,130,1,3,89,108,109,118,119,82,83,70,71,100,101,102,103,84,85,116,117,72,73,214,215,238,239,232,233,204,205,0,0,0,0,0,0,0,0,0,0,0,0,0,0,0,0,0,0,0,0,0,0,0,0,0,0,0,0,0,0,0,0,0,0,0,0,0,0,0,0,0,0,0,0,0,0,0,0,0,0,0},
  {64,65,66,67,68,69,70,71,72,73,74,75,76,77,78,79,0,1,2,3,4,5,6,7,8,9,10,11,12,13,14,15,0,1,2,3,4,5,6,7,8,9,10,11,12,13,14,15,198,197,194,199,204,203,206,200,4,6,0,2,5,7,1,3,12,14,8,10,13,15,9,11,0,2,8,10,4,6,12,14,1,3,9,11,5,7,13,15,70,71,86,87,90,91,74,75,66,67,68,69,80,81,108,109,110,111,104,105,0,2,4,6,8,10,1,3,5,7,12,14,9,11,13,15,4,6,5,7,12,14,8,10,0,2,13,15,9,11,1,3,0,2,1,3,4,6,8,10,12,14,5,7,9,11,13,15,8,10,12,14,0,2,9,11,13,15,1,3,4,6,5,7,8,10,0,2,9,11,12,14,1,3,4,6,13,15,5,7,4,6,5,7,8,10,12,14,9,11,13,15,0,2,1,3,4,6,12,14,8,10,5,7,13,15,0,2,9,11,1,3,64,65,78,79,90,91,106,107,94,95,68,69,96,97,74,75,98,99,66,67,208,209,92,93,242,243,240,241,216,0,0,0,0,0,0,0,0,0,0,0,0,0,0,0,0,0,0,0,0,0,0,0,0,0,0,0,0,0,0,0,0,0,0,0,0,0,0,0,0,0,0,0,0,0,0,0},
  {0,1,2,3,4,5,6,7,8,9,10,11,12,13,14,15,64,65,66,67,68,69,70,71,72,73,74,75,76,77,78,79,0,1,2,3,4,5,6,7,8,9,10,11,12,13,14,15,0,2,8,10,1,3,9,11,12,14,4,6,13,15,5,7,197,199,203,201,207,205,195,193,4,6,12,14,8,10,0,2,5,7,13,15,9,11,1,3,88,89,94,95,116,117,118,119,106,107,78,79,82,83,112,113,84,85,102,136,138,128,130,137,139,129,131,140,142,141,143,132,134,133,135,66,71,70,77,69,73,72,64,65,78,67,75,79,74,76,68,12,14,4,6,0,2,13,15,5,7,8,10,1,3,9,11,8,10,12,14,0,2,9,11,13,15,1,3,4,6,5,7,8,10,9,11,4,6,0,2,12,14,5,7,1,3,13,15,4,6,12,14,8,10,5,7,13,15,9,11,0,2,1,3,4,6,12,14,136,138,5,7,13,15,137,139,128,130,129,131,90,91,106,107,92,93,116,117,72,73,76,77,108,109,110,111,80,81,198,199,66,67,202,203,226,0,0,0,0,0,0,0,0,0,0,0,0,0,0,0,0,0,0,0,0,0,0,0,0,0,0,0,0,0,0,0,0,0,0,0,0,0,0,0,0,0,0,0,0,0,0,0,0,0,0,0,0},
  {64,65,66,67,68,69,70,71,72,73,74,75,76,77,78,79,0,1,2,3,4,5,6,7,8,9,10,11,12,13,14,15,72,78,70,71,64,66,76,78,65,67,77,79,68,70,69,71,72,74,73,75,12,14,8,10,13,15,9,11,0,2,4,6,1,3,5,7,109,86,87,96,97,82,83,74,75,110,111,76,77,88,89,118,119,68,69,100,101,104,105,102,103,90,91,64,65,70,71,80,81,112,113,90,91,102,103,118,119,104,105,114,115,106,107,94,95,68,69,12,14,4,6,13,15,0,2,8,10,5,7,1,3,9,11,0,2,1,3,4,6,8,10,12,14,5,7,9,11,13,15,76,70,68,66,65,8,10,12,14,0,2,9,11,13,15,1,3,4,6,5,7,8,10,9,11,4,6,0,2,12,14,5,7,1,3,13,15,4,6,12,14,8,10,5,7,13,15,9,11,0,2,1,3,132,134,140,142,136,138,133,135,141,143,128,130,137,139,129,131,109,118,119,82,83,70,71,100,101,102,103,84,85,116,117,72,73,86,87,110,111,232,233,204,205,0,0,0,0,0,0,0,0,0,0,0,0,0,0,0,0,0,0,0,0,0,0,0,0,0,0,0,0,0,0,0,0,0,0,0,0,0,0,0,0,0,0,0,0,0,0,0,0,0,0,0},
  {64,65,66,67,68,69,70,71,72,73,74,75,76,77,78,79,0,1,2,3,0,1,2,3,4,5,6,7,8,9,10,11,12,13,14,15,64,66,76,78,65,67,77,79,68,70,69,71,72,74,73,75,64,66,72,74,65,67,73,75,76,78,68,70,77,79,69,71,70,71,64,65,98,99,92,93,78,79,112,113,94,95,72,73,80,81,84,85,114,115,116,117,106,107,66,67,108,109,86,87,64,65,70,71,80,81,112,113,90,91,102,103,118,119,104,105,114,115,106,107,94,95,4,6,5,7,12,14,8,10,0,2,13,15,9,11,1,3,0,2,1,3,4,6,8,10,12,14,5,7,9,11,13,15,8,10,12,14,0,2,9,11,13,15,1,3,4,6,5,7,8,10,9,11,4,6,0,2,12,14,5,7,1,3,13,15,4,6,5,7,8,10,12,14,9,11,13,15,0,2,1,3,4,6,12,14,8,10,5,7,13,15,0,2,9,11,1,3,85,104,105,72,73,86,87,102,103,90,91,118,119,68,69,206,207,114,115,66,67,110,111,94,95,216,217,204,205,0,0,0,0,0,0,0,0,0,0,0,0,0,0,0,0,0,0,0,0,0,0,0,0,0,0,0,0,0,0,0,0,0,0,0,0,0,0,0,0,0,0,0,0,0,0,0,0,0},
  {0,1,2,3,4,5,6,7,8,9,10,11,12,13,14,15,0,1,2,3,4,5,6,7,8,9,10,11,12,13,14,15,0,1,2,3,4,5,6,7,8,9,10,11,12,13,14,15,0,2,8,10,1,3,9,11,12,14,4,6,13,15,5,7,4,6,12,14,8,10,0,2,5,7,13,15,9,11,1,3,4,6,0,2,5,7,1,3,12,14,8,10,13,15,9,11,0,2,8,10,4,6,12,14,1,3,137,139,5,7,141,143,0,2,4,6,8,10,1,3,5,7,12,14,9,11,13,15,4,6,5,7,12,14,8,10,0,2,13,15,9,11,1,3,0,2,1,3,4,6,8,10,12,14,5,7,9,11,13,15,8,10,12,14,0,2,9,11,13,15,1,3,4,6,5,7,8,10,9,11,4,6,0,2,12,14,5,7,1,3,13,15,4,6,12,14,8,10,5,7,13,15,9,11,0,2,1,3,4,6,140,142,136,138,5,7,141,143,128,130,137,139,129,131,108,109,118,119,82,83,70,71,100,101,102,103,84,85,116,117,72,73,86,87,110,111,232,233,204,205,0,0,0,0,0,0,0,0,0,0,0,0,0,0,0,0,0,0,0,0,0,0,0,0,0,0,0,0,0,0,0,0,0,0,0,0,0,0,0,0,0,0,0,0,0,0},
  {0,1,2,3,4,5,6,7,8,9,10,11,12,13,14,15,0,1,2,3,4,5,6,7,8,9,10,11,12,13,14,15,74,66,76,79,70,72,64,67,71,69,78,68,75,65,77,73,0,2,8,10,1,3,9,11,12,14,4,6,13,15,5,7,0,2,8,10,4,6,12,14,1,3,9,11,5,7,13,15,4,6,8,10,0,2,5,7,9,11,12,14,1,3,13,15,136,138,128,130,137,139,129,131,140,142,141,143,132,134,133,135,86,87,114,115,102,103,98,99,100,101,90,91,70,71,204,205,68,206,207,246,247,194,195,238,239,242,243,232,233,218,76,78,68,70,64,66,77,79,69,71,72,74,65,67,73,75,8,10,0,2,9,11,12,14,1,3,4,6,13,15,5,7,12,14,8,10,4,6,0,2,13,15,9,11,5,7,1,3,12,14,8,10,13,15,4,6,9,11,5,7,0,2,1,3,110,111,82,83,70,71,68,69,102,103,108,109,86,87,114,115,98,99,66,67,84,85,96,97,74,75,103,208,209,96,97,76,77,218,219,236,237,0,0,0,0,0,0,0,0,0,0,0,0,0,0,0,0,0,0,0,0,0,0,0,0,0,0,0,0,0,0,0,0,0,0,0,0,0,0,0,0,0,0,0,0,0,0,0,0,0,0,0,0,0},
  {0,1,2,3,4,5,6,7,8,9,10,11,12,13,14,15,0,1,2,3,0,1,2,3,4,5,6,7,8,9,10,11,12,13,14,15,64,66,76,78,65,67,77,79,68,70,69,71,72,74,73,75,12,14,8,10,13,15,9,11,0,2,4,6,1,3,5,7,4,6,0,2,5,7,1,3,12,14,8,10,13,15,9,11,4,6,8,10,0,2,5,7,9,11,12,14,1,3,13,15,136,138,128,130,137,139,129,131,140,142,141,143,132,134,133,135,108,109,204,205,88,89,114,115,96,97,102,103,116,117,246,247,0,2,1,3,4,6,8,10,12,14,5,7,9,11,13,15,8,10,12,14,0,2,9,11,13,15,1,3,4,6,5,7,8,10,9,11,4,6,0,2,12,14,5,7,1,3,13,15,12,14,8,10,4,6,0,2,13,15,9,11,5,7,1,3,132,134,140,142,136,138,133,135,141,143,128,130,137,139,129,131,99,102,103,86,87,104,105,78,79,118,119,114,115,88,89,112,113,100,101,64,65,84,85,94,95,224,225,210,211,196,197,0,0,0,0,0,0,0,0,0,0,0,0,0,0,0,0,0,0,0,0,0,0,0,0,0,0,0,0,0,0,0,0,0,0,0,0,0,0,0,0,0,0,0,0,0,0,0,0,0,0,0,0,0},
  {64,65,66,67,68,69,70,71,72,73,74,75,76,77,78,79,0,1,2,3,0,1,2,3,4,5,6,7,8,9,10,11,12,13,14,15,64,66,76,78,65,67,77,79,68,70,69,71,72,74,73,75,64,66,72,74,65,67,73,75,76,78,68,70,77,79,69,71,4,6,12,14,8,10,0,2,5,7,13,15,9,11,1,3,88,89,94,95,116,117,118,119,106,107,78,79,82,83,112,113,84,85,102,103,98,99,136,138,128,130,137,139,129,131,140,142,141,143,132,134,133,135,12,14,4,6,13,15,0,2,8,10,5,7,1,3,9,11,0,2,1,3,4,6,8,10,12,14,5,7,9,11,13,15,8,10,12,14,0,2,9,11,13,15,1,3,4,6,5,7,8,10,9,11,4,6,0,2,12,14,5,7,1,3,13,15,4,6,5,7,8,10,12,14,9,11,13,15,0,2,1,3,4,6,12,14,8,10,5,7,13,15,0,2,9,11,1,3,69,102,103,108,109,86,87,114,115,98,99,66,67,84,85,96,97,74,75,68,69,104,105,108,109,102,103,244,245,0,0,0,0,0,0,0,0,0,0,0,0,0,0,0,0,0,0,0,0,0,0,0,0,0,0,0,0,0,0,0,0,0,0,0,0,0,0,0,0,0,0,0,0,0,0,0,0,0},
  {64,65,66,67,68,69,70,71,72,73,74,75,76,77,78,79,0,1,2,3,0,1,2,3,4,5,6,7,8,9,10,11,12,13,14,15,64,66,76,78,65,67,77,79,68,70,69,71,72,74,73,75,12,14,8,10,13,15,9,11,0,2,4,6,1,3,5,7,4,6,12,14,8,10,0,2,5,7,13,15,9,11,1,3,0,2,8,10,4,6,12,14,1,3,9,11,5,7,13,15,136,138,128,130,137,139,129,131,140,142,141,143,132,134,133,135,94,95,108,109,76,77,88,89,114,115,96,97,102,103,116,117,118,119,0,2,1,3,4,6,8,10,12,14,5,7,9,11,13,15,8,10,12,14,0,2,9,11,13,15,1,3,4,6,5,7,8,10,9,11,4,6,0,2,12,14,5,7,1,3,13,15,4,6,5,7,8,10,12,14,9,11,13,15,0,2,1,3,4,6,12,14,8,10,5,7,13,15,0,2,9,11,1,3,118,119,76,77,74,75,68,69,72,73,100,101,110,111,84,85,78,79,116,117,94,95,242,243,214,215,240,241,226,227,0,0,0,0,0,0,0,0,0,0,0,0,0,0,0,0,0,0,0,0,0,0,0,0,0,0,0,0,0,0,0,0,0,0,0,0,0,0,0,0,0,0,0,0,0,0,0,0,0,0,0,0},
  {64,65,66,67,68,69,70,71,72,73,74,75,76,77,78,79,64,65,66,67,68,69,70,71,72,73,74,75,76,77,78,79,0,1,2,3,4,5,6,7,8,9,10,11,12,13,14,15,0,2,8,10,1,3,9,11,12,14,4,6,13,15,5,7,12,14,8,10,13,15,9,11,0,2,4,6,1,3,5,7,4,6,12,14,8,10,0,2,5,7,13,15,9,11,1,3,68,70,76,78,72,74,64,66,69,71,77,79,73,75,65,67,72,73,80,81,106,107,116,117,108,109,64,65,94,95,86,87,114,115,102,103,226,234,235,224,225,216,217,198,199,206,207,246,247,194,195,64,71,78,77,69,72,75,70,74,79,76,73,68,67,66,65,196,198,192,194,197,199,193,195,200,202,204,206,201,203,205,207,12,14,8,10,4,6,0,2,13,15,9,11,5,7,1,3,12,14,8,10,13,15,132,134,9,11,133,135,128,130,1,3,196,198,204,206,200,202,69,71,205,207,201,203,192,194,193,195,81,66,67,90,91,96,97,114,115,74,75,198,199,238,239,210,211,0,0,0,0,0,0,0,0,0,0,0,0,0,0,0,0,0,0,0,0,0,0,0,0,0,0,0,0,0,0,0,0,0,0,0,0,0,0,0,0,0,0,0,0,0,0,0,0,0,0,0,0},
  {64,65,66,67,68,69,70,71,72,73,74,75,76,77,78,79,0,1,2,3,0,1,2,3,4,5,6,7,8,9,10,11,12,13,14,15,64,66,76,78,65,67,77,79,68,70,69,71,72,74,73,75,4,6,0,2,5,7,1,3,12,14,8,10,13,15,9,11,76,78,72,74,77,79,73,75,64,66,68,70,65,67,69,71,4,6,12,14,8,10,0,2,5,7,13,15,9,11,1,3,8,10,128,130,9,11,1,3,140,142,13,15,132,134,133,135,107,94,95,108,109,76,77,88,89,114,115,96,97,102,103,116,117,118,119,71,72,69,66,64,78,74,77,76,75,73,79,68,65,67,70,8,10,12,14,0,2,9,11,13,15,1,3,4,6,5,7,8,10,0,2,9,11,12,14,1,3,4,6,13,15,5,7,4,6,12,14,8,10,5,7,13,15,9,11,0,2,1,3,4,6,12,14,8,10,5,7,13,15,0,2,9,11,1,3,64,65,78,79,90,91,106,107,94,95,68,69,96,97,74,102,103,208,209,96,97,76,77,218,219,236,237,0,0,0,0,0,0,0,0,0,0,0,0,0,0,0,0,0,0,0,0,0,0,0,0,0,0,0,0,0,0,0,0,0,0,0,0,0,0,0,0,0,0,0,0,0,0,0,0,0,0,0,0,0,0},
  {0,1,2,3,4,5,6,7,8,9,10,11,12,13,14,15,0,1,2,3,79,75,77,73,0,1,2,3,4,5,6,7,8,9,10,11,12,13,14,15,0,2,8,10,1,3,9,11,12,14,4,6,13,15,5,7,4,6,8,10,0,2,5,7,9,11,12,14,1,3,13,15,4,6,8,10,0,2,5,7,9,11,12,14,1,3,13,15,4,6,12,14,8,10,0,2,5,7,13,15,9,11,1,3,72,73,80,81,98,99,74,75,110,111,112,113,86,87,92,93,78,79,64,65,66,67,84,85,68,69,90,91,104,218,219,220,221,230,231,196,197,71,69,72,78,64,77,75,74,79,73,67,76,70,68,66,65,8,10,0,2,9,11,12,14,1,3,4,6,13,15,5,7,12,14,8,10,4,6,0,2,13,15,9,11,5,7,1,3,12,14,8,10,13,15,4,6,9,11,5,7,0,2,1,3,196,198,204,206,200,202,197,199,205,207,192,194,201,203,193,195,78,79,106,235,86,87,94,95,76,77,220,221,200,201,98,99,212,213,0,0,0,0,0,0,0,0,0,0,0,0,0,0,0,0,0,0,0,0,0,0,0,0,0,0,0,0,0,0,0,0,0,0,0,0,0,0,0,0,0,0,0,0,0,0,0,0,0,0,0,0,0,0,0,0,0},
  {64,65,66,67,68,69,70,71,72,73,74,75,76,77,78,79,0,1,2,3,72,78,70,71,0,2,12,14,1,3,13,15,4,6,5,7,8,10,9,11,12,14,8,10,13,15,9,11,0,2,4,6,1,3,5,7,4,6,8,10,0,2,5,7,9,11,12,14,1,3,13,15,8,10,0,2,9,11,1,3,12,14,13,15,132,134,5,7,95,70,71,76,77,106,107,96,97,64,65,78,79,90,91,80,81,102,69,110,111,82,83,74,75,96,97,118,119,104,105,94,223,244,245,234,235,224,225,216,217,198,199,71,69,72,78,64,77,75,74,79,73,67,76,70,68,66,65,8,10,0,2,9,11,12,14,1,3,4,6,13,15,5,7,12,14,8,10,4,6,0,2,13,15,9,11,5,7,1,3,4,6,12,14,8,10,5,7,13,15,9,11,0,2,1,3,68,70,69,71,200,202,204,206,201,203,205,207,192,194,193,195,64,65,78,79,90,91,106,107,94,95,112,113,228,229,64,193,216,217,246,247,0,0,0,0,0,0,0,0,0,0,0,0,0,0,0,0,0,0,0,0,0,0,0,0,0,0,0,0,0,0,0,0,0,0,0,0,0,0,0,0,0,0,0,0,0,0,0,0,0,0,0,0,0,0,0,0,0,0,0,0,0,0,0,0,0},
  {64,65,66,67,68,69,70,71,72,73,74,75,76,77,78,79,0,1,2,3,0,1,2,3,4,5,6,7,8,9,10,11,12,13,14,15,64,66,76,78,65,67,77,79,68,70,69,71,72,74,73,75,12,14,8,10,13,15,9,11,0,2,4,6,1,3,5,7,70,71,64,65,98,99,92,93,78,79,112,113,94,95,72,73,80,81,84,85,114,115,116,117,106,107,66,67,111,98,99,66,67,94,95,70,71,76,77,106,107,96,97,64,65,78,79,90,91,80,81,102,103,104,105,236,237,240,241,72,105,70,71,210,211,100,101,106,71,72,69,66,64,78,74,77,76,75,73,79,68,65,67,70,64,71,70,74,77,69,78,72,76,78,74,77,71,70,64,66,69,207,200,75,68,204,73,195,65,4,6,5,7,8,10,12,14,9,11,13,15,0,2,1,3,12,14,8,10,13,15,132,134,9,11,133,135,0,2,1,3,118,119,76,77,74,75,68,69,72,73,100,101,110,111,84,85,206,207,116,117,94,95,114,115,214,215,112,113,98,99,192,193,0,0,0,0,0,0,0,0,0,0,0,0,0,0,0,0,0,0,0,0,0,0,0,0,0,0,0,0,0,0,0,0,0,0,0,0,0,0,0,0,0,0,0,0,0,0,0,0,0,0,0,0,0,0,0},
  {64,65,66,67,68,69,70,71,72,73,74,75,76,77,78,79,0,1,2,3,64,65,66,67,68,69,70,71,72,73,74,75,76,77,78,79,64,66,76,78,65,67,77,79,68,70,69,71,72,74,73,75,4,6,0,2,5,7,1,3,12,14,8,10,13,15,9,11,4,6,12,14,8,10,0,2,5,7,13,15,9,11,1,3,4,6,12,14,8,10,0,2,5,7,13,15,137,139,129,131,92,93,72,73,80,81,106,107,116,117,108,109,64,65,94,95,86,87,114,115,102,103,98,99,100,101,90,91,70,71,207,246,247,194,195,238,239,242,243,232,233,218,4,6,8,10,5,7,0,2,12,14,9,11,1,3,13,15,64,71,78,74,77,70,73,69,66,72,76,79,68,65,67,75,12,14,8,10,4,6,0,2,13,15,9,11,5,7,1,3,12,14,8,10,13,15,4,6,9,11,5,7,0,2,1,3,204,206,200,202,205,207,196,198,201,203,197,199,192,194,193,195,71,66,67,112,113,98,99,86,87,110,111,114,115,88,89,118,119,68,69,230,231,0,0,0,0,0,0,0,0,0,0,0,0,0,0,0,0,0,0,0,0,0,0,0,0,0,0,0,0,0,0,0,0,0,0,0,0,0,0,0,0,0,0,0,0,0,0,0,0,0,0,0,0,0},
  {64,65,66,67,68,69,70,71,72,73,74,75,76,77,78,79,0,1,2,3,0,1,2,3,4,5,6,7,8,9,10,11,12,13,14,15,64,66,76,78,65,67,77,79,68,70,69,71,72,74,73,75,12,14,8,10,13,15,9,11,0,2,4,6,1,3,5,7,4,6,0,2,5,7,1,3,12,14,8,10,13,15,9,11,4,6,8,10,0,2,5,7,9,11,12,14,1,3,13,15,82,83,98,99,108,109,92,93,78,79,84,85,100,101,66,67,74,75,112,113,84,85,88,89,66,67,78,79,92,93,4,6,5,7,0,2,8,10,12,14,1,3,9,11,13,15,4,6,8,10,5,7,0,2,12,14,9,11,1,3,13,15,8,10,0,2,9,11,12,14,1,3,4,6,13,15,5,7,12,14,8,10,4,6,0,2,13,15,9,11,5,7,1,3,12,14,8,10,13,15,132,134,9,11,5,7,0,2,1,3,196,198,69,71,200,202,204,206,201,203,205,207,192,194,193,195,78,79,106,107,86,87,94,95,76,77,220,221,200,201,98,99,212,213,208,0,0,0,0,0,0,0,0,0,0,0,0,0,0,0,0,0,0,0,0,0,0,0,0,0,0,0,0,0,0,0,0,0,0,0,0,0,0,0,0,0,0,0,0,0,0,0,0,0,0,0},
  {0,1,2,3,4,5,6,7,8,9,10,11,12,13,14,15,0,1,2,3,0,1,2,3,4,5,6,7,8,9,10,11,12,13,14,15,64,66,76,78,65,67,77,79,68,70,69,71,72,74,73,75,4,6,0,2,5,7,1,3,12,14,8,10,13,15,9,11,4,6,8,10,0,2,5,7,9,11,12,14,1,3,13,15,0,2,8,10,4,6,12,14,1,3,137,139,5,7,13,15,80,81,102,103,104,105,108,109,112,113,72,73,116,117,82,83,100,101,74,75,86,87,92,93,118,119,68,69,4,6,5,7,0,2,8,10,12,14,1,3,9,11,13,15,4,6,8,10,5,7,0,2,12,14,9,11,1,3,13,15,8,10,0,2,9,11,12,14,1,3,4,6,13,15,5,7,200,207,194,204,192,195,202,196,199,206,198,197,205,201,193,203,12,14,8,10,13,15,4,6,9,11,5,7,0,2,1,3,132,134,12,14,136,138,133,135,13,15,137,139,128,130,129,131,106,107,70,71,66,67,112,113,98,99,86,87,110,111,242,243,88,89,118,119,196,197,0,0,0,0,0,0,0,0,0,0,0,0,0,0,0,0,0,0,0,0,0,0,0,0,0,0,0,0,0,0,0,0,0,0,0,0,0,0,0,0,0,0,0,0,0,0,0,0,0,0},
  {64,65,66,67,68,69,70,71,72,73,74,75,76,77,78,79,0,1,2,3,4,5,6,7,8,9,10,11,12,13,14,15,0,1,2,3,72,76,64,70,66,74,71,78,67,79,65,69,75,68,73,77,4,6,0,2,5,7,1,3,12,14,8,10,13,15,9,11,4,6,8,10,0,2,5,7,9,11,12,14,1,3,13,15,0,2,8,10,4,6,12,14,1,3,137,139,5,7,141,143,192,194,200,202,68,70,204,206,193,195,201,203,197,199,205,207,111,82,83,74,75,96,97,118,119,104,105,4,6,5,7,0,2,8,10,12,14,1,3,9,11,13,15,76,78,68,70,0,2,13,15,5,7,8,10,1,3,9,11,8,10,0,2,9,11,12,14,1,3,4,6,13,15,5,7,12,14,8,10,4,6,0,2,13,15,9,11,5,7,1,3,4,6,12,14,8,10,5,7,13,15,9,11,0,2,1,3,12,14,136,138,132,134,0,2,141,143,137,139,133,135,129,131,64,65,84,85,92,93,104,105,74,75,206,207,100,101,82,83,200,201,116,117,222,223,234,0,0,0,0,0,0,0,0,0,0,0,0,0,0,0,0,0,0,0,0,0,0,0,0,0,0,0,0,0,0,0,0,0,0,0,0,0,0,0,0,0,0,0,0,0,0,0,0,0,0},
  {64,65,66,67,68,69,70,71,72,73,74,75,76,77,78,79,0,1,2,3,4,5,6,7,8,9,10,11,12,13,14,15,69,76,67,65,64,66,76,78,65,67,77,79,68,70,69,71,72,74,73,75,12,14,8,10,13,15,9,11,0,2,4,6,1,3,5,7,4,6,8,10,0,2,5,7,9,11,12,14,1,3,13,15,90,91,70,71,72,73,66,67,64,65,84,85,92,93,80,81,86,87,94,95,76,77,88,89,106,107,78,79,96,0,2,4,6,8,10,1,3,5,7,12,14,9,11,13,15,4,6,5,7,0,2,8,10,12,14,1,3,9,11,13,15,4,6,8,10,5,7,0,2,12,14,9,11,1,3,13,15,132,134,128,130,133,135,129,131,136,138,140,142,137,139,141,143,8,10,9,11,4,6,0,2,12,14,5,7,1,3,13,15,4,6,12,14,8,10,5,7,13,15,9,11,0,2,1,3,132,134,140,142,136,138,133,135,141,143,128,130,137,139,129,131,104,105,78,79,118,119,114,115,88,89,112,113,100,101,64,65,84,85,94,95,96,97,210,211,196,197,0,0,0,0,0,0,0,0,0,0,0,0,0,0,0,0,0,0,0,0,0,0,0,0,0,0,0,0,0,0,0,0,0,0,0,0,0,0,0,0,0,0,0,0,0},
  {64,65,66,67,68,69,70,71,72,73,74,75,76,77,78,79,0,1,2,3,0,1,2,3,4,5,6,7,8,9,10,11,12,13,14,15,0,1,2,3,4,5,6,7,8,9,10,11,12,13,14,15,0,2,8,10,1,3,9,11,12,14,4,6,13,15,5,7,4,6,8,10,0,2,5,7,9,11,12,14,1,3,13,15,4,6,12,14,8,10,0,2,5,7,13,15,9,11,1,3,103,104,105,108,109,112,113,72,73,116,117,82,83,100,101,74,75,86,87,92,93,118,119,68,69,76,78,68,70,77,79,64,66,72,74,69,71,65,67,73,75,0,2,1,3,4,6,8,10,12,14,5,7,9,11,13,15,132,134,128,130,133,135,129,131,136,138,140,142,137,139,141,143,8,10,9,11,4,6,0,2,12,14,5,7,1,3,13,15,4,6,12,14,8,10,5,7,13,15,9,11,0,2,1,3,132,134,140,142,136,138,133,135,141,143,128,130,137,139,129,131,65,112,113,98,99,88,89,86,87,84,85,90,91,106,107,68,69,104,105,76,77,116,117,110,111,102,103,194,195,0,0,0,0,0,0,0,0,0,0,0,0,0,0,0,0,0,0,0,0,0,0,0,0,0,0,0,0,0,0,0,0,0,0,0,0,0,0,0,0,0,0,0,0,0,0},
  {64,65,66,67,68,69,70,71,72,73,74,75,76,77,78,79,0,1,2,3,4,5,6,7,8,9,10,11,12,13,14,15,64,67,72,77,69,73,78,76,76,69,70,72,74,66,71,75,67,77,68,73,79,206,64,65,4,6,8,10,0,2,5,7,9,11,12,14,1,3,13,15,4,6,12,14,8,10,0,2,5,7,13,15,9,11,1,3,0,2,8,10,4,6,12,14,1,3,9,11,5,7,13,15,0,2,4,6,8,10,1,3,5,7,12,14,9,11,13,15,4,6,5,7,12,14,8,10,0,2,13,15,9,11,1,3,0,2,1,3,4,6,8,10,12,14,5,7,9,11,13,15,8,10,12,14,0,2,9,11,13,15,1,3,4,6,5,7,8,10,0,2,9,11,12,14,1,3,4,6,13,15,5,7,12,14,8,10,4,6,0,2,13,15,9,11,5,7,1,3,4,6,12,14,8,10,5,7,13,15,9,11,0,2,1,3,116,117,64,65,118,119,80,81,94,95,76,77,112,113,110,111,82,83,70,71,68,112,113,228,229,64,65,88,217,246,247,0,0,0,0,0,0,0,0,0,0,0,0,0,0,0,0,0,0,0,0,0,0,0,0,0,0,0,0,0,0,0,0,0,0,0,0,0,0,0,0,0,0,0,0,0,0,0,0,0},
  {64,65,66,67,68,69,70,71,72,73,74,75,76,77,78,79,0,1,2,3,0,1,2,3,4,5,6,7,8,9,10,11,12,13,14,15,64,66,76,78,65,67,77,79,68,70,69,71,72,74,73,75,12,14,8,10,13,15,9,11,0,2,4,6,1,3,5,7,4,6,8,10,0,2,5,7,9,11,12,14,1,3,13,15,64,65,70,71,80,81,112,113,90,91,102,103,118,119,104,105,114,115,106,107,94,95,68,69,82,83,98,99,108,109,92,12,14,4,6,13,15,0,2,8,10,5,7,1,3,9,11,4,6,5,7,0,2,8,10,12,14,1,3,9,11,13,15,76,78,68,70,64,66,77,79,69,71,72,74,65,67,73,75,132,134,128,130,133,135,129,131,136,138,140,142,137,139,141,143,12,14,8,10,4,6,0,2,13,15,9,11,5,7,1,3,4,6,12,14,8,10,5,7,13,15,9,11,0,2,1,3,4,6,12,14,136,138,5,7,13,15,137,139,128,130,129,131,64,65,84,85,92,93,104,105,74,75,206,207,100,101,82,83,72,73,116,117,222,223,234,235,198,0,0,0,0,0,0,0,0,0,0,0,0,0,0,0,0,0,0,0,0,0,0,0,0,0,0,0,0,0,0,0,0,0,0,0,0,0,0,0,0,0,0,0,0},
  {0,1,2,3,4,5,6,7,8,9,10,11,12,13,14,15,64,65,66,67,68,69,70,71,72,73,74,75,76,77,78,79,0,1,2,3,4,5,6,7,8,9,10,11,12,13,14,15,0,2,8,10,1,3,9,11,12,14,4,6,13,15,5,7,4,6,8,10,0,2,5,7,9,11,12,14,1,3,13,15,103,98,99,72,73,92,93,64,65,100,101,96,97,114,115,76,77,70,71,86,87,90,91,74,75,66,67,68,69,0,2,4,6,8,10,1,3,5,7,12,14,9,11,13,15,12,14,4,6,13,15,0,2,8,10,5,7,1,3,9,11,0,2,1,3,4,6,8,10,12,14,5,7,9,11,13,15,132,134,128,130,133,135,129,131,136,138,140,142,137,139,141,143,79,67,75,65,8,10,0,2,9,11,12,14,1,3,4,6,13,15,5,7,4,6,12,14,8,10,5,7,13,15,9,11,0,2,1,3,8,10,9,11,4,6,0,2,140,142,133,135,1,3,141,143,64,65,80,81,92,93,108,109,106,107,70,71,66,67,90,91,88,89,82,83,224,225,232,233,230,231,0,0,0,0,0,0,0,0,0,0,0,0,0,0,0,0,0,0,0,0,0,0,0,0,0,0,0,0,0,0,0,0,0,0,0,0,0,0,0,0,0,0,0,0,0},
  {64,65,66,67,68,69,70,71,72,73,74,75,76,77,78,79,0,1,2,3,64,65,66,67,68,69,70,71,72,73,74,75,76,77,78,79,64,66,76,78,65,67,77,79,68,70,69,71,72,74,73,75,4,6,0,2,5,7,1,3,12,14,8,10,13,15,9,11,4,6,8,10,0,2,5,7,9,11,12,14,1,3,13,15,90,91,70,71,72,73,66,67,64,65,84,85,92,93,80,81,86,87,94,95,76,77,88,89,106,107,78,79,96,97,0,2,4,6,8,10,1,3,5,7,12,14,9,11,13,15,4,6,5,7,0,2,8,10,12,14,1,3,9,11,13,15,12,14,4,6,0,2,13,15,5,7,8,10,1,3,9,11,64,71,70,74,77,69,78,72,76,68,66,73,8,10,9,11,4,6,0,2,12,14,5,7,1,3,13,15,4,6,12,14,8,10,5,7,13,15,9,11,0,2,1,3,12,14,8,10,13,15,4,6,9,11,5,7,0,2,1,3,106,107,104,105,92,93,88,89,72,73,90,91,100,101,206,207,116,117,64,65,118,119,80,209,222,223,204,0,0,0,0,0,0,0,0,0,0,0,0,0,0,0,0,0,0,0,0,0,0,0,0,0,0,0,0,0,0,0,0,0,0,0,0,0,0,0,0,0,0,0,0,0,0,0},
  {0,1,2,3,4,5,6,7,8,9,10,11,12,13,14,15,0,1,2,3,64,65,66,67,68,69,70,71,72,73,74,75,76,77,78,79,64,66,76,78,65,67,77,79,68,70,69,71,72,74,73,75,64,66,72,74,65,67,73,75,76,78,68,70,77,79,69,71,4,6,8,10,0,2,5,7,9,11,12,14,1,3,13,15,68,70,64,66,69,71,65,67,76,78,72,74,77,79,73,75,136,138,128,130,137,139,129,131,140,142,141,143,132,134,133,135,64,66,68,70,72,74,65,67,69,71,76,78,73,75,77,79,4,6,5,7,0,2,8,10,12,14,1,3,9,11,13,15,4,6,8,10,5,7,0,2,12,14,9,11,1,3,13,15,64,71,78,74,77,70,73,69,66,72,76,79,68,65,67,75,12,14,8,10,4,6,0,2,13,15,9,11,5,7,1,3,12,14,8,10,13,15,132,134,9,11,133,135,0,2,1,3,204,206,200,202,205,207,196,198,201,203,197,199,192,194,193,195,107,70,71,66,67,112,113,98,99,86,87,110,111,242,243,88,89,118,119,196,197,0,0,0,0,0,0,0,0,0,0,0,0,0,0,0,0,0,0,0,0,0,0,0,0,0,0,0,0,0,0,0,0,0,0,0,0,0,0,0,0,0,0,0,0,0,0,0},
  {64,65,66,67,68,69,70,71,72,73,74,75,76,77,78,79,0,1,2,3,72,78,70,71,0,1,2,3,4,5,6,7,8,9,10,11,12,13,14,15,0,2,8,10,1,3,9,11,12,14,4,6,13,15,5,7,12,14,8,10,13,15,9,11,0,2,4,6,1,3,5,7,4,6,12,14,8,10,0,2,5,7,13,15,9,11,1,3,136,138,128,130,137,139,129,131,140,142,141,143,132,134,133,135,75,88,89,76,77,96,97,86,87,72,73,116,117,110,111,4,6,5,7,12,14,8,10,0,2,13,15,9,11,1,3,12,14,4,6,0,2,13,15,5,7,8,10,1,3,9,11,132,134,128,130,133,135,129,131,136,138,140,142,137,139,141,143,8,10,9,11,4,6,0,2,12,14,5,7,1,3,13,15,4,6,5,7,8,10,12,14,9,11,13,15,0,2,1,3,12,14,8,10,13,15,132,134,9,11,133,135,128,130,129,131,116,117,96,97,74,75,64,65,112,113,82,83,106,107,84,80,81,66,67,90,91,96,97,242,243,74,75,198,199,0,0,0,0,0,0,0,0,0,0,0,0,0,0,0,0,0,0,0,0,0,0,0,0,0,0,0,0,0,0,0,0,0,0,0,0,0,0,0,0,0,0,0,0,0,0,0,0,0,0,0,0},
  {0,1,2,3,4,5,6,7,8,9,10,11,12,13,14,15,0,1,2,3,0,1,2,3,4,5,6,7,8,9,10,11,12,13,14,15,0,1,2,3,76,69,70,72,74,66,71,75,67,77,68,73,79,78,64,65,12,14,8,10,13,15,9,11,0,2,4,6,1,3,5,7,4,6,8,10,0,2,5,7,9,11,12,14,1,3,13,15,128,130,136,138,4,6,140,142,129,131,137,139,133,135,141,143,0,2,4,6,8,10,1,3,5,7,12,14,9,11,13,15,95,108,109,76,77,88,89,114,115,96,97,102,103,244,245,246,247,219,220,221,230,231,196,197,4,6,8,10,5,7,0,2,12,14,9,11,1,3,13,15,64,71,70,74,77,69,78,72,76,68,66,73,79,67,75,65,12,14,8,10,4,6,0,2,13,15,9,11,5,7,1,3,12,14,8,10,13,15,4,6,9,11,5,7,0,2,1,3,76,78,72,74,77,79,68,70,73,75,69,71,64,66,65,67,82,83,70,71,100,101,102,103,84,85,116,117,72,73,86,87,110,111,232,233,204,205,0,0,0,0,0,0,0,0,0,0,0,0,0,0,0,0,0,0,0,0,0,0,0,0,0,0,0,0,0,0,0,0,0,0,0,0,0,0,0,0,0,0,0,0,0,0,0,0,0,0},
  {64,65,66,67,68,69,70,71,72,73,74,75,76,77,78,79,0,1,2,3,4,5,6,7,8,9,10,11,12,13,14,15,70,64,76,66,74,72,79,71,78,67,69,65,75,77,68,73,0,2,8,10,1,3,9,11,12,14,4,6,13,15,5,7,4,6,12,14,8,10,0,2,5,7,13,15,9,11,1,3,4,6,12,14,8,10,0,2,5,7,13,15,9,11,1,3,136,138,128,130,137,139,129,131,140,142,141,143,132,134,133,135,12,14,4,6,13,15,0,2,8,10,5,7,1,3,9,11,4,6,5,7,0,2,8,10,12,14,1,3,9,11,13,15,4,6,8,10,5,7,0,2,12,14,9,11,1,3,13,15,132,134,128,130,133,135,129,131,136,138,140,142,137,139,141,143,8,10,9,11,4,6,0,2,12,14,5,7,1,3,13,15,4,6,12,14,8,10,5,7,13,15,9,11,0,2,1,3,8,10,0,2,9,11,140,142,1,3,132,134,141,143,133,135,92,93,108,109,98,99,80,81,100,101,70,71,110,111,82,83,68,69,104,105,108,109,102,103,244,245,0,0,0,0,0,0,0,0,0,0,0,0,0,0,0,0,0,0,0,0,0,0,0,0,0,0,0,0,0,0,0,0,0,0,0,0,0,0,0,0,0,0,0,0,0,0},
  {0,1,2,3,4,5,6,7,8,9,10,11,12,13,14,15,0,1,2,3,0,1,2,3,4,5,6,7,8,9,10,11,12,13,14,15,64,66,76,78,65,67,77,79,68,70,69,71,72,74,73,75,12,14,8,10,13,15,9,11,0,2,4,6,1,3,5,7,4,6,0,2,5,7,1,3,12,14,8,10,13,15,9,11,90,91,70,71,72,73,66,67,64,65,84,85,92,93,80,81,86,87,94,95,76,77,88,89,106,107,78,79,96,97,108,109,72,73,80,81,98,99,74,75,110,111,240,241,86,87,92,93,206,207,192,193,0,2,1,3,4,6,8,10,12,14,5,7,9,11,13,15,8,10,12,14,0,2,9,11,13,15,1,3,4,6,5,7,8,10,9,11,4,6,0,2,12,14,5,7,1,3,13,15,4,6,5,7,8,10,12,14,9,11,13,15,0,2,1,3,132,134,5,7,136,138,140,142,9,11,141,143,128,130,129,131,104,105,72,73,86,87,102,103,90,91,118,119,68,69,206,207,114,115,66,67,110,111,222,223,216,217,204,205,0,0,0,0,0,0,0,0,0,0,0,0,0,0,0,0,0,0,0,0,0,0,0,0,0,0,0,0,0,0,0,0,0,0,0,0,0,0,0,0,0,0,0,0,0,0,0,0,0,0,0,0},
  {64,65,66,67,68,69,70,71,72,73,74,75,76,77,78,79,0,1,2,3,0,1,2,3,4,5,6,7,8,9,10,11,12,13,14,15,64,66,76,78,65,67,77,79,68,70,69,71,72,74,73,75,12,14,8,10,13,15,9,11,0,2,4,6,1,3,5,7,4,6,8,10,0,2,5,7,9,11,12,14,1,3,13,15,0,2,8,10,4,6,12,14,1,3,9,11,5,7,13,15,99,102,103,68,69,110,111,104,105,73,116,117,82,83,100,101,74,75,86,87,92,93,118,119,68,69,4,6,5,7,12,14,8,10,0,2,13,15,9,11,1,3,79,68,65,67,70,64,71,78,77,69,72,75,70,74,79,76,73,68,67,66,65,8,10,0,2,9,11,12,14,1,3,4,6,13,15,5,7,12,14,8,10,4,6,0,2,13,15,9,11,5,7,1,3,4,6,12,14,8,10,5,7,13,15,0,2,9,11,1,3,80,81,96,97,92,93,108,109,70,71,82,83,100,101,78,206,207,106,107,86,87,94,95,76,77,220,221,200,201,226,227,0,0,0,0,0,0,0,0,0,0,0,0,0,0,0,0,0,0,0,0,0,0,0,0,0,0,0,0,0,0,0,0,0,0,0,0,0,0,0,0,0,0,0,0,0,0,0,0,0,0,0,0,0,0},
};

struct alignas(64) Params {
  CUtensorMap a[6];
  CUtensorMap w[4];
  CUtensorMap ow;
  CUtensorMap xr;
  const bf16 *x0, *wqkv;
  bf16* out;
  uint32_t swap;
  uint32_t jobs[NPAIR][JMAX];
  uint8_t kseq[NPAIR][KMAX];
};

template <class T> __device__ __forceinline__ T* at(T* base, uint32_t bytes) {
  T* r;
  asm("{\n.reg .u32 lo, hi;\nmov.b64 {lo, hi}, %1;\nadd.cc.u32 lo, lo, %2;\naddc.u32 hi, hi, 0;\nmov.b64 %0, {lo, hi};\n}" : "=l"(r) : "l"(base), "r"(bytes));
  return r;
}
#define SCR(sm, member, bytes) reinterpret_cast<decltype(&scratch_base()->member[0])>(at((sm).scratch, offsetof(Scratch, member) + (bytes)))
#define counter(line, word) SCR(sm, cnt, (line) * 128 + (word) * 4)
#define TRS(st, slot) do {} while (0)
#define TRX(cond, job, bit, slot, reg) do {} while (0)
#define TR(job, slot) do {} while (0)
#define TRI(cond, job, slot) do {} while (0)
#define TRK(cond, job, slot) do {} while (0)
#define TRC(job, slot) do {} while (0)

__device__ __forceinline__ uint32_t smem_u32(const void* p) { return (uint32_t)__cvta_generic_to_shared(p); }
__device__ __forceinline__ void mbar_init(uint32_t bar, uint32_t cnt) { asm volatile("mbarrier.init.shared::cta.b64 [%0], %1;" ::"r"(bar), "r"(cnt) : "memory"); }
__device__ __forceinline__ void mbar_expect_tx(uint32_t bar, uint32_t bytes) { asm volatile("mbarrier.arrive.expect_tx.shared::cta.b64 _, [%0], %1;" ::"r"(bar), "r"(bytes) : "memory"); }
__device__ __forceinline__ void mbar_arrive_n(uint32_t bar, uint32_t cnt) { asm volatile("mbarrier.arrive.shared::cta.b64 _, [%0], %1;" ::"r"(bar), "r"(cnt) : "memory"); }
__device__ __forceinline__ void mbar_arrive_cl_if(uint32_t cond, uint32_t bar) {
  asm volatile("{\n.reg .pred p;\nsetp.ne.u32 p, %1, 0;\n@p mbarrier.arrive.shared::cluster.b64 _, [%0];\n}" ::"r"(bar), "r"(cond) : "memory");
}
__device__ __forceinline__ void mbar_arrive_warp(uint32_t bar) {
  asm volatile("{\n.reg .pred p;\nbar.warp.sync -1;\nelect.sync _|p, -1;\n@p mbarrier.arrive.shared::cta.b64 _, [%0];\n}" ::"r"(bar) : "memory");
}
__device__ __forceinline__ uint32_t mapa(uint32_t addr, uint32_t cta) { uint32_t r; asm("mapa.shared::cluster.u32 %0, %1, %2;" : "=r"(r) : "r"(addr), "r"(cta)); return r; }
__device__ __forceinline__ bool mbar_test(uint32_t bar, uint32_t parity) {
  uint32_t ok;
  asm volatile("{\n.reg .pred p;\nmbarrier.test_wait.parity.shared::cta.b64 p, [%1], %2;\nselp.u32 %0, 1, 0, p;\n}\n" : "=r"(ok) : "r"(bar), "r"(parity) : "memory");
  return ok;
}
__device__ __forceinline__ void mbar_wait(uint32_t bar, uint32_t parity) {
  asm volatile(
      "{\n.reg .pred p;\n.reg .u32 n;\nmov.u32 n, 0;\n"
      "WAIT:\nmbarrier.try_wait.parity.shared::cta.b64 p, [%0], %1;\n@p bra DONE;\n"
      "add.u32 n, n, 1;\nsetp.lt.u32 p, n, %2;\n@p bra WAIT;\ntrap;\nDONE:\n}\n" ::"r"(bar), "r"(parity), "n"(SPIN_LIMIT) : "memory");
}
template <int ID, int N> __device__ __forceinline__ void bar_sync() { asm volatile("bar.sync %0, %1;" ::"n"(ID), "n"(N) : "memory"); }
template <int ID, int N> __device__ __forceinline__ void bar_arrive() { asm volatile("bar.arrive %0, %1;" ::"n"(ID), "n"(N) : "memory"); }
__device__ __forceinline__ uint32_t ld_relaxed(const uint32_t* p) { uint32_t v; asm volatile("ld.relaxed.gpu.global.u32 %0, [%1];" : "=r"(v) : "l"(p) : "memory"); return v; }
__device__ __forceinline__ void red_relaxed(uint32_t* p, uint32_t v) { asm volatile("red.relaxed.gpu.global.add.u32 [%0], %1;" ::"l"(p), "r"(v) : "memory"); }
__device__ __forceinline__ void red_release(uint32_t* p, uint32_t v) {
  asm volatile("fence.release.gpu;\nred.relaxed.gpu.global.add.u32 [%0], %1;" ::"l"(p), "r"(v) : "memory");
}
__device__ __forceinline__ bool elect() {
  uint32_t p;
  asm volatile("{\n.reg .pred P;\nelect.sync _|P, 0xffffffff;\nselp.u32 %0, 1, 0, P;\n}\n" : "=r"(p));
  return p;
}
__device__ __forceinline__ void fence_acquire() { asm volatile("fence.acquire.gpu;" ::: "memory"); }
__device__ __forceinline__ void wait_count(const uint32_t* p, uint32_t target) {
  for (uint32_t n = 0; !__all_sync(~0u, (int)(ld_relaxed(p) - target) >= 0); n++) {
    __nanosleep(200);
    if (n > SPIN_LIMIT) __trap();
  }
  fence_acquire();
}
__device__ __forceinline__ void fence_proxy_async() { asm volatile("fence.proxy.async.global;" ::: "memory"); }
__device__ __forceinline__ void fence_proxy_async_smem() { asm volatile("fence.proxy.async.shared::cta;" ::: "memory"); }
__device__ __forceinline__ void tma4d_mc(uint32_t dst, const CUtensorMap* tm, int c1, int c2, uint32_t bar, uint64_t pol) {
  asm volatile("cp.async.bulk.tensor.4d.shared::cluster.global.mbarrier::complete_tx::bytes.multicast::cluster.L2::cache_hint [%0], [%1, {%3, %4, %5, %3}], [%2], %6, %7;"
               ::"r"(dst), "l"(tm), "r"(bar), "r"(0), "r"(c1), "r"(c2), "h"((uint16_t)3), "l"(pol) : "memory");
}
__device__ __forceinline__ void tma3d(uint32_t dst, const CUtensorMap* tm, int c0, int c1, int c2, uint32_t bar, uint64_t pol) {
  asm volatile("cp.async.bulk.tensor.3d.shared::cluster.global.mbarrier::complete_tx::bytes.L2::cache_hint [%0], [%1, {%3, %4, %5}], [%2], %6;"
               ::"r"(dst), "l"(tm), "r"(bar), "r"(c0), "r"(c1), "r"(c2), "l"(pol) : "memory");
}
__device__ __forceinline__ void tma3d_reduce_add(const CUtensorMap* tm, int c0, int c1, int c2, uint32_t src) {
  asm volatile("cp.reduce.async.bulk.tensor.3d.global.shared::cta.add.tile.bulk_group [%0, {%2, %3, %4}], [%1];"
               ::"l"(tm), "r"(src), "r"(c0), "r"(c1), "r"(c2) : "memory");
}
__device__ __forceinline__ void tma3d_store(const CUtensorMap* tm, int c0, int c1, int c2, uint32_t src) {
  asm volatile("cp.async.bulk.tensor.3d.global.shared::cta.tile.bulk_group [%0, {%2, %3, %4}], [%1];"
               ::"l"(tm), "r"(src), "r"(c0), "r"(c1), "r"(c2) : "memory");
}
__device__ __forceinline__ void bulk_commit() { asm volatile("cp.async.bulk.commit_group;" ::: "memory"); }
template <int N> __device__ __forceinline__ void bulk_wait_read() { asm volatile("cp.async.bulk.wait_group.read %0;" ::"n"(N) : "memory"); }
__device__ __forceinline__ void bulk_wait() { asm volatile("cp.async.bulk.wait_group 0;" ::: "memory"); }
__device__ __forceinline__ uint2 lds64(uint32_t a) { uint2 v; asm volatile("ld.shared.v2.u32 {%0,%1}, [%2];" : "=r"(v.x), "=r"(v.y) : "r"(a) : "memory"); return v; }
__device__ __forceinline__ float lds32f(uint32_t a) { float v; asm volatile("ld.shared.f32 %0, [%1];" : "=f"(v) : "r"(a) : "memory"); return v; }
__device__ __forceinline__ uint4 lds128(uint32_t a) { uint4 v; asm volatile("ld.shared.v4.u32 {%0,%1,%2,%3}, [%4];" : "=r"(v.x), "=r"(v.y), "=r"(v.z), "=r"(v.w) : "r"(a) : "memory"); return v; }
__device__ __forceinline__ uint2 lds64v(uint32_t a) { uint2 v; asm volatile("ld.volatile.shared.v2.u32 {%0,%1}, [%2];" : "=r"(v.x), "=r"(v.y) : "r"(a) : "memory"); return v; }
__device__ __forceinline__ uint4 lds128v(uint32_t a) { uint4 v; asm volatile("ld.volatile.shared.v4.u32 {%0,%1,%2,%3}, [%4];" : "=r"(v.x), "=r"(v.y), "=r"(v.z), "=r"(v.w) : "r"(a) : "memory"); return v; }
__device__ __forceinline__ void sts32(uint32_t a, uint32_t v) { asm volatile("st.shared.u32 [%0], %1;" ::"r"(a), "r"(v) : "memory"); }
__device__ __forceinline__ void sts64(uint32_t a, uint2 v) { asm volatile("st.shared.v2.u32 [%0], {%1,%2};" ::"r"(a), "r"(v.x), "r"(v.y) : "memory"); }
__device__ __forceinline__ void stg128(void* p, uint4 v) { asm volatile("st.global.L1::no_allocate.v4.u32 [%0], {%1,%2,%3,%4};" ::"l"(p), "r"(v.x), "r"(v.y), "r"(v.z), "r"(v.w) : "memory"); }
__device__ __forceinline__ uint4 ldg128(const void* p) { uint4 v; asm volatile("ld.relaxed.gpu.global.v4.u32 {%0,%1,%2,%3}, [%4];" : "=r"(v.x), "=r"(v.y), "=r"(v.z), "=r"(v.w) : "l"(p) : "memory"); return v; }
__device__ __forceinline__ void prefetch_tm(const CUtensorMap* tm) { asm volatile("prefetch.tensormap [%0];" ::"l"(tm) : "memory"); }
template <int N> __device__ __forceinline__ void wg_wait() { asm volatile("wgmma.wait_group.sync.aligned %0;" ::"n"(N) : "memory"); }
__device__ __forceinline__ void cluster_arrive() { asm volatile("barrier.cluster.arrive.relaxed.aligned;" ::: "memory"); }
__device__ __forceinline__ void cluster_wait() { asm volatile("barrier.cluster.wait.acquire.aligned;" ::: "memory"); }
__device__ __forceinline__ uint32_t pack_bf16(float lo, float hi) { uint32_t r; asm("cvt.rn.bf16x2.f32 %0, %1, %2;" : "=r"(r) : "f"(hi), "f"(lo)); return r; }
__device__ __forceinline__ float bf_lo(uint32_t v) { return __uint_as_float(v << 16); }
__device__ __forceinline__ float bf_hi(uint32_t v) { return __uint_as_float(v & 0xffff0000u); }
__device__ __forceinline__ uint32_t dup_hi(uint32_t v) { return __byte_perm(v, 0, 0x3232); }
__device__ __forceinline__ float bf_round(float x) { return __bfloat162float(__float2bfloat16_rn(x)); }
__device__ __forceinline__ uint32_t bf2_add(uint32_t a, uint32_t b) { uint32_t r; asm("add.rn.bf16x2 %0, %1, %2;" : "=r"(r) : "r"(a), "r"(b)); return r; }
__device__ __forceinline__ uint32_t bf2_mul(uint32_t a, uint32_t b) { uint32_t r; asm("mul.rn.bf16x2 %0, %1, %2;" : "=r"(r) : "r"(a), "r"(b)); return r; }
__device__ __forceinline__ uint32_t bf2_fma(uint32_t a, uint32_t b, uint32_t c) { uint32_t r; asm("fma.rn.bf16x2 %0, %1, %2, %3;" : "=r"(r) : "r"(a), "r"(b), "r"(c)); return r; }
__device__ __forceinline__ uint4 add8(uint4 a, uint4 b) { return make_uint4(bf2_add(a.x, b.x), bf2_add(a.y, b.y), bf2_add(a.z, b.z), bf2_add(a.w, b.w)); }
__device__ __forceinline__ uint4 fma8(uint32_t a, uint4 b, uint4 c) { return make_uint4(bf2_fma(a, b.x, c.x), bf2_fma(a, b.y, c.y), bf2_fma(a, b.z, c.z), bf2_fma(a, b.w, c.w)); }
__device__ __forceinline__ void stsm4(uint32_t a, uint32_t r0, uint32_t r1, uint32_t r2, uint32_t r3) {
  asm volatile("stmatrix.sync.aligned.m8n8.x4.shared.b16 [%0], {%1,%2,%3,%4};" ::"r"(a), "r"(r0), "r"(r1), "r"(r2), "r"(r3) : "memory");
}
__device__ __forceinline__ void ldsm4(uint32_t a, uint32_t (&r)[4]) {
  asm volatile("ldmatrix.sync.aligned.m8n8.x4.shared.b16 {%0,%1,%2,%3}, [%4];" : "=r"(r[0]), "=r"(r[1]), "=r"(r[2]), "=r"(r[3]) : "r"(a) : "memory");
}
__device__ __forceinline__ void ldsm4t(uint32_t a, uint32_t (&r)[4]) {
  asm volatile("ldmatrix.sync.aligned.m8n8.x4.trans.shared.b16 {%0,%1,%2,%3}, [%4];" : "=r"(r[0]), "=r"(r[1]), "=r"(r[2]), "=r"(r[3]) : "r"(a) : "memory");
}
__device__ __forceinline__ void mma16816(float (&c)[4], uint32_t a0, uint32_t a1, uint32_t a2, uint32_t a3, uint32_t b0, uint32_t b1) {
  asm volatile("mma.sync.aligned.m16n8k16.row.col.f32.bf16.bf16.f32 {%0,%1,%2,%3}, {%4,%5,%6,%7}, {%8,%9}, {%0,%1,%2,%3};"
               : "+f"(c[0]), "+f"(c[1]), "+f"(c[2]), "+f"(c[3]) : "r"(a0), "r"(a1), "r"(a2), "r"(a3), "r"(b0), "r"(b1));
}
__device__ __forceinline__ void mma1688(float (&c)[4], uint32_t a0, uint32_t a1, uint32_t b0) {
  asm volatile("mma.sync.aligned.m16n8k8.row.col.f32.bf16.bf16.f32 {%0,%1,%2,%3}, {%4,%5}, {%6}, {%0,%1,%2,%3};"
               : "+f"(c[0]), "+f"(c[1]), "+f"(c[2]), "+f"(c[3]) : "r"(a0), "r"(a1), "r"(b0));
}
__device__ __forceinline__ float ex2(float x) { float y; asm("ex2.approx.ftz.f32 %0, %1;" : "=f"(y) : "f"(x)); return y; }
__device__ __forceinline__ float sqrt_fast(float x) { float y; asm("sqrt.approx.f32 %0, %1;" : "=f"(y) : "f"(x)); return y; }
__device__ __forceinline__ float tanh_fast(float x) { float y; asm("tanh.approx.f32 %0, %1;" : "=f"(y) : "f"(x)); return y; }
__device__ __forceinline__ float rcp(float x) { float y; asm("rcp.approx.ftz.f32 %0, %1;" : "=f"(y) : "f"(x)); return y; }
__device__ __forceinline__ uint32_t opaque_zero() { uint32_t z; asm volatile("mov.u32 %0, %%ctaid.y;" : "=r"(z)); return z; }
__device__ __forceinline__ int fresh_tid() { int t; asm volatile("mov.u32 %0, %%tid.x;" : "=r"(t)); return t; }

__device__ __forceinline__ void first_kstep(float (&d)[128], uint32_t a, uint32_t b) {
  asm volatile("{\n.reg .u32 t;\n.reg .u64 da, db;\nwgmma.fence.sync.aligned;\n"
    "add.u32 t, %128, 0;\nmov.b64 da, {t, %130};\nadd.u32 t, %129, 0;\nmov.b64 db, {t, %130};\n"
    "wgmma.mma_async.sync.aligned.m64n256k16.f32.bf16.bf16 {%0, %1, %2, %3, %4, %5, %6, %7, %8, %9, %10, %11, %12, %13, %14, %15, %16, %17, %18, %19, %20, %21, %22, %23, %24, %25, %26, %27, %28, %29, %30, %31, %32, %33, %34, %35, %36, %37, %38, %39, %40, %41, %42, %43, %44, %45, %46, %47, %48, %49, %50, %51, %52, %53, %54, %55, %56, %57, %58, %59, %60, %61, %62, %63, %64, %65, %66, %67, %68, %69, %70, %71, %72, %73, %74, %75, %76, %77, %78, %79, %80, %81, %82, %83, %84, %85, %86, %87, %88, %89, %90, %91, %92, %93, %94, %95, %96, %97, %98, %99, %100, %101, %102, %103, %104, %105, %106, %107, %108, %109, %110, %111, %112, %113, %114, %115, %116, %117, %118, %119, %120, %121, %122, %123, %124, %125, %126, %127}, da, db, 0, 1, 1, 0, 1;\nwgmma.commit_group.sync.aligned;\n"
    "add.u32 t, %128, 2;\nmov.b64 da, {t, %130};\nadd.u32 t, %129, 128;\nmov.b64 db, {t, %130};\n"
    "wgmma.mma_async.sync.aligned.m64n256k16.f32.bf16.bf16 {%0, %1, %2, %3, %4, %5, %6, %7, %8, %9, %10, %11, %12, %13, %14, %15, %16, %17, %18, %19, %20, %21, %22, %23, %24, %25, %26, %27, %28, %29, %30, %31, %32, %33, %34, %35, %36, %37, %38, %39, %40, %41, %42, %43, %44, %45, %46, %47, %48, %49, %50, %51, %52, %53, %54, %55, %56, %57, %58, %59, %60, %61, %62, %63, %64, %65, %66, %67, %68, %69, %70, %71, %72, %73, %74, %75, %76, %77, %78, %79, %80, %81, %82, %83, %84, %85, %86, %87, %88, %89, %90, %91, %92, %93, %94, %95, %96, %97, %98, %99, %100, %101, %102, %103, %104, %105, %106, %107, %108, %109, %110, %111, %112, %113, %114, %115, %116, %117, %118, %119, %120, %121, %122, %123, %124, %125, %126, %127}, da, db, 1, 1, 1, 0, 1;\n"
    "add.u32 t, %128, 4;\nmov.b64 da, {t, %130};\nadd.u32 t, %129, 1024;\nmov.b64 db, {t, %130};\n"
    "wgmma.mma_async.sync.aligned.m64n256k16.f32.bf16.bf16 {%0, %1, %2, %3, %4, %5, %6, %7, %8, %9, %10, %11, %12, %13, %14, %15, %16, %17, %18, %19, %20, %21, %22, %23, %24, %25, %26, %27, %28, %29, %30, %31, %32, %33, %34, %35, %36, %37, %38, %39, %40, %41, %42, %43, %44, %45, %46, %47, %48, %49, %50, %51, %52, %53, %54, %55, %56, %57, %58, %59, %60, %61, %62, %63, %64, %65, %66, %67, %68, %69, %70, %71, %72, %73, %74, %75, %76, %77, %78, %79, %80, %81, %82, %83, %84, %85, %86, %87, %88, %89, %90, %91, %92, %93, %94, %95, %96, %97, %98, %99, %100, %101, %102, %103, %104, %105, %106, %107, %108, %109, %110, %111, %112, %113, %114, %115, %116, %117, %118, %119, %120, %121, %122, %123, %124, %125, %126, %127}, da, db, 1, 1, 1, 0, 1;\n"
    "add.u32 t, %128, 6;\nmov.b64 da, {t, %130};\nadd.u32 t, %129, 1152;\nmov.b64 db, {t, %130};\n"
    "wgmma.mma_async.sync.aligned.m64n256k16.f32.bf16.bf16 {%0, %1, %2, %3, %4, %5, %6, %7, %8, %9, %10, %11, %12, %13, %14, %15, %16, %17, %18, %19, %20, %21, %22, %23, %24, %25, %26, %27, %28, %29, %30, %31, %32, %33, %34, %35, %36, %37, %38, %39, %40, %41, %42, %43, %44, %45, %46, %47, %48, %49, %50, %51, %52, %53, %54, %55, %56, %57, %58, %59, %60, %61, %62, %63, %64, %65, %66, %67, %68, %69, %70, %71, %72, %73, %74, %75, %76, %77, %78, %79, %80, %81, %82, %83, %84, %85, %86, %87, %88, %89, %90, %91, %92, %93, %94, %95, %96, %97, %98, %99, %100, %101, %102, %103, %104, %105, %106, %107, %108, %109, %110, %111, %112, %113, %114, %115, %116, %117, %118, %119, %120, %121, %122, %123, %124, %125, %126, %127}, da, db, 1, 1, 1, 0, 1;\nwgmma.commit_group.sync.aligned;\n"
    "}\n"
    : "=f"(d[0]), "=f"(d[1]), "=f"(d[2]), "=f"(d[3]), "=f"(d[4]), "=f"(d[5]), "=f"(d[6]), "=f"(d[7]), "=f"(d[8]), "=f"(d[9]), "=f"(d[10]), "=f"(d[11]), "=f"(d[12]), "=f"(d[13]), "=f"(d[14]), "=f"(d[15]), "=f"(d[16]), "=f"(d[17]), "=f"(d[18]), "=f"(d[19]), "=f"(d[20]), "=f"(d[21]), "=f"(d[22]), "=f"(d[23]), "=f"(d[24]), "=f"(d[25]), "=f"(d[26]), "=f"(d[27]), "=f"(d[28]), "=f"(d[29]), "=f"(d[30]), "=f"(d[31]), "=f"(d[32]), "=f"(d[33]), "=f"(d[34]), "=f"(d[35]), "=f"(d[36]), "=f"(d[37]), "=f"(d[38]), "=f"(d[39]), "=f"(d[40]), "=f"(d[41]), "=f"(d[42]), "=f"(d[43]), "=f"(d[44]), "=f"(d[45]), "=f"(d[46]), "=f"(d[47]), "=f"(d[48]), "=f"(d[49]), "=f"(d[50]), "=f"(d[51]), "=f"(d[52]), "=f"(d[53]), "=f"(d[54]), "=f"(d[55]), "=f"(d[56]), "=f"(d[57]), "=f"(d[58]), "=f"(d[59]), "=f"(d[60]), "=f"(d[61]), "=f"(d[62]), "=f"(d[63]), "=f"(d[64]), "=f"(d[65]), "=f"(d[66]), "=f"(d[67]), "=f"(d[68]), "=f"(d[69]), "=f"(d[70]), "=f"(d[71]), "=f"(d[72]), "=f"(d[73]), "=f"(d[74]), "=f"(d[75]), "=f"(d[76]), "=f"(d[77]), "=f"(d[78]), "=f"(d[79]), "=f"(d[80]), "=f"(d[81]), "=f"(d[82]), "=f"(d[83]), "=f"(d[84]), "=f"(d[85]), "=f"(d[86]), "=f"(d[87]), "=f"(d[88]), "=f"(d[89]), "=f"(d[90]), "=f"(d[91]), "=f"(d[92]), "=f"(d[93]), "=f"(d[94]), "=f"(d[95]), "=f"(d[96]), "=f"(d[97]), "=f"(d[98]), "=f"(d[99]), "=f"(d[100]), "=f"(d[101]), "=f"(d[102]), "=f"(d[103]), "=f"(d[104]), "=f"(d[105]), "=f"(d[106]), "=f"(d[107]), "=f"(d[108]), "=f"(d[109]), "=f"(d[110]), "=f"(d[111]), "=f"(d[112]), "=f"(d[113]), "=f"(d[114]), "=f"(d[115]), "=f"(d[116]), "=f"(d[117]), "=f"(d[118]), "=f"(d[119]), "=f"(d[120]), "=f"(d[121]), "=f"(d[122]), "=f"(d[123]), "=f"(d[124]), "=f"(d[125]), "=f"(d[126]), "=f"(d[127])
    : "r"(a), "r"(b), "n"(0x40000040) : "memory");
}
__device__ __forceinline__ void kstep(float (&d)[128], uint32_t a, uint32_t b) {
  asm volatile("{\n.reg .u32 t;\n.reg .u64 da, db;\nwgmma.fence.sync.aligned;\n"
    "add.u32 t, %128, 0;\nmov.b64 da, {t, %130};\nadd.u32 t, %129, 0;\nmov.b64 db, {t, %130};\n"
    "wgmma.mma_async.sync.aligned.m64n256k16.f32.bf16.bf16 {%0, %1, %2, %3, %4, %5, %6, %7, %8, %9, %10, %11, %12, %13, %14, %15, %16, %17, %18, %19, %20, %21, %22, %23, %24, %25, %26, %27, %28, %29, %30, %31, %32, %33, %34, %35, %36, %37, %38, %39, %40, %41, %42, %43, %44, %45, %46, %47, %48, %49, %50, %51, %52, %53, %54, %55, %56, %57, %58, %59, %60, %61, %62, %63, %64, %65, %66, %67, %68, %69, %70, %71, %72, %73, %74, %75, %76, %77, %78, %79, %80, %81, %82, %83, %84, %85, %86, %87, %88, %89, %90, %91, %92, %93, %94, %95, %96, %97, %98, %99, %100, %101, %102, %103, %104, %105, %106, %107, %108, %109, %110, %111, %112, %113, %114, %115, %116, %117, %118, %119, %120, %121, %122, %123, %124, %125, %126, %127}, da, db, 1, 1, 1, 0, 1;\nwgmma.commit_group.sync.aligned;\n"
    "add.u32 t, %128, 2;\nmov.b64 da, {t, %130};\nadd.u32 t, %129, 128;\nmov.b64 db, {t, %130};\n"
    "wgmma.mma_async.sync.aligned.m64n256k16.f32.bf16.bf16 {%0, %1, %2, %3, %4, %5, %6, %7, %8, %9, %10, %11, %12, %13, %14, %15, %16, %17, %18, %19, %20, %21, %22, %23, %24, %25, %26, %27, %28, %29, %30, %31, %32, %33, %34, %35, %36, %37, %38, %39, %40, %41, %42, %43, %44, %45, %46, %47, %48, %49, %50, %51, %52, %53, %54, %55, %56, %57, %58, %59, %60, %61, %62, %63, %64, %65, %66, %67, %68, %69, %70, %71, %72, %73, %74, %75, %76, %77, %78, %79, %80, %81, %82, %83, %84, %85, %86, %87, %88, %89, %90, %91, %92, %93, %94, %95, %96, %97, %98, %99, %100, %101, %102, %103, %104, %105, %106, %107, %108, %109, %110, %111, %112, %113, %114, %115, %116, %117, %118, %119, %120, %121, %122, %123, %124, %125, %126, %127}, da, db, 1, 1, 1, 0, 1;\n"
    "add.u32 t, %128, 4;\nmov.b64 da, {t, %130};\nadd.u32 t, %129, 1024;\nmov.b64 db, {t, %130};\n"
    "wgmma.mma_async.sync.aligned.m64n256k16.f32.bf16.bf16 {%0, %1, %2, %3, %4, %5, %6, %7, %8, %9, %10, %11, %12, %13, %14, %15, %16, %17, %18, %19, %20, %21, %22, %23, %24, %25, %26, %27, %28, %29, %30, %31, %32, %33, %34, %35, %36, %37, %38, %39, %40, %41, %42, %43, %44, %45, %46, %47, %48, %49, %50, %51, %52, %53, %54, %55, %56, %57, %58, %59, %60, %61, %62, %63, %64, %65, %66, %67, %68, %69, %70, %71, %72, %73, %74, %75, %76, %77, %78, %79, %80, %81, %82, %83, %84, %85, %86, %87, %88, %89, %90, %91, %92, %93, %94, %95, %96, %97, %98, %99, %100, %101, %102, %103, %104, %105, %106, %107, %108, %109, %110, %111, %112, %113, %114, %115, %116, %117, %118, %119, %120, %121, %122, %123, %124, %125, %126, %127}, da, db, 1, 1, 1, 0, 1;\n"
    "add.u32 t, %128, 6;\nmov.b64 da, {t, %130};\nadd.u32 t, %129, 1152;\nmov.b64 db, {t, %130};\n"
    "wgmma.mma_async.sync.aligned.m64n256k16.f32.bf16.bf16 {%0, %1, %2, %3, %4, %5, %6, %7, %8, %9, %10, %11, %12, %13, %14, %15, %16, %17, %18, %19, %20, %21, %22, %23, %24, %25, %26, %27, %28, %29, %30, %31, %32, %33, %34, %35, %36, %37, %38, %39, %40, %41, %42, %43, %44, %45, %46, %47, %48, %49, %50, %51, %52, %53, %54, %55, %56, %57, %58, %59, %60, %61, %62, %63, %64, %65, %66, %67, %68, %69, %70, %71, %72, %73, %74, %75, %76, %77, %78, %79, %80, %81, %82, %83, %84, %85, %86, %87, %88, %89, %90, %91, %92, %93, %94, %95, %96, %97, %98, %99, %100, %101, %102, %103, %104, %105, %106, %107, %108, %109, %110, %111, %112, %113, %114, %115, %116, %117, %118, %119, %120, %121, %122, %123, %124, %125, %126, %127}, da, db, 1, 1, 1, 0, 1;\nwgmma.commit_group.sync.aligned;\n"
    "}\n"
    : "+f"(d[0]), "+f"(d[1]), "+f"(d[2]), "+f"(d[3]), "+f"(d[4]), "+f"(d[5]), "+f"(d[6]), "+f"(d[7]), "+f"(d[8]), "+f"(d[9]), "+f"(d[10]), "+f"(d[11]), "+f"(d[12]), "+f"(d[13]), "+f"(d[14]), "+f"(d[15]), "+f"(d[16]), "+f"(d[17]), "+f"(d[18]), "+f"(d[19]), "+f"(d[20]), "+f"(d[21]), "+f"(d[22]), "+f"(d[23]), "+f"(d[24]), "+f"(d[25]), "+f"(d[26]), "+f"(d[27]), "+f"(d[28]), "+f"(d[29]), "+f"(d[30]), "+f"(d[31]), "+f"(d[32]), "+f"(d[33]), "+f"(d[34]), "+f"(d[35]), "+f"(d[36]), "+f"(d[37]), "+f"(d[38]), "+f"(d[39]), "+f"(d[40]), "+f"(d[41]), "+f"(d[42]), "+f"(d[43]), "+f"(d[44]), "+f"(d[45]), "+f"(d[46]), "+f"(d[47]), "+f"(d[48]), "+f"(d[49]), "+f"(d[50]), "+f"(d[51]), "+f"(d[52]), "+f"(d[53]), "+f"(d[54]), "+f"(d[55]), "+f"(d[56]), "+f"(d[57]), "+f"(d[58]), "+f"(d[59]), "+f"(d[60]), "+f"(d[61]), "+f"(d[62]), "+f"(d[63]), "+f"(d[64]), "+f"(d[65]), "+f"(d[66]), "+f"(d[67]), "+f"(d[68]), "+f"(d[69]), "+f"(d[70]), "+f"(d[71]), "+f"(d[72]), "+f"(d[73]), "+f"(d[74]), "+f"(d[75]), "+f"(d[76]), "+f"(d[77]), "+f"(d[78]), "+f"(d[79]), "+f"(d[80]), "+f"(d[81]), "+f"(d[82]), "+f"(d[83]), "+f"(d[84]), "+f"(d[85]), "+f"(d[86]), "+f"(d[87]), "+f"(d[88]), "+f"(d[89]), "+f"(d[90]), "+f"(d[91]), "+f"(d[92]), "+f"(d[93]), "+f"(d[94]), "+f"(d[95]), "+f"(d[96]), "+f"(d[97]), "+f"(d[98]), "+f"(d[99]), "+f"(d[100]), "+f"(d[101]), "+f"(d[102]), "+f"(d[103]), "+f"(d[104]), "+f"(d[105]), "+f"(d[106]), "+f"(d[107]), "+f"(d[108]), "+f"(d[109]), "+f"(d[110]), "+f"(d[111]), "+f"(d[112]), "+f"(d[113]), "+f"(d[114]), "+f"(d[115]), "+f"(d[116]), "+f"(d[117]), "+f"(d[118]), "+f"(d[119]), "+f"(d[120]), "+f"(d[121]), "+f"(d[122]), "+f"(d[123]), "+f"(d[124]), "+f"(d[125]), "+f"(d[126]), "+f"(d[127])
    : "r"(a), "r"(b), "n"(0x40000040) : "memory");
}
__device__ __forceinline__ void first_kstep(float (&d)[96], uint32_t a, uint32_t b) {
  asm volatile("{\n.reg .u32 t;\n.reg .u64 da, db;\nwgmma.fence.sync.aligned;\n"
    "add.u32 t, %96, 0;\nmov.b64 da, {t, %98};\nadd.u32 t, %97, 0;\nmov.b64 db, {t, %98};\n"
    "wgmma.mma_async.sync.aligned.m64n192k16.f32.bf16.bf16 {%0, %1, %2, %3, %4, %5, %6, %7, %8, %9, %10, %11, %12, %13, %14, %15, %16, %17, %18, %19, %20, %21, %22, %23, %24, %25, %26, %27, %28, %29, %30, %31, %32, %33, %34, %35, %36, %37, %38, %39, %40, %41, %42, %43, %44, %45, %46, %47, %48, %49, %50, %51, %52, %53, %54, %55, %56, %57, %58, %59, %60, %61, %62, %63, %64, %65, %66, %67, %68, %69, %70, %71, %72, %73, %74, %75, %76, %77, %78, %79, %80, %81, %82, %83, %84, %85, %86, %87, %88, %89, %90, %91, %92, %93, %94, %95}, da, db, 0, 1, 1, 0, 1;\nwgmma.commit_group.sync.aligned;\n"
    "add.u32 t, %96, 2;\nmov.b64 da, {t, %98};\nadd.u32 t, %97, 128;\nmov.b64 db, {t, %98};\n"
    "wgmma.mma_async.sync.aligned.m64n192k16.f32.bf16.bf16 {%0, %1, %2, %3, %4, %5, %6, %7, %8, %9, %10, %11, %12, %13, %14, %15, %16, %17, %18, %19, %20, %21, %22, %23, %24, %25, %26, %27, %28, %29, %30, %31, %32, %33, %34, %35, %36, %37, %38, %39, %40, %41, %42, %43, %44, %45, %46, %47, %48, %49, %50, %51, %52, %53, %54, %55, %56, %57, %58, %59, %60, %61, %62, %63, %64, %65, %66, %67, %68, %69, %70, %71, %72, %73, %74, %75, %76, %77, %78, %79, %80, %81, %82, %83, %84, %85, %86, %87, %88, %89, %90, %91, %92, %93, %94, %95}, da, db, 1, 1, 1, 0, 1;\n"
    "add.u32 t, %96, 4;\nmov.b64 da, {t, %98};\nadd.u32 t, %97, 1024;\nmov.b64 db, {t, %98};\n"
    "wgmma.mma_async.sync.aligned.m64n192k16.f32.bf16.bf16 {%0, %1, %2, %3, %4, %5, %6, %7, %8, %9, %10, %11, %12, %13, %14, %15, %16, %17, %18, %19, %20, %21, %22, %23, %24, %25, %26, %27, %28, %29, %30, %31, %32, %33, %34, %35, %36, %37, %38, %39, %40, %41, %42, %43, %44, %45, %46, %47, %48, %49, %50, %51, %52, %53, %54, %55, %56, %57, %58, %59, %60, %61, %62, %63, %64, %65, %66, %67, %68, %69, %70, %71, %72, %73, %74, %75, %76, %77, %78, %79, %80, %81, %82, %83, %84, %85, %86, %87, %88, %89, %90, %91, %92, %93, %94, %95}, da, db, 1, 1, 1, 0, 1;\n"
    "add.u32 t, %96, 6;\nmov.b64 da, {t, %98};\nadd.u32 t, %97, 1152;\nmov.b64 db, {t, %98};\n"
    "wgmma.mma_async.sync.aligned.m64n192k16.f32.bf16.bf16 {%0, %1, %2, %3, %4, %5, %6, %7, %8, %9, %10, %11, %12, %13, %14, %15, %16, %17, %18, %19, %20, %21, %22, %23, %24, %25, %26, %27, %28, %29, %30, %31, %32, %33, %34, %35, %36, %37, %38, %39, %40, %41, %42, %43, %44, %45, %46, %47, %48, %49, %50, %51, %52, %53, %54, %55, %56, %57, %58, %59, %60, %61, %62, %63, %64, %65, %66, %67, %68, %69, %70, %71, %72, %73, %74, %75, %76, %77, %78, %79, %80, %81, %82, %83, %84, %85, %86, %87, %88, %89, %90, %91, %92, %93, %94, %95}, da, db, 1, 1, 1, 0, 1;\nwgmma.commit_group.sync.aligned;\n"
    "}\n"
    : "=f"(d[0]), "=f"(d[1]), "=f"(d[2]), "=f"(d[3]), "=f"(d[4]), "=f"(d[5]), "=f"(d[6]), "=f"(d[7]), "=f"(d[8]), "=f"(d[9]), "=f"(d[10]), "=f"(d[11]), "=f"(d[12]), "=f"(d[13]), "=f"(d[14]), "=f"(d[15]), "=f"(d[16]), "=f"(d[17]), "=f"(d[18]), "=f"(d[19]), "=f"(d[20]), "=f"(d[21]), "=f"(d[22]), "=f"(d[23]), "=f"(d[24]), "=f"(d[25]), "=f"(d[26]), "=f"(d[27]), "=f"(d[28]), "=f"(d[29]), "=f"(d[30]), "=f"(d[31]), "=f"(d[32]), "=f"(d[33]), "=f"(d[34]), "=f"(d[35]), "=f"(d[36]), "=f"(d[37]), "=f"(d[38]), "=f"(d[39]), "=f"(d[40]), "=f"(d[41]), "=f"(d[42]), "=f"(d[43]), "=f"(d[44]), "=f"(d[45]), "=f"(d[46]), "=f"(d[47]), "=f"(d[48]), "=f"(d[49]), "=f"(d[50]), "=f"(d[51]), "=f"(d[52]), "=f"(d[53]), "=f"(d[54]), "=f"(d[55]), "=f"(d[56]), "=f"(d[57]), "=f"(d[58]), "=f"(d[59]), "=f"(d[60]), "=f"(d[61]), "=f"(d[62]), "=f"(d[63]), "=f"(d[64]), "=f"(d[65]), "=f"(d[66]), "=f"(d[67]), "=f"(d[68]), "=f"(d[69]), "=f"(d[70]), "=f"(d[71]), "=f"(d[72]), "=f"(d[73]), "=f"(d[74]), "=f"(d[75]), "=f"(d[76]), "=f"(d[77]), "=f"(d[78]), "=f"(d[79]), "=f"(d[80]), "=f"(d[81]), "=f"(d[82]), "=f"(d[83]), "=f"(d[84]), "=f"(d[85]), "=f"(d[86]), "=f"(d[87]), "=f"(d[88]), "=f"(d[89]), "=f"(d[90]), "=f"(d[91]), "=f"(d[92]), "=f"(d[93]), "=f"(d[94]), "=f"(d[95])
    : "r"(a), "r"(b), "n"(0x40000040) : "memory");
}
__device__ __forceinline__ void kstep(float (&d)[96], uint32_t a, uint32_t b) {
  asm volatile("{\n.reg .u32 t;\n.reg .u64 da, db;\nwgmma.fence.sync.aligned;\n"
    "add.u32 t, %96, 0;\nmov.b64 da, {t, %98};\nadd.u32 t, %97, 0;\nmov.b64 db, {t, %98};\n"
    "wgmma.mma_async.sync.aligned.m64n192k16.f32.bf16.bf16 {%0, %1, %2, %3, %4, %5, %6, %7, %8, %9, %10, %11, %12, %13, %14, %15, %16, %17, %18, %19, %20, %21, %22, %23, %24, %25, %26, %27, %28, %29, %30, %31, %32, %33, %34, %35, %36, %37, %38, %39, %40, %41, %42, %43, %44, %45, %46, %47, %48, %49, %50, %51, %52, %53, %54, %55, %56, %57, %58, %59, %60, %61, %62, %63, %64, %65, %66, %67, %68, %69, %70, %71, %72, %73, %74, %75, %76, %77, %78, %79, %80, %81, %82, %83, %84, %85, %86, %87, %88, %89, %90, %91, %92, %93, %94, %95}, da, db, 1, 1, 1, 0, 1;\nwgmma.commit_group.sync.aligned;\n"
    "add.u32 t, %96, 2;\nmov.b64 da, {t, %98};\nadd.u32 t, %97, 128;\nmov.b64 db, {t, %98};\n"
    "wgmma.mma_async.sync.aligned.m64n192k16.f32.bf16.bf16 {%0, %1, %2, %3, %4, %5, %6, %7, %8, %9, %10, %11, %12, %13, %14, %15, %16, %17, %18, %19, %20, %21, %22, %23, %24, %25, %26, %27, %28, %29, %30, %31, %32, %33, %34, %35, %36, %37, %38, %39, %40, %41, %42, %43, %44, %45, %46, %47, %48, %49, %50, %51, %52, %53, %54, %55, %56, %57, %58, %59, %60, %61, %62, %63, %64, %65, %66, %67, %68, %69, %70, %71, %72, %73, %74, %75, %76, %77, %78, %79, %80, %81, %82, %83, %84, %85, %86, %87, %88, %89, %90, %91, %92, %93, %94, %95}, da, db, 1, 1, 1, 0, 1;\n"
    "add.u32 t, %96, 4;\nmov.b64 da, {t, %98};\nadd.u32 t, %97, 1024;\nmov.b64 db, {t, %98};\n"
    "wgmma.mma_async.sync.aligned.m64n192k16.f32.bf16.bf16 {%0, %1, %2, %3, %4, %5, %6, %7, %8, %9, %10, %11, %12, %13, %14, %15, %16, %17, %18, %19, %20, %21, %22, %23, %24, %25, %26, %27, %28, %29, %30, %31, %32, %33, %34, %35, %36, %37, %38, %39, %40, %41, %42, %43, %44, %45, %46, %47, %48, %49, %50, %51, %52, %53, %54, %55, %56, %57, %58, %59, %60, %61, %62, %63, %64, %65, %66, %67, %68, %69, %70, %71, %72, %73, %74, %75, %76, %77, %78, %79, %80, %81, %82, %83, %84, %85, %86, %87, %88, %89, %90, %91, %92, %93, %94, %95}, da, db, 1, 1, 1, 0, 1;\n"
    "add.u32 t, %96, 6;\nmov.b64 da, {t, %98};\nadd.u32 t, %97, 1152;\nmov.b64 db, {t, %98};\n"
    "wgmma.mma_async.sync.aligned.m64n192k16.f32.bf16.bf16 {%0, %1, %2, %3, %4, %5, %6, %7, %8, %9, %10, %11, %12, %13, %14, %15, %16, %17, %18, %19, %20, %21, %22, %23, %24, %25, %26, %27, %28, %29, %30, %31, %32, %33, %34, %35, %36, %37, %38, %39, %40, %41, %42, %43, %44, %45, %46, %47, %48, %49, %50, %51, %52, %53, %54, %55, %56, %57, %58, %59, %60, %61, %62, %63, %64, %65, %66, %67, %68, %69, %70, %71, %72, %73, %74, %75, %76, %77, %78, %79, %80, %81, %82, %83, %84, %85, %86, %87, %88, %89, %90, %91, %92, %93, %94, %95}, da, db, 1, 1, 1, 0, 1;\nwgmma.commit_group.sync.aligned;\n"
    "}\n"
    : "+f"(d[0]), "+f"(d[1]), "+f"(d[2]), "+f"(d[3]), "+f"(d[4]), "+f"(d[5]), "+f"(d[6]), "+f"(d[7]), "+f"(d[8]), "+f"(d[9]), "+f"(d[10]), "+f"(d[11]), "+f"(d[12]), "+f"(d[13]), "+f"(d[14]), "+f"(d[15]), "+f"(d[16]), "+f"(d[17]), "+f"(d[18]), "+f"(d[19]), "+f"(d[20]), "+f"(d[21]), "+f"(d[22]), "+f"(d[23]), "+f"(d[24]), "+f"(d[25]), "+f"(d[26]), "+f"(d[27]), "+f"(d[28]), "+f"(d[29]), "+f"(d[30]), "+f"(d[31]), "+f"(d[32]), "+f"(d[33]), "+f"(d[34]), "+f"(d[35]), "+f"(d[36]), "+f"(d[37]), "+f"(d[38]), "+f"(d[39]), "+f"(d[40]), "+f"(d[41]), "+f"(d[42]), "+f"(d[43]), "+f"(d[44]), "+f"(d[45]), "+f"(d[46]), "+f"(d[47]), "+f"(d[48]), "+f"(d[49]), "+f"(d[50]), "+f"(d[51]), "+f"(d[52]), "+f"(d[53]), "+f"(d[54]), "+f"(d[55]), "+f"(d[56]), "+f"(d[57]), "+f"(d[58]), "+f"(d[59]), "+f"(d[60]), "+f"(d[61]), "+f"(d[62]), "+f"(d[63]), "+f"(d[64]), "+f"(d[65]), "+f"(d[66]), "+f"(d[67]), "+f"(d[68]), "+f"(d[69]), "+f"(d[70]), "+f"(d[71]), "+f"(d[72]), "+f"(d[73]), "+f"(d[74]), "+f"(d[75]), "+f"(d[76]), "+f"(d[77]), "+f"(d[78]), "+f"(d[79]), "+f"(d[80]), "+f"(d[81]), "+f"(d[82]), "+f"(d[83]), "+f"(d[84]), "+f"(d[85]), "+f"(d[86]), "+f"(d[87]), "+f"(d[88]), "+f"(d[89]), "+f"(d[90]), "+f"(d[91]), "+f"(d[92]), "+f"(d[93]), "+f"(d[94]), "+f"(d[95])
    : "r"(a), "r"(b), "n"(0x40000040) : "memory");
}
__device__ __forceinline__ void half_kstep0(float (&d)[64], uint32_t a, uint32_t b) {
  asm volatile("{\n.reg .u32 t;\n.reg .u64 da, db;\nwgmma.fence.sync.aligned;\n"
    "add.u32 t, %64, 0;\nmov.b64 da, {t, %66};\nadd.u32 t, %65, 0;\nmov.b64 db, {t, %66};\n"
    "wgmma.mma_async.sync.aligned.m64n128k16.f32.bf16.bf16 {%0, %1, %2, %3, %4, %5, %6, %7, %8, %9, %10, %11, %12, %13, %14, %15, %16, %17, %18, %19, %20, %21, %22, %23, %24, %25, %26, %27, %28, %29, %30, %31, %32, %33, %34, %35, %36, %37, %38, %39, %40, %41, %42, %43, %44, %45, %46, %47, %48, %49, %50, %51, %52, %53, %54, %55, %56, %57, %58, %59, %60, %61, %62, %63}, da, db, 1, 1, 1, 0, 1;\n"
    "add.u32 t, %64, 2;\nmov.b64 da, {t, %66};\nadd.u32 t, %65, 128;\nmov.b64 db, {t, %66};\n"
    "wgmma.mma_async.sync.aligned.m64n128k16.f32.bf16.bf16 {%0, %1, %2, %3, %4, %5, %6, %7, %8, %9, %10, %11, %12, %13, %14, %15, %16, %17, %18, %19, %20, %21, %22, %23, %24, %25, %26, %27, %28, %29, %30, %31, %32, %33, %34, %35, %36, %37, %38, %39, %40, %41, %42, %43, %44, %45, %46, %47, %48, %49, %50, %51, %52, %53, %54, %55, %56, %57, %58, %59, %60, %61, %62, %63}, da, db, 1, 1, 1, 0, 1;\n"
    "add.u32 t, %64, 4;\nmov.b64 da, {t, %66};\nadd.u32 t, %65, 1024;\nmov.b64 db, {t, %66};\n"
    "wgmma.mma_async.sync.aligned.m64n128k16.f32.bf16.bf16 {%0, %1, %2, %3, %4, %5, %6, %7, %8, %9, %10, %11, %12, %13, %14, %15, %16, %17, %18, %19, %20, %21, %22, %23, %24, %25, %26, %27, %28, %29, %30, %31, %32, %33, %34, %35, %36, %37, %38, %39, %40, %41, %42, %43, %44, %45, %46, %47, %48, %49, %50, %51, %52, %53, %54, %55, %56, %57, %58, %59, %60, %61, %62, %63}, da, db, 1, 1, 1, 0, 1;\n"
    "add.u32 t, %64, 6;\nmov.b64 da, {t, %66};\nadd.u32 t, %65, 1152;\nmov.b64 db, {t, %66};\n"
    "wgmma.mma_async.sync.aligned.m64n128k16.f32.bf16.bf16 {%0, %1, %2, %3, %4, %5, %6, %7, %8, %9, %10, %11, %12, %13, %14, %15, %16, %17, %18, %19, %20, %21, %22, %23, %24, %25, %26, %27, %28, %29, %30, %31, %32, %33, %34, %35, %36, %37, %38, %39, %40, %41, %42, %43, %44, %45, %46, %47, %48, %49, %50, %51, %52, %53, %54, %55, %56, %57, %58, %59, %60, %61, %62, %63}, da, db, 1, 1, 1, 0, 1;\n"
    "wgmma.commit_group.sync.aligned;\n}\n"
    : "+f"(d[0]), "+f"(d[1]), "+f"(d[2]), "+f"(d[3]), "+f"(d[4]), "+f"(d[5]), "+f"(d[6]), "+f"(d[7]), "+f"(d[8]), "+f"(d[9]), "+f"(d[10]), "+f"(d[11]), "+f"(d[12]), "+f"(d[13]), "+f"(d[14]), "+f"(d[15]), "+f"(d[16]), "+f"(d[17]), "+f"(d[18]), "+f"(d[19]), "+f"(d[20]), "+f"(d[21]), "+f"(d[22]), "+f"(d[23]), "+f"(d[24]), "+f"(d[25]), "+f"(d[26]), "+f"(d[27]), "+f"(d[28]), "+f"(d[29]), "+f"(d[30]), "+f"(d[31]), "+f"(d[32]), "+f"(d[33]), "+f"(d[34]), "+f"(d[35]), "+f"(d[36]), "+f"(d[37]), "+f"(d[38]), "+f"(d[39]), "+f"(d[40]), "+f"(d[41]), "+f"(d[42]), "+f"(d[43]), "+f"(d[44]), "+f"(d[45]), "+f"(d[46]), "+f"(d[47]), "+f"(d[48]), "+f"(d[49]), "+f"(d[50]), "+f"(d[51]), "+f"(d[52]), "+f"(d[53]), "+f"(d[54]), "+f"(d[55]), "+f"(d[56]), "+f"(d[57]), "+f"(d[58]), "+f"(d[59]), "+f"(d[60]), "+f"(d[61]), "+f"(d[62]), "+f"(d[63])
    : "r"(a), "r"(b), "n"(0x40000040) : "memory");
}
__device__ __forceinline__ void half_kstep1(float (&d)[64], uint32_t a, uint32_t b) {
  asm volatile("{\n.reg .u32 t;\n.reg .u64 da, db;\nwgmma.fence.sync.aligned;\n"
    "add.u32 t, %64, 0;\nmov.b64 da, {t, %66};\nadd.u32 t, %65, 512;\nmov.b64 db, {t, %66};\n"
    "wgmma.mma_async.sync.aligned.m64n128k16.f32.bf16.bf16 {%0, %1, %2, %3, %4, %5, %6, %7, %8, %9, %10, %11, %12, %13, %14, %15, %16, %17, %18, %19, %20, %21, %22, %23, %24, %25, %26, %27, %28, %29, %30, %31, %32, %33, %34, %35, %36, %37, %38, %39, %40, %41, %42, %43, %44, %45, %46, %47, %48, %49, %50, %51, %52, %53, %54, %55, %56, %57, %58, %59, %60, %61, %62, %63}, da, db, 1, 1, 1, 0, 1;\n"
    "add.u32 t, %64, 2;\nmov.b64 da, {t, %66};\nadd.u32 t, %65, 640;\nmov.b64 db, {t, %66};\n"
    "wgmma.mma_async.sync.aligned.m64n128k16.f32.bf16.bf16 {%0, %1, %2, %3, %4, %5, %6, %7, %8, %9, %10, %11, %12, %13, %14, %15, %16, %17, %18, %19, %20, %21, %22, %23, %24, %25, %26, %27, %28, %29, %30, %31, %32, %33, %34, %35, %36, %37, %38, %39, %40, %41, %42, %43, %44, %45, %46, %47, %48, %49, %50, %51, %52, %53, %54, %55, %56, %57, %58, %59, %60, %61, %62, %63}, da, db, 1, 1, 1, 0, 1;\n"
    "add.u32 t, %64, 4;\nmov.b64 da, {t, %66};\nadd.u32 t, %65, 1536;\nmov.b64 db, {t, %66};\n"
    "wgmma.mma_async.sync.aligned.m64n128k16.f32.bf16.bf16 {%0, %1, %2, %3, %4, %5, %6, %7, %8, %9, %10, %11, %12, %13, %14, %15, %16, %17, %18, %19, %20, %21, %22, %23, %24, %25, %26, %27, %28, %29, %30, %31, %32, %33, %34, %35, %36, %37, %38, %39, %40, %41, %42, %43, %44, %45, %46, %47, %48, %49, %50, %51, %52, %53, %54, %55, %56, %57, %58, %59, %60, %61, %62, %63}, da, db, 1, 1, 1, 0, 1;\n"
    "add.u32 t, %64, 6;\nmov.b64 da, {t, %66};\nadd.u32 t, %65, 1664;\nmov.b64 db, {t, %66};\n"
    "wgmma.mma_async.sync.aligned.m64n128k16.f32.bf16.bf16 {%0, %1, %2, %3, %4, %5, %6, %7, %8, %9, %10, %11, %12, %13, %14, %15, %16, %17, %18, %19, %20, %21, %22, %23, %24, %25, %26, %27, %28, %29, %30, %31, %32, %33, %34, %35, %36, %37, %38, %39, %40, %41, %42, %43, %44, %45, %46, %47, %48, %49, %50, %51, %52, %53, %54, %55, %56, %57, %58, %59, %60, %61, %62, %63}, da, db, 1, 1, 1, 0, 1;\n"
    "wgmma.commit_group.sync.aligned;\n}\n"
    : "+f"(d[0]), "+f"(d[1]), "+f"(d[2]), "+f"(d[3]), "+f"(d[4]), "+f"(d[5]), "+f"(d[6]), "+f"(d[7]), "+f"(d[8]), "+f"(d[9]), "+f"(d[10]), "+f"(d[11]), "+f"(d[12]), "+f"(d[13]), "+f"(d[14]), "+f"(d[15]), "+f"(d[16]), "+f"(d[17]), "+f"(d[18]), "+f"(d[19]), "+f"(d[20]), "+f"(d[21]), "+f"(d[22]), "+f"(d[23]), "+f"(d[24]), "+f"(d[25]), "+f"(d[26]), "+f"(d[27]), "+f"(d[28]), "+f"(d[29]), "+f"(d[30]), "+f"(d[31]), "+f"(d[32]), "+f"(d[33]), "+f"(d[34]), "+f"(d[35]), "+f"(d[36]), "+f"(d[37]), "+f"(d[38]), "+f"(d[39]), "+f"(d[40]), "+f"(d[41]), "+f"(d[42]), "+f"(d[43]), "+f"(d[44]), "+f"(d[45]), "+f"(d[46]), "+f"(d[47]), "+f"(d[48]), "+f"(d[49]), "+f"(d[50]), "+f"(d[51]), "+f"(d[52]), "+f"(d[53]), "+f"(d[54]), "+f"(d[55]), "+f"(d[56]), "+f"(d[57]), "+f"(d[58]), "+f"(d[59]), "+f"(d[60]), "+f"(d[61]), "+f"(d[62]), "+f"(d[63])
    : "r"(a), "r"(b), "n"(0x40000040) : "memory");
}

__device__ __forceinline__ void sum_columns(float (&d)[4], uint32_t a, uint32_t b) {
  asm volatile("{\n.reg .u32 t;\n.reg .u64 da, db;\nmov.b64 db, {%5, 0};\nwgmma.fence.sync.aligned;\n"
               "add.u32 t, %4, 0;\nmov.b64 da, {t, %6};\nwgmma.mma_async.sync.aligned.m64n8k16.f32.bf16.bf16 {%0, %1, %2, %3}, da, db, 1, 1, 1, 1, 0;\n"
               "add.u32 t, %4, 128;\nmov.b64 da, {t, %6};\nwgmma.mma_async.sync.aligned.m64n8k16.f32.bf16.bf16 {%0, %1, %2, %3}, da, db, 1, 1, 1, 1, 0;\n"
               "add.u32 t, %4, 256;\nmov.b64 da, {t, %6};\nwgmma.mma_async.sync.aligned.m64n8k16.f32.bf16.bf16 {%0, %1, %2, %3}, da, db, 1, 1, 1, 1, 0;\n"
               "add.u32 t, %4, 384;\nmov.b64 da, {t, %6};\nwgmma.mma_async.sync.aligned.m64n8k16.f32.bf16.bf16 {%0, %1, %2, %3}, da, db, 1, 1, 1, 1, 0;\n"
               "add.u32 t, %4, 512;\nmov.b64 da, {t, %6};\nwgmma.mma_async.sync.aligned.m64n8k16.f32.bf16.bf16 {%0, %1, %2, %3}, da, db, 1, 1, 1, 1, 0;\n"
               "add.u32 t, %4, 640;\nmov.b64 da, {t, %6};\nwgmma.mma_async.sync.aligned.m64n8k16.f32.bf16.bf16 {%0, %1, %2, %3}, da, db, 1, 1, 1, 1, 0;\n"
               "add.u32 t, %4, 768;\nmov.b64 da, {t, %6};\nwgmma.mma_async.sync.aligned.m64n8k16.f32.bf16.bf16 {%0, %1, %2, %3}, da, db, 1, 1, 1, 1, 0;\n"
               "add.u32 t, %4, 896;\nmov.b64 da, {t, %6};\nwgmma.mma_async.sync.aligned.m64n8k16.f32.bf16.bf16 {%0, %1, %2, %3}, da, db, 1, 1, 1, 1, 0;\n"
               "add.u32 t, %4, 1024;\nmov.b64 da, {t, %6};\nwgmma.mma_async.sync.aligned.m64n8k16.f32.bf16.bf16 {%0, %1, %2, %3}, da, db, 1, 1, 1, 1, 0;\n"
               "add.u32 t, %4, 1152;\nmov.b64 da, {t, %6};\nwgmma.mma_async.sync.aligned.m64n8k16.f32.bf16.bf16 {%0, %1, %2, %3}, da, db, 1, 1, 1, 1, 0;\n"
               "add.u32 t, %4, 1280;\nmov.b64 da, {t, %6};\nwgmma.mma_async.sync.aligned.m64n8k16.f32.bf16.bf16 {%0, %1, %2, %3}, da, db, 1, 1, 1, 1, 0;\n"
               "add.u32 t, %4, 1408;\nmov.b64 da, {t, %6};\nwgmma.mma_async.sync.aligned.m64n8k16.f32.bf16.bf16 {%0, %1, %2, %3}, da, db, 1, 1, 1, 1, 0;\n"
               "add.u32 t, %4, 1536;\nmov.b64 da, {t, %6};\nwgmma.mma_async.sync.aligned.m64n8k16.f32.bf16.bf16 {%0, %1, %2, %3}, da, db, 1, 1, 1, 1, 0;\n"
               "add.u32 t, %4, 1664;\nmov.b64 da, {t, %6};\nwgmma.mma_async.sync.aligned.m64n8k16.f32.bf16.bf16 {%0, %1, %2, %3}, da, db, 1, 1, 1, 1, 0;\n"
               "add.u32 t, %4, 1792;\nmov.b64 da, {t, %6};\nwgmma.mma_async.sync.aligned.m64n8k16.f32.bf16.bf16 {%0, %1, %2, %3}, da, db, 1, 1, 1, 1, 0;\n"
               "add.u32 t, %4, 1920;\nmov.b64 da, {t, %6};\nwgmma.mma_async.sync.aligned.m64n8k16.f32.bf16.bf16 {%0, %1, %2, %3}, da, db, 1, 1, 1, 1, 0;\n"
               "wgmma.commit_group.sync.aligned;\nwgmma.wait_group.sync.aligned 0;\n}"
               : "+f"(d[0]), "+f"(d[1]), "+f"(d[2]), "+f"(d[3]) : "r"(a), "r"(b), "n"(0x40000040) : "memory");
}
struct Job {
  uint32_t type, layer, R, col, nk;
  __device__ __forceinline__ explicit Job(uint32_t j) : type(j & 3), layer((j >> 2) & 1), R((j >> 3) & 7), col((j >> 6) & 63), nk((j >> 12) & 63) {}
  __device__ __forceinline__ uint32_t inst() const { return layer * 2 + (type >> 1); }
};
struct Smem {
  char* scratch;
  uint32_t base;
  __device__ __forceinline__ uint32_t stage(uint32_t s) const { return base + (s & (NSTAGE - 1)) * STAGE; }
  __device__ __forceinline__ uint32_t slot(uint32_t c) const { return base + STG_OFF + c * SLOT; }
  __device__ __forceinline__ uint32_t full(uint32_t s) const { return base + BAR_OFF + (s & (NSTAGE - 1)) * 8; }
  __device__ __forceinline__ uint32_t empty(uint32_t s) const { return base + BAR_OFF + 32 + (s & (NSTAGE - 1)) * 8; }
  __device__ __forceinline__ uint32_t filled(uint32_t u) const { return base + BAR_OFF + 64 + u * 8; }
  __device__ __forceinline__ uint32_t vacant(uint32_t u) const { return base + BAR_OFF + 96 + u * 8; }
  __device__ __forceinline__ uint32_t summed(uint32_t s) const { return base + BAR_OFF + 128 + (s & (NSTAGE - 1)) * 8; }
  __device__ __forceinline__ uint32_t aux_full() const { return base + BAR_OFF + 160; }
  __device__ __forceinline__ uint32_t boot() const { return base + BAR_OFF + 168; }
  __device__ __forceinline__ uint32_t xchg_full() const { return base + BAR_OFF + 176; }
  __device__ __forceinline__ uint32_t wgmma_done() const { return base + BAR_OFF + 184; }
  __device__ __forceinline__ uint32_t mma_done() const { return base + BAR_OFF + 192; }
  __device__ __forceinline__ uint32_t kv_ready(int w) const { return base + BAR_OFF + 208 + w * 8; }
  __device__ __forceinline__ uint32_t pair_id() const { return base + BAR_OFF + 280; }
  __device__ __forceinline__ uint32_t stats() const { return base + AUX_OFF; }
  __device__ __forceinline__ uint32_t sums() const { return base + AUX_OFF + 1088; }
  __device__ __forceinline__ uint32_t xchg() const { return base + AUX_OFF + 1600; }
};
__device__ __forceinline__ uint32_t par(uint32_t s) { return (s / NSTAGE) & 1; }

__device__ __forceinline__ void st_word(u64* p, uint32_t lo, uint32_t hi) {
  asm volatile("st.relaxed.gpu.global.u64 [%0], %1;" ::"l"(p), "l"(((u64)hi << 32) | lo) : "memory");
}
__device__ __forceinline__ uint2 ld_word(const u64* p) {
  u64 v;
  asm volatile("ld.relaxed.gpu.global.u64 %0, [%1];" : "=l"(v) : "l"(p) : "memory");
  return make_uint2((uint32_t)v, (uint32_t)(v >> 32));
}
__device__ __forceinline__ void add_moments(uint4 v, float (&m)[4]) {
  const uint32_t w[4] = {v.x, v.y, v.z, v.w};
#pragma unroll
  for (int c = 0; c < 4; c++) {
    const float lo = bf_lo(w[c]), hi = bf_hi(w[c]);
    m[0] += lo; m[1] += hi; m[2] = fmaf(lo, lo, m[2]); m[3] = fmaf(hi, hi, m[3]);
  }
}
__device__ __forceinline__ void publish_stats(const Smem& sm, float s, float q, uint32_t idx, bool valid, uint32_t e1) {
  const float mean = s * (1.f / D), var = fmaxf(q * (1.f / D) - mean * mean, 0.f);
  const u64 word = ((u64)((__float_as_uint(-bf_round(mean)) & 0xffff0000u) | (e1 & 0xffff)) << 32) | __float_as_uint(rcp(bf_round(sqrt_fast(bf_round(bf_round(var) + 1e-5f)))));
  asm volatile("{\n.reg .pred p;\nsetp.ne.u32 p, %2, 0;\n@p st.relaxed.gpu.global.u64 [%0], %1;\n}" ::"l"(SCR(sm, stats, idx * 8)), "l"(word), "r"((uint32_t)valid) : "memory");
}
__device__ __forceinline__ void stats_task(const Smem& sm, uint32_t jw, int rank, int w, uint32_t e1, const bf16* x) {
  const uint32_t inst = (jw >> 22) & 3, lane = fresh_tid() & 31, steps = (jw >> 31) * 2 + 2;
  uint32_t row = ((jw >> 24) & 127) * 8 + (w - 1) * 4 + (lane >> 3);
  wait_count(counter(C_X + inst * 16 + (row >> 7) * 2 + rank, lane & 7), e1 * (inst & 1 ? 56 : 16));
  const uint4* p = at(reinterpret_cast<const uint4*>(x), (row * 2 + rank) * (D * 2) + (lane & 7) * 16);
  uint4 v[8];
  float m[4] = {0.f, 0.f, 0.f, 0.f};
#pragma unroll
  for (int i = 0; i < 8; i++) v[i] = ldg128(p + i * 8);
#pragma unroll 1
  for (uint32_t it = 1; it <= steps; it++) {
    p = at(p, it & 1 ? 1024 : 8 * D * 4 - 1024);
#pragma unroll
    for (int i = 0; i < 8; i++) {
      add_moments(v[i], m);
      if (it < steps) v[i] = ldg128(p + i * 8);
    }
    if (!(it & 1)) {
      m[0] += m[1]; m[2] += m[3];
#pragma unroll
      for (int o = 1; o <= 4; o <<= 1) { m[0] += __shfl_xor_sync(~0u, m[0], o); m[2] += __shfl_xor_sync(~0u, m[2], o); }
      publish_stats(sm, m[0], m[2], (inst + 1) * S + rank * (S / 2) + row, (lane & 7) == 0, e1);
      m[0] = m[1] = m[2] = m[3] = 0.f;
      row += 8;
    }
  }
}
struct Stager {
  uint2 st[5], cs[4];
  __device__ __forceinline__ void load(const Smem& sm, const Job& J, int rank, int lane, bool sums) {
#pragma unroll
    for (int i = 0; i < 5; i++) st[i] = ld_word(SCR(sm, stats, (J.inst() * S + rank * (S / 2) + J.R * 128 + min(max(lane - 8 + 32 * i, J.R && J.type == T_Q ? -8 : 0), 127)) * 8));
#pragma unroll
    for (int i = 0; i < 4; i++)
      if (sums && (i < 3 || J.type == T_G)) cs[i] = ld_word(SCR(sm, cs, ((J.col + J.type * 8) * 128 + lane) * 8) + i * 32);
  }
  __device__ __forceinline__ void store(const Smem& sm, const Job& J, int rank, int lane, bool sums, uint32_t e1) {
    for (uint32_t n = 0;; n++) {
      uint32_t bad = (st[1].y ^ e1) | (st[2].y ^ e1) | (st[3].y ^ e1);
      bad |= (st[0].y ^ e1) | (st[4].y ^ e1);
      if (sums) bad |= (cs[0].y ^ e1) | (cs[1].y ^ e1) | (cs[2].y ^ e1);
      if (J.type == T_G) bad |= cs[3].y ^ e1;
      if (__all_sync(~0u, (bad & 0xffff) == 0)) break;
      __nanosleep(300);
      if (n > SPIN_LIMIT) __trap();
      load(sm, J, rank, lane, sums);
    }
#pragma unroll
    for (int i = 0; i < 5; i++) {
      if (i < 4 || lane < 8) sts64(sm.stats() + (lane + 32 * i) * 8, st[i]);
      if (i < 4 && sums && (i < 3 || J.type == T_G)) sts32(sm.sums() + (lane + 32 * i) * 4, cs[i].x);
    }
  }
};
__device__ __forceinline__ void add_cols(float (&a)[8], uint4 x, uint4 y) {
  const uint4 t = add8(x, y);
  a[0] += bf_lo(t.x); a[1] += bf_hi(t.x); a[2] += bf_lo(t.y); a[3] += bf_hi(t.y);
  a[4] += bf_lo(t.z); a[5] += bf_hi(t.z); a[6] += bf_lo(t.w); a[7] += bf_hi(t.w);
}
__device__ __forceinline__ void reduce_cols(float (&a)[8], int lane) {
#pragma unroll
  for (int i = 0; i < 4; i++) { const bool up = lane & 16; const float o = __shfl_xor_sync(~0u, up ? a[i] : a[i + 4], 16); a[i] = (up ? a[i + 4] : a[i]) + o; }
#pragma unroll
  for (int i = 0; i < 2; i++) { const bool up = lane & 8; const float o = __shfl_xor_sync(~0u, up ? a[i] : a[i + 2], 8); a[i] = (up ? a[i + 2] : a[i]) + o; }
}
template <class Fn>
__device__ __forceinline__ uint32_t qkv_col_sums(const Smem& sm, int rank, int w, int lane, Fn between) {
  float a[8] = {0.f, 0.f, 0.f, 0.f, 0.f, 0.f, 0.f, 0.f};
#pragma unroll 1
  for (int s = 0; s < D / 64; s++) {
    between(s);
    const uint32_t p = sm.stage(s) + SLOT + rank * SLOT + w * 4096 + (lane >> 3) * 128 + (((lane & 7) ^ (lane >> 3)) << 4);
    uint4 v[8];
    mbar_wait(sm.full(s), par(s));
#pragma unroll
    for (int j = 0; j < 8; j++) v[j] = lds128((p ^ ((j & 1) * 64)) + j * 512);
    __syncwarp();
    mbar_arrive_cl_if(lane < 2, mapa(sm.summed(s), lane & 1));
    add_cols(a, add8(v[0], v[1]), add8(v[2], v[3]));
    add_cols(a, add8(v[4], v[5]), add8(v[6], v[7]));
  }
  reduce_cols(a, lane);
  const uint32_t slot = sm.xchg() + (w * 32 + lane) * 8;
  asm volatile("st.async.weak.shared::cluster.mbarrier::complete_tx::bytes.v2.b32 [%0], {%1, %2}, [%3];"
               ::"r"(mapa(slot, rank ^ 1)), "r"(__float_as_uint(a[0])), "r"(__float_as_uint(a[1])), "r"(mapa(sm.xchg_full(), rank ^ 1)) : "memory");
  mbar_wait(sm.xchg_full(), 0);
  const uint2 o = lds64(slot);
  return pack_bf16(a[0] + __uint_as_float(o.x), a[1] + __uint_as_float(o.y));
}

constexpr float LOGIT_SCALE = 0.17677669529663687f * 1.4426950408889634f;
constexpr float MASKED = -1e30f;
enum { A_CS = 16, A_NM = 40, A_KT = 42, A_KU = 44, A_CT = 46, A_CU = 48, A_BIAS = 50, A_MASK = 52, A_ZERO = 53 };
__device__ __forceinline__ void attention_prepare(uint32_t (&r)[64], const Smem& sm, int W, int lane, bool first) {
  const int i = lane >> 2, c = (lane & 3) * 2;
  r[A_ZERO] = opaque_zero();
  r[A_MASK] = (c > i ? 0xffffu : 0u) | (c + 1 > i ? 0xffff0000u : 0u);
  const uint32_t a = sm.stats() + W * 128;
  const uint2 r0 = lds64(a + 64 + i * 8), r1 = lds64(a + 128 + i * 8);
#pragma unroll
  for (int y = 0; y < 2; y++) {
    const uint32_t k = a + (c + y + (c + y > i ? 0 : 8)) * 8;
    const float kt = lds32f(k), ku = lds32f(k + 64);
    r[A_KT + y] = __float_as_uint(kt); r[A_CT + y] = __float_as_uint(__uint_as_float(r0.x) * LOGIT_SCALE * kt);
    r[A_KU + y] = __float_as_uint(ku); r[A_CU + y] = __float_as_uint(__uint_as_float(r1.x) * LOGIT_SCALE * ku);
    r[A_BIAS + y] = __float_as_uint(first && W == 0 && c + y > i ? MASKED : 0.f);
  }
#pragma unroll
  for (int j = 0; j < 6; j++) {
    const uint4 v = lds128(sm.sums() + c * 48 + j * 16);
    r[A_CS + 4 * j] = v.x; r[A_CS + 4 * j + 1] = v.y; r[A_CS + 4 * j + 2] = v.z; r[A_CS + 4 * j + 3] = v.w;
  }
  r[A_NM] = dup_hi(r0.y); r[A_NM + 1] = dup_hi(r1.y);
}
__device__ __forceinline__ bool attention(const float (&acc)[96], uint32_t (&r)[64], const Smem& sm, int W, int lane, uint32_t t8, uint32_t t16,
                                          bool halo, uint32_t block, uint32_t tag, uint32_t parity, uint32_t next_bar, uint32_t next_parity, int ji) {
#define TRW W
  const uint32_t own = (W >> 2) * SLOT;
  const uint32_t pk = W == 0 ? (halo ? 4096 : 1024) : W == 4 ? 7168 : own - 1024;
  const uint32_t pv = W == 0 && halo ? 6144 : pk + 8192;
  uint32_t x[48];
  auto pack = [&](int j0, int step, int count) {
#pragma unroll
    for (int j = j0; j < j0 + step * count; j += step) x[j] = bf2_fma(r[A_NM + j % 2], r[A_CS + j / 2], pack_bf16(acc[2 * j], acc[2 * j + 1]));
  };
  auto put8 = [&](uint32_t a, int j) {
    stsm4(t8 + a, x[j], x[j + 2], x[j + 4], x[j + 6]);
    stsm4((t8 ^ 64) + a, x[j + 8], x[j + 10], x[j + 12], x[j + 14]);
  };
  uint32_t k0[2][4], v0[2][4], v12[4][4];
  pack(17, 2, 8);
  put8(own + 1024, 17);
  pack(32, 1, 16);
#pragma unroll
  for (int j = 0; j < 4; j++) stsm4((t16 ^ (j << 5)) + (own + 8192), x[32 + 4 * j], x[33 + 4 * j], x[34 + 4 * j], x[35 + 4 * j]);
  mbar_arrive_warp(sm.kv_ready(W));
  pack(16, 2, 8);
  pack(0, 1, 16);
  if (W == 0) {
    put8(0, 16);
#pragma unroll
    for (int j = 0; j < 4; j++) stsm4(lane & 8 ? sm.xchg() : (t16 ^ (j << 5)) + 2048, x[4 * j], x[4 * j + 1], x[4 * j + 2], x[4 * j + 3]);
  }
  mbar_wait(sm.kv_ready(W - 1), parity);
#pragma unroll
  for (int h = 0; h < 2; h++) ldsm4((t8 ^ (h * 64)) + pk, k0[h]);
#pragma unroll
  for (int j = 0; j < 4; j++) ldsm4t((t16 ^ (j << 5)) + (own + 8192), v12[j]);
#pragma unroll
  for (int h = 0; h < 2; h++) ldsm4t((t8 ^ (h * 64)) + pv, v0[h]);
  if (W < 4) mbar_wait(sm.wgmma_done(), parity);
  const bool next_full = mbar_test(next_bar, next_parity);
  TRC(ji, 20);
  float s0[2][4], s1[2][4], s2[2][4];
#pragma unroll
  for (int h = 0; h < 2; h++) {
#pragma unroll
    for (int y = 0; y < 4; y++) s0[h][y] = s1[h][y] = s2[h][y] = 0.f;
  }
#pragma unroll
  for (int ks = 0; ks < 2; ks++)
#pragma unroll
    for (int h = 0; h < 2; h++) {
      const int n = 8 * h + 4 * ks;
      mma16816(s1[h], x[n], x[n + 1], x[n + 2], x[n + 3], x[16 + n], x[18 + n]);
      mma16816(s2[h], x[n], x[n + 1], x[n + 2], x[n + 3], x[17 + n], x[19 + n]);
      mma16816(s0[h], x[n], x[n + 1], x[n + 2], x[n + 3], k0[h][2 * ks], k0[h][2 * ks + 1]);
    }
  const uint32_t mask = r[A_MASK];
  const bool after[2] = {(mask & 1) != 0, (int)mask < 0};
  float lt[2][2], lu[2][2], mt[2], mu[2];
#pragma unroll
  for (int h = 0; h < 2; h++) {
#pragma unroll
    for (int y = 0; y < 2; y++) {
      lt[h][y] = fmaf(after[y] ? s0[h][y] : s1[h][y], __uint_as_float(r[A_CT + y]), __uint_as_float(r[A_BIAS + y]));
      lu[h][y] = (after[y] ? s1[h][2 + y] : s2[h][2 + y]) * __uint_as_float(r[A_CU + y]);
    }
    mt[h] = fmaxf(lt[h][0], lt[h][1]);
    mu[h] = fmaxf(lu[h][0], lu[h][1]);
  }
#pragma unroll
  for (int d = 1; d <= 2; d++)
#pragma unroll
    for (int h = 0; h < 2; h++) {
      mt[h] = fmaxf(mt[h], __shfl_xor_sync(~0u, mt[h], d));
      mu[h] = fmaxf(mu[h], __shfl_xor_sync(~0u, mu[h], d));
    }
  float o[2][4][4];
#pragma unroll
  for (int h = 0; h < 2; h++) {
#pragma unroll
    for (int y = 0; y < 2; y++) { lt[h][y] = ex2(lt[h][y] - mt[h]); lu[h][y] = ex2(lu[h][y] - mu[h]); }
    const uint32_t pt = pack_bf16(lt[h][0] * __uint_as_float(r[A_KT]), lt[h][1] * __uint_as_float(r[A_KT + 1]));
    const uint32_t pu = pack_bf16(lu[h][0] * __uint_as_float(r[A_KU]), lu[h][1] * __uint_as_float(r[A_KU + 1]));
#pragma unroll
    for (int n = 0; n < 4; n++) {
      o[h][n][0] = o[h][n][1] = o[h][n][2] = o[h][n][3] = 0.f;
      mma16816(o[h][n], pt & ~mask, pu & mask, 0u, pu & ~mask, v12[2 * h + n / 2][n % 2 * 2], v12[2 * h + n / 2][n % 2 * 2 + 1]);
    }
#pragma unroll
    for (int n = 0; n < 4; n++) mma1688(o[h][n], pt & mask, 0u, v0[h][n]);
    mt[h] = lt[h][0] + lt[h][1];
    mu[h] = lu[h][0] + lu[h][1];
  }
#pragma unroll
  for (int d = 1; d <= 2; d++)
#pragma unroll
    for (int h = 0; h < 2; h++) {
      mt[h] += __shfl_xor_sync(~0u, mt[h], d);
      mu[h] += __shfl_xor_sync(~0u, mu[h], d);
    }
  uint32_t dep = 0;
#pragma unroll
  for (int n = 0; n < 3; n++) dep |= __float_as_uint(o[n % 2][n / 2][0]);
  mbar_arrive_warp(sm.mma_done() + (dep & r[A_ZERO]));
  TRC(ji, 22);
  if (W == 7) {
    ulonglong2* exp = SCR(sm, halo, (block * 256 + lane) * 16);
#pragma unroll
    for (int m = 0; m < 8; m++)
      asm volatile("st.relaxed.gpu.global.v2.u64 [%0], {%1,%2};" ::"l"(exp + m * 32), "l"(((u64)tag << 32) | x[17 + 4 * m]), "l"(((u64)tag << 32) | x[19 + 4 * m]) : "memory");
  }
#pragma unroll
  for (int h = 0; h < 2; h++) {
    const float rt = rcp(mt[h]), ru = rcp(mu[h]);
#pragma unroll
    for (int n = 0; n < 4; n++) {
      r[8 * h + 2 * n] = pack_bf16(o[h][n][0] * rt, o[h][n][1] * rt);
      r[8 * h + 2 * n + 1] = pack_bf16(o[h][n][2] * ru, o[h][n][3] * ru);
    }
  }
  return next_full;
}
__device__ __forceinline__ void import_halo(const Smem& sm, const ulonglong2* halo, uint32_t tag, int lane) {
  u64 x[16];
  for (uint32_t n = 0;; n++) {
#pragma unroll
    for (int m = 0; m < 8; m++)
      asm volatile("ld.relaxed.gpu.global.v2.u64 {%0,%1}, [%2];" : "=l"(x[2 * m]), "=l"(x[2 * m + 1]) : "l"(halo + m * 32) : "memory");
    uint32_t bad = 0;
#pragma unroll
    for (int m = 0; m < 16; m++) bad |= (uint32_t)(x[m] >> 32) ^ tag;
    if (__all_sync(~0u, bad == 0)) break;
    __nanosleep(300);
    if (n > SPIN_LIMIT) __trap();
  }
  const uint32_t a = sm.slot(0) + 4096 + (lane & 7) * 128 + (((lane >> 3) ^ (lane & 7)) << 4);
#pragma unroll
  for (int m = 0; m < 4; m++) stsm4((a ^ ((m & 1) * 64)) + (m >> 1) * 2048, (uint32_t)x[4 * m], (uint32_t)x[4 * m + 1], (uint32_t)x[4 * m + 2], (uint32_t)x[4 * m + 3]);
}
__device__ __forceinline__ void unpack8(uint4 v, float* f) {
  f[0] = bf_lo(v.x); f[1] = bf_hi(v.x); f[2] = bf_lo(v.y); f[3] = bf_hi(v.y);
  f[4] = bf_lo(v.z); f[5] = bf_hi(v.z); f[6] = bf_lo(v.w); f[7] = bf_hi(v.w);
}
__device__ __forceinline__ void boundary_rows(const Smem& sm, int h, int lane, uint32_t out) {
  const int i = lane >> 2, u = h * 4 + (lane & 3);
  uint4 r[8];
  float x[8], l[8], ik[8];
  unpack8(lds128(sm.slot(0) + 2048 + i * 128 + ((u ^ i) << 4)), x);
#pragma unroll
  for (int j = 0; j < 8; j++) {
    r[j] = lds128(sm.slot(0) + j * 128 + (j > i ? 4096 : 0) + ((u ^ j) << 4));
    ik[j] = lds32f(sm.stats() + j * 8 + (j > i ? 0 : 64));
  }
  const float cq = lds32f(sm.stats() + 64 + i * 8) * LOGIT_SCALE;
#pragma unroll
  for (int j = 0; j < 8; j++) {
    float kf[8];
    unpack8(r[j], kf);
    r[j] = lds128(sm.slot(0) + j * 128 + (j > i ? 6144 : 8192) + ((u ^ j) << 4));
    l[j] = 0.f;
#pragma unroll
    for (int d = 0; d < 8; d++) l[j] = fmaf(x[d], kf[d], l[j]);
  }
#pragma unroll
  for (int d = 1; d <= 2; d++)
#pragma unroll
    for (int j = 0; j < 8; j++) l[j] += __shfl_xor_sync(~0u, l[j], d);
  float m = MASKED, sum = 0.f;
#pragma unroll
  for (int j = 0; j < 8; j++) { l[j] *= cq * ik[j]; m = fmaxf(m, l[j]); }
#pragma unroll
  for (int j = 0; j < 8; j++) { l[j] = ex2(l[j] - m); sum += l[j]; }
  const float rs = rcp(sum);
#pragma unroll
  for (int d = 0; d < 8; d++) x[d] = 0.f;
#pragma unroll
  for (int j = 0; j < 8; j++) {
    const float pw = l[j] * ik[j] * rs;
    float vf[8];
    unpack8(r[j], vf);
#pragma unroll
    for (int d = 0; d < 8; d++) x[d] = fmaf(pw, vf[d], x[d]);
  }
  stg128(SCR(sm, o, out + i * (2 * D) + u * 16), make_uint4(pack_bf16(x[0], x[1]), pack_bf16(x[2], x[3]), pack_bf16(x[4], x[5]), pack_bf16(x[6], x[7])));
}
__device__ __forceinline__ uint32_t swiglu2(uint32_t g, uint32_t u, float hinv, float hinv2) {
  const float a = bf_lo(g) * hinv, b = bf_hi(g) * hinv, a2 = bf_lo(g) * hinv2, b2 = bf_hi(g) * hinv2;
  return bf2_mul(pack_bf16(fmaf(a2, tanh_fast(a), a2), fmaf(b2, tanh_fast(b), b2)), u);
}

__device__ __forceinline__ const uint32_t* dep_counter(const Smem& sm, uint32_t jw, int rank, uint32_t k) {
  const Job J(jw);
  const uint32_t b = J.R * 2 + rank;
  const uint32_t line = J.type == T_O ? C_O + J.layer * 16 + b : J.type == T_D ? C_H + J.layer * 16 + b : C_X + max((int)J.inst() - 1, 0) * 16 + b;
  return counter(line, J.type & 1 ? k >> (J.type >> 1) : (k >> 2) * 2 + (k & 1));
}
__device__ __forceinline__ void producer(const Params& P, const Smem& sm, const uint32_t* jobs, const uint8_t* kseq, int rank, int lane, uint32_t launches) {
  const uint32_t e1 = __shfl_sync(~0u, launches, 0) + 1;
  uint32_t s = (jobs[0] & JOB_C) ? 0 : NSTAGE;
  uint32_t end = 0, poll = 0;
  uint64_t keep, stream;
  asm("createpolicy.fractional.L2::evict_unchanged.b64 %0, 1.0;" : "=l"(keep));
  asm("createpolicy.fractional.L2::evict_first.b64 %0, 1.0;" : "=l"(stream));
  const uint32_t* dep = counter(0, 0);
  const uint32_t summed_end = (jobs[0] & JOB_C) ? 0 : D / 64 + NSTAGE;
  for (int ji = 0;; ji++) {
    const uint32_t jw = jobs[ji];
    const Job J(jw);
    if (J.nk == 0) break;
    const bool isC = jw & JOB_C, isX = isC && (jw & JOB_X);
    const uint32_t target = (jw & 7) == 0 ? 0 : e1 * (J.type == T_Q ? 56 : J.type == T_G ? 16 : 1);
    const uint32_t g = J.col * 2 + rank;
    const CUtensorMap* tmA = &P.a[isC ? 4 + isX : (jw & 7) == 4 ? 2 : J.type];
    const CUtensorMap* tmB = &P.w[J.type];
    const uint32_t bytes = isC ? 32768 : J.type == T_Q ? 40960 : STAGE, bcol = J.col << (J.type == T_Q ? 0 : J.type == T_G ? 1 : 2);
    const uint32_t a0 = isX ? 0 : (g >> 2) * 128 + (g & 1) * 64, a1 = isX ? g * 64 : J.R * 128, ak = isX ? 0 : 256, a2 = isC ? (g >> 1) & 1 : rank;
    end += J.nk;
    uint32_t sa = s, spins = 0;
    auto issue_a = [&](uint32_t k) { TRS(sa, 1); tma3d(sm.stage(sa), tmA, isC ? a0 : (k & 63) * 64, isC ? a1 + k * ak : a1, isX ? k * 4 : a2, sm.full(sa), (k & K_LAST_A) ? stream : keep); };
    auto issue_b = [&](uint32_t k) {
      mbar_expect_tx(sm.full(s), bytes);
      TRS(s, 0);
      if (!isC) tma4d_mc(sm.stage(s) + SLOT + rank * SLOT, tmB, (k & 63) * 64 + rank * 32, bcol, sm.full(s), (k & K_LAST_B) ? stream : keep);
    };
    TRI(lane == 0, ji, 6);
    TRK(lane == 0, ji, 24);
    while (true) {
      const uint32_t missing = __ballot_sync(~0u, (int)(poll - target) < 0 && lane < J.nk);
      uint32_t lim = end;
      if (missing) lim += __ffs(missing) - 1 - J.nk;
      if (lim > sa) {
        fence_acquire();
        fence_proxy_async();
        TRI(sa == end - J.nk && lane == 0, ji, 7);
#pragma unroll 1
        for (; sa < min(lim, s); sa++) {
          const uint32_t k = kseq[sa];
          if (elect()) issue_a(k);
        }
#pragma unroll 1
        for (int phase = 0;; phase++) {
          const uint32_t upto = phase == 2 ? lim : phase == 1 ? lim - LOOK : min((int)lim - LOOK, (int)sa + MID);
#pragma unroll 1
          for (; (int)sa < (int)upto; sa++, s++) {
            const uint32_t k = kseq[s];
            uint32_t stage = sm.stage(s), bar = sm.full(s), c0 = isC ? a0 : (k & 63) * 64, c1 = isC ? a1 + k * ak : a1, kb = (k & 63) * 64 + rank * 32, c2 = isX ? k * 4 : a2;
            uint64_t pa = (k & K_LAST_A) ? stream : keep, pb = (k & K_LAST_B) ? stream : keep;
            asm volatile("" : "+r"(stage), "+r"(bar), "+r"(c0), "+r"(c1), "+r"(kb), "+r"(c2), "+l"(pa), "+l"(pb));
            if (s < summed_end) mbar_wait(sm.summed(s), par(s) ^ 1);
            mbar_wait(bar + 32, par(s) ^ 1);
            TRS(s, 0);
            asm volatile("{\n.reg .pred p, q;\nelect.sync _|p, -1;\nsetp.eq.and.u32 q, %14, 0, p;\n"
                         "@q cp.async.bulk.tensor.4d.shared::cluster.global.mbarrier::complete_tx::bytes.multicast::cluster.L2::cache_hint [%3], [%4, {%5, %6, %7, %5}], [%0], %8, %9;\n"
                         "@p cp.async.bulk.tensor.3d.shared::cluster.global.mbarrier::complete_tx::bytes.L2::cache_hint [%2], [%10, {%11, %12, %13}], [%0], %15;\n"
                         "@p mbarrier.arrive.expect_tx.shared::cta.b64 _, [%0], %1;\n}"
                         ::"r"(bar), "r"(bytes), "r"(stage), "r"(stage + SLOT + rank * SLOT), "l"(tmB), "r"(0), "r"(kb), "r"(bcol), "h"((uint16_t)3), "l"(pb),
                           "l"(tmA), "r"(c0), "r"(c1), "r"(c2), "r"((uint32_t)isC), "l"(pa) : "memory");
            TRS(s, 1);
          }
          if (phase == 2) break;
          if (phase == 1) poll = ld_relaxed(dep);
          else if (lim == end) dep = dep_counter(sm, jobs[ji + 1], rank, (reinterpret_cast<const uint32_t*>(kseq)[(end + lane) >> 2] >> ((end + lane) % 4 * 8)) & 63);
        }
        if (lim == end) break;
      } else {
        if (s < min(end, sa + NSTAGE) && __all_sync(~0u, mbar_test(sm.empty(s), par(s) ^ 1))) {
          const uint32_t k = kseq[s];
          if (s < summed_end) mbar_wait(sm.summed(s), par(s) ^ 1);
          if (elect()) issue_b(k);
          s++;
        }
        poll = ld_relaxed(dep);
        if (++spins > SPIN_LIMIT) __trap();
      }
    }
    TRI(lane == 0, ji, 8);
  }
}

__global__ void __cluster_dims__(2, 1, 1) __launch_bounds__(384, 1) mega_kernel(char* scratch, uint32_t by_place, const __grid_constant__ Params P) {
#undef TRW
#define TRW warp
  extern __shared__ __align__(1024) uint8_t smem_raw[];
  TRX(threadIdx.x == 320, JMAX - 1, 0, 1, "%%globaltimer_lo");
  TRX(threadIdx.x == 320, JMAX - 1, 0, 25, "%%clock");
  TRX(threadIdx.x == 320, JMAX - 1, 0, 28, "%%smid");
  Smem sm;
  sm.scratch = scratch;
  sm.base = smem_u32(smem_raw);
  if ((sm.base & 0x3FFFF) != SMEM_BASE) __trap();
  const int warp = __shfl_sync(~0u, threadIdx.x >> 5, 0);
  const int rank = blockIdx.x & 1;
  uint32_t smid;
  asm("mov.u32 %0, %%smid;" : "=r"(smid));
  const uint32_t pair = !by_place ? blockIdx.x >> 1 : smid < 2 * NPAIR - 8 ? (smid >> 1) + 4 : (smid >> 1) + 4 - NPAIR;
  const uint32_t* jobs = P.jobs[pair];
  const uint32_t launches = ld_relaxed(counter(C_EP, blockIdx.x + threadIdx.y));
  if (warp == 10) {
    if (elect()) {
      for (int i = 0; i < NSTAGE; i++) mbar_init(sm.full(i), 1);
      mbar_init(sm.boot(), 1);
      asm volatile("fence.mbarrier_init.release.cluster;" ::: "memory");
    }
    cluster_arrive();
    const uint32_t first = jobs[0];
    const bool isC = first & JOB_C;
    if (elect()) {
      prefetch_tm(&P.a[0]);
      prefetch_tm(&P.w[0]);
    }
    uint64_t keep;
    asm("createpolicy.fractional.L2::evict_unchanged.b64 %0, 1.0;" : "=l"(keep));
    const Job J(first);
    if (!isC) {
      if (elect()) {
        mbar_expect_tx(sm.full(0), 40960);
        tma3d(sm.stage(0), &P.a[0], 0, J.R * 128, rank, sm.full(0), keep);
        TRS(0, 1);
      }
      TRX(threadIdx.x == 320, JMAX - 1, 0, 26, "%%clock");
      cluster_wait();
      TRX(threadIdx.x == 320, JMAX - 1, 0, 27, "%%clock");
      if (elect()) {
        tma4d_mc(sm.stage(0) + SLOT + rank * SLOT, &P.w[0], rank * 32, J.col, sm.full(0), keep);
        TRS(0, 0);
      }
#pragma unroll 1
      for (int k = 1; k < NSTAGE; k++) {
        if (elect()) {
          tma4d_mc(sm.stage(k) + SLOT + rank * SLOT, &P.w[0], k * 64 + rank * 32, J.col, sm.full(k), keep);
          TRS(k, 0);
          mbar_expect_tx(sm.full(k), 40960);
          tma3d(sm.stage(k), &P.a[0], k * 64, J.R * 128, rank, sm.full(k), keep);
          TRS(k, 1);
        }
      }
    } else {
      cluster_wait();
      if (!(first & JOB_X)) mbar_wait(sm.boot(), 0);
    }
  } else {
    if (warp < 8 && elect()) {
      mbar_init(sm.kv_ready(warp), 1);
      if (warp == 3) {
        mbar_init(sm.aux_full(), 3); mbar_init(sm.wgmma_done(), 4); mbar_init(sm.mma_done(), 8); mbar_init(sm.xchg_full(), 1); mbar_init(sm.kv_ready(-1), 1);
        mbar_expect_tx(sm.xchg_full(), 768);
      } else if (warp > 3) {
        mbar_init(sm.empty(warp), 4); mbar_init(sm.summed(warp), 6); mbar_init(sm.filled(warp - 4), 4); mbar_init(sm.vacant(warp - 4), 3);
      }
      asm volatile("fence.mbarrier_init.release.cluster;" ::: "memory");
    }
    cluster_arrive();
  }
  TRI(threadIdx.x == 0, JMAX - 1, 0);

  if (warp < 8) {
    asm volatile("setmaxnreg.inc.sync.aligned.u32 208;");
    const uint32_t e1 = launches + 1;
    cluster_wait();
    const uint32_t wg = warp >> 2;
    uint32_t rel = (threadIdx.x & 95) == 0 ? mapa(sm.empty(0), (threadIdx.x & 32) ? rank ^ 1 : rank) : 0;
    uint32_t dst = sm.slot(0) + (warp & 3) * 2048 + (threadIdx.x & 15) * 128 + ((((threadIdx.x >> 4) & 1) ^ (threadIdx.x & 7)) << 4);
    uint32_t t8 = sm.slot(0) + (warp & 3) * 2048 + (threadIdx.x & 7) * 128 + ((((threadIdx.x >> 3) & 3) ^ (threadIdx.x & 7)) << 4);
    rel = __shfl_sync(~0u, rel, threadIdx.x);
    dst = __shfl_sync(~0u, dst, threadIdx.x);
    t8 = __shfl_sync(~0u, t8, threadIdx.x);
    const uint32_t da0 = ((SMEM_BASE >> 4) | (1 << 16)) + wg * 512, dba = (255 << 16) + 1024 - wg * 512;
    uint32_t pend[64], todo = 0, pbar = 0, vbar = sm.vacant(0), ppar = 0, poff = 0, direct = 0;
    uint32_t s = 0, na = 0, nb = 0, ready = 0;
    auto release = [&](uint32_t st) { mbar_arrive_cl_if(rel, rel + (st & (NSTAGE - 1)) * 8); };
    auto flush = [&](bool vacant) {
      if (__all_sync(~0u, vacant)) {
        const uint32_t a = dst + poff;
        if (todo & 2) {
#pragma unroll
          for (int j = 0; j < 4; j++) stsm4(a ^ (j << 5), pend[4 * j], pend[4 * j + 1], pend[4 * j + 2], pend[4 * j + 3]);
          if (todo == 2) {
#pragma unroll
            for (int j = 0; j < 4; j++) stsm4((a ^ (j << 5)) + 8192, pend[16 + 4 * j], pend[17 + 4 * j], pend[18 + 4 * j], pend[19 + 4 * j]);
          }
        } else {
#pragma unroll
          for (int j = 0; j < 8; j++) stsm4((a ^ ((j & 3) << 5)) + (j >> 2) * 8192, pend[32 + 4 * j], pend[33 + 4 * j], pend[34 + 4 * j], pend[35 + 4 * j]);
        }
        mbar_arrive_warp(pbar);
        pbar += 16; vbar += 16; ppar = ~nb & 1;
        todo = todo == 2;
      }
    };
    uint32_t jw = jobs[0];
#pragma unroll
    for (int i = 0; i < 64; i++) pend[i] = 0;
    for (int ji = 0;; ji++) {
      const uint32_t cur = jw, nk = (jw >> 12) & 63, isQ = (jw & 3) == T_Q;
      jw = jobs[ji + 1];
      if (__builtin_expect((cur & JOB_C) || !ready, 0)) {
        for (uint32_t spins = 0; todo && ((cur & JOB_C) || !ready);) {
          if (direct && todo == 1) {
            vbar = sm.empty(s); ppar = par(s) ^ 1; poff = sm.stage(s) - sm.slot(0) + wg * SLOT;
          }
          flush(mbar_test(vbar, ppar));
          ready = __all_sync(~0u, mbar_test(sm.full(s), par(s)));
          if (++spins > SPIN_LIMIT) __trap();
        }
        if (cur & JOB_C) {
          if (nk == 0) break;
          TRC(ji, 16);
          constexpr uint32_t ONES = 0x3f803f80;
          const uint32_t lane = fresh_tid() & 31, g = ((cur >> 6) & 63) * 2 + rank;
          if (!(cur & JOB_X)) {
            float d[4] = {0.f, 0.f, 0.f, 0.f};
            sts32(sm.xchg() + 128 + lane * 4, ONES);
            fence_proxy_async_smem();
            bar_sync<9, 256>();
#pragma unroll 1
            for (int i = 0; i < 4; i++, s++) {
              mbar_wait(sm.full(s), par(s));
              if (!wg) sum_columns(d, da0 + (s & (NSTAGE - 1)) * (STAGE / 16), (SMEM_BASE + AUX_OFF + 1600 + 128) >> 4);
              release(s);
            }
            const float c = lane & 1 ? d[2] : d[0], c1 = __shfl_down_sync(~0u, c, 4);
            asm volatile("{\n.reg .pred p;\nsetp.eq.u32 p, %2, 0;\n@p st.relaxed.gpu.global.u64 [%0], %1;\n}"
                         ::"l"(SCR(sm, cs, (16 * 128 + g * 32 + (warp & 3) * 8 + (lane & 1) * 4 + (lane >> 3)) * 8)), "l"(((u64)e1 << 32) | pack_bf16(c, c1)), "r"((lane & 6) | wg) : "memory");
          } else {
            float a[6][4];
#pragma unroll
            for (int n = 0; n < 24; n++) pend[n] = 0;
#pragma unroll 1
            for (int i = 0;; i++) {
              const uint32_t p = dst - sm.slot(0) + sm.stage(s) + wg * SLOT;
              mbar_wait(sm.full(s), par(s));
              uint32_t v[8][4];
#pragma unroll
              for (int n = 0; n < 24; n++) a[n / 4][n % 4] = __uint_as_float(pend[n]);
#pragma unroll
              for (int j = 0; j < 8; j++) ldsm4((p ^ ((j & 3) << 5)) + (j >> 2) * 8192, v[j]);
#pragma unroll
              for (int j = 0; j < 8; j++) {
                mma16816(a[4 + (j & 1)], v[j][0], v[j][1], v[j][2], v[j][3], ONES, ONES);
#pragma unroll
                for (int n = 0; n < 4; n++) mma1688(a[n], v[j][n & 2], v[j][(n & 2) + 1], v[j][n]);
              }
#pragma unroll
              for (int n = 0; n < 24; n++) pend[n] = __float_as_uint(a[n / 4][n % 4]);
              if (i == 3) break;
              bar_sync<9, 256>();
              release(s++);
            }
            const uint32_t part = sm.stage(s) + 2 * SLOT + lane * 8, row = g * 64 + (warp & 3) * 16 + wg * 8 + (lane >> 2);
            const bool odd = lane & 4;
            const float s0 = a[4][0] + a[5][0], q0 = odd ? a[0][1] + a[2][1] : a[0][0] + a[2][0];
            const float s1 = a[4][2] + a[5][2], q1 = odd ? a[1][3] + a[3][3] : a[1][2] + a[3][2];
            sts64(part + warp * 256, make_uint2(__float_as_uint(wg ? s0 : s1), __float_as_uint(wg ? q0 : q1)));
            bar_sync<9, 256>();
            const uint2 o = lds64(part + (warp ^ 4) * 256);
            fence_proxy_async_smem();
            bar_sync<9, 256>();
            release(s++);
            publish_stats(sm, (wg ? s1 : s0) + __uint_as_float(o.x), (wg ? q1 : q0) + __uint_as_float(o.y), (row & 1) * (S / 2) + (row >> 1), (lane & 3) == lane >> 3, e1);
          }
          ready = 0;
          TRC(ji, 18);
          continue;
        }
        if (!ready) mbar_wait(sm.full(s), par(s));
      }
      auto mainloop = [&](auto& acc, uint32_t nk, uint32_t last_lead, auto near_end) {
        const uint32_t lead = (jw >> 12) % 64 == 0 ? min(last_lead, nk - 2) : 2, turn = wg ? lead : nk - 2, hurry = nk - lead - wg;
        uint32_t owed = 0;
        uint32_t da = da0 + (s & (NSTAGE - 1)) * (STAGE / 16);
        if (todo == 3) mbar_wait(vbar, ppar);
        if (wg) bar_sync<13, 256>();
        TRC(ji, 16);
        first_kstep(acc, da, da + dba);
        if (!wg) bar_arrive<13, 256>();
        constexpr uint32_t CLEAR = sizeof(acc) == 96 * 4 ? PREP + 2 : 3;
        for (uint32_t left = nk - 1;; left--) {
          for (uint32_t spins = 0;; spins++) {
            const bool vacant = mbar_test(vbar, ppar), next_full = mbar_test(sm.full(s + 1), par(s + 1));
            wg_wait<2>();
            mbar_arrive_cl_if(owed, owed + ((s - 1) & (NSTAGE - 1)) * 8);
            owed = 0;
            ready = __all_sync(~0u, next_full);
            if (!todo) {
              near_end(left, vacant);
              break;
            }
            const bool go = ready && left >= max(CLEAR, lead + 1);
            if (!(go && spins)) flush(vacant);
            if (go) break;
            if (spins > SPIN_LIMIT) __trap();
          }
          if (left == 0) break;
          if (!ready) mbar_wait(sm.full(s + 1), par(s + 1));
          owed = rel;
          if (left == turn) {
            wg_wait<0>();
            release(s);
            owed = 0;
            if (wg) bar_sync<1, 256>();
          }
          if (left - lead < hurry) wg_wait<1>();
          s++;
          da = da0 + (s & (NSTAGE - 1)) * (STAGE / 16);
          kstep(acc, da, da + dba);
          if (left == 1 + wg * 64) bar_arrive<1, 256>();
        }
      };
      if (isQ) {
        float acc[96];
        const uint32_t lane = (((dst - SMEM_BASE) >> 7) & 15) | ((dst ^ (dst >> 3)) & 16), qpar = (na ^ nb) & 1;
        uint32_t prepare_at = PREP;
        mainloop(acc, nk, LAST_LEAD, [&](uint32_t left, bool aux_full) {
          if (left == PREP + 1) {
            vbar = sm.aux_full(); ppar = qpar;
          } else if (left == prepare_at) {
            if (left == 0) mbar_wait(vbar, ppar);
            if (left == 0 || __all_sync(~0u, aux_full)) attention_prepare(pend, sm, warp, lane, !(cur & 0x38));
            else prepare_at--;
          }
        });
        wg_wait<0>();
        release(s);
        u64 token = 0;
        asm volatile("{\n.reg .pred p;\nsetp.eq.u32 p, %2, 0;\n@p mbarrier.arrive.shared::cta.b64 %0, [%1];\n}" : "+l"(token) : "r"(sm.wgmma_done()), "r"(lane + 1 - wg) : "memory");
        pend[A_NM + 1] |= (uint32_t)token & pend[A_ZERO];
        TRC(ji, 18);
        ready = __all_sync(~0u, attention(acc, pend, sm, warp, lane, t8, dst, cur & JOB_EARLY, (((cur >> 2) & 1) * 16 + ((cur >> 3) & 7) * 2 + rank) * 16 + ((cur >> 6) & 15), e1, qpar,
                                          sm.full(s + 1), par(s + 1), ji));
        todo = 3; pbar = sm.filled(wg); vbar = sm.mma_done(); ppar = qpar; poff = SLOT + wg * 8192;
      } else {
        float acc[128];
        direct = (cur & 1) && (jw >> 12) % 64 == 0;
        const bool split = direct && nk >= SPLIT_MIN;
        mainloop(acc, split ? nk - 3 : nk, split ? 0 : LAST_LEAD, [](uint32_t, bool) {});
        pbar = sm.filled(wg); vbar = pbar + 32; ppar = na & 1; poff = wg * SLOT;
        nb++;
        todo = 2;
        if (__builtin_expect(split, 0)) {
          const uint32_t s0 = s;
          uint32_t d[3];
#pragma unroll
          for (int i = 0; i < 3; i++) d[i] = da0 + ((s0 + 1 + i) & (NSTAGE - 1)) * (STAGE / 16);
          wg_wait<0>();
          release(s0);
          float lo[64], hi[64];
#pragma unroll
          for (int i = 0; i < 64; i++) {
            asm volatile("mov.b32 %0, %1;" : "=f"(lo[i]) : "f"(acc[i]));
            asm volatile("mov.b32 %0, %1;" : "=f"(hi[i]) : "f"(acc[64 + i]));
          }
          if (wg) {
            bar_sync<1, 256>();
            bar_sync<3, 256>();
          }
          mbar_wait(sm.full(s0 + 1), par(s0 + 1));
          half_kstep0(lo, d[0], d[0] + dba);
          mbar_wait(sm.full(s0 + 2), par(s0 + 2));
          half_kstep0(lo, d[1], d[1] + dba);
          half_kstep1(hi, d[0], d[0] + dba);
          mbar_wait(sm.full(s0 + 3), par(s0 + 3));
          half_kstep0(lo, d[2], d[2] + dba);
          half_kstep1(hi, d[1], d[1] + dba);
          half_kstep1(hi, d[2], d[2] + dba);
          if (!wg) bar_arrive<3, 256>();
          s += 3;
          wg_wait<2>();
#pragma unroll
          for (int i = 0; i < 32; i++) pend[i] = pack_bf16(lo[2 * i], lo[2 * i + 1]);
          mbar_wait(vbar, ppar);
          flush(true);
          wg_wait<0>();
          TRC(ji, 18);
#pragma unroll
          for (int i = 0; i < 32; i++) pend[32 + i] = pack_bf16(hi[2 * i], hi[2 * i + 1]);
        } else {
          wg_wait<0>();
          release(s);
          const bool next_full = mbar_test(sm.full(s + 1), par(s + 1));
          TRC(ji, 18);
#pragma unroll
          for (int i = 0; i < 64; i++) {
            const int j = (i & 15) + (i & 16) * 2 + (i >> 5) * 16;
            pend[i] = pack_bf16(acc[2 * j], acc[2 * j + 1]);
          }
          ready = __all_sync(~0u, next_full);
        }
      }
      na++;
      s++;
    }
  } else {
    asm volatile("setmaxnreg.dec.sync.aligned.u32 88;");
    if (warp == 10) {
      producer(P, sm, jobs, P.kseq[pair], rank, threadIdx.x & 31, launches);
    } else {
      const uint32_t e1 = __shfl_sync(~0u, launches, 0) + 1;
      const int w = min(warp - 8, 2);
      cluster_wait();
      if (w == 1) asm volatile("st.shared::cluster.u32 [%0], %1;" ::"r"(mapa(sm.pair_id(), rank ^ 1)), "r"(pair) : "memory");
      const uint32_t boot = jobs[JMAX - 1] >> 24, pieces = (boot & 127) == 127 ? 0 : 1 + (boot >> 7), piece0 = (boot & 127) * 2 + rank * pieces;
      auto copy_rows = [&](uint32_t step, uint32_t n) {
        constexpr int IN = 2 * SLOT / BOOT_PIECES, OUT = 2 * SLOT / BOOT_OUT;
        const uint32_t rows = (piece0 + n) * 32768;
        if (step == BOOT_STEP) mbar_wait(sm.boot(), n & 1);
        if (elect()) {
          if (step == 0) mbar_expect_tx(sm.boot(), pieces ? 2 * SLOT : 0);
          if (step < BOOT_PIECES && pieces)
            asm volatile("cp.async.bulk.shared::cluster.global.mbarrier::complete_tx::bytes [%0], [%1], %2, [%3];"
                         ::"r"(sm.slot(0) + step * IN), "l"(at(P.x0, rows + step * IN)), "n"(IN), "r"(sm.boot()) : "memory");
          if (step - BOOT_STEP < BOOT_OUT && pieces) {
            asm volatile("cp.async.bulk.global.shared::cta.bulk_group [%0], [%1], %2;"
                         ::"l"(at(P.out, rows + (step - BOOT_STEP) * OUT)), "r"(sm.slot(0) + (step - BOOT_STEP) * OUT), "n"(OUT) : "memory");
            bulk_commit();
          }
        }
        if (step == BOOT_STEP + BOOT_OUT) {
          bulk_wait();
          if (n + 1 >= pieces && elect()) {
            mbar_arrive_n(sm.vacant(0), 3);
            mbar_arrive_n(sm.vacant(1), 3);
          }
        }
      };
      if (jobs[0] & JOB_C) {
        if (w == 2) {
          if (jobs[0] & JOB_X) mbar_wait(sm.full(3), 0);
#pragma unroll 1
          for (uint32_t n = 0; n == 0 || n < pieces; n++) {
#pragma unroll 1
            for (int i = 0; i <= BOOT_STEP + BOOT_OUT; i++) {
              copy_rows(i, n);
              bulk_wait_read<0>();
            }
          }
        }
      } else {
        const int lane = threadIdx.x & 31, word = (lane >> 3) * 24 + w * 8 + (lane & 7);
        Stager st;
        const uint32_t cs = qkv_col_sums(sm, rank, w, lane, [&](int s) {
          if (w == 2) copy_rows(s - 1, 0);
          if (w == 0 && s == ST_STEP) st.load(sm, Job(jobs[0]), rank, lane, false);
          if (w == 0 && s == ST_STEP + 2) st.store(sm, Job(jobs[0]), rank, lane, false, e1);
        });
        sts32(sm.sums() + word * 4, cs);
        mbar_arrive_warp(sm.aux_full());
        if ((jobs[0] & 0x38) == 0 && rank == 0) st_word(SCR(sm, cs, (((jobs[0] >> 6) & 15) * 128 + word) * 8), cs, e1);
      }
      bar_sync<2, 96>();
      if (w == 2 && pieces && elect()) {
        red_release(counter(C_RD + (piece0 >> 4) * 2, 0), pieces);
        red_relaxed(counter(C_RD + (piece0 >> 4) * 2 + 1, 0), pieces);
      }
      uint32_t na = 0, nb = 0, stages = 0;
      for (int ji = 0;; ji++) {
        const uint32_t jw = jobs[ji];
        const Job J(jw);
        if (J.nk == 0) break;
        stages += J.nk;
        if (w != 0 && ((jw >> 22) & 3) != 3) {
          stats_task(sm, jw, rank, w, e1, P.out);
          TRI(threadIdx.x == 11 * 32, ji, 10);
        }
        if (jw & JOB_C) continue;
        const int lane = fresh_tid() & 31;
        const uint32_t b = J.R * 2 + rank;
        if (w == 0 && !(J.type & 1) && ji != 0) {
          Stager st;
          st.load(sm, J, rank, lane, true);
          st.store(sm, J, rank, lane, true, e1);
          TRI(lane == 0, ji, 9);
        }
        if (J.type == T_G) {
          bar_sync<2, 96>();
          constexpr int PER = 16 / NG;
          const uint32_t swap = P.swap, never = jw, ac = sm.sums() + (lane & 7) * 16;
          uint32_t ag[NG], au[NG], as = sm.stats() + 64 + w * NG * 32 + (lane >> 3) * 8;
          uint32_t ho = (rank * (S / 2) + J.R * 128 + w * NG * 4 + (lane >> 3)) * (F * 2) + J.col * 256 + (lane & 7) * 16;
          uint4 cg = lds128(ac + (swap >> 5)), cu = lds128(ac + 256 - (swap >> 5)), g4[NG], u4[NG];
          uint2 st[NG];
          auto load = [&] {
#pragma unroll
            for (int i = 0; i < NG; i++) { st[i] = lds64v(as + i * 32); g4[i] = lds128v(ag[i]); u4[i] = lds128v(au[i]); }
          };
#pragma unroll
          for (int i = 0; i < NG; i++) {
            const uint32_t a = (sm.slot(0) + (w * NG + i) * 512 + (lane >> 3) * 128 + (((lane & 7) ^ (lane >> 3)) << 4)) ^ (((w * NG + i) & 1) << 6);
            ag[i] = a + swap; au[i] = a + (swap ^ 8192);
          }
          mbar_wait(sm.filled(0), na & 1);
          mbar_wait(sm.filled(1), na & 1);
          load();
          if (w == 2 && elect()) red_relaxed(counter(C_RD + J.inst() * 16 + b, 0), 1);
          TRI(threadIdx.x == 11 * 32, ji, 3);
#pragma unroll 1
          for (uint32_t g = w; g < 4 * PER; g += 3) {
            float hinv[NG], hinv2[NG];
            uint4 gc[NG], uc[NG];
            const bool turn = ((g + 3) ^ g) & PER, half = ((g + 3) ^ g) & (2 * PER);
#pragma unroll
            for (int i = 0; i < NG; i++) {
              hinv[i] = 0.5f * __uint_as_float(st[i].x);
              hinv2[i] = hinv[i] * __uint_as_float(st[i].x);
              asm volatile("" : "+f"(hinv[i]), "+f"(hinv2[i]));
              gc[i] = fma8(dup_hi(st[i].y), cg, g4[i]);
              uc[i] = fma8(dup_hi(st[i].y), cu, u4[i]);
              ag[i] = (ag[i] + NG * 1536) ^ ((NG & 1) << 6);
              au[i] = (au[i] + NG * 1536) ^ ((NG & 1) << 6);
            }
            as += NG * 96;
            if (turn) {
              mbar_arrive_warp(sm.vacant((g / PER) ^ 2));
              if (half) {
                cg = lds128(ac + (swap >> 5) + 128); cu = lds128(ac + 384 - (swap >> 5));
                as -= 1024;
              }
#pragma unroll
              for (int i = 0; i < NG; i++) { ag[i] += half ? -3 * 8192 : 8192; au[i] += half ? -3 * 8192 : 8192; }
              TRX(threadIdx.x == 11 * 32 && g < 3 * PER, ji, 25, 25 + g / PER * 2, "%%clock");
              if (g < 3 * PER) mbar_wait(sm.filled(g / PER + 1), (g < PER ? na : nb) & 1);
              TRX(threadIdx.x == 11 * 32 && g < 3 * PER, ji, 25, 26 + g / PER * 2, "%%clock");
            }
            load();
            if (g == never) mbar_wait(sm.boot(), 0);
            bf16* out = SCR(sm, h, ho);
#pragma unroll
            for (int i = 0; i < NG; i++)
              stg128(out + i * 4 * F, make_uint4(swiglu2(gc[i].x, uc[i].x, hinv[i], hinv2[i]), swiglu2(gc[i].y, uc[i].y, hinv[i], hinv2[i]),
                                                 swiglu2(gc[i].z, uc[i].z, hinv[i], hinv2[i]), swiglu2(gc[i].w, uc[i].w, hinv[i], hinv2[i])));
            ho += NG * 12 * F * 2 - (half ? 128 * F * 2 - 128 : 0);
          }
          bar_sync<2, 96>();
          TRI(threadIdx.x == 11 * 32, ji, 4);
          if (w == 2 && elect()) red_release(counter(C_H + J.layer * 16 + b, J.col), 1);
          TRI(threadIdx.x == 11 * 32, ji, 5);
        } else if (J.type == T_Q) {
          const bool late = J.R > 0 && !(jw & JOB_EARLY);
          if (w == 0) {
            __syncwarp();
            if (ji != 0 && elect()) mbar_arrive_n(sm.aux_full(), 3);
#pragma unroll 1
            for (int phase = 0; phase < 2; phase++) {
              if (J.R > 0 && phase == late) import_halo(sm, SCR(sm, halo, (((J.layer * 16 + b - 2) * 16 + J.col) * 256 + lane) * 16), e1, lane);
              if (phase == 0) {
                mbar_arrive_warp(sm.kv_ready(-1));
                TRI(lane == 0, ji, 11);
#pragma unroll 1
                for (int h = 0; h < 2; h++) {
                  mbar_wait(sm.filled(h), na & 1);
                  TRI(lane == 0, ji, 3);
                  fence_proxy_async_smem();
                  bulk_wait_read<0>();
                  if (elect()) {
                    tma3d_store(&P.ow, J.col * 64, J.R * 128 + h * 64, rank, sm.slot(1) + h * 8192);
                    bulk_commit();
                  }
                }
                if (J.layer && elect()) red_relaxed(counter(C_RD + 32 + b, 0), 1);
              }
            }
            bulk_wait();
          }
          if (late && w < 2) {
            bar_sync<7, 64>();
            boundary_rows(sm, w, lane, rank * O_PLANE + J.R * 128 * (D * 2) + J.col * 128);
            bar_sync<7, 64>();
          }
          TRI(threadIdx.x == 256, ji, 4);
          if (w == 0 && elect()) {
            mbar_arrive_n(sm.vacant(0), 3);
            mbar_arrive_n(sm.vacant(1), 3);
            red_release(counter(C_O + J.layer * 16 + b, J.col), 1);
          }
          TRI(threadIdx.x == 256, ji, 5);
        } else if (w == 0) {
          wait_count(counter(C_RD + J.inst() * 16 + b, 0), e1 * (J.type == T_D ? 28 : 16));
          fence_proxy_async();
          const bool last = Job(jobs[ji + 1]).nk == 0, split = last && J.nk >= SPLIT_MIN;
#pragma unroll 1
          for (uint32_t v = 0; v < 4; v++) {
            const uint32_t u = last ? (v >> 1) + (v & 1) * 2 : v;
            mbar_wait(sm.filled(u), (u & 2 ? nb : na) & 1);
            TRI(u == 0 && lane == 0, ji, 3);
            fence_proxy_async_smem();
            const uint32_t src = (last && (u & 2) ? sm.stage(stages) : sm.slot(0)) + (u & 1) * SLOT;
#pragma unroll 1
            for (uint32_t p = 0; p < 16384 / PIECE; p++) {
              if (elect()) {
                tma3d_reduce_add(&P.xr, J.col * 256 + (split ? (u & 2) * 64 + p * PIECE / 8192 * 64 : (u & 2) * 32 + p * PIECE / 8192 * 128), J.R * 128 + (u & 1) * 64 + p * PIECE % 8192 / 128, rank, src + p * PIECE);
                bulk_commit();
              }
              if (!last) bulk_wait_read<DEPTH - 1>();
            }
            if (!last) {
              bulk_wait();
              if (elect()) mbar_arrive_n(sm.vacant(u ^ 2), 3);
            }
            if (u == 1 && J.inst() != 3) bar_arrive<8, 64>();
          }
          bulk_wait();
        }
        if ((J.type & 1) && J.inst() != 3 && w < 2) {
          if (w == 1) bar_sync<8, 64>();
          TRX(lane == 0, ji, 4, w ? 12 : 4, "%%globaltimer_lo");
          if (elect()) red_release(counter(C_X + J.inst() * 16 + b, J.col * 2 + 1 - w), J.nk);
          TRX(lane == 0, ji, 5, w ? 13 : 5, "%%globaltimer_lo");
          if (w == 1) bar_arrive<10, 64>(); else bar_sync<10, 64>();
        }
        na++;
        nb += J.type != T_Q;
      }
      TRI(threadIdx.x == 8 * 32, JMAX - 1, 6);
      TRK(threadIdx.x == 8 * 32, JMAX - 1, 24);
      if (w == 0 && elect()) red_relaxed(counter(C_EP, blockIdx.x), 1);
      if (w == 2 && __float_as_uint(lds32f(sm.pair_id())) != pair) __trap();
    }
  }
  cluster_arrive();
  cluster_wait();
}

typedef CUresult (*EncodeFn)(CUtensorMap*, CUtensorMapDataType, cuuint32_t, void*, const cuuint64_t*, const cuuint64_t*, const cuuint32_t*,
                             const cuuint32_t*, CUtensorMapInterleave, CUtensorMapSwizzle, CUtensorMapL2promotion, CUtensorMapFloatOOBfill);
struct Dim { cuuint64_t size, stride; cuuint32_t box; };
template <int N> void encode(EncodeFn fn, CUtensorMap* m, const void* ptr, const Dim (&d)[N]) {
  cuuint64_t dims[N], strides[N];
  cuuint32_t box[N], es[N];
  for (int i = 0; i < N; i++) { dims[i] = d[i].size; strides[i] = d[i].stride; box[i] = d[i].box; es[i] = 1; }
  fn(m, CU_TENSOR_MAP_DATA_TYPE_BFLOAT16, N, const_cast<void*>(ptr), dims, strides + 1, box, es, CU_TENSOR_MAP_INTERLEAVE_NONE,
     CU_TENSOR_MAP_SWIZZLE_128B, CU_TENSOR_MAP_L2_PROMOTION_L2_128B, CU_TENSOR_MAP_FLOAT_OOB_FILL_NONE);
}

}

extern "C" void kernel_launch(void* const* d_in, const int* in_sizes, int n_in, void* d_out, int out_size) {
  (void)in_sizes; (void)n_in; (void)out_size;
  static EncodeFn fn = nullptr;
  static Scratch* scr;
  static int sms;
  if (!fn) {
    void* p = nullptr;
    cudaDriverEntryPointQueryResult q;
    cudaGetDriverEntryPoint("cuTensorMapEncodeTiled", &p, cudaEnableDefault, &q);
    fn = (EncodeFn)p;
    scr = scratch_base();
    int device = 0;
    cudaGetDevice(&device);
    cudaDeviceGetAttribute(&sms, cudaDevAttrMultiProcessorCount, device);
    cudaFuncSetAttribute(mega_kernel, cudaFuncAttributeMaxDynamicSharedMemorySize, SMEM_BYTES);
  }
  static Params P;
  const char *wg = (const char*)d_in[4], *wu = (const char*)d_in[5], *w0 = wg < wu ? wg : wu;
  const cuuint64_t plane = wg < wu ? wu - wg : wg - wu;
  P.swap = wg < wu ? 0 : 8192;
  encode(fn, &P.a[0], d_in[0], {{D, 2, 64}, {S / 2, D * 4, 128}, {2, D * 2, 1}});
  encode(fn, &P.a[1], scr->o, {{D, 2, 64}, {S / 2, D * 2, 128}, {2, O_PLANE, 1}});
  encode(fn, &P.ow, scr->o, {{D, 2, 64}, {S / 2, D * 2, 64}, {2, O_PLANE, 1}});
  encode(fn, &P.a[2], d_out, {{D, 2, 64}, {S / 2, D * 4, 128}, {2, D * 2, 1}});
  encode(fn, &P.a[3], scr->h, {{F, 2, 64}, {S / 2, F * 2, 128}, {2, (cuuint64_t)F * S, 1}});
  encode(fn, &P.a[4], w0, {{F, 2, 64}, {D, F * 2, 256}, {2, plane, 1}});
  encode(fn, &P.a[5], d_in[0], {{64, 2, 64}, {S, D * 2, 64}, {16, 128, 4}});
  encode(fn, &P.w[T_Q], d_in[1], {{64, 2, 64}, {D, 3 * D * 2, 32}, {16, 128, 1}, {3, D * 2, 3}});
  encode(fn, &P.w[T_O], d_in[2], {{64, 2, 64}, {D, D * 2, 32}, {16, 128, 4}, {1, (cuuint64_t)D * D * 2, 1}});
  encode(fn, &P.w[T_G], w0, {{64, 2, 64}, {D, F * 2, 32}, {F / 64, 128, 2}, {2, plane, 2}});
  encode(fn, &P.w[T_D], d_in[6], {{64, 2, 64}, {F, D * 2, 32}, {16, 128, 4}, {1, (cuuint64_t)F * D * 2, 1}});
  encode(fn, &P.xr, d_out, {{D, 2, 64}, {S / 2, D * 4, PIECE / 128}, {2, D * 2, 1}});
  memcpy(P.jobs, kJobs, sizeof(kJobs));
  memcpy(P.kseq, kSeq, sizeof(kSeq));
  P.x0 = (const bf16*)d_in[0];
  P.wqkv = (const bf16*)d_in[1];
  P.out = (bf16*)d_out;
  mega_kernel<<<2 * NPAIR, 384, SMEM_BYTES>>>((char*)scr, sms == 2 * NPAIR, P);
}
```

```cpp
#include <cuda_runtime.h>
#include <cuda_bf16.h>
#include <cuda.h>
#include <stddef.h>
#include <stdint.h>
#include <string.h>

namespace {

typedef __nv_bfloat16 bf16;
typedef unsigned long long u64;
constexpr int S = 2048, D = 1024, F = 3584;
constexpr int STAGE = 49152, NSTAGE = 4, SLOT = 16384;
constexpr int STG_OFF = NSTAGE * STAGE, BAR_OFF = STG_OFF + 2 * SLOT, AUX_OFF = BAR_OFF + 336;
constexpr int SMEM_BYTES = AUX_OFF + 2736;
constexpr int SMEM_BASE = 1024;
constexpr int NPAIR = 66, JMAX = 24, KMAX = 296;
constexpr int T_Q = 0, T_O = 1, T_G = 2, T_D = 3;
constexpr uint32_t JOB_C = 1u << 18;
constexpr uint32_t K_LAST_A = 64, K_LAST_B = 128;
constexpr uint32_t JOB_EARLY = 1u << 21;
constexpr uint32_t JOB_X = JOB_EARLY;
constexpr int BOOT_PIECES = 4, BOOT_OUT = 8, BOOT_STEP = 5, ST_STEP = 9;
constexpr int SPLIT_MIN = 7;
constexpr int PREP = 3, LAST_LEAD = 3;
constexpr int LOOK = 2, MID = 7;
constexpr int NG = 2, PIECE = 8192, DEPTH = 2;
constexpr uint32_t SPIN_LIMIT = 1u << 21;

constexpr int C_X = 0;
constexpr int C_O = C_X + 48;
constexpr int C_H = C_O + 32;
constexpr int C_RD = C_H + 32;
constexpr int C_EP = C_RD + 64;
constexpr int C_LINES = C_EP + 5;

struct Scratch {
  bf16 h[S * F];
  uint32_t cnt[256 * 32];
  bf16 o[S / 2 * D];
  u64 stats[4 * S];
  bf16 o1[S / 2 * D];
  u64 cs[44 * 128];
  ulonglong2 halo[2 * 16 * 16 * 8 * 32];
};
constexpr uint32_t O_PLANE = offsetof(Scratch, o1) - offsetof(Scratch, o);
static_assert(C_LINES <= 256, "");
constexpr size_t PAGE = 2 << 20;
__device__ __align__(1024) char g_scratch[sizeof(Scratch) + PAGE];
Scratch* scratch_base() {
  char* p;
  cudaGetSymbolAddress((void**)&p, g_scratch);
  return (Scratch*)(p + (-(size_t)p & (PAGE - 1)));
}

uint32_t kJobs[NPAIR][JMAX] = {
  {0xe44200,0xc10020,0xc44040,0xc08009,0xc10082,0x4101001a,0xc10022,0xc1800b,0x184170b3,0x46610054,0x5b610034,0x7d41000e,0xc1001e,0xc10076,0xc10096,0xc14037,0xc40000,0xc40000,0xc40000,0xc40000,0xc40000,0xc40000,0xc40000,0x80c40000},
  {0xe44000,0xc10018,0xc44080,0xc08009,0xc10021,0x22010052,0xc10092,0xc100aa,0xc09013,0x16410004,0x2d61004c,0x3461002c,0x4e410086,0xc10056,0x618100ae,0xc100b6,0xc1b02f,0xc40000,0xc40000,0xc40000,0xc40000,0xc40000,0xc40000,0x82c40000},
  {0xc10000,0xc44140,0xc04001,0xc10042,0x3a01004a,0xc1006a,0xc100b2,0xc1201b,0x26413033,0x6440b00d,0x681001d,0x3281002d,0xd48100a6,0xc101be,0xc1e007,0xc40000,0xc40000,0xc40000,0xc40000,0xc40000,0xc40000,0xc40000,0xc40000,0x7fc40000},
  {0xc10010,0xc440c0,0xc04001,0xc10002,0x3b01008a,0xc1019a,0xc101aa,0xc0800b,0x1a40d01b,0xc10014,0x66410064,0x2810006,0xc1008e,0xc10066,0xc1007e,0xc0e087,0xc1003f,0xc40000,0xc40000,0xc40000,0xc40000,0xc40000,0xc40000,0x7fc40000},
  {0xc10048,0xe10058,0xe10070,0xc05039,0x21010012,0x7a01b003,0xc1003a,0x29410044,0x3561001c,0x4f61005c,0x5761003c,0x7e41004e,0x6081009e,0xc100be,0xc1c00f,0xc40000,0xc40000,0xc40000,0xc40000,0xc40000,0xc40000,0xc40000,0xc40000,0x7fc40000},
  {0xe44240,0xc443c0,0xe10158,0xc10130,0xc040e1,0x170101ca,0x620101da,0xc101f2,0x641905b,0xc07063,0x324100c5,0x7a61016c,0x12a1013c,0x288101d6,0xc101ee,0xc10236,0xc1a04f,0xc40000,0xc40000,0xc40000,0xc40000,0xc40000,0xc40000,0x84c40000},
  {0xe44280,0xc44780,0xc10228,0x1f044840,0xe10270,0xc103ca,0x5e01039a,0xc103b2,0xc1042a,0xc103ba,0x6d4180bb,0x8810506,0xc100b5,0xd2810426,0xc103be,0xc1f097,0xc40000,0xc40000,0xc40000,0xc40000,0xc40000,0xc40000,0xc40000,0x86c40000},
  {0xe44380,0xc102d0,0xc040c1,0xc10091,0x1101044a,0x67010452,0xc1046a,0xc104f2,0x2c4170ab,0x5240e0bb,0x5810486,0xc104ce,0xc10466,0xc1047e,0xc1f09f,0xc40000,0xc40000,0xc40000,0xc40000,0xc40000,0xc40000,0xc40000,0xc40000,0x88c40000},
  {0xe442c0,0xc10320,0xc040c1,0x1d210338,0xc1054a,0x610105e2,0x7301e0cb,0xc10344,0xc1030c,0xc040bb,0x6041036c,0x1ca1033c,0x29810596,0x6c8105a6,0xc106f6,0xc1d0df,0xc40000,0xc40000,0xc40000,0xc40000,0xc40000,0xc40000,0xc40000,0x8ac40000},
  {0xe443c0,0xc10390,0xc44d80,0xc100d1,0x1501060a,0x64010612,0x720180c3,0x24106ba,0xc1038c,0x404103dc,0xc103f4,0x2c80c0e5,0x4d810656,0xc1066e,0xc1069e,0xc1a0ef,0xc40000,0xc40000,0xc40000,0xc40000,0xc40000,0xc40000,0xc40000,0x8cc40000},
  {0xc10088,0xe100e0,0xc10011,0x270100ca,0x6c01015a,0x7c01800b,0xc0d023,0x2140f0b3,0x516100dc,0xc10106,0xc1010e,0xc10166,0xc1013e,0xc1f017,0xc40000,0xc40000,0xc40000,0xc40000,0xc40000,0xc40000,0xc40000,0xc40000,0xc40000,0xec40000},
  {0xc10198,0xc101b0,0x1b0445c0,0xc44600,0xc446c0,0xc1030a,0x5d010322,0xc102f2,0xc0e04b,0xc101c4,0xc1707b,0x79410055,0xc07065,0xb0810075,0xd0810326,0xc10336,0xc1d05f,0xc40000,0xc40000,0xc40000,0xc40000,0xc40000,0xc40000,0xfc40000},
  {0xc10050,0xc10060,0xc10038,0x29210078,0x3e010062,0xc10032,0x441901b,0x2461000c,0x36610024,0x5d410074,0x228100ad,0x5b810026,0xc1006e,0xc1005e,0xc1203f,0xc40000,0xc40000,0xc40000,0xc40000,0xc40000,0xc40000,0xc40000,0xc40000,0x10c40000},
  {0xe44040,0xc444c0,0xc10168,0xc10049,0x1601024a,0x63010252,0xc10262,0xc1027a,0xc18073,0x55410045,0x48101c6,0xc1034e,0xc1035e,0xc1023e,0xc1e04f,0xc40000,0xc40000,0xc40000,0xc40000,0xc40000,0xc40000,0xc40000,0xc40000,0x91c40000},
  {0xe44080,0xc44700,0xe10220,0xc09089,0xc103c2,0x5a010412,0xc10512,0xc103f2,0x1e41c0a3,0x4961021c,0x58410234,0x36a1027c,0x4881041e,0x7281051e,0xc10436,0xc1909f,0xc40000,0xc40000,0xc40000,0xc40000,0xc40000,0xc40000,0xc40000,0x93c40000},
  {0xe44180,0xc44880,0xe102a0,0xc04081,0x1c2102f8,0xc104ca,0x66010462,0xc104ea,0xc104ba,0xc104fa,0xc102d4,0xc102ac,0x1d8104c6,0xc104d6,0x6d8104a6,0xc1053e,0xc0f087,0xc0c0b7,0xc40000,0xc40000,0xc40000,0xc40000,0xc40000,0x95c40000},
  {0xe440c0,0xc44ac0,0xc10328,0xc07041,0xc080c9,0xc0c0e1,0xb2010592,0xc105aa,0xc106e2,0x1d4130db,0xc090e3,0x484100fb,0xc810546,0x3f81054e,0x5d810566,0xc1057e,0xc200c7,0xc40000,0xc40000,0xc40000,0xc40000,0xc40000,0xc40000,0x97c40000},
  {0xe441c0,0xc44c40,0xc10398,0xc44d40,0xe103f0,0xc100f1,0xd0010692,0xc10632,0xc10672,0xc1067a,0x6f6103cc,0x736103a4,0x13810606,0xc1064e,0xc10626,0xc1067e,0xc0f0e7,0xc0e0ff,0xc40000,0xc40000,0xc40000,0xc40000,0xc40000,0x99c40000},
  {0xe44300,0xc100a0,0xc04001,0xc100c2,0x3c010112,0x7b01d003,0x741013a,0x234100c4,0x374100d4,0xc100ac,0x39a100fc,0xc10156,0x6981012e,0xc1019e,0xc1b01f,0xc40000,0xc40000,0xc40000,0xc40000,0xc40000,0xc40000,0xc40000,0xc40000,0x9bc40000},
  {0xe44340,0xc101d8,0xc09041,0xc10051,0x24010352,0xc1032a,0xc1b053,0x12410073,0xe101dc,0xe101ac,0xc10286,0x40810296,0x758102a6,0xc102e6,0xc19057,0xc40000,0xc40000,0xc40000,0xc40000,0xc40000,0xc40000,0xc40000,0xc40000,0x9dc40000},
  {0xc10008,0xc44000,0xc44100,0xe10068,0xc10029,0x3601009a,0xc1002a,0xc100a2,0xc1007a,0x3041803b,0xc0b095,0x10810046,0x41810016,0x7881002e,0xc1003e,0xc19037,0xc40000,0xc40000,0xc40000,0xc40000,0xc40000,0xc40000,0xc40000,0x1fc40000},
  {0xc10110,0xc44440,0xe10160,0xc101c2,0x4201021a,0xc10222,0xc10272,0xc101fa,0x3f410104,0x5e610114,0xc100dd,0x2081024e,0x5c8101e6,0xc101fe,0xc10047,0xc1007f,0xc40000,0xc40000,0xc40000,0xc40000,0xc40000,0xc40000,0xc40000,0x20c40000},
  {0xc10200,0xc44a00,0xc10260,0x3010402,0x4301050a,0xc10422,0xc0808b,0xc10432,0xc10244,0xe10214,0xc0b08d,0x7810386,0xc1050e,0x5f8103e6,0xc103fe,0xc1f0a7,0xc40000,0xc40000,0xc40000,0xc40000,0xc40000,0xc40000,0xc40000,0x7fc40000},
  {0xc102c0,0xc44900,0xc102b0,0x40449c0,0x120100b1,0x3801045a,0xc10472,0xa41a093,0x3d8102c4,0x4fa10294,0xe102e4,0xe102bc,0xc10516,0xc104e6,0xc104fe,0xc1b08f,0xc40000,0xc40000,0xc40000,0xc40000,0xc40000,0xc40000,0xc40000,0x7fc40000},
  {0xc10308,0xe10350,0xc44b00,0xe10378,0xc070f9,0x3f01059a,0xc105f2,0xc105ba,0x134105fa,0xe1034c,0xe10364,0xc106c6,0xc10556,0xc1055e,0xc105f6,0xc1e0ef,0xc40000,0xc40000,0xc40000,0xc40000,0xc40000,0xc40000,0xc40000,0x21c40000},
  {0xc10388,0xe103e0,0xc44d00,0xc10682,0x5801065a,0xc106aa,0xc41b0d3,0xc110eb,0x4a4130fb,0x3810686,0xc106ce,0xc106ee,0xc106a6,0xc1e0d7,0xc40000,0xc40000,0xc40000,0xc40000,0xc40000,0xc40000,0xc40000,0xc40000,0xc40000,0x22c40000},
  {0xe44100,0xc44180,0xe100d8,0xc44280,0xc10019,0x1001010a,0xc0b039,0xc10172,0xc1016a,0x1441a02b,0x4241009c,0xb8100f4,0x24810146,0x5981003d,0xf08100f6,0xc19017,0xc0c03f,0xc40000,0xc40000,0xc40000,0xc40000,0xc40000,0xc40000,0xa3c40000},
  {0xe44140,0xc101a0,0xc44640,0xc10059,0x1301028a,0x6501029a,0xc08079,0x71014053,0xc180e3,0xc0e07b,0xc101b4,0x37a101bc,0x4981007d,0x668102b6,0xc1033e,0xc1806f,0xc40000,0xc40000,0xc40000,0xc40000,0xc40000,0xc40000,0xc40000,0xa5c40000},
  {0x2e010040,0xe10028,0xe10030,0xc1000a,0x6801005a,0xc10072,0x40f013,0x104100ba,0x56410005,0x7161006c,0x14a1007c,0x2a810035,0x68810036,0xc1018e,0xc18027,0xc40000,0xc40000,0xc40000,0xc40000,0xc40000,0xc40000,0xc40000,0xc40000,0x7fc40000},
  {0xc10150,0xe10118,0xc44680,0xc10069,0x2f0101d2,0x7701c043,0x541023a,0x2241006b,0x4741011c,0xc10174,0x2f81020e,0xc1025e,0x7a8101f6,0xc10256,0xc0c05f,0xc0a077,0xc40000,0xc40000,0xc40000,0xc40000,0xc40000,0xc40000,0xc40000,0x27c40000},
  {0xc10208,0xc44740,0xc447c0,0xc04081,0xc07089,0x100a9,0xb00103da,0x7501d083,0x34103fa,0xe1020c,0xe10254,0xe1022c,0xc1038e,0xc1039e,0x768103b6,0xc1d08f,0xc0a0bf,0xc40000,0xc40000,0xc40000,0xc40000,0xc40000,0xc40000,0x28c40000},
  {0xc10290,0xc44940,0xc102f0,0x5010099,0x200080b9,0xd201049a,0xc104a2,0xc1047a,0xc0e09b,0x3e6102cc,0x5f40707b,0xc102f4,0x2b81048e,0xc1049e,0x7b8104b6,0xc104de,0xc160b7,0xc40000,0xc40000,0xc40000,0xc40000,0xc40000,0xc40000,0x29c40000},
  {0xc10318,0xc10358,0xc44b80,0xc10542,0x59010552,0xc1056a,0xc10572,0xc1c0eb,0x4b610314,0x59610374,0x7f61037c,0x158100fd,0x648105ae,0xc105e6,0xc180c7,0xc40000,0xc40000,0xc40000,0xc40000,0xc40000,0xc40000,0xc40000,0xc40000,0x2ac40000},
  {0xc103c0,0xc44c00,0xc103e8,0x6010602,0x4401061a,0xc090f9,0x7401a0cb,0xc170e3,0xc0d0fb,0xc103ec,0xc040e5,0x2e81068e,0xc1065e,0x7e8106b6,0xc1b0df,0xc0a0ff,0xc40000,0xc40000,0xc40000,0xc40000,0xc40000,0xc40000,0xc40000,0x7fc40000},
  {0xc100c8,0xc44240,0xc100b0,0x7010102,0x450100da,0xc1012a,0xc100f2,0xc100fa,0xe1008c,0xe10094,0xc0500d,0x1810186,0xc10196,0x6781016e,0xc100fe,0xc1d02f,0xc40000,0xc40000,0xc40000,0xc40000,0xc40000,0xc40000,0xc40000,0x2bc40000},
  {0xc101d0,0xe101e0,0xc100a1,0x250102ca,0x6e01031a,0x7e0102b2,0xc102ba,0xc0a06b,0x3161018c,0x676101ec,0x744102c6,0xc102d6,0x6f8102ae,0xc1032e,0xc1b067,0xc40000,0xc40000,0xc40000,0xc40000,0xc40000,0xc40000,0xc40000,0xc40000,0x2cc40000},
  {0xc10108,0xe10170,0xe10138,0xc08079,0x3701025a,0xc10232,0xc1404b,0x1b410144,0x2e610154,0x38610164,0x68410206,0xc101ce,0xc10226,0xc1037e,0xc1d067,0xc40000,0xc40000,0xc40000,0xc40000,0xc40000,0xc40000,0xc40000,0xc40000,0x2dc40000},
  {0xc10218,0xc10258,0xc10278,0x2a01040a,0xc080b9,0xc103ea,0xc1308b,0x1f41053a,0xc10085,0x7c61026c,0x16810406,0x478103d6,0x738103ae,0xc1042e,0xc19097,0xc40000,0xc40000,0xc40000,0xc40000,0xc40000,0xc40000,0xc40000,0xc40000,0x2ec40000},
  {0xc102c8,0xe102a8,0xc04081,0x1010482,0x5b010492,0x7601b083,0x941809b,0xe1028c,0xe102a4,0xc05095,0x11810446,0x42810496,0xc1046e,0xc104be,0xc190a7,0xc40000,0xc40000,0xc40000,0xc40000,0xc40000,0xc40000,0xc40000,0xc40000,0x2fc40000},
  {0xc10348,0xc44bc0,0xc10370,0x80105c2,0x4601058a,0x790200c3,0x14160db,0x3c410354,0x61610324,0x754105c6,0xc105d6,0x658106e6,0xc105fe,0xc1d0cf,0xc40000,0xc40000,0xc40000,0xc40000,0xc40000,0xc40000,0xc40000,0xc40000,0xc40000,0x30c40000},
  {0xc103d0,0xc103a8,0xc103f8,0x2b01064a,0x6901062a,0xc1069a,0xc106b2,0x27410384,0x394103d4,0x7b6103e4,0x17810646,0x448106d6,0xc106ae,0xc106be,0xc1a0e7,0xc40000,0xc40000,0xc40000,0xc40000,0xc40000,0xc40000,0xc40000,0xc40000,0x31c40000},
  {0xc100d0,0xe100a8,0xc100d9,0x2801018a,0x6d010132,0x7d010162,0xc1017a,0xc1102b,0x4140d03b,0xfa100ec,0x1b8100ce,0xc1015e,0x7d810136,0xc1a007,0xc0b037,0xc40000,0xc40000,0xc40000,0xc40000,0xc40000,0xc40000,0xc40000,0xc40000,0x32c40000},
  {0xc10190,0xc44580,0xc101f0,0x9010282,0x47010292,0xc102da,0xc102e2,0xc1033a,0xc10073,0x536101e4,0xc10306,0xc10356,0xc1029e,0xc102be,0xc1f057,0xc40000,0xc40000,0xc40000,0xc40000,0xc40000,0xc40000,0xc40000,0xc40000,0x33c40000},
  {0xc10148,0xc44400,0xc10128,0xa010202,0x4801020a,0xc101ea,0xc1604b,0x1c41037a,0x6e61010c,0x76610124,0x18810246,0xc10216,0x63810266,0xc1027e,0xc13047,0xc0a0bf,0xc40000,0xc40000,0xc40000,0xc40000,0xc40000,0xc40000,0xc40000,0x34c40000},
  {0xc10248,0xc44a40,0xc10268,0xb010382,0x490103d2,0xc103aa,0xc10532,0xc1043a,0xc120b3,0x50410264,0x8103c6,0xc10396,0xc103a6,0xc1043e,0xc1e0af,0xc40000,0xc40000,0xc40000,0xc40000,0xc40000,0xc40000,0xc40000,0xc40000,0x35c40000},
  {0xc10288,0x2c2102d8,0xe102b8,0xc1048a,0x6a0104d2,0xc104aa,0xc1052a,0x284150ab,0x5440e0bb,0xa81009d,0x34a102fc,0x4a81045e,0xc10476,0xc104ee,0xc110bf,0xc40000,0xc40000,0xc40000,0xc40000,0xc40000,0xc40000,0xc40000,0xc40000,0x36c40000},
  {0xc10340,0xc44a80,0xc10368,0xc010582,0x4a0106da,0xc105d2,0xc105ea,0xc106fa,0xc130f3,0x654100cd,0x1f810586,0xc105ce,0x6e8105ee,0xc105be,0xc0f0e7,0xc0c0f7,0xc40000,0xc40000,0xc40000,0xc40000,0xc40000,0xc40000,0xc40000,0x7fc40000},
  {0xc103d8,0xc44cc0,0xc040c1,0xc103b8,0x140106ca,0x5f010662,0xc106a2,0xc106ea,0xc1d0f3,0xc080fb,0xe8100d5,0x2381060e,0x5881061e,0xc10636,0xc106fe,0xc120ff,0xc40000,0xc40000,0xc40000,0xc40000,0xc40000,0xc40000,0xc40000,0x37c40000},
  {0xc10080,0xc441c0,0xc04001,0xc10142,0x3d0100d2,0xc101a2,0xc101ba,0xc12023,0x2540d02b,0x4340c03b,0x72410015,0x2681014e,0xc1011e,0xc100ee,0xc101a6,0xc0a027,0xc0a03f,0xc40000,0xc40000,0xc40000,0xc40000,0xc40000,0xc40000,0x7fc40000},
  {0xc10180,0xc44500,0xc101f8,0xd010302,0x4b0102d2,0x7801c043,0x8420063,0xc080f3,0x6241004d,0x1e809065,0x218100f5,0xd6810366,0xc102f6,0xc2006f,0xc40000,0xc40000,0xc40000,0xc40000,0xc40000,0xc40000,0xc40000,0xc40000,0xc40000,0x7fc40000},
  {0xc10140,0xc44380,0xc10120,0xe010342,0x4c01035a,0xc1022a,0xc1026a,0xc1e06b,0x4540c07b,0xc10134,0x3581006d,0x458101de,0x7c810276,0xc10376,0xc15077,0xc40000,0xc40000,0xc40000,0xc40000,0xc40000,0xc40000,0xc40000,0xc40000,0x7fc40000},
  {0xc10240,0xc44800,0xe10230,0xc10502,0x4d010392,0xc1041a,0xc103a2,0xc1209b,0x2040c0ab,0x4441025c,0xd810274,0x2581040e,0xc103de,0x7f8103f6,0xc10526,0xc130bf,0xc40000,0xc40000,0xc40000,0xc40000,0xc40000,0xc40000,0xc40000,0x7fc40000},
  {0xc10298,0xc448c0,0xc102e8,0xf010442,0x4e0104da,0xc10522,0xc104b2,0xc1c0a3,0x4c41029c,0x706102b4,0x1981044e,0x5a8100bd,0x6a810536,0xc1052e,0xc160b7,0xc40000,0xc40000,0xc40000,0xc40000,0xc40000,0xc40000,0xc40000,0xc40000,0x38c40000},
  {0xc10300,0xe10330,0xc44dc0,0xc100e9,0xb401055a,0xc105a2,0xc105b2,0xc106f2,0xc0b0eb,0x4d61035c,0x5a61032c,0xc1058e,0xc1059e,0x7781056e,0xc105de,0xc170f7,0xc40000,0xc40000,0xc40000,0xc40000,0xc40000,0xc40000,0xc40000,0x7fc40000},
  {0xc103c8,0xe103a0,0xc04081,0x2010642,0x5c010652,0xc10622,0xb41d0d3,0x3c8103c4,0x4ba1039c,0xe103b4,0xe103bc,0xc10616,0xc1062e,0xc1063e,0xc1a0d7,0xc40000,0xc40000,0xc40000,0xc40000,0xc40000,0xc40000,0xc40000,0xc40000,0x39c40000},
  {0xc100c0,0xc442c0,0xc100b8,0x192100f8,0x2301014a,0xc100e2,0xc100ea,0xc19023,0x336100cc,0x694100e4,0x3aa100bc,0xc10116,0xc101ae,0xc1017e,0xc1d01f,0xc40000,0xc40000,0xc40000,0xc40000,0xc40000,0xc40000,0xc40000,0xc40000,0x7fc40000},
  {0xc10188,0xe101a8,0xc080c9,0x18010071,0x400102a2,0xc102ea,0xc10332,0x11410184,0x2f6101d4,0x3a6101a4,0x6a410346,0xc102ce,0xc102de,0xc1036e,0xc15047,0xc0a07f,0xc40000,0xc40000,0xc40000,0xc40000,0xc40000,0xc40000,0xc40000,0x3ac40000},
  {0xc10100,0xc44480,0xc10178,0xc10242,0x4f010212,0xc101e2,0xe41f05b,0x2b61014c,0x3b61015c,0x6b61012c,0x7761017c,0x1a81021e,0x7481022e,0xc1026e,0xc19077,0xc40000,0xc40000,0xc40000,0xc40000,0xc40000,0xc40000,0xc40000,0xc40000,0x7fc40000},
  {0xc10210,0x2d210250,0xe10238,0xc1038a,0x6b0103e2,0x7001d08b,0x19410204,0xe1024c,0xe10224,0xe1023c,0xc040a5,0x4e8103ce,0xc103ee,0xc10416,0xc1a0af,0xc40000,0xc40000,0xc40000,0xc40000,0xc40000,0xc40000,0xc40000,0xc40000,0x3bc40000},
  {0xc10280,0xc44980,0xc102e0,0xc104c2,0x5401051a,0xc104e2,0xd41e093,0xc10284,0xc102dc,0xc102ec,0xc0c0a5,0x3e810456,0x6b8104ae,0xc104f6,0xc1b087,0xc40000,0xc40000,0xc40000,0xc40000,0xc40000,0xc40000,0xc40000,0xc40000,0x7fc40000},
  {0xc10310,0xc44b40,0xc10360,0xc106c2,0x550105ca,0xc10562,0xc105da,0xc1057a,0xc10304,0xc1031c,0xc10334,0x278100ed,0x438106de,0xc10576,0xc105b6,0xc150f7,0xc40000,0xc40000,0xc40000,0xc40000,0xc40000,0xc40000,0xc40000,0x3cc40000},
  {0xc10380,0xc44c80,0xc040c1,0x1e2103b0,0xc1068a,0x600106d2,0xc1066a,0xc1063a,0xc0f0db,0x3d610394,0x6c4103ac,0x3ba103fc,0xc10696,0xc10666,0xc10676,0xc0f0cf,0xc0e0ff,0xc40000,0xc40000,0xc40000,0xc40000,0xc40000,0xc40000,0x7fc40000},
  {0xc10090,0xc44200,0xc100e8,0x1a044340,0xc10031,0x39010152,0xc10122,0xc101b2,0x17410084,0xc11033,0x5c40703b,0xc100b4,0x2d810025,0x468100de,0x79810176,0xc101b6,0xc16027,0xc40000,0xc40000,0xc40000,0xc40000,0xc40000,0xc40000,0x3dc40000},
  {0xc101c8,0xc101e8,0xc10061,0x2601034a,0x6f0102aa,0x7f01036a,0xc102fa,0xe101cc,0xc1019c,0xc101f4,0x38a101fc,0x4c810316,0xc102ee,0xc1030e,0xc0c0cf,0xc0e07f,0xc40000,0xc40000,0xc40000,0xc40000,0xc40000,0xc40000,0xc40000,0x3ec40000},
  {0xc10098,0xc44300,0xc100f0,0xc10182,0x56010192,0xc1011a,0xf420013,0x2a414033,0x636100a4,0x784100c6,0xc100d6,0x628100e6,0xc10126,0xc1c00f,0xc40000,0xc40000,0xc40000,0xc40000,0xc40000,0xc40000,0xc40000,0xc40000,0xc40000,0x3fc40000},
  {0xc101c0,0xc44540,0xc101b8,0xc102c2,0x57010312,0xc10362,0xc10372,0xc09053,0x15411063,0xc10194,0xc0508d,0x981005d,0x3381028e,0x5e81031e,0xc102fe,0xc0f05f,0xc1007f,0xc40000,0xc40000,0xc40000,0xc40000,0xc40000,0xc40000,0x7fc40000},
};
uint8_t kSeq[NPAIR][KMAX] = {
  {0,1,2,3,0,1,2,3,4,5,6,7,8,9,10,11,12,13,14,15,0,1,2,3,64,67,72,78,76,70,66,74,64,66,76,78,65,67,77,79,68,70,69,71,72,74,73,75,4,6,0,2,5,7,1,3,12,14,8,10,13,15,9,11,4,6,8,10,0,2,5,7,9,11,12,14,1,3,13,15,88,89,94,95,116,117,118,119,106,107,78,79,82,83,112,113,84,85,102,103,98,99,72,73,72,73,80,81,98,99,74,75,110,111,112,113,86,87,92,93,78,79,64,65,66,67,84,68,70,69,71,76,78,72,74,64,66,77,79,73,75,65,67,68,70,72,74,69,71,64,66,76,78,73,75,65,67,77,79,8,10,0,2,9,11,12,14,1,3,4,6,13,15,5,7,12,14,8,10,4,6,0,2,13,15,9,11,5,7,1,3,12,14,8,10,13,15,4,6,9,11,5,7,0,2,1,3,200,202,73,75,196,198,192,194,204,206,197,199,193,195,205,207,71,66,67,112,113,98,99,86,87,110,111,114,115,88,89,118,119,196,197,230,0,0,0,0,0,0,0,0,0,0,0,0,0,0,0,0,0,0,0,0,0,0,0,0,0,0,0,0,0,0,0,0,0,0,0,0,0,0,0,0,0,0,0,0,0,0,0,0,0,0,0,0,0},
  {0,1,2,3,0,1,2,3,4,5,6,7,8,9,10,11,12,13,14,15,0,1,2,3,77,69,73,79,65,68,75,71,70,64,76,66,74,72,79,71,78,67,69,65,75,77,68,73,12,14,8,10,13,15,9,11,0,2,4,6,1,3,5,7,76,78,72,74,77,79,73,75,64,66,68,70,65,67,69,71,4,6,12,14,8,10,0,2,5,7,13,15,9,11,1,3,114,115,100,101,74,75,116,117,118,0,2,4,6,8,10,1,3,5,7,12,14,9,11,13,15,76,78,68,70,77,79,64,66,72,74,69,71,65,67,73,75,12,14,4,6,0,2,13,15,5,7,8,10,1,3,9,11,8,10,12,14,0,2,9,11,13,15,1,3,4,6,5,7,8,10,9,11,4,6,0,2,12,14,5,7,1,3,13,15,4,6,12,14,8,10,5,7,13,15,9,11,0,2,1,3,12,14,8,10,13,15,4,6,9,11,5,7,128,130,1,3,99,64,65,80,81,92,93,108,109,106,107,70,71,66,67,90,91,88,89,82,83,224,225,232,233,230,231,0,0,0,0,0,0,0,0,0,0,0,0,0,0,0,0,0,0,0,0,0,0,0,0,0,0,0,0,0,0,0,0,0,0,0,0,0,0,0,0,0,0,0,0,0,0,0,0,0,0,0,0},
  {64,65,66,67,68,69,70,71,72,73,74,75,76,77,78,79,0,1,2,3,79,75,77,73,0,2,12,14,1,3,13,15,4,6,5,7,8,10,9,11,64,66,72,74,65,67,73,75,76,78,68,70,77,79,69,71,4,6,12,14,8,10,0,2,5,7,13,15,9,11,1,3,0,2,8,10,4,6,12,14,1,3,9,11,5,7,13,15,83,98,99,108,109,92,93,78,79,84,85,100,101,66,67,74,75,88,66,67,84,85,68,69,90,91,104,105,70,71,210,211,228,229,106,107,222,71,72,69,66,64,78,74,77,76,75,73,64,71,78,77,69,72,75,70,74,79,76,73,68,67,66,65,64,71,78,74,77,70,73,69,66,72,76,79,68,65,67,75,4,6,5,7,8,10,12,14,9,11,13,15,0,2,1,3,4,6,12,14,8,10,5,7,13,15,0,2,9,11,1,3,106,107,104,105,92,93,88,89,72,73,90,91,100,101,78,79,116,117,64,65,118,119,208,209,94,95,76,77,240,241,0,0,0,0,0,0,0,0,0,0,0,0,0,0,0,0,0,0,0,0,0,0,0,0,0,0,0,0,0,0,0,0,0,0,0,0,0,0,0,0,0,0,0,0,0,0,0,0,0,0,0,0,0,0,0,0,0,0,0,0,0,0,0,0,0,0},
  {0,1,2,3,4,5,6,7,8,9,10,11,12,13,14,15,0,1,2,3,66,74,68,64,0,2,12,14,1,3,13,15,4,6,5,7,8,10,9,11,64,66,72,74,65,67,73,75,76,78,68,70,77,79,69,71,4,6,0,2,5,7,1,3,12,14,8,10,13,15,9,11,4,6,12,14,8,10,128,130,5,7,13,15,9,11,129,131,92,93,64,65,100,101,96,97,89,76,77,96,97,86,87,72,73,116,117,110,111,4,6,5,7,12,14,8,10,0,2,13,15,9,11,1,3,0,2,1,3,4,6,8,10,12,14,5,7,9,11,13,15,8,10,12,14,0,2,9,11,13,15,1,3,4,6,5,7,8,10,0,2,9,11,12,14,1,3,4,6,13,15,5,7,4,6,5,7,8,10,12,14,9,11,13,15,0,2,1,3,4,6,12,14,8,10,5,7,13,15,0,2,9,11,1,3,77,112,113,110,111,82,83,70,71,68,69,102,103,108,80,81,66,67,90,91,96,97,242,243,202,203,70,199,238,239,0,0,0,0,0,0,0,0,0,0,0,0,0,0,0,0,0,0,0,0,0,0,0,0,0,0,0,0,0,0,0,0,0,0,0,0,0,0,0,0,0,0,0,0,0,0,0,0,0,0,0,0,0,0,0,0,0,0,0,0,0},
  {64,65,66,67,68,69,70,71,72,73,74,75,76,77,78,79,64,65,66,67,68,69,70,71,72,73,74,75,76,77,78,79,64,65,66,67,68,69,70,71,72,73,74,75,76,77,78,79,198,69,194,199,204,12,14,8,10,13,15,9,11,0,2,4,6,1,3,5,7,70,71,64,65,98,99,92,93,78,79,112,113,94,95,72,73,80,81,84,85,114,115,116,117,106,107,66,136,138,128,130,137,139,129,131,140,142,141,143,132,134,133,135,0,2,4,6,8,10,1,3,5,7,12,14,9,11,13,15,4,6,5,7,0,2,8,10,12,14,1,3,9,11,13,15,68,70,69,71,64,66,72,74,76,78,65,67,73,75,77,79,132,134,128,130,133,135,129,131,136,138,140,142,137,139,141,143,8,10,0,2,9,11,12,14,1,3,4,6,13,15,5,7,12,14,8,10,4,6,0,2,13,15,9,11,5,7,1,3,4,6,12,14,8,10,5,7,13,15,0,2,137,139,1,3,92,93,108,109,98,99,80,81,100,101,70,71,116,117,96,97,74,75,64,65,112,113,82,83,234,235,212,213,0,0,0,0,0,0,0,0,0,0,0,0,0,0,0,0,0,0,0,0,0,0,0,0,0,0,0,0,0,0,0,0,0,0,0,0,0,0,0,0,0,0,0,0},
  {0,1,2,3,0,1,2,3,0,1,2,3,4,5,6,7,8,9,10,11,12,13,14,15,0,1,2,3,4,5,6,7,8,9,10,11,12,13,14,15,70,64,76,66,0,2,8,10,1,3,9,11,12,14,4,6,13,15,5,7,4,6,0,2,5,7,1,3,12,14,8,10,13,15,9,11,0,2,8,10,4,6,12,14,1,3,9,11,5,7,13,15,93,78,79,84,85,100,101,66,67,74,75,88,89,76,77,96,97,86,87,72,73,116,117,110,111,84,85,88,89,114,115,110,66,71,70,77,69,73,72,64,65,78,67,75,79,74,76,68,12,14,4,6,0,2,13,15,5,7,8,10,1,3,9,11,132,134,128,130,133,135,129,131,136,138,140,142,137,139,141,143,8,10,9,11,4,6,0,2,12,14,5,7,1,3,13,15,4,6,12,14,8,10,5,7,13,15,9,11,0,2,1,3,140,142,136,138,141,143,132,134,137,139,133,135,128,130,129,131,72,73,86,87,102,103,90,91,118,119,68,69,206,207,114,115,66,67,110,111,94,95,88,217,204,205,0,0,0,0,0,0,0,0,0,0,0,0,0,0,0,0,0,0,0,0,0,0,0,0,0,0,0,0,0,0,0,0,0,0,0,0,0,0,0,0,0,0,0,0,0,0,0,0,0,0},
  {0,1,2,3,0,1,2,3,0,1,2,3,4,5,6,7,8,9,10,11,12,13,14,15,0,1,2,3,0,1,2,3,4,5,6,7,8,9,10,11,12,13,14,15,0,2,8,10,1,3,9,11,12,14,4,6,13,15,5,7,4,6,0,2,5,7,1,3,12,14,8,10,13,15,9,11,0,2,8,10,4,6,12,14,1,3,9,11,5,7,13,15,4,6,12,14,8,10,0,2,5,7,13,15,137,11,1,3,136,138,128,130,137,139,129,131,140,142,141,143,132,134,133,135,204,205,236,237,240,241,210,211,226,227,228,229,192,193,200,201,208,209,202,203,212,213,214,215,8,10,12,14,0,2,9,11,13,15,1,3,4,6,5,7,78,74,77,71,70,64,66,69,79,200,75,68,204,73,195,65,4,6,5,7,8,10,12,14,9,11,13,15,0,2,1,3,132,134,140,142,136,138,133,135,141,143,128,130,137,139,129,131,99,102,103,86,87,104,105,78,79,118,119,114,115,88,89,112,113,100,101,64,65,84,85,94,95,224,225,82,83,196,197,0,0,0,0,0,0,0,0,0,0,0,0,0,0,0,0,0,0,0,0,0,0,0,0,0,0,0,0,0,0,0,0,0,0,0,0,0,0,0,0,0,0,0,0,0,0,0,0,0,0,0,0,0},
  {0,1,2,3,0,1,2,3,4,5,6,7,8,9,10,11,12,13,14,15,66,74,68,64,64,74,76,66,68,70,65,72,79,67,69,71,78,75,77,73,0,2,8,10,1,3,9,11,12,14,4,6,13,15,5,7,12,14,8,10,13,15,9,11,0,2,4,6,1,3,5,7,4,6,12,14,8,10,0,2,5,7,13,15,9,11,1,3,0,2,8,10,4,6,12,14,1,3,9,11,5,7,13,15,99,100,101,90,91,70,71,76,77,68,69,110,111,82,83,74,75,96,97,118,119,104,105,238,239,242,243,232,233,218,219,220,221,230,231,196,197,8,10,12,14,0,2,9,11,13,15,1,3,4,6,5,7,8,10,0,2,9,11,12,14,1,3,4,6,13,15,5,7,4,6,5,7,8,10,12,14,9,11,13,15,0,2,1,3,4,6,140,142,136,138,133,135,141,143,128,130,137,139,129,131,80,81,96,97,92,93,108,109,70,71,82,83,100,101,78,79,74,75,114,115,94,95,118,119,200,201,192,193,240,241,226,0,0,0,0,0,0,0,0,0,0,0,0,0,0,0,0,0,0,0,0,0,0,0,0,0,0,0,0,0,0,0,0,0,0,0,0,0,0,0,0,0,0,0,0,0,0,0,0,0,0,0,0,0,0,0,0,0,0,0,0},
  {0,1,2,3,0,1,2,3,4,5,6,7,8,9,10,11,12,13,14,15,69,76,67,65,0,1,2,3,4,5,6,7,8,9,10,11,12,13,14,15,0,2,8,10,1,3,9,11,12,14,4,6,13,15,5,7,4,6,8,10,0,2,5,7,9,11,12,14,1,3,13,15,88,89,94,95,116,117,118,119,106,107,78,79,82,83,112,113,84,85,102,103,98,99,72,73,92,93,64,65,100,101,0,2,4,6,8,10,1,3,5,7,12,14,9,11,13,15,12,14,4,6,13,15,0,2,8,10,5,7,1,3,9,11,222,223,244,245,12,14,4,6,0,2,13,15,5,7,8,10,1,3,9,11,132,134,128,130,133,135,129,131,136,138,140,142,137,139,141,143,8,10,9,11,4,6,0,2,12,14,5,7,1,3,13,15,4,6,5,7,8,10,12,14,9,11,13,15,0,2,1,3,12,14,8,10,13,15,4,6,9,11,5,7,0,2,1,3,65,112,113,98,99,88,89,86,87,84,85,90,91,106,235,68,69,104,105,76,77,116,117,110,111,102,103,194,195,0,0,0,0,0,0,0,0,0,0,0,0,0,0,0,0,0,0,0,0,0,0,0,0,0,0,0,0,0,0,0,0,0,0,0,0,0,0,0,0,0,0,0,0,0,0,0,0,0},
  {0,1,2,3,0,1,2,3,4,5,6,7,8,9,10,11,12,13,14,15,0,1,2,3,64,74,76,66,68,70,65,72,79,67,69,71,78,75,77,73,0,2,8,10,1,3,9,11,12,14,4,6,13,15,5,7,12,14,8,10,13,15,9,11,0,2,4,6,1,3,5,7,96,97,82,83,74,75,110,111,76,77,88,89,118,119,68,69,100,101,104,105,102,103,90,91,136,138,128,130,9,11,129,131,140,142,141,143,132,134,133,135,12,14,4,6,13,15,0,2,8,10,5,7,1,3,9,11,4,6,5,7,0,2,8,10,12,14,1,3,9,11,13,15,4,6,8,10,5,7,0,2,12,14,9,11,1,3,13,15,77,69,78,72,76,68,66,73,79,67,75,65,8,10,9,11,4,6,0,2,12,14,5,7,1,3,13,15,4,6,12,14,8,10,5,7,13,15,9,11,0,2,1,3,12,14,8,10,132,134,0,2,141,143,9,11,133,135,129,131,64,65,80,81,92,93,108,109,106,107,70,71,66,67,90,91,88,89,82,83,96,97,232,233,230,231,0,0,0,0,0,0,0,0,0,0,0,0,0,0,0,0,0,0,0,0,0,0,0,0,0,0,0,0,0,0,0,0,0,0,0,0,0,0,0,0,0,0,0,0,0,0,0,0,0,0},
  {64,65,66,67,68,69,70,71,72,73,74,75,76,77,78,79,0,1,2,3,4,5,6,7,8,9,10,11,12,13,14,15,64,74,76,66,68,70,65,72,79,67,69,71,78,75,77,73,0,2,8,10,1,3,9,11,12,14,4,6,13,15,5,7,4,6,0,2,5,7,1,3,12,14,8,10,13,15,9,11,114,115,76,77,70,71,86,87,90,91,74,75,66,67,68,69,80,81,108,109,110,111,104,105,84,85,88,89,114,115,110,111,98,99,66,67,94,85,68,69,90,91,104,105,70,71,210,211,100,101,234,235,4,6,5,7,0,2,8,10,12,14,1,3,9,11,13,15,8,10,12,14,0,2,9,11,13,15,1,3,4,6,5,7,8,10,0,2,9,11,12,14,1,3,4,6,13,15,5,7,4,6,5,7,8,10,12,14,9,11,13,15,0,2,1,3,4,6,12,14,8,10,133,135,13,15,0,2,137,139,1,3,99,102,103,86,87,104,105,78,79,118,119,114,115,88,89,112,113,100,101,64,65,84,85,94,95,224,225,210,211,196,197,0,0,0,0,0,0,0,0,0,0,0,0,0,0,0,0,0,0,0,0,0,0,0,0,0,0,0,0,0,0,0,0,0,0,0,0,0,0,0,0,0,0,0,0,0,0,0,0,0,0,0,0,0},
  {0,1,2,3,4,5,6,7,8,9,10,11,12,13,14,15,0,1,2,3,4,5,6,7,8,9,10,11,12,13,14,15,0,1,2,3,0,1,2,3,0,1,2,3,0,2,8,10,1,3,9,11,12,14,4,6,13,15,5,7,4,6,8,10,0,2,5,7,9,11,12,14,1,3,13,15,0,2,8,10,4,6,12,14,1,3,9,11,5,7,13,15,72,73,92,93,64,65,100,101,96,97,114,115,76,77,0,2,4,6,8,10,1,3,5,7,12,14,9,11,13,15,204,205,108,109,112,113,210,211,226,227,228,229,192,193,200,201,208,209,202,203,212,213,214,71,69,72,78,64,77,75,74,79,73,67,76,70,68,66,65,68,66,73,79,67,75,65,78,74,77,71,70,64,194,69,207,200,75,196,204,73,195,65,4,6,5,7,8,10,12,14,9,11,13,15,0,2,1,3,12,14,8,10,13,15,4,6,9,11,5,7,0,2,1,3,65,112,113,98,99,88,89,86,87,84,85,90,91,106,107,68,69,104,105,76,77,116,117,238,239,102,103,194,195,0,0,0,0,0,0,0,0,0,0,0,0,0,0,0,0,0,0,0,0,0,0,0,0,0,0,0,0,0,0,0,0,0,0,0,0,0,0,0,0,0,0,0,0,0,0,0,0,0,0,0},
  {0,1,2,3,4,5,6,7,8,9,10,11,12,13,14,15,0,1,2,3,4,5,6,7,8,9,10,11,12,13,14,15,0,1,2,3,4,5,6,7,8,9,10,11,12,13,14,15,64,65,66,67,68,69,70,71,72,73,74,75,76,77,78,79,4,6,8,10,0,2,5,7,9,11,12,14,1,3,13,15,0,2,8,10,4,6,12,14,1,3,9,11,5,7,13,15,64,65,70,71,80,81,112,113,90,91,102,103,118,119,104,105,114,115,106,107,94,95,68,69,82,12,14,4,6,13,15,0,2,8,10,5,7,1,3,9,11,0,2,1,3,4,6,8,10,12,14,5,7,9,11,13,15,68,70,72,74,69,71,64,66,76,78,73,75,65,67,77,79,64,71,78,74,77,70,73,69,66,72,76,79,68,65,67,75,4,6,5,7,8,10,12,14,9,11,13,15,0,2,1,3,4,6,12,14,8,10,5,7,13,15,9,11,0,2,1,3,204,206,200,202,196,198,192,194,205,207,201,203,197,199,193,195,78,79,106,107,86,87,94,95,76,77,220,221,72,73,98,227,212,213,0,0,0,0,0,0,0,0,0,0,0,0,0,0,0,0,0,0,0,0,0,0,0,0,0,0,0,0,0,0,0,0,0,0,0,0,0,0,0,0,0,0,0,0,0},
  {0,1,2,3,0,1,2,3,0,1,2,3,4,5,6,7,8,9,10,11,12,13,14,15,64,67,72,77,69,73,78,76,70,66,74,79,65,68,75,71,0,2,8,10,1,3,9,11,12,14,4,6,13,15,5,7,12,14,8,10,13,15,9,11,0,2,4,6,1,3,5,7,4,6,8,10,0,2,5,7,9,11,12,14,1,3,13,15,136,138,128,130,137,139,129,131,140,142,141,143,132,134,133,135,78,79,64,65,66,67,84,85,68,69,90,91,104,105,70,71,210,211,100,101,106,107,222,223,66,71,70,77,69,73,72,64,65,78,67,75,79,74,76,68,8,10,12,14,0,2,9,11,13,15,1,3,4,6,5,7,8,10,0,2,9,11,12,14,1,3,4,6,13,15,5,7,12,14,8,10,4,6,0,2,13,15,9,11,5,7,1,3,4,6,12,14,8,10,5,7,141,143,0,2,137,139,1,3,92,93,108,109,98,99,80,81,100,101,70,71,116,117,96,97,74,75,64,65,112,113,82,83,106,107,212,213,232,233,0,0,0,0,0,0,0,0,0,0,0,0,0,0,0,0,0,0,0,0,0,0,0,0,0,0,0,0,0,0,0,0,0,0,0,0,0,0,0,0,0,0,0,0,0,0,0,0,0,0,0,0,0,0,0,0,0,0},
  {0,1,2,3,0,1,2,3,0,1,2,3,4,5,6,7,8,9,10,11,12,13,14,15,64,67,72,77,69,73,78,76,70,64,66,76,78,65,67,77,79,68,70,69,71,72,74,73,75,12,14,8,10,13,15,9,11,0,2,4,6,1,3,5,7,76,78,72,74,77,79,73,75,64,66,68,70,65,67,69,71,0,2,8,10,4,6,12,14,1,3,9,11,5,7,13,15,84,85,88,89,114,115,110,111,98,99,66,67,94,95,70,71,76,77,106,107,96,97,64,65,78,79,90,91,4,6,5,7,0,2,8,10,12,14,1,3,9,11,13,15,4,6,8,10,5,7,0,2,12,14,9,11,1,3,13,15,132,134,128,130,133,135,129,131,136,138,140,142,137,139,141,143,12,14,8,10,4,6,0,2,13,15,9,11,5,7,1,3,12,14,8,10,4,6,0,2,13,15,9,11,5,7,1,3,12,14,8,10,13,15,132,134,9,11,133,135,128,130,129,131,99,88,89,86,87,84,85,90,91,234,235,68,69,104,105,76,77,116,117,110,111,102,103,194,195,0,0,0,0,0,0,0,0,0,0,0,0,0,0,0,0,0,0,0,0,0,0,0,0,0,0,0,0,0,0,0,0,0,0,0,0,0,0,0,0,0,0,0,0,0,0,0,0,0,0},
  {0,1,2,3,0,1,2,3,0,1,2,3,4,5,6,7,8,9,10,11,12,13,14,15,79,75,77,73,0,1,2,3,4,5,6,7,8,9,10,11,12,13,14,15,0,2,8,10,1,3,9,11,12,14,4,6,13,15,5,7,4,6,8,10,0,2,5,7,9,11,12,14,1,3,13,15,4,6,12,14,8,10,0,2,5,7,13,15,9,11,1,3,136,138,128,130,137,139,129,131,140,142,141,143,132,134,133,135,136,138,128,130,137,139,129,131,140,142,141,143,132,134,133,135,4,6,5,7,12,14,8,10,0,2,13,15,9,11,1,3,12,14,4,6,0,2,13,15,5,7,8,10,1,3,9,11,8,10,12,14,0,2,9,11,13,15,1,3,4,6,5,7,8,10,9,11,4,6,0,2,12,14,5,7,1,3,13,15,4,6,5,7,8,10,12,14,9,11,13,15,0,2,1,3,4,6,12,14,8,10,5,7,13,15,0,2,9,11,1,3,109,86,87,114,115,98,99,66,67,84,85,96,97,74,75,102,103,80,81,96,97,76,77,218,219,236,237,0,0,0,0,0,0,0,0,0,0,0,0,0,0,0,0,0,0,0,0,0,0,0,0,0,0,0,0,0,0,0,0,0,0,0,0,0,0,0,0,0,0,0,0,0,0,0,0,0},
  {0,1,2,3,0,1,2,3,0,1,2,3,4,5,6,7,8,9,10,11,12,13,14,15,72,78,70,71,66,74,68,70,66,74,79,65,68,75,71,74,72,79,71,78,67,69,65,75,77,68,73,12,14,8,10,13,15,9,11,0,2,4,6,1,3,5,7,4,6,12,14,8,10,0,2,5,7,13,15,9,11,1,3,4,6,8,10,0,2,5,7,9,11,12,14,1,3,13,15,68,69,82,83,98,99,108,109,92,93,78,79,84,85,100,101,66,67,74,75,86,87,92,93,118,119,68,69,216,217,198,199,206,207,246,247,194,195,238,239,242,243,232,233,8,10,12,14,0,2,9,11,13,15,1,3,4,6,5,7,8,10,0,2,9,11,12,14,1,3,4,6,13,15,5,7,4,6,5,7,8,10,12,14,9,11,13,15,0,2,1,3,132,134,140,142,136,138,133,135,141,143,128,130,137,139,129,131,106,107,104,105,92,93,88,89,72,73,90,91,100,101,78,79,116,117,64,65,118,119,208,209,94,95,76,77,240,241,238,239,0,0,0,0,0,0,0,0,0,0,0,0,0,0,0,0,0,0,0,0,0,0,0,0,0,0,0,0,0,0,0,0,0,0,0,0,0,0,0,0,0,0,0,0,0,0,0,0,0,0,0,0,0,0,0,0,0},
  {0,1,2,3,0,1,2,3,0,1,2,3,4,5,6,7,8,9,10,11,12,13,14,15,0,1,2,3,0,1,2,3,4,5,6,7,8,9,10,11,12,13,14,15,76,69,70,72,74,66,71,75,67,77,68,73,79,206,64,65,12,14,8,10,13,15,9,11,0,2,4,6,1,3,5,7,0,2,8,10,4,6,12,14,1,3,9,11,5,7,13,15,0,2,8,10,4,6,12,14,1,3,9,11,5,7,13,15,136,138,128,130,137,139,129,131,140,142,141,143,132,134,133,135,12,14,4,6,13,15,0,2,8,10,5,7,1,3,9,11,0,2,1,3,4,6,8,10,12,14,5,7,9,11,13,15,8,10,12,14,0,2,9,11,13,15,1,3,4,6,5,7,8,10,0,2,9,11,12,14,1,3,4,6,13,15,5,7,4,6,5,7,8,10,12,14,9,11,13,15,0,2,1,3,4,6,140,142,136,138,5,7,141,143,0,2,137,139,129,131,75,98,99,66,67,80,81,92,93,114,115,112,113,88,89,110,111,82,83,68,69,104,105,108,109,102,103,244,245,0,0,0,0,0,0,0,0,0,0,0,0,0,0,0,0,0,0,0,0,0,0,0,0,0,0,0,0,0,0,0,0,0,0,0,0,0,0,0,0,0,0,0,0,0,0,0},
  {0,1,2,3,0,1,2,3,4,5,6,7,8,9,10,11,12,13,14,15,69,76,67,65,0,2,12,14,1,3,13,15,4,6,5,7,8,10,9,11,12,14,8,10,13,15,9,11,0,2,4,6,1,3,5,7,67,108,109,86,87,96,97,82,83,74,75,110,111,76,77,88,89,118,119,68,69,100,101,104,105,102,103,90,91,136,138,128,130,137,139,129,131,140,142,141,143,132,134,133,135,0,2,4,6,8,10,1,3,5,7,12,14,9,11,13,15,4,6,5,7,12,14,8,10,0,2,13,15,9,11,1,3,12,14,4,6,0,2,13,15,5,7,8,10,1,3,9,11,132,134,128,130,133,135,129,131,136,138,140,142,137,139,141,143,8,10,9,11,4,6,0,2,12,14,5,7,1,3,13,15,4,6,12,14,8,10,5,7,13,15,9,11,0,2,1,3,12,14,8,10,4,6,0,2,13,15,9,11,5,7,1,3,80,81,96,97,92,93,108,109,70,71,82,83,100,101,206,207,74,75,114,115,94,95,118,119,200,201,192,0,0,0,0,0,0,0,0,0,0,0,0,0,0,0,0,0,0,0,0,0,0,0,0,0,0,0,0,0,0,0,0,0,0,0,0,0,0,0,0,0,0,0,0,0,0,0,0,0,0,0,0,0,0,0,0},
  {0,1,2,3,0,1,2,3,4,5,6,7,8,9,10,11,12,13,14,15,64,79,75,77,73,69,76,67,65,64,74,76,66,68,70,65,72,79,67,69,71,78,75,77,73,12,14,8,10,13,15,9,11,0,2,4,6,1,3,5,7,4,6,12,14,8,10,0,2,5,7,13,15,9,11,1,3,76,77,88,89,106,107,78,79,96,97,108,109,114,115,100,101,74,75,116,117,118,119,82,83,112,113,98,72,73,80,81,98,99,74,75,110,111,112,113,86,87,92,93,4,6,5,7,0,2,8,10,12,14,1,3,9,11,13,15,12,14,4,6,0,2,13,15,5,7,8,10,1,3,9,11,8,10,12,14,0,2,9,11,13,15,1,3,4,6,5,7,8,10,9,11,4,6,0,2,12,14,5,7,1,3,13,15,4,6,5,7,8,10,12,14,9,11,13,15,0,2,1,3,132,134,133,135,136,138,140,142,137,139,141,143,128,130,129,131,90,91,106,107,92,93,116,117,72,73,76,77,108,109,110,111,208,209,70,71,66,67,202,203,226,0,0,0,0,0,0,0,0,0,0,0,0,0,0,0,0,0,0,0,0,0,0,0,0,0,0,0,0,0,0,0,0,0,0,0,0,0,0,0,0,0,0,0,0,0,0,0,0,0,0,0,0,0,0,0},
  {64,65,66,67,68,69,70,71,72,73,74,75,76,77,78,79,0,1,2,3,0,1,2,3,64,65,66,67,68,69,70,71,72,73,74,75,76,77,78,79,72,76,64,70,66,74,71,78,67,79,65,197,75,68,73,77,4,6,0,2,5,7,1,3,12,14,8,10,13,15,9,11,4,6,12,14,8,10,0,2,5,7,13,15,9,11,1,3,68,70,72,74,64,66,69,71,73,75,76,78,65,67,77,79,136,138,128,130,137,139,129,131,140,142,141,143,132,134,133,135,76,77,108,109,112,113,82,83,226,227,100,101,64,65,200,201,208,209,202,203,212,213,214,215,71,69,72,78,64,77,75,74,79,73,67,8,10,12,14,0,2,9,11,13,15,1,3,4,6,5,7,8,10,9,11,4,6,0,2,12,14,5,7,1,3,13,15,4,6,12,14,8,10,5,7,13,15,9,11,0,2,1,3,132,134,140,142,136,138,133,135,141,143,128,130,137,139,129,131,64,65,84,85,92,93,104,105,74,75,78,79,100,101,82,83,72,73,116,117,222,223,234,235,198,0,0,0,0,0,0,0,0,0,0,0,0,0,0,0,0,0,0,0,0,0,0,0,0,0,0,0,0,0,0,0,0,0,0,0,0,0,0,0,0,0,0,0,0,0,0,0,0,0,0,0,0},
  {0,1,2,3,4,5,6,7,8,9,10,11,12,13,14,15,0,1,2,3,64,65,66,67,68,69,70,71,72,73,74,75,76,77,78,79,64,66,76,78,65,67,77,79,68,70,69,71,72,74,73,75,4,6,0,2,5,7,1,3,12,14,8,10,13,15,9,11,4,6,8,10,0,2,5,7,9,11,12,14,1,3,13,15,0,2,8,10,4,6,12,14,1,3,9,11,5,7,13,15,136,138,128,130,137,139,129,131,140,142,141,143,132,134,133,135,64,66,68,70,72,74,65,67,69,71,76,78,73,75,77,79,68,70,69,71,76,78,72,74,64,66,77,79,73,75,65,67,64,71,78,77,69,72,75,70,74,79,76,73,68,67,66,65,8,10,0,2,9,11,12,14,1,3,4,6,13,15,5,7,4,6,5,7,8,10,12,14,9,11,13,15,0,2,1,3,132,134,140,142,136,138,133,135,141,143,128,130,137,139,129,131,106,107,104,105,92,93,88,89,72,73,90,91,100,101,78,79,84,85,80,81,66,67,90,91,96,97,242,243,202,203,198,199,0,0,0,0,0,0,0,0,0,0,0,0,0,0,0,0,0,0,0,0,0,0,0,0,0,0,0,0,0,0,0,0,0,0,0,0,0,0,0,0,0,0,0,0,0,0,0,0,0,0,0,0},
  {64,65,66,67,68,69,70,71,72,73,74,75,76,77,78,79,0,1,2,3,64,65,66,67,68,69,70,71,72,73,74,75,76,77,78,79,64,66,76,78,65,67,77,79,68,70,69,71,72,74,73,75,64,66,72,74,65,67,73,75,76,78,68,70,77,79,69,71,4,6,8,10,0,2,5,7,9,11,12,14,1,3,13,15,80,81,108,109,110,111,104,105,0,2,8,10,4,6,12,14,1,3,9,11,5,7,13,15,0,2,4,6,8,10,1,3,5,7,12,14,9,11,13,15,4,6,5,7,12,14,8,10,0,2,13,15,9,11,1,3,71,72,69,66,64,78,74,77,76,75,73,8,10,12,14,0,2,9,11,13,15,1,3,4,6,5,7,8,10,0,2,9,11,12,14,1,3,4,6,13,15,5,7,4,6,5,7,8,10,12,14,9,11,13,15,0,2,1,3,132,134,140,142,136,138,133,135,141,143,128,130,137,139,129,131,64,65,78,79,90,91,106,107,94,95,68,69,96,97,74,75,98,99,66,67,80,81,220,221,242,243,112,113,216,217,236,0,0,0,0,0,0,0,0,0,0,0,0,0,0,0,0,0,0,0,0,0,0,0,0,0,0,0,0,0,0,0,0,0,0,0,0,0,0,0,0,0,0,0,0,0,0,0,0,0,0},
  {64,65,66,67,68,69,70,71,72,73,74,75,76,77,78,79,0,1,2,3,0,1,2,3,4,5,6,7,8,9,10,11,12,13,14,15,0,1,2,3,76,69,70,72,74,66,71,75,67,77,68,73,79,78,64,65,4,6,0,2,5,7,1,3,12,14,8,10,13,15,9,11,0,2,8,10,4,6,12,14,1,3,9,11,5,7,13,15,108,109,114,115,100,101,74,75,116,117,118,119,82,83,112,113,98,99,102,103,68,69,110,111,104,105,0,2,4,6,8,10,1,3,5,7,12,14,9,11,13,15,4,6,5,7,12,14,8,10,0,2,13,15,9,11,1,3,64,66,65,67,68,70,72,74,76,78,69,71,73,75,77,79,132,134,128,130,133,135,129,131,136,138,140,142,137,139,141,143,8,10,9,11,4,6,0,2,12,14,5,7,1,3,13,15,4,6,5,7,8,10,12,14,9,11,13,15,0,2,1,3,4,6,12,14,8,10,5,7,13,15,0,2,9,11,1,3,105,72,73,86,87,102,103,90,91,118,119,68,69,78,79,114,115,66,67,110,111,94,95,216,217,204,205,0,0,0,0,0,0,0,0,0,0,0,0,0,0,0,0,0,0,0,0,0,0,0,0,0,0,0,0,0,0,0,0,0,0,0,0,0,0,0,0,0,0,0},
  {64,65,66,67,68,69,70,71,72,73,74,75,76,77,78,79,64,65,66,67,68,69,70,71,72,73,74,75,76,77,78,79,0,1,2,3,0,1,2,3,4,5,6,7,8,9,10,11,12,13,14,15,198,197,194,199,204,203,206,4,6,0,2,5,7,1,3,12,14,8,10,13,15,9,11,0,2,8,10,4,6,12,14,1,3,9,11,5,7,13,15,136,138,128,130,9,11,129,131,140,142,141,143,132,134,133,135,136,138,128,130,137,139,129,131,140,142,141,143,132,134,133,135,12,14,4,6,13,15,0,2,8,10,5,7,1,3,9,11,0,2,1,3,4,6,8,10,12,14,5,7,9,11,13,15,8,10,12,14,0,2,9,11,13,15,1,3,4,6,5,7,8,10,9,11,4,6,0,2,12,14,5,7,1,3,13,15,12,14,8,10,4,6,0,2,13,15,9,11,5,7,1,3,12,14,8,10,13,15,4,6,9,11,5,7,0,2,1,3,118,119,76,77,74,75,68,69,72,73,100,101,110,111,84,85,206,207,116,117,94,95,242,243,86,87,240,241,226,227,0,0,0,0,0,0,0,0,0,0,0,0,0,0,0,0,0,0,0,0,0,0,0,0,0,0,0,0,0,0,0,0,0,0,0,0,0,0,0,0,0,0,0,0,0,0,0},
  {64,65,66,67,68,69,70,71,72,73,74,75,76,77,78,79,0,1,2,3,4,5,6,7,8,9,10,11,12,13,14,15,0,1,2,3,64,66,76,78,65,67,77,79,68,70,69,71,72,74,73,75,4,6,0,2,5,7,1,3,12,14,8,10,13,15,9,11,4,6,12,14,8,10,0,2,5,7,13,15,9,11,1,3,97,108,109,114,115,100,101,74,75,116,117,118,119,82,83,112,113,98,99,102,103,68,69,110,111,104,105,114,115,102,103,98,99,100,101,90,91,70,71,76,77,68,69,110,193,200,201,208,209,202,203,212,213,214,215,222,223,244,245,234,235,224,225,8,10,12,14,0,2,9,11,13,15,1,3,4,6,5,7,8,10,0,2,9,11,12,14,1,3,4,6,13,15,5,7,4,6,12,14,8,10,5,7,13,15,9,11,0,2,1,3,4,6,5,7,8,10,140,142,9,11,13,15,0,2,1,3,90,91,106,107,92,93,116,117,72,73,76,77,108,109,110,111,80,81,70,71,66,67,74,75,98,99,102,103,214,215,0,0,0,0,0,0,0,0,0,0,0,0,0,0,0,0,0,0,0,0,0,0,0,0,0,0,0,0,0,0,0,0,0,0,0,0,0,0,0,0,0,0,0,0,0,0,0,0,0,0,0,0,0,0,0},
  {0,1,2,3,0,1,2,3,0,1,2,3,4,5,6,7,8,9,10,11,12,13,14,15,0,1,2,3,74,66,76,79,70,72,64,67,71,69,78,68,75,65,77,73,0,2,8,10,1,3,9,11,12,14,4,6,13,15,5,7,203,206,200,202,196,201,207,205,195,192,193,0,2,8,10,4,6,12,14,1,3,9,11,5,7,13,15,4,6,12,14,8,10,0,2,5,7,13,15,137,139,129,131,112,113,84,85,88,89,66,67,78,79,92,93,72,73,80,81,106,107,116,117,236,237,64,65,94,95,4,6,5,7,0,2,8,10,12,14,1,3,9,11,13,15,4,6,8,10,5,7,0,2,12,14,9,11,1,3,13,15,72,74,76,78,64,66,73,75,77,79,65,67,68,70,69,71,72,79,194,76,192,67,202,196,199,206,198,197,205,201,193,203,12,14,8,10,13,15,4,6,9,11,5,7,0,2,1,3,90,91,106,107,92,93,116,117,72,73,76,77,108,109,110,111,80,81,70,71,66,67,74,75,98,82,83,68,69,104,105,108,109,102,103,244,245,0,0,0,0,0,0,0,0,0,0,0,0,0,0,0,0,0,0,0,0,0,0,0,0,0,0,0,0,0,0,0,0,0,0,0,0,0,0,0,0,0,0,0,0,0,0,0,0,0,0},
  {0,1,2,3,0,1,2,3,4,5,6,7,8,9,10,11,12,13,14,15,0,1,2,3,74,66,76,79,70,72,64,67,71,69,78,68,75,65,77,73,0,2,8,10,1,3,9,11,12,14,4,6,13,15,5,7,4,6,0,2,5,7,1,3,12,14,8,10,13,15,9,11,202,196,201,207,205,195,192,193,90,91,70,71,72,73,66,67,64,65,84,85,92,93,80,81,86,87,94,95,84,85,88,89,114,115,110,111,98,99,66,67,94,95,70,71,76,77,106,107,96,97,64,65,215,222,223,244,245,234,235,224,225,216,217,198,199,206,4,6,8,10,5,7,0,2,12,14,9,11,1,3,13,15,132,134,128,130,133,135,129,131,136,138,140,142,137,139,141,143,72,79,194,76,192,67,202,196,199,206,198,197,205,201,193,203,12,14,8,10,13,15,4,6,9,11,5,7,0,2,1,3,4,6,12,14,136,138,5,7,13,15,128,130,137,139,129,131,80,81,92,93,108,109,106,107,70,71,66,67,90,91,88,89,82,83,224,225,232,233,230,231,0,0,0,0,0,0,0,0,0,0,0,0,0,0,0,0,0,0,0,0,0,0,0,0,0,0,0,0,0,0,0,0,0,0,0,0,0,0,0,0,0,0,0,0,0,0,0,0,0,0,0,0,0,0},
  {64,65,66,67,68,69,70,71,72,73,74,75,76,77,78,79,0,1,2,3,4,5,6,7,8,9,10,11,12,13,14,15,64,65,66,67,68,69,70,71,72,73,74,75,76,77,78,79,0,2,8,10,1,3,9,11,12,14,4,6,13,15,5,7,4,6,0,2,5,7,1,3,12,14,8,10,13,15,9,11,0,2,8,10,4,6,12,14,1,3,9,11,5,7,13,15,119,82,83,112,113,98,99,102,103,68,69,110,111,104,105,200,202,192,194,201,203,193,195,204,206,205,207,196,198,197,199,66,71,70,77,69,73,72,64,65,78,67,75,79,74,76,68,76,78,68,70,64,66,77,79,69,71,72,74,65,67,73,75,132,134,128,130,133,135,129,131,136,138,140,142,137,139,141,143,78,74,77,71,70,64,194,69,207,200,75,196,204,73,195,65,12,14,8,10,13,15,4,6,9,11,5,7,0,2,1,3,72,74,64,66,73,75,76,78,65,67,196,198,77,79,197,199,68,69,96,97,74,75,98,99,66,67,80,81,92,93,114,115,112,113,88,89,108,109,246,247,0,0,0,0,0,0,0,0,0,0,0,0,0,0,0,0,0,0,0,0,0,0,0,0,0,0,0,0,0,0,0,0,0,0,0,0,0,0,0,0,0,0,0,0,0,0,0,0,0},
  {0,1,2,3,4,5,6,7,8,9,10,11,12,13,14,15,64,65,66,67,68,69,70,71,72,73,74,75,76,77,78,79,0,1,2,3,72,76,64,70,66,74,71,78,67,79,65,197,75,68,73,77,12,14,8,10,13,15,9,11,0,2,4,6,1,3,5,7,108,109,86,87,96,97,82,83,74,75,110,111,76,77,88,89,118,119,68,69,100,101,104,105,102,103,90,91,136,138,128,130,137,139,129,131,140,142,141,143,132,134,133,135,76,77,68,69,110,111,82,83,74,75,96,97,118,119,104,105,4,6,5,7,0,2,8,10,12,14,1,3,9,11,13,15,4,6,8,10,5,7,0,2,12,14,9,11,1,3,13,15,8,10,0,2,9,11,12,14,1,3,4,6,13,15,5,7,12,14,8,10,4,6,0,2,13,15,9,11,5,7,1,3,12,14,8,10,13,15,132,134,9,11,5,7,0,2,1,3,136,138,9,11,132,134,0,2,140,142,133,135,129,131,141,143,79,74,75,114,115,94,95,118,119,72,73,64,208,209,96,97,76,77,218,219,236,237,0,0,0,0,0,0,0,0,0,0,0,0,0,0,0,0,0,0,0,0,0,0,0,0,0,0,0,0,0,0,0,0,0,0,0,0,0,0,0,0,0,0,0,0,0,0,0,0,0,0},
  {64,65,66,67,68,69,70,71,72,73,74,75,76,77,78,79,0,1,2,3,0,1,2,3,66,74,68,64,66,74,79,65,68,75,71,72,76,64,70,66,74,71,78,67,79,65,69,75,68,73,77,4,6,0,2,5,7,1,3,12,14,8,10,13,15,9,11,70,71,64,65,98,99,92,93,78,79,112,113,94,95,72,73,80,81,84,85,114,115,116,117,106,107,66,67,108,136,138,128,130,137,139,129,131,140,142,141,143,132,134,133,135,12,14,4,6,13,15,0,2,8,10,5,7,1,3,9,11,4,6,5,7,12,14,8,10,0,2,13,15,9,11,1,3,76,78,4,6,0,2,13,15,5,7,8,10,1,3,9,11,8,10,0,2,9,11,12,14,1,3,4,6,13,15,5,7,12,14,8,10,4,6,0,2,13,15,9,11,5,7,1,3,12,14,8,10,13,15,4,6,9,11,5,7,0,2,1,3,92,93,108,109,98,99,80,81,100,101,70,71,116,117,96,97,74,75,64,65,112,113,82,83,234,235,84,85,104,112,113,228,229,192,193,216,217,246,247,0,0,0,0,0,0,0,0,0,0,0,0,0,0,0,0,0,0,0,0,0,0,0,0,0,0,0,0,0,0,0,0,0,0,0,0,0,0,0,0,0,0,0,0,0,0,0,0,0},
  {0,1,2,3,4,5,6,7,8,9,10,11,12,13,14,15,0,1,2,3,0,1,2,3,4,5,6,7,8,9,10,11,12,13,14,15,74,66,76,79,70,72,64,67,71,69,78,68,75,65,77,73,198,194,204,206,200,202,196,192,4,6,0,2,5,7,1,3,12,14,8,10,13,15,9,11,4,6,8,10,0,2,5,7,9,11,12,14,1,3,13,15,136,138,128,130,137,139,129,131,140,142,141,143,132,134,133,135,88,89,76,77,96,97,86,87,72,73,116,117,110,111,12,14,4,6,13,15,0,2,8,10,5,7,1,3,9,11,219,220,221,230,231,196,197,4,6,8,10,5,7,0,2,12,14,9,11,1,3,13,15,8,10,0,2,9,11,12,14,1,3,4,6,13,15,5,7,12,14,8,10,4,6,0,2,13,15,9,11,5,7,1,3,12,14,8,10,13,15,4,6,9,11,5,7,0,2,1,3,12,14,8,10,132,134,0,2,13,15,9,11,133,135,1,3,64,65,84,85,92,93,104,105,74,75,206,207,100,101,82,83,200,201,116,117,222,223,0,0,0,0,0,0,0,0,0,0,0,0,0,0,0,0,0,0,0,0,0,0,0,0,0,0,0,0,0,0,0,0,0,0,0,0,0,0,0,0,0,0,0,0,0,0,0,0,0},
  {0,1,2,3,4,5,6,7,8,9,10,11,12,13,14,15,64,65,66,67,68,69,70,71,72,73,74,75,76,77,78,79,0,1,2,3,64,66,76,78,65,67,77,79,68,70,69,71,72,74,73,75,12,14,8,10,13,15,9,11,0,2,4,6,1,3,5,7,4,6,12,14,8,10,0,2,5,7,13,15,9,11,1,3,0,2,8,10,4,6,12,14,1,3,9,11,5,7,13,15,112,113,84,85,88,89,66,67,78,79,92,93,72,73,80,81,106,107,116,117,108,109,64,65,94,95,86,87,4,6,5,7,12,14,8,10,0,2,13,15,9,11,1,3,4,6,8,10,5,7,0,2,12,14,9,11,1,3,13,15,132,134,128,130,133,135,129,131,136,138,140,142,137,139,141,143,200,207,194,204,192,195,202,196,199,206,198,197,205,201,193,203,4,6,12,14,8,10,5,7,13,15,9,11,0,2,1,3,4,6,5,7,136,138,140,142,9,11,141,143,128,130,129,131,82,83,70,71,68,69,102,103,108,109,86,87,114,115,98,99,66,67,84,85,224,225,202,203,0,0,0,0,0,0,0,0,0,0,0,0,0,0,0,0,0,0,0,0,0,0,0,0,0,0,0,0,0,0,0,0,0,0,0,0,0,0,0,0,0,0,0,0,0,0,0,0},
  {64,65,66,67,68,69,70,71,72,73,74,75,76,77,78,79,0,1,2,3,0,1,2,3,4,5,6,7,8,9,10,11,12,13,14,15,64,66,76,78,65,67,77,79,68,70,69,71,72,74,73,75,4,6,0,2,5,7,1,3,12,14,8,10,13,15,9,11,200,202,196,201,207,205,195,192,193,96,97,114,115,76,77,70,71,86,87,90,91,74,75,66,67,68,69,80,81,108,109,110,111,104,105,78,79,90,91,80,81,102,103,104,105,108,109,112,113,72,73,116,117,82,83,100,101,74,204,205,236,237,240,241,210,211,226,227,228,229,192,12,14,4,6,0,2,13,15,5,7,8,10,1,3,9,11,64,71,70,74,8,10,0,2,9,11,12,14,1,3,4,6,13,15,5,7,12,14,8,10,4,6,0,2,13,15,9,11,5,7,1,3,12,14,8,10,13,15,4,6,9,11,5,7,0,2,1,3,80,81,96,97,92,93,108,109,70,71,82,83,100,101,78,79,74,75,114,115,94,95,118,119,72,73,64,112,113,228,229,192,193,216,217,246,247,0,0,0,0,0,0,0,0,0,0,0,0,0,0,0,0,0,0,0,0,0,0,0,0,0,0,0,0,0,0,0,0,0,0,0,0,0,0,0,0,0,0,0,0,0,0,0,0,0,0,0,0},
  {64,65,66,67,68,69,70,71,72,73,74,75,76,77,78,79,0,1,2,3,0,1,2,3,4,5,6,7,8,9,10,11,12,13,14,15,64,66,76,78,65,67,77,79,68,70,69,71,72,74,73,75,4,6,0,2,5,7,1,3,12,14,8,10,13,15,9,11,4,6,12,14,8,10,0,2,5,7,13,15,9,11,1,3,0,2,8,10,4,6,12,14,1,3,9,11,5,7,13,15,136,138,128,130,137,139,129,131,140,142,141,143,132,134,133,135,12,14,4,6,13,15,0,2,8,10,5,7,1,3,9,11,68,70,69,71,76,78,72,74,64,66,77,79,73,75,65,67,79,68,65,67,70,8,10,12,14,0,2,9,11,13,15,1,3,4,6,5,7,8,10,9,11,4,6,0,2,12,14,5,7,1,3,13,15,4,6,12,14,8,10,5,7,13,15,9,11,0,2,1,3,132,134,140,142,136,138,133,135,141,143,128,130,137,139,129,131,118,119,76,77,74,75,68,69,72,73,100,101,110,111,84,85,206,207,116,117,94,95,242,243,214,215,240,241,226,0,0,0,0,0,0,0,0,0,0,0,0,0,0,0,0,0,0,0,0,0,0,0,0,0,0,0,0,0,0,0,0,0,0,0,0,0,0,0,0,0,0,0,0,0,0,0,0,0,0},
  {0,1,2,3,4,5,6,7,8,9,10,11,12,13,14,15,0,1,2,3,4,5,6,7,8,9,10,11,12,13,14,15,70,64,76,66,74,72,79,71,78,67,69,65,75,77,68,73,0,2,8,10,1,3,9,11,12,14,4,6,13,15,5,7,4,6,0,2,5,7,1,3,12,14,8,10,13,15,9,11,0,2,8,10,4,6,12,14,1,3,9,11,5,7,13,15,136,138,128,130,137,139,129,131,140,142,141,143,132,134,133,135,112,113,84,85,88,89,66,67,78,79,76,78,68,70,77,79,64,66,72,74,69,71,65,67,73,75,12,14,4,6,0,2,13,15,5,7,8,10,1,3,9,11,8,10,12,14,0,2,9,11,13,15,1,3,4,6,5,7,8,10,9,11,4,6,0,2,12,14,5,7,1,3,13,15,4,6,12,14,8,10,5,7,13,15,9,11,0,2,1,3,4,6,12,14,8,10,5,7,13,15,9,11,128,130,1,3,89,108,109,118,119,82,83,70,71,100,101,102,103,84,85,116,117,72,73,214,215,238,239,232,233,204,205,0,0,0,0,0,0,0,0,0,0,0,0,0,0,0,0,0,0,0,0,0,0,0,0,0,0,0,0,0,0,0,0,0,0,0,0,0,0,0,0,0,0,0,0,0,0,0,0,0,0,0},
  {64,65,66,67,68,69,70,71,72,73,74,75,76,77,78,79,0,1,2,3,4,5,6,7,8,9,10,11,12,13,14,15,0,1,2,3,4,5,6,7,8,9,10,11,12,13,14,15,198,197,194,199,204,203,206,200,4,6,0,2,5,7,1,3,12,14,8,10,13,15,9,11,0,2,8,10,4,6,12,14,1,3,9,11,5,7,13,15,70,71,86,87,90,91,74,75,66,67,68,69,80,81,108,109,110,111,104,105,0,2,4,6,8,10,1,3,5,7,12,14,9,11,13,15,4,6,5,7,12,14,8,10,0,2,13,15,9,11,1,3,0,2,1,3,4,6,8,10,12,14,5,7,9,11,13,15,8,10,12,14,0,2,9,11,13,15,1,3,4,6,5,7,8,10,0,2,9,11,12,14,1,3,4,6,13,15,5,7,4,6,5,7,8,10,12,14,9,11,13,15,0,2,1,3,4,6,12,14,8,10,5,7,13,15,0,2,9,11,1,3,64,65,78,79,90,91,106,107,94,95,68,69,96,97,74,75,98,99,66,67,208,209,92,93,242,243,240,241,216,0,0,0,0,0,0,0,0,0,0,0,0,0,0,0,0,0,0,0,0,0,0,0,0,0,0,0,0,0,0,0,0,0,0,0,0,0,0,0,0,0,0,0,0,0,0,0},
  {0,1,2,3,4,5,6,7,8,9,10,11,12,13,14,15,64,65,66,67,68,69,70,71,72,73,74,75,76,77,78,79,0,1,2,3,4,5,6,7,8,9,10,11,12,13,14,15,0,2,8,10,1,3,9,11,12,14,4,6,13,15,5,7,197,199,203,201,207,205,195,193,4,6,12,14,8,10,0,2,5,7,13,15,9,11,1,3,88,89,94,95,116,117,118,119,106,107,78,79,82,83,112,113,84,85,102,136,138,128,130,137,139,129,131,140,142,141,143,132,134,133,135,66,71,70,77,69,73,72,64,65,78,67,75,79,74,76,68,12,14,4,6,0,2,13,15,5,7,8,10,1,3,9,11,8,10,12,14,0,2,9,11,13,15,1,3,4,6,5,7,8,10,9,11,4,6,0,2,12,14,5,7,1,3,13,15,4,6,12,14,8,10,5,7,13,15,9,11,0,2,1,3,4,6,12,14,136,138,5,7,13,15,137,139,128,130,129,131,90,91,106,107,92,93,116,117,72,73,76,77,108,109,110,111,80,81,198,199,66,67,202,203,226,0,0,0,0,0,0,0,0,0,0,0,0,0,0,0,0,0,0,0,0,0,0,0,0,0,0,0,0,0,0,0,0,0,0,0,0,0,0,0,0,0,0,0,0,0,0,0,0,0,0,0,0},
  {64,65,66,67,68,69,70,71,72,73,74,75,76,77,78,79,0,1,2,3,4,5,6,7,8,9,10,11,12,13,14,15,72,78,70,71,64,66,76,78,65,67,77,79,68,70,69,71,72,74,73,75,12,14,8,10,13,15,9,11,0,2,4,6,1,3,5,7,109,86,87,96,97,82,83,74,75,110,111,76,77,88,89,118,119,68,69,100,101,104,105,102,103,90,91,64,65,70,71,80,81,112,113,90,91,102,103,118,119,104,105,114,115,106,107,94,95,68,69,12,14,4,6,13,15,0,2,8,10,5,7,1,3,9,11,0,2,1,3,4,6,8,10,12,14,5,7,9,11,13,15,76,70,68,66,65,8,10,12,14,0,2,9,11,13,15,1,3,4,6,5,7,8,10,9,11,4,6,0,2,12,14,5,7,1,3,13,15,4,6,12,14,8,10,5,7,13,15,9,11,0,2,1,3,132,134,140,142,136,138,133,135,141,143,128,130,137,139,129,131,109,118,119,82,83,70,71,100,101,102,103,84,85,116,117,72,73,86,87,110,111,232,233,204,205,0,0,0,0,0,0,0,0,0,0,0,0,0,0,0,0,0,0,0,0,0,0,0,0,0,0,0,0,0,0,0,0,0,0,0,0,0,0,0,0,0,0,0,0,0,0,0,0,0,0,0},
  {64,65,66,67,68,69,70,71,72,73,74,75,76,77,78,79,0,1,2,3,0,1,2,3,4,5,6,7,8,9,10,11,12,13,14,15,64,66,76,78,65,67,77,79,68,70,69,71,72,74,73,75,64,66,72,74,65,67,73,75,76,78,68,70,77,79,69,71,70,71,64,65,98,99,92,93,78,79,112,113,94,95,72,73,80,81,84,85,114,115,116,117,106,107,66,67,108,109,86,87,64,65,70,71,80,81,112,113,90,91,102,103,118,119,104,105,114,115,106,107,94,95,4,6,5,7,12,14,8,10,0,2,13,15,9,11,1,3,0,2,1,3,4,6,8,10,12,14,5,7,9,11,13,15,8,10,12,14,0,2,9,11,13,15,1,3,4,6,5,7,8,10,9,11,4,6,0,2,12,14,5,7,1,3,13,15,4,6,5,7,8,10,12,14,9,11,13,15,0,2,1,3,4,6,12,14,8,10,5,7,13,15,0,2,9,11,1,3,85,104,105,72,73,86,87,102,103,90,91,118,119,68,69,206,207,114,115,66,67,110,111,94,95,216,217,204,205,0,0,0,0,0,0,0,0,0,0,0,0,0,0,0,0,0,0,0,0,0,0,0,0,0,0,0,0,0,0,0,0,0,0,0,0,0,0,0,0,0,0,0,0,0,0,0,0,0},
  {0,1,2,3,4,5,6,7,8,9,10,11,12,13,14,15,0,1,2,3,4,5,6,7,8,9,10,11,12,13,14,15,0,1,2,3,4,5,6,7,8,9,10,11,12,13,14,15,0,2,8,10,1,3,9,11,12,14,4,6,13,15,5,7,4,6,12,14,8,10,0,2,5,7,13,15,9,11,1,3,4,6,0,2,5,7,1,3,12,14,8,10,13,15,9,11,0,2,8,10,4,6,12,14,1,3,137,139,5,7,141,143,0,2,4,6,8,10,1,3,5,7,12,14,9,11,13,15,4,6,5,7,12,14,8,10,0,2,13,15,9,11,1,3,0,2,1,3,4,6,8,10,12,14,5,7,9,11,13,15,8,10,12,14,0,2,9,11,13,15,1,3,4,6,5,7,8,10,9,11,4,6,0,2,12,14,5,7,1,3,13,15,4,6,12,14,8,10,5,7,13,15,9,11,0,2,1,3,4,6,140,142,136,138,5,7,141,143,128,130,137,139,129,131,108,109,118,119,82,83,70,71,100,101,102,103,84,85,116,117,72,73,86,87,110,111,232,233,204,205,0,0,0,0,0,0,0,0,0,0,0,0,0,0,0,0,0,0,0,0,0,0,0,0,0,0,0,0,0,0,0,0,0,0,0,0,0,0,0,0,0,0,0,0,0,0},
  {0,1,2,3,4,5,6,7,8,9,10,11,12,13,14,15,0,1,2,3,4,5,6,7,8,9,10,11,12,13,14,15,74,66,76,79,70,72,64,67,71,69,78,68,75,65,77,73,0,2,8,10,1,3,9,11,12,14,4,6,13,15,5,7,0,2,8,10,4,6,12,14,1,3,9,11,5,7,13,15,4,6,8,10,0,2,5,7,9,11,12,14,1,3,13,15,136,138,128,130,137,139,129,131,140,142,141,143,132,134,133,135,86,87,114,115,102,103,98,99,100,101,90,91,70,71,204,205,68,206,207,246,247,194,195,238,239,242,243,232,233,218,76,78,68,70,64,66,77,79,69,71,72,74,65,67,73,75,8,10,0,2,9,11,12,14,1,3,4,6,13,15,5,7,12,14,8,10,4,6,0,2,13,15,9,11,5,7,1,3,12,14,8,10,13,15,4,6,9,11,5,7,0,2,1,3,110,111,82,83,70,71,68,69,102,103,108,109,86,87,114,115,98,99,66,67,84,85,96,97,74,75,103,208,209,96,97,76,77,218,219,236,237,0,0,0,0,0,0,0,0,0,0,0,0,0,0,0,0,0,0,0,0,0,0,0,0,0,0,0,0,0,0,0,0,0,0,0,0,0,0,0,0,0,0,0,0,0,0,0,0,0,0,0,0,0},
  {0,1,2,3,4,5,6,7,8,9,10,11,12,13,14,15,0,1,2,3,0,1,2,3,4,5,6,7,8,9,10,11,12,13,14,15,64,66,76,78,65,67,77,79,68,70,69,71,72,74,73,75,12,14,8,10,13,15,9,11,0,2,4,6,1,3,5,7,4,6,0,2,5,7,1,3,12,14,8,10,13,15,9,11,4,6,8,10,0,2,5,7,9,11,12,14,1,3,13,15,136,138,128,130,137,139,129,131,140,142,141,143,132,134,133,135,108,109,204,205,88,89,114,115,96,97,102,103,116,117,246,247,0,2,1,3,4,6,8,10,12,14,5,7,9,11,13,15,8,10,12,14,0,2,9,11,13,15,1,3,4,6,5,7,8,10,9,11,4,6,0,2,12,14,5,7,1,3,13,15,12,14,8,10,4,6,0,2,13,15,9,11,5,7,1,3,132,134,140,142,136,138,133,135,141,143,128,130,137,139,129,131,99,102,103,86,87,104,105,78,79,118,119,114,115,88,89,112,113,100,101,64,65,84,85,94,95,224,225,210,211,196,197,0,0,0,0,0,0,0,0,0,0,0,0,0,0,0,0,0,0,0,0,0,0,0,0,0,0,0,0,0,0,0,0,0,0,0,0,0,0,0,0,0,0,0,0,0,0,0,0,0,0,0,0,0},
  {64,65,66,67,68,69,70,71,72,73,74,75,76,77,78,79,0,1,2,3,0,1,2,3,4,5,6,7,8,9,10,11,12,13,14,15,64,66,76,78,65,67,77,79,68,70,69,71,72,74,73,75,64,66,72,74,65,67,73,75,76,78,68,70,77,79,69,71,4,6,12,14,8,10,0,2,5,7,13,15,9,11,1,3,88,89,94,95,116,117,118,119,106,107,78,79,82,83,112,113,84,85,102,103,98,99,136,138,128,130,137,139,129,131,140,142,141,143,132,134,133,135,12,14,4,6,13,15,0,2,8,10,5,7,1,3,9,11,0,2,1,3,4,6,8,10,12,14,5,7,9,11,13,15,8,10,12,14,0,2,9,11,13,15,1,3,4,6,5,7,8,10,9,11,4,6,0,2,12,14,5,7,1,3,13,15,4,6,5,7,8,10,12,14,9,11,13,15,0,2,1,3,4,6,12,14,8,10,5,7,13,15,0,2,9,11,1,3,69,102,103,108,109,86,87,114,115,98,99,66,67,84,85,96,97,74,75,68,69,104,105,108,109,102,103,244,245,0,0,0,0,0,0,0,0,0,0,0,0,0,0,0,0,0,0,0,0,0,0,0,0,0,0,0,0,0,0,0,0,0,0,0,0,0,0,0,0,0,0,0,0,0,0,0,0,0},
  {64,65,66,67,68,69,70,71,72,73,74,75,76,77,78,79,0,1,2,3,0,1,2,3,4,5,6,7,8,9,10,11,12,13,14,15,64,66,76,78,65,67,77,79,68,70,69,71,72,74,73,75,12,14,8,10,13,15,9,11,0,2,4,6,1,3,5,7,4,6,12,14,8,10,0,2,5,7,13,15,9,11,1,3,0,2,8,10,4,6,12,14,1,3,9,11,5,7,13,15,136,138,128,130,137,139,129,131,140,142,141,143,132,134,133,135,94,95,108,109,76,77,88,89,114,115,96,97,102,103,116,117,118,119,0,2,1,3,4,6,8,10,12,14,5,7,9,11,13,15,8,10,12,14,0,2,9,11,13,15,1,3,4,6,5,7,8,10,9,11,4,6,0,2,12,14,5,7,1,3,13,15,4,6,5,7,8,10,12,14,9,11,13,15,0,2,1,3,4,6,12,14,8,10,5,7,13,15,0,2,9,11,1,3,118,119,76,77,74,75,68,69,72,73,100,101,110,111,84,85,78,79,116,117,94,95,242,243,214,215,240,241,226,227,0,0,0,0,0,0,0,0,0,0,0,0,0,0,0,0,0,0,0,0,0,0,0,0,0,0,0,0,0,0,0,0,0,0,0,0,0,0,0,0,0,0,0,0,0,0,0,0,0,0,0,0},
  {64,65,66,67,68,69,70,71,72,73,74,75,76,77,78,79,64,65,66,67,68,69,70,71,72,73,74,75,76,77,78,79,0,1,2,3,4,5,6,7,8,9,10,11,12,13,14,15,0,2,8,10,1,3,9,11,12,14,4,6,13,15,5,7,12,14,8,10,13,15,9,11,0,2,4,6,1,3,5,7,4,6,12,14,8,10,0,2,5,7,13,15,9,11,1,3,68,70,76,78,72,74,64,66,69,71,77,79,73,75,65,67,72,73,80,81,106,107,116,117,108,109,64,65,94,95,86,87,114,115,102,103,226,234,235,224,225,216,217,198,199,206,207,246,247,194,195,64,71,78,77,69,72,75,70,74,79,76,73,68,67,66,65,196,198,192,194,197,199,193,195,200,202,204,206,201,203,205,207,12,14,8,10,4,6,0,2,13,15,9,11,5,7,1,3,12,14,8,10,13,15,132,134,9,11,133,135,128,130,1,3,196,198,204,206,200,202,69,71,205,207,201,203,192,194,193,195,81,66,67,90,91,96,97,114,115,74,75,198,199,238,239,210,211,0,0,0,0,0,0,0,0,0,0,0,0,0,0,0,0,0,0,0,0,0,0,0,0,0,0,0,0,0,0,0,0,0,0,0,0,0,0,0,0,0,0,0,0,0,0,0,0,0,0,0,0},
  {64,65,66,67,68,69,70,71,72,73,74,75,76,77,78,79,0,1,2,3,0,1,2,3,4,5,6,7,8,9,10,11,12,13,14,15,64,66,76,78,65,67,77,79,68,70,69,71,72,74,73,75,4,6,0,2,5,7,1,3,12,14,8,10,13,15,9,11,76,78,72,74,77,79,73,75,64,66,68,70,65,67,69,71,4,6,12,14,8,10,0,2,5,7,13,15,9,11,1,3,8,10,128,130,9,11,1,3,140,142,13,15,132,134,133,135,107,94,95,108,109,76,77,88,89,114,115,96,97,102,103,116,117,118,119,71,72,69,66,64,78,74,77,76,75,73,79,68,65,67,70,8,10,12,14,0,2,9,11,13,15,1,3,4,6,5,7,8,10,0,2,9,11,12,14,1,3,4,6,13,15,5,7,4,6,12,14,8,10,5,7,13,15,9,11,0,2,1,3,4,6,12,14,8,10,5,7,13,15,0,2,9,11,1,3,64,65,78,79,90,91,106,107,94,95,68,69,96,97,74,102,103,208,209,96,97,76,77,218,219,236,237,0,0,0,0,0,0,0,0,0,0,0,0,0,0,0,0,0,0,0,0,0,0,0,0,0,0,0,0,0,0,0,0,0,0,0,0,0,0,0,0,0,0,0,0,0,0,0,0,0,0,0,0,0,0},
  {0,1,2,3,4,5,6,7,8,9,10,11,12,13,14,15,0,1,2,3,79,75,77,73,0,1,2,3,4,5,6,7,8,9,10,11,12,13,14,15,0,2,8,10,1,3,9,11,12,14,4,6,13,15,5,7,4,6,8,10,0,2,5,7,9,11,12,14,1,3,13,15,4,6,8,10,0,2,5,7,9,11,12,14,1,3,13,15,4,6,12,14,8,10,0,2,5,7,13,15,9,11,1,3,72,73,80,81,98,99,74,75,110,111,112,113,86,87,92,93,78,79,64,65,66,67,84,85,68,69,90,91,104,218,219,220,221,230,231,196,197,71,69,72,78,64,77,75,74,79,73,67,76,70,68,66,65,8,10,0,2,9,11,12,14,1,3,4,6,13,15,5,7,12,14,8,10,4,6,0,2,13,15,9,11,5,7,1,3,12,14,8,10,13,15,4,6,9,11,5,7,0,2,1,3,196,198,204,206,200,202,197,199,205,207,192,194,201,203,193,195,78,79,106,235,86,87,94,95,76,77,220,221,200,201,98,99,212,213,0,0,0,0,0,0,0,0,0,0,0,0,0,0,0,0,0,0,0,0,0,0,0,0,0,0,0,0,0,0,0,0,0,0,0,0,0,0,0,0,0,0,0,0,0,0,0,0,0,0,0,0,0,0,0,0,0},
  {64,65,66,67,68,69,70,71,72,73,74,75,76,77,78,79,0,1,2,3,72,78,70,71,0,2,12,14,1,3,13,15,4,6,5,7,8,10,9,11,12,14,8,10,13,15,9,11,0,2,4,6,1,3,5,7,4,6,8,10,0,2,5,7,9,11,12,14,1,3,13,15,8,10,0,2,9,11,1,3,12,14,13,15,132,134,5,7,95,70,71,76,77,106,107,96,97,64,65,78,79,90,91,80,81,102,69,110,111,82,83,74,75,96,97,118,119,104,105,94,223,244,245,234,235,224,225,216,217,198,199,71,69,72,78,64,77,75,74,79,73,67,76,70,68,66,65,8,10,0,2,9,11,12,14,1,3,4,6,13,15,5,7,12,14,8,10,4,6,0,2,13,15,9,11,5,7,1,3,4,6,12,14,8,10,5,7,13,15,9,11,0,2,1,3,68,70,69,71,200,202,204,206,201,203,205,207,192,194,193,195,64,65,78,79,90,91,106,107,94,95,112,113,228,229,64,193,216,217,246,247,0,0,0,0,0,0,0,0,0,0,0,0,0,0,0,0,0,0,0,0,0,0,0,0,0,0,0,0,0,0,0,0,0,0,0,0,0,0,0,0,0,0,0,0,0,0,0,0,0,0,0,0,0,0,0,0,0,0,0,0,0,0,0,0,0},
  {64,65,66,67,68,69,70,71,72,73,74,75,76,77,78,79,0,1,2,3,0,1,2,3,4,5,6,7,8,9,10,11,12,13,14,15,64,66,76,78,65,67,77,79,68,70,69,71,72,74,73,75,12,14,8,10,13,15,9,11,0,2,4,6,1,3,5,7,70,71,64,65,98,99,92,93,78,79,112,113,94,95,72,73,80,81,84,85,114,115,116,117,106,107,66,67,111,98,99,66,67,94,95,70,71,76,77,106,107,96,97,64,65,78,79,90,91,80,81,102,103,104,105,236,237,240,241,72,105,70,71,210,211,100,101,106,71,72,69,66,64,78,74,77,76,75,73,79,68,65,67,70,64,71,70,74,77,69,78,72,76,78,74,77,71,70,64,66,69,207,200,75,68,204,73,195,65,4,6,5,7,8,10,12,14,9,11,13,15,0,2,1,3,12,14,8,10,13,15,132,134,9,11,133,135,0,2,1,3,118,119,76,77,74,75,68,69,72,73,100,101,110,111,84,85,206,207,116,117,94,95,114,115,214,215,112,113,98,99,192,193,0,0,0,0,0,0,0,0,0,0,0,0,0,0,0,0,0,0,0,0,0,0,0,0,0,0,0,0,0,0,0,0,0,0,0,0,0,0,0,0,0,0,0,0,0,0,0,0,0,0,0,0,0,0,0},
  {64,65,66,67,68,69,70,71,72,73,74,75,76,77,78,79,0,1,2,3,64,65,66,67,68,69,70,71,72,73,74,75,76,77,78,79,64,66,76,78,65,67,77,79,68,70,69,71,72,74,73,75,4,6,0,2,5,7,1,3,12,14,8,10,13,15,9,11,4,6,12,14,8,10,0,2,5,7,13,15,9,11,1,3,4,6,12,14,8,10,0,2,5,7,13,15,137,139,129,131,92,93,72,73,80,81,106,107,116,117,108,109,64,65,94,95,86,87,114,115,102,103,98,99,100,101,90,91,70,71,207,246,247,194,195,238,239,242,243,232,233,218,4,6,8,10,5,7,0,2,12,14,9,11,1,3,13,15,64,71,78,74,77,70,73,69,66,72,76,79,68,65,67,75,12,14,8,10,4,6,0,2,13,15,9,11,5,7,1,3,12,14,8,10,13,15,4,6,9,11,5,7,0,2,1,3,204,206,200,202,205,207,196,198,201,203,197,199,192,194,193,195,71,66,67,112,113,98,99,86,87,110,111,114,115,88,89,118,119,68,69,230,231,0,0,0,0,0,0,0,0,0,0,0,0,0,0,0,0,0,0,0,0,0,0,0,0,0,0,0,0,0,0,0,0,0,0,0,0,0,0,0,0,0,0,0,0,0,0,0,0,0,0,0,0,0},
  {64,65,66,67,68,69,70,71,72,73,74,75,76,77,78,79,0,1,2,3,0,1,2,3,4,5,6,7,8,9,10,11,12,13,14,15,64,66,76,78,65,67,77,79,68,70,69,71,72,74,73,75,12,14,8,10,13,15,9,11,0,2,4,6,1,3,5,7,4,6,0,2,5,7,1,3,12,14,8,10,13,15,9,11,4,6,8,10,0,2,5,7,9,11,12,14,1,3,13,15,82,83,98,99,108,109,92,93,78,79,84,85,100,101,66,67,74,75,112,113,84,85,88,89,66,67,78,79,92,93,4,6,5,7,0,2,8,10,12,14,1,3,9,11,13,15,4,6,8,10,5,7,0,2,12,14,9,11,1,3,13,15,8,10,0,2,9,11,12,14,1,3,4,6,13,15,5,7,12,14,8,10,4,6,0,2,13,15,9,11,5,7,1,3,12,14,8,10,13,15,132,134,9,11,5,7,0,2,1,3,196,198,69,71,200,202,204,206,201,203,205,207,192,194,193,195,78,79,106,107,86,87,94,95,76,77,220,221,200,201,98,99,212,213,208,0,0,0,0,0,0,0,0,0,0,0,0,0,0,0,0,0,0,0,0,0,0,0,0,0,0,0,0,0,0,0,0,0,0,0,0,0,0,0,0,0,0,0,0,0,0,0,0,0,0,0},
  {0,1,2,3,4,5,6,7,8,9,10,11,12,13,14,15,0,1,2,3,0,1,2,3,4,5,6,7,8,9,10,11,12,13,14,15,64,66,76,78,65,67,77,79,68,70,69,71,72,74,73,75,4,6,0,2,5,7,1,3,12,14,8,10,13,15,9,11,4,6,8,10,0,2,5,7,9,11,12,14,1,3,13,15,0,2,8,10,4,6,12,14,1,3,137,139,5,7,13,15,80,81,102,103,104,105,108,109,112,113,72,73,116,117,82,83,100,101,74,75,86,87,92,93,118,119,68,69,4,6,5,7,0,2,8,10,12,14,1,3,9,11,13,15,4,6,8,10,5,7,0,2,12,14,9,11,1,3,13,15,8,10,0,2,9,11,12,14,1,3,4,6,13,15,5,7,200,207,194,204,192,195,202,196,199,206,198,197,205,201,193,203,12,14,8,10,13,15,4,6,9,11,5,7,0,2,1,3,132,134,12,14,136,138,133,135,13,15,137,139,128,130,129,131,106,107,70,71,66,67,112,113,98,99,86,87,110,111,242,243,88,89,118,119,196,197,0,0,0,0,0,0,0,0,0,0,0,0,0,0,0,0,0,0,0,0,0,0,0,0,0,0,0,0,0,0,0,0,0,0,0,0,0,0,0,0,0,0,0,0,0,0,0,0,0,0},
  {64,65,66,67,68,69,70,71,72,73,74,75,76,77,78,79,0,1,2,3,4,5,6,7,8,9,10,11,12,13,14,15,0,1,2,3,72,76,64,70,66,74,71,78,67,79,65,69,75,68,73,77,4,6,0,2,5,7,1,3,12,14,8,10,13,15,9,11,4,6,8,10,0,2,5,7,9,11,12,14,1,3,13,15,0,2,8,10,4,6,12,14,1,3,137,139,5,7,141,143,192,194,200,202,68,70,204,206,193,195,201,203,197,199,205,207,111,82,83,74,75,96,97,118,119,104,105,4,6,5,7,0,2,8,10,12,14,1,3,9,11,13,15,76,78,68,70,0,2,13,15,5,7,8,10,1,3,9,11,8,10,0,2,9,11,12,14,1,3,4,6,13,15,5,7,12,14,8,10,4,6,0,2,13,15,9,11,5,7,1,3,4,6,12,14,8,10,5,7,13,15,9,11,0,2,1,3,12,14,136,138,132,134,0,2,141,143,137,139,133,135,129,131,64,65,84,85,92,93,104,105,74,75,206,207,100,101,82,83,200,201,116,117,222,223,234,0,0,0,0,0,0,0,0,0,0,0,0,0,0,0,0,0,0,0,0,0,0,0,0,0,0,0,0,0,0,0,0,0,0,0,0,0,0,0,0,0,0,0,0,0,0,0,0,0,0},
  {64,65,66,67,68,69,70,71,72,73,74,75,76,77,78,79,0,1,2,3,4,5,6,7,8,9,10,11,12,13,14,15,69,76,67,65,64,66,76,78,65,67,77,79,68,70,69,71,72,74,73,75,12,14,8,10,13,15,9,11,0,2,4,6,1,3,5,7,4,6,8,10,0,2,5,7,9,11,12,14,1,3,13,15,90,91,70,71,72,73,66,67,64,65,84,85,92,93,80,81,86,87,94,95,76,77,88,89,106,107,78,79,96,0,2,4,6,8,10,1,3,5,7,12,14,9,11,13,15,4,6,5,7,0,2,8,10,12,14,1,3,9,11,13,15,4,6,8,10,5,7,0,2,12,14,9,11,1,3,13,15,132,134,128,130,133,135,129,131,136,138,140,142,137,139,141,143,8,10,9,11,4,6,0,2,12,14,5,7,1,3,13,15,4,6,12,14,8,10,5,7,13,15,9,11,0,2,1,3,132,134,140,142,136,138,133,135,141,143,128,130,137,139,129,131,104,105,78,79,118,119,114,115,88,89,112,113,100,101,64,65,84,85,94,95,96,97,210,211,196,197,0,0,0,0,0,0,0,0,0,0,0,0,0,0,0,0,0,0,0,0,0,0,0,0,0,0,0,0,0,0,0,0,0,0,0,0,0,0,0,0,0,0,0,0,0},
  {64,65,66,67,68,69,70,71,72,73,74,75,76,77,78,79,0,1,2,3,0,1,2,3,4,5,6,7,8,9,10,11,12,13,14,15,0,1,2,3,4,5,6,7,8,9,10,11,12,13,14,15,0,2,8,10,1,3,9,11,12,14,4,6,13,15,5,7,4,6,8,10,0,2,5,7,9,11,12,14,1,3,13,15,4,6,12,14,8,10,0,2,5,7,13,15,9,11,1,3,103,104,105,108,109,112,113,72,73,116,117,82,83,100,101,74,75,86,87,92,93,118,119,68,69,76,78,68,70,77,79,64,66,72,74,69,71,65,67,73,75,0,2,1,3,4,6,8,10,12,14,5,7,9,11,13,15,132,134,128,130,133,135,129,131,136,138,140,142,137,139,141,143,8,10,9,11,4,6,0,2,12,14,5,7,1,3,13,15,4,6,12,14,8,10,5,7,13,15,9,11,0,2,1,3,132,134,140,142,136,138,133,135,141,143,128,130,137,139,129,131,65,112,113,98,99,88,89,86,87,84,85,90,91,106,107,68,69,104,105,76,77,116,117,110,111,102,103,194,195,0,0,0,0,0,0,0,0,0,0,0,0,0,0,0,0,0,0,0,0,0,0,0,0,0,0,0,0,0,0,0,0,0,0,0,0,0,0,0,0,0,0,0,0,0,0},
  {64,65,66,67,68,69,70,71,72,73,74,75,76,77,78,79,0,1,2,3,4,5,6,7,8,9,10,11,12,13,14,15,64,67,72,77,69,73,78,76,76,69,70,72,74,66,71,75,67,77,68,73,79,206,64,65,4,6,8,10,0,2,5,7,9,11,12,14,1,3,13,15,4,6,12,14,8,10,0,2,5,7,13,15,9,11,1,3,0,2,8,10,4,6,12,14,1,3,9,11,5,7,13,15,0,2,4,6,8,10,1,3,5,7,12,14,9,11,13,15,4,6,5,7,12,14,8,10,0,2,13,15,9,11,1,3,0,2,1,3,4,6,8,10,12,14,5,7,9,11,13,15,8,10,12,14,0,2,9,11,13,15,1,3,4,6,5,7,8,10,0,2,9,11,12,14,1,3,4,6,13,15,5,7,12,14,8,10,4,6,0,2,13,15,9,11,5,7,1,3,4,6,12,14,8,10,5,7,13,15,9,11,0,2,1,3,116,117,64,65,118,119,80,81,94,95,76,77,112,113,110,111,82,83,70,71,68,112,113,228,229,64,65,88,217,246,247,0,0,0,0,0,0,0,0,0,0,0,0,0,0,0,0,0,0,0,0,0,0,0,0,0,0,0,0,0,0,0,0,0,0,0,0,0,0,0,0,0,0,0,0,0,0,0,0,0},
  {64,65,66,67,68,69,70,71,72,73,74,75,76,77,78,79,0,1,2,3,0,1,2,3,4,5,6,7,8,9,10,11,12,13,14,15,64,66,76,78,65,67,77,79,68,70,69,71,72,74,73,75,12,14,8,10,13,15,9,11,0,2,4,6,1,3,5,7,4,6,8,10,0,2,5,7,9,11,12,14,1,3,13,15,64,65,70,71,80,81,112,113,90,91,102,103,118,119,104,105,114,115,106,107,94,95,68,69,82,83,98,99,108,109,92,12,14,4,6,13,15,0,2,8,10,5,7,1,3,9,11,4,6,5,7,0,2,8,10,12,14,1,3,9,11,13,15,76,78,68,70,64,66,77,79,69,71,72,74,65,67,73,75,132,134,128,130,133,135,129,131,136,138,140,142,137,139,141,143,12,14,8,10,4,6,0,2,13,15,9,11,5,7,1,3,4,6,12,14,8,10,5,7,13,15,9,11,0,2,1,3,4,6,12,14,136,138,5,7,13,15,137,139,128,130,129,131,64,65,84,85,92,93,104,105,74,75,206,207,100,101,82,83,72,73,116,117,222,223,234,235,198,0,0,0,0,0,0,0,0,0,0,0,0,0,0,0,0,0,0,0,0,0,0,0,0,0,0,0,0,0,0,0,0,0,0,0,0,0,0,0,0,0,0,0,0},
  {0,1,2,3,4,5,6,7,8,9,10,11,12,13,14,15,64,65,66,67,68,69,70,71,72,73,74,75,76,77,78,79,0,1,2,3,4,5,6,7,8,9,10,11,12,13,14,15,0,2,8,10,1,3,9,11,12,14,4,6,13,15,5,7,4,6,8,10,0,2,5,7,9,11,12,14,1,3,13,15,103,98,99,72,73,92,93,64,65,100,101,96,97,114,115,76,77,70,71,86,87,90,91,74,75,66,67,68,69,0,2,4,6,8,10,1,3,5,7,12,14,9,11,13,15,12,14,4,6,13,15,0,2,8,10,5,7,1,3,9,11,0,2,1,3,4,6,8,10,12,14,5,7,9,11,13,15,132,134,128,130,133,135,129,131,136,138,140,142,137,139,141,143,79,67,75,65,8,10,0,2,9,11,12,14,1,3,4,6,13,15,5,7,4,6,12,14,8,10,5,7,13,15,9,11,0,2,1,3,8,10,9,11,4,6,0,2,140,142,133,135,1,3,141,143,64,65,80,81,92,93,108,109,106,107,70,71,66,67,90,91,88,89,82,83,224,225,232,233,230,231,0,0,0,0,0,0,0,0,0,0,0,0,0,0,0,0,0,0,0,0,0,0,0,0,0,0,0,0,0,0,0,0,0,0,0,0,0,0,0,0,0,0,0,0,0},
  {64,65,66,67,68,69,70,71,72,73,74,75,76,77,78,79,0,1,2,3,64,65,66,67,68,69,70,71,72,73,74,75,76,77,78,79,64,66,76,78,65,67,77,79,68,70,69,71,72,74,73,75,4,6,0,2,5,7,1,3,12,14,8,10,13,15,9,11,4,6,8,10,0,2,5,7,9,11,12,14,1,3,13,15,90,91,70,71,72,73,66,67,64,65,84,85,92,93,80,81,86,87,94,95,76,77,88,89,106,107,78,79,96,97,0,2,4,6,8,10,1,3,5,7,12,14,9,11,13,15,4,6,5,7,0,2,8,10,12,14,1,3,9,11,13,15,12,14,4,6,0,2,13,15,5,7,8,10,1,3,9,11,64,71,70,74,77,69,78,72,76,68,66,73,8,10,9,11,4,6,0,2,12,14,5,7,1,3,13,15,4,6,12,14,8,10,5,7,13,15,9,11,0,2,1,3,12,14,8,10,13,15,4,6,9,11,5,7,0,2,1,3,106,107,104,105,92,93,88,89,72,73,90,91,100,101,206,207,116,117,64,65,118,119,80,209,222,223,204,0,0,0,0,0,0,0,0,0,0,0,0,0,0,0,0,0,0,0,0,0,0,0,0,0,0,0,0,0,0,0,0,0,0,0,0,0,0,0,0,0,0,0,0,0,0,0},
  {0,1,2,3,4,5,6,7,8,9,10,11,12,13,14,15,0,1,2,3,64,65,66,67,68,69,70,71,72,73,74,75,76,77,78,79,64,66,76,78,65,67,77,79,68,70,69,71,72,74,73,75,64,66,72,74,65,67,73,75,76,78,68,70,77,79,69,71,4,6,8,10,0,2,5,7,9,11,12,14,1,3,13,15,68,70,64,66,69,71,65,67,76,78,72,74,77,79,73,75,136,138,128,130,137,139,129,131,140,142,141,143,132,134,133,135,64,66,68,70,72,74,65,67,69,71,76,78,73,75,77,79,4,6,5,7,0,2,8,10,12,14,1,3,9,11,13,15,4,6,8,10,5,7,0,2,12,14,9,11,1,3,13,15,64,71,78,74,77,70,73,69,66,72,76,79,68,65,67,75,12,14,8,10,4,6,0,2,13,15,9,11,5,7,1,3,12,14,8,10,13,15,132,134,9,11,133,135,0,2,1,3,204,206,200,202,205,207,196,198,201,203,197,199,192,194,193,195,107,70,71,66,67,112,113,98,99,86,87,110,111,242,243,88,89,118,119,196,197,0,0,0,0,0,0,0,0,0,0,0,0,0,0,0,0,0,0,0,0,0,0,0,0,0,0,0,0,0,0,0,0,0,0,0,0,0,0,0,0,0,0,0,0,0,0,0},
  {64,65,66,67,68,69,70,71,72,73,74,75,76,77,78,79,0,1,2,3,72,78,70,71,0,1,2,3,4,5,6,7,8,9,10,11,12,13,14,15,0,2,8,10,1,3,9,11,12,14,4,6,13,15,5,7,12,14,8,10,13,15,9,11,0,2,4,6,1,3,5,7,4,6,12,14,8,10,0,2,5,7,13,15,9,11,1,3,136,138,128,130,137,139,129,131,140,142,141,143,132,134,133,135,75,88,89,76,77,96,97,86,87,72,73,116,117,110,111,4,6,5,7,12,14,8,10,0,2,13,15,9,11,1,3,12,14,4,6,0,2,13,15,5,7,8,10,1,3,9,11,132,134,128,130,133,135,129,131,136,138,140,142,137,139,141,143,8,10,9,11,4,6,0,2,12,14,5,7,1,3,13,15,4,6,5,7,8,10,12,14,9,11,13,15,0,2,1,3,12,14,8,10,13,15,132,134,9,11,133,135,128,130,129,131,116,117,96,97,74,75,64,65,112,113,82,83,106,107,84,80,81,66,67,90,91,96,97,242,243,74,75,198,199,0,0,0,0,0,0,0,0,0,0,0,0,0,0,0,0,0,0,0,0,0,0,0,0,0,0,0,0,0,0,0,0,0,0,0,0,0,0,0,0,0,0,0,0,0,0,0,0,0,0,0,0},
  {0,1,2,3,4,5,6,7,8,9,10,11,12,13,14,15,0,1,2,3,0,1,2,3,4,5,6,7,8,9,10,11,12,13,14,15,0,1,2,3,76,69,70,72,74,66,71,75,67,77,68,73,79,78,64,65,12,14,8,10,13,15,9,11,0,2,4,6,1,3,5,7,4,6,8,10,0,2,5,7,9,11,12,14,1,3,13,15,128,130,136,138,4,6,140,142,129,131,137,139,133,135,141,143,0,2,4,6,8,10,1,3,5,7,12,14,9,11,13,15,95,108,109,76,77,88,89,114,115,96,97,102,103,244,245,246,247,219,220,221,230,231,196,197,4,6,8,10,5,7,0,2,12,14,9,11,1,3,13,15,64,71,70,74,77,69,78,72,76,68,66,73,79,67,75,65,12,14,8,10,4,6,0,2,13,15,9,11,5,7,1,3,12,14,8,10,13,15,4,6,9,11,5,7,0,2,1,3,76,78,72,74,77,79,68,70,73,75,69,71,64,66,65,67,82,83,70,71,100,101,102,103,84,85,116,117,72,73,86,87,110,111,232,233,204,205,0,0,0,0,0,0,0,0,0,0,0,0,0,0,0,0,0,0,0,0,0,0,0,0,0,0,0,0,0,0,0,0,0,0,0,0,0,0,0,0,0,0,0,0,0,0,0,0,0,0},
  {64,65,66,67,68,69,70,71,72,73,74,75,76,77,78,79,0,1,2,3,4,5,6,7,8,9,10,11,12,13,14,15,70,64,76,66,74,72,79,71,78,67,69,65,75,77,68,73,0,2,8,10,1,3,9,11,12,14,4,6,13,15,5,7,4,6,12,14,8,10,0,2,5,7,13,15,9,11,1,3,4,6,12,14,8,10,0,2,5,7,13,15,9,11,1,3,136,138,128,130,137,139,129,131,140,142,141,143,132,134,133,135,12,14,4,6,13,15,0,2,8,10,5,7,1,3,9,11,4,6,5,7,0,2,8,10,12,14,1,3,9,11,13,15,4,6,8,10,5,7,0,2,12,14,9,11,1,3,13,15,132,134,128,130,133,135,129,131,136,138,140,142,137,139,141,143,8,10,9,11,4,6,0,2,12,14,5,7,1,3,13,15,4,6,12,14,8,10,5,7,13,15,9,11,0,2,1,3,8,10,0,2,9,11,140,142,1,3,132,134,141,143,133,135,92,93,108,109,98,99,80,81,100,101,70,71,110,111,82,83,68,69,104,105,108,109,102,103,244,245,0,0,0,0,0,0,0,0,0,0,0,0,0,0,0,0,0,0,0,0,0,0,0,0,0,0,0,0,0,0,0,0,0,0,0,0,0,0,0,0,0,0,0,0,0,0},
  {0,1,2,3,4,5,6,7,8,9,10,11,12,13,14,15,0,1,2,3,0,1,2,3,4,5,6,7,8,9,10,11,12,13,14,15,64,66,76,78,65,67,77,79,68,70,69,71,72,74,73,75,12,14,8,10,13,15,9,11,0,2,4,6,1,3,5,7,4,6,0,2,5,7,1,3,12,14,8,10,13,15,9,11,90,91,70,71,72,73,66,67,64,65,84,85,92,93,80,81,86,87,94,95,76,77,88,89,106,107,78,79,96,97,108,109,72,73,80,81,98,99,74,75,110,111,240,241,86,87,92,93,206,207,192,193,0,2,1,3,4,6,8,10,12,14,5,7,9,11,13,15,8,10,12,14,0,2,9,11,13,15,1,3,4,6,5,7,8,10,9,11,4,6,0,2,12,14,5,7,1,3,13,15,4,6,5,7,8,10,12,14,9,11,13,15,0,2,1,3,132,134,5,7,136,138,140,142,9,11,141,143,128,130,129,131,104,105,72,73,86,87,102,103,90,91,118,119,68,69,206,207,114,115,66,67,110,111,222,223,216,217,204,205,0,0,0,0,0,0,0,0,0,0,0,0,0,0,0,0,0,0,0,0,0,0,0,0,0,0,0,0,0,0,0,0,0,0,0,0,0,0,0,0,0,0,0,0,0,0,0,0,0,0,0,0},
  {64,65,66,67,68,69,70,71,72,73,74,75,76,77,78,79,0,1,2,3,0,1,2,3,4,5,6,7,8,9,10,11,12,13,14,15,64,66,76,78,65,67,77,79,68,70,69,71,72,74,73,75,12,14,8,10,13,15,9,11,0,2,4,6,1,3,5,7,4,6,8,10,0,2,5,7,9,11,12,14,1,3,13,15,0,2,8,10,4,6,12,14,1,3,9,11,5,7,13,15,99,102,103,68,69,110,111,104,105,73,116,117,82,83,100,101,74,75,86,87,92,93,118,119,68,69,4,6,5,7,12,14,8,10,0,2,13,15,9,11,1,3,79,68,65,67,70,64,71,78,77,69,72,75,70,74,79,76,73,68,67,66,65,8,10,0,2,9,11,12,14,1,3,4,6,13,15,5,7,12,14,8,10,4,6,0,2,13,15,9,11,5,7,1,3,4,6,12,14,8,10,5,7,13,15,0,2,9,11,1,3,80,81,96,97,92,93,108,109,70,71,82,83,100,101,78,206,207,106,107,86,87,94,95,76,77,220,221,200,201,226,227,0,0,0,0,0,0,0,0,0,0,0,0,0,0,0,0,0,0,0,0,0,0,0,0,0,0,0,0,0,0,0,0,0,0,0,0,0,0,0,0,0,0,0,0,0,0,0,0,0,0,0,0,0,0},
};

struct alignas(64) Params {
  CUtensorMap a[6];
  CUtensorMap w[4];
  CUtensorMap ow;
  CUtensorMap xr;
  const bf16 *x0, *wqkv;
  bf16* out;
  uint32_t swap;
  uint32_t jobs[NPAIR][JMAX];
  uint8_t kseq[NPAIR][KMAX];
};

template <class T> __device__ __forceinline__ T* at(T* base, uint32_t bytes) {
  T* r;
  asm("{\n.reg .u32 lo, hi;\nmov.b64 {lo, hi}, %1;\nadd.cc.u32 lo, lo, %2;\naddc.u32 hi, hi, 0;\nmov.b64 %0, {lo, hi};\n}" : "=l"(r) : "l"(base), "r"(bytes));
  return r;
}
#define SCR(sm, member, bytes) reinterpret_cast<decltype(&scratch_base()->member[0])>(at((sm).scratch, offsetof(Scratch, member) + (bytes)))
#define counter(line, word) SCR(sm, cnt, (line) * 128 + (word) * 4)
#define TRS(st, slot) do {} while (0)
#define TRX(cond, job, bit, slot, reg) do {} while (0)
#define TR(job, slot) do {} while (0)
#define TRI(cond, job, slot) do {} while (0)
#define TRK(cond, job, slot) do {} while (0)
#define TRC(job, slot) do {} while (0)

__device__ __forceinline__ uint32_t smem_u32(const void* p) { return (uint32_t)__cvta_generic_to_shared(p); }
__device__ __forceinline__ void mbar_init(uint32_t bar, uint32_t cnt) { asm volatile("mbarrier.init.shared::cta.b64 [%0], %1;" ::"r"(bar), "r"(cnt) : "memory"); }
__device__ __forceinline__ void mbar_expect_tx(uint32_t bar, uint32_t bytes) { asm volatile("mbarrier.arrive.expect_tx.shared::cta.b64 _, [%0], %1;" ::"r"(bar), "r"(bytes) : "memory"); }
__device__ __forceinline__ void mbar_arrive_n(uint32_t bar, uint32_t cnt) { asm volatile("mbarrier.arrive.shared::cta.b64 _, [%0], %1;" ::"r"(bar), "r"(cnt) : "memory"); }
__device__ __forceinline__ void mbar_arrive_cl_if(uint32_t cond, uint32_t bar) {
  asm volatile("{\n.reg .pred p;\nsetp.ne.u32 p, %1, 0;\n@p mbarrier.arrive.shared::cluster.b64 _, [%0];\n}" ::"r"(bar), "r"(cond) : "memory");
}
__device__ __forceinline__ void mbar_arrive_warp(uint32_t bar) {
  asm volatile("{\n.reg .pred p;\nbar.warp.sync -1;\nelect.sync _|p, -1;\n@p mbarrier.arrive.shared::cta.b64 _, [%0];\n}" ::"r"(bar) : "memory");
}
__device__ __forceinline__ uint32_t mapa(uint32_t addr, uint32_t cta) { uint32_t r; asm("mapa.shared::cluster.u32 %0, %1, %2;" : "=r"(r) : "r"(addr), "r"(cta)); return r; }
__device__ __forceinline__ bool mbar_test(uint32_t bar, uint32_t parity) {
  uint32_t ok;
  asm volatile("{\n.reg .pred p;\nmbarrier.test_wait.parity.shared::cta.b64 p, [%1], %2;\nselp.u32 %0, 1, 0, p;\n}\n" : "=r"(ok) : "r"(bar), "r"(parity) : "memory");
  return ok;
}
__device__ __forceinline__ void mbar_wait(uint32_t bar, uint32_t parity) {
  asm volatile(
      "{\n.reg .pred p;\n.reg .u32 n;\nmov.u32 n, 0;\n"
      "WAIT:\nmbarrier.try_wait.parity.shared::cta.b64 p, [%0], %1;\n@p bra DONE;\n"
      "add.u32 n, n, 1;\nsetp.lt.u32 p, n, %2;\n@p bra WAIT;\ntrap;\nDONE:\n}\n" ::"r"(bar), "r"(parity), "n"(SPIN_LIMIT) : "memory");
}
template <int ID, int N> __device__ __forceinline__ void bar_sync() { asm volatile("bar.sync %0, %1;" ::"n"(ID), "n"(N) : "memory"); }
template <int ID, int N> __device__ __forceinline__ void bar_arrive() { asm volatile("bar.arrive %0, %1;" ::"n"(ID), "n"(N) : "memory"); }
__device__ __forceinline__ uint32_t ld_relaxed(const uint32_t* p) { uint32_t v; asm volatile("ld.relaxed.gpu.global.u32 %0, [%1];" : "=r"(v) : "l"(p) : "memory"); return v; }
__device__ __forceinline__ void red_relaxed(uint32_t* p, uint32_t v) { asm volatile("red.relaxed.gpu.global.add.u32 [%0], %1;" ::"l"(p), "r"(v) : "memory"); }
__device__ __forceinline__ void red_release(uint32_t* p, uint32_t v) {
  asm volatile("fence.release.gpu;\nred.relaxed.gpu.global.add.u32 [%0], %1;" ::"l"(p), "r"(v) : "memory");
}
__device__ __forceinline__ bool elect() {
  uint32_t p;
  asm volatile("{\n.reg .pred P;\nelect.sync _|P, 0xffffffff;\nselp.u32 %0, 1, 0, P;\n}\n" : "=r"(p));
  return p;
}
__device__ __forceinline__ void fence_acquire() { asm volatile("fence.acquire.gpu;" ::: "memory"); }
__device__ __forceinline__ void wait_count(const uint32_t* p, uint32_t target) {
  for (uint32_t n = 0; !__all_sync(~0u, (int)(ld_relaxed(p) - target) >= 0); n++) {
    __nanosleep(200);
    if (n > SPIN_LIMIT) __trap();
  }
  fence_acquire();
}
__device__ __forceinline__ void fence_proxy_async() { asm volatile("fence.proxy.async.global;" ::: "memory"); }
__device__ __forceinline__ void fence_proxy_async_smem() { asm volatile("fence.proxy.async.shared::cta;" ::: "memory"); }
__device__ __forceinline__ void tma4d_mc(uint32_t dst, const CUtensorMap* tm, int c1, int c2, uint32_t bar, uint64_t pol) {
  asm volatile("cp.async.bulk.tensor.4d.shared::cluster.global.mbarrier::complete_tx::bytes.multicast::cluster.L2::cache_hint [%0], [%1, {%3, %4, %5, %3}], [%2], %6, %7;"
               ::"r"(dst), "l"(tm), "r"(bar), "r"(0), "r"(c1), "r"(c2), "h"((uint16_t)3), "l"(pol) : "memory");
}
__device__ __forceinline__ void tma3d(uint32_t dst, const CUtensorMap* tm, int c0, int c1, int c2, uint32_t bar, uint64_t pol) {
  asm volatile("cp.async.bulk.tensor.3d.shared::cluster.global.mbarrier::complete_tx::bytes.L2::cache_hint [%0], [%1, {%3, %4, %5}], [%2], %6;"
               ::"r"(dst), "l"(tm), "r"(bar), "r"(c0), "r"(c1), "r"(c2), "l"(pol) : "memory");
}
__device__ __forceinline__ void tma3d_reduce_add(const CUtensorMap* tm, int c0, int c1, int c2, uint32_t src) {
  asm volatile("cp.reduce.async.bulk.tensor.3d.global.shared::cta.add.tile.bulk_group [%0, {%2, %3, %4}], [%1];"
               ::"l"(tm), "r"(src), "r"(c0), "r"(c1), "r"(c2) : "memory");
}
__device__ __forceinline__ void tma3d_store(const CUtensorMap* tm, int c0, int c1, int c2, uint32_t src) {
  asm volatile("cp.async.bulk.tensor.3d.global.shared::cta.tile.bulk_group [%0, {%2, %3, %4}], [%1];"
               ::"l"(tm), "r"(src), "r"(c0), "r"(c1), "r"(c2) : "memory");
}
__device__ __forceinline__ void bulk_commit() { asm volatile("cp.async.bulk.commit_group;" ::: "memory"); }
template <int N> __device__ __forceinline__ void bulk_wait_read() { asm volatile("cp.async.bulk.wait_group.read %0;" ::"n"(N) : "memory"); }
__device__ __forceinline__ void bulk_wait() { asm volatile("cp.async.bulk.wait_group 0;" ::: "memory"); }
__device__ __forceinline__ uint2 lds64(uint32_t a) { uint2 v; asm volatile("ld.shared.v2.u32 {%0,%1}, [%2];" : "=r"(v.x), "=r"(v.y) : "r"(a) : "memory"); return v; }
__device__ __forceinline__ float lds32f(uint32_t a) { float v; asm volatile("ld.shared.f32 %0, [%1];" : "=f"(v) : "r"(a) : "memory"); return v; }
__device__ __forceinline__ uint4 lds128(uint32_t a) { uint4 v; asm volatile("ld.shared.v4.u32 {%0,%1,%2,%3}, [%4];" : "=r"(v.x), "=r"(v.y), "=r"(v.z), "=r"(v.w) : "r"(a) : "memory"); return v; }
__device__ __forceinline__ uint2 lds64v(uint32_t a) { uint2 v; asm volatile("ld.volatile.shared.v2.u32 {%0,%1}, [%2];" : "=r"(v.x), "=r"(v.y) : "r"(a) : "memory"); return v; }
__device__ __forceinline__ uint4 lds128v(uint32_t a) { uint4 v; asm volatile("ld.volatile.shared.v4.u32 {%0,%1,%2,%3}, [%4];" : "=r"(v.x), "=r"(v.y), "=r"(v.z), "=r"(v.w) : "r"(a) : "memory"); return v; }
__device__ __forceinline__ void sts32(uint32_t a, uint32_t v) { asm volatile("st.shared.u32 [%0], %1;" ::"r"(a), "r"(v) : "memory"); }
__device__ __forceinline__ void sts64(uint32_t a, uint2 v) { asm volatile("st.shared.v2.u32 [%0], {%1,%2};" ::"r"(a), "r"(v.x), "r"(v.y) : "memory"); }
__device__ __forceinline__ void stg128(void* p, uint4 v) { asm volatile("st.global.L1::no_allocate.v4.u32 [%0], {%1,%2,%3,%4};" ::"l"(p), "r"(v.x), "r"(v.y), "r"(v.z), "r"(v.w) : "memory"); }
__device__ __forceinline__ uint4 ldg128(const void* p) { uint4 v; asm volatile("ld.relaxed.gpu.global.v4.u32 {%0,%1,%2,%3}, [%4];" : "=r"(v.x), "=r"(v.y), "=r"(v.z), "=r"(v.w) : "l"(p) : "memory"); return v; }
__device__ __forceinline__ void prefetch_tm(const CUtensorMap* tm) { asm volatile("prefetch.tensormap [%0];" ::"l"(tm) : "memory"); }
template <int N> __device__ __forceinline__ void wg_wait() { asm volatile("wgmma.wait_group.sync.aligned %0;" ::"n"(N) : "memory"); }
__device__ __forceinline__ void cluster_arrive() { asm volatile("barrier.cluster.arrive.relaxed.aligned;" ::: "memory"); }
__device__ __forceinline__ void cluster_wait() { asm volatile("barrier.cluster.wait.acquire.aligned;" ::: "memory"); }
__device__ __forceinline__ uint32_t pack_bf16(float lo, float hi) { uint32_t r; asm("cvt.rn.bf16x2.f32 %0, %1, %2;" : "=r"(r) : "f"(hi), "f"(lo)); return r; }
__device__ __forceinline__ float bf_lo(uint32_t v) { return __uint_as_float(v << 16); }
__device__ __forceinline__ float bf_hi(uint32_t v) { return __uint_as_float(v & 0xffff0000u); }
__device__ __forceinline__ uint32_t dup_hi(uint32_t v) { return __byte_perm(v, 0, 0x3232); }
__device__ __forceinline__ float bf_round(float x) { return __bfloat162float(__float2bfloat16_rn(x)); }
__device__ __forceinline__ uint32_t bf2_add(uint32_t a, uint32_t b) { uint32_t r; asm("add.rn.bf16x2 %0, %1, %2;" : "=r"(r) : "r"(a), "r"(b)); return r; }
__device__ __forceinline__ uint32_t bf2_mul(uint32_t a, uint32_t b) { uint32_t r; asm("mul.rn.bf16x2 %0, %1, %2;" : "=r"(r) : "r"(a), "r"(b)); return r; }
__device__ __forceinline__ uint32_t bf2_fma(uint32_t a, uint32_t b, uint32_t c) { uint32_t r; asm("fma.rn.bf16x2 %0, %1, %2, %3;" : "=r"(r) : "r"(a), "r"(b), "r"(c)); return r; }
__device__ __forceinline__ uint4 add8(uint4 a, uint4 b) { return make_uint4(bf2_add(a.x, b.x), bf2_add(a.y, b.y), bf2_add(a.z, b.z), bf2_add(a.w, b.w)); }
__device__ __forceinline__ uint4 fma8(uint32_t a, uint4 b, uint4 c) { return make_uint4(bf2_fma(a, b.x, c.x), bf2_fma(a, b.y, c.y), bf2_fma(a, b.z, c.z), bf2_fma(a, b.w, c.w)); }
__device__ __forceinline__ void stsm4(uint32_t a, uint32_t r0, uint32_t r1, uint32_t r2, uint32_t r3) {
  asm volatile("stmatrix.sync.aligned.m8n8.x4.shared.b16 [%0], {%1,%2,%3,%4};" ::"r"(a), "r"(r0), "r"(r1), "r"(r2), "r"(r3) : "memory");
}
__device__ __forceinline__ void ldsm4(uint32_t a, uint32_t (&r)[4]) {
  asm volatile("ldmatrix.sync.aligned.m8n8.x4.shared.b16 {%0,%1,%2,%3}, [%4];" : "=r"(r[0]), "=r"(r[1]), "=r"(r[2]), "=r"(r[3]) : "r"(a) : "memory");
}
__device__ __forceinline__ void ldsm4t(uint32_t a, uint32_t (&r)[4]) {
  asm volatile("ldmatrix.sync.aligned.m8n8.x4.trans.shared.b16 {%0,%1,%2,%3}, [%4];" : "=r"(r[0]), "=r"(r[1]), "=r"(r[2]), "=r"(r[3]) : "r"(a) : "memory");
}
__device__ __forceinline__ void mma16816(float (&c)[4], uint32_t a0, uint32_t a1, uint32_t a2, uint32_t a3, uint32_t b0, uint32_t b1) {
  asm volatile("mma.sync.aligned.m16n8k16.row.col.f32.bf16.bf16.f32 {%0,%1,%2,%3}, {%4,%5,%6,%7}, {%8,%9}, {%0,%1,%2,%3};"
               : "+f"(c[0]), "+f"(c[1]), "+f"(c[2]), "+f"(c[3]) : "r"(a0), "r"(a1), "r"(a2), "r"(a3), "r"(b0), "r"(b1));
}
__device__ __forceinline__ void mma1688(float (&c)[4], uint32_t a0, uint32_t a1, uint32_t b0) {
  asm volatile("mma.sync.aligned.m16n8k8.row.col.f32.bf16.bf16.f32 {%0,%1,%2,%3}, {%4,%5}, {%6}, {%0,%1,%2,%3};"
               : "+f"(c[0]), "+f"(c[1]), "+f"(c[2]), "+f"(c[3]) : "r"(a0), "r"(a1), "r"(b0));
}
__device__ __forceinline__ float ex2(float x) { float y; asm("ex2.approx.ftz.f32 %0, %1;" : "=f"(y) : "f"(x)); return y; }
__device__ __forceinline__ float sqrt_fast(float x) { float y; asm("sqrt.approx.f32 %0, %1;" : "=f"(y) : "f"(x)); return y; }
__device__ __forceinline__ float tanh_fast(float x) { float y; asm("tanh.approx.f32 %0, %1;" : "=f"(y) : "f"(x)); return y; }
__device__ __forceinline__ float rcp(float x) { float y; asm("rcp.approx.ftz.f32 %0, %1;" : "=f"(y) : "f"(x)); return y; }
__device__ __forceinline__ uint32_t opaque_zero() { uint32_t z; asm volatile("mov.u32 %0, %%ctaid.y;" : "=r"(z)); return z; }
__device__ __forceinline__ int fresh_tid() { int t; asm volatile("mov.u32 %0, %%tid.x;" : "=r"(t)); return t; }

__device__ __forceinline__ void first_kstep(float (&d)[128], uint32_t a, uint32_t b) {
  asm volatile("{\n.reg .u32 t;\n.reg .u64 da, db;\nwgmma.fence.sync.aligned;\n"
    "add.u32 t, %128, 0;\nmov.b64 da, {t, %130};\nadd.u32 t, %129, 0;\nmov.b64 db, {t, %130};\n"
    "wgmma.mma_async.sync.aligned.m64n256k16.f32.bf16.bf16 {%0, %1, %2, %3, %4, %5, %6, %7, %8, %9, %10, %11, %12, %13, %14, %15, %16, %17, %18, %19, %20, %21, %22, %23, %24, %25, %26, %27, %28, %29, %30, %31, %32, %33, %34, %35, %36, %37, %38, %39, %40, %41, %42, %43, %44, %45, %46, %47, %48, %49, %50, %51, %52, %53, %54, %55, %56, %57, %58, %59, %60, %61, %62, %63, %64, %65, %66, %67, %68, %69, %70, %71, %72, %73, %74, %75, %76, %77, %78, %79, %80, %81, %82, %83, %84, %85, %86, %87, %88, %89, %90, %91, %92, %93, %94, %95, %96, %97, %98, %99, %100, %101, %102, %103, %104, %105, %106, %107, %108, %109, %110, %111, %112, %113, %114, %115, %116, %117, %118, %119, %120, %121, %122, %123, %124, %125, %126, %127}, da, db, 0, 1, 1, 0, 1;\nwgmma.commit_group.sync.aligned;\n"
    "add.u32 t, %128, 2;\nmov.b64 da, {t, %130};\nadd.u32 t, %129, 128;\nmov.b64 db, {t, %130};\n"
    "wgmma.mma_async.sync.aligned.m64n256k16.f32.bf16.bf16 {%0, %1, %2, %3, %4, %5, %6, %7, %8, %9, %10, %11, %12, %13, %14, %15, %16, %17, %18, %19, %20, %21, %22, %23, %24, %25, %26, %27, %28, %29, %30, %31, %32, %33, %34, %35, %36, %37, %38, %39, %40, %41, %42, %43, %44, %45, %46, %47, %48, %49, %50, %51, %52, %53, %54, %55, %56, %57, %58, %59, %60, %61, %62, %63, %64, %65, %66, %67, %68, %69, %70, %71, %72, %73, %74, %75, %76, %77, %78, %79, %80, %81, %82, %83, %84, %85, %86, %87, %88, %89, %90, %91, %92, %93, %94, %95, %96, %97, %98, %99, %100, %101, %102, %103, %104, %105, %106, %107, %108, %109, %110, %111, %112, %113, %114, %115, %116, %117, %118, %119, %120, %121, %122, %123, %124, %125, %126, %127}, da, db, 1, 1, 1, 0, 1;\n"
    "add.u32 t, %128, 4;\nmov.b64 da, {t, %130};\nadd.u32 t, %129, 1024;\nmov.b64 db, {t, %130};\n"
    "wgmma.mma_async.sync.aligned.m64n256k16.f32.bf16.bf16 {%0, %1, %2, %3, %4, %5, %6, %7, %8, %9, %10, %11, %12, %13, %14, %15, %16, %17, %18, %19, %20, %21, %22, %23, %24, %25, %26, %27, %28, %29, %30, %31, %32, %33, %34, %35, %36, %37, %38, %39, %40, %41, %42, %43, %44, %45, %46, %47, %48, %49, %50, %51, %52, %53, %54, %55, %56, %57, %58, %59, %60, %61, %62, %63, %64, %65, %66, %67, %68, %69, %70, %71, %72, %73, %74, %75, %76, %77, %78, %79, %80, %81, %82, %83, %84, %85, %86, %87, %88, %89, %90, %91, %92, %93, %94, %95, %96, %97, %98, %99, %100, %101, %102, %103, %104, %105, %106, %107, %108, %109, %110, %111, %112, %113, %114, %115, %116, %117, %118, %119, %120, %121, %122, %123, %124, %125, %126, %127}, da, db, 1, 1, 1, 0, 1;\n"
    "add.u32 t, %128, 6;\nmov.b64 da, {t, %130};\nadd.u32 t, %129, 1152;\nmov.b64 db, {t, %130};\n"
    "wgmma.mma_async.sync.aligned.m64n256k16.f32.bf16.bf16 {%0, %1, %2, %3, %4, %5, %6, %7, %8, %9, %10, %11, %12, %13, %14, %15, %16, %17, %18, %19, %20, %21, %22, %23, %24, %25, %26, %27, %28, %29, %30, %31, %32, %33, %34, %35, %36, %37, %38, %39, %40, %41, %42, %43, %44, %45, %46, %47, %48, %49, %50, %51, %52, %53, %54, %55, %56, %57, %58, %59, %60, %61, %62, %63, %64, %65, %66, %67, %68, %69, %70, %71, %72, %73, %74, %75, %76, %77, %78, %79, %80, %81, %82, %83, %84, %85, %86, %87, %88, %89, %90, %91, %92, %93, %94, %95, %96, %97, %98, %99, %100, %101, %102, %103, %104, %105, %106, %107, %108, %109, %110, %111, %112, %113, %114, %115, %116, %117, %118, %119, %120, %121, %122, %123, %124, %125, %126, %127}, da, db, 1, 1, 1, 0, 1;\nwgmma.commit_group.sync.aligned;\n"
    "}\n"
    : "=f"(d[0]), "=f"(d[1]), "=f"(d[2]), "=f"(d[3]), "=f"(d[4]), "=f"(d[5]), "=f"(d[6]), "=f"(d[7]), "=f"(d[8]), "=f"(d[9]), "=f"(d[10]), "=f"(d[11]), "=f"(d[12]), "=f"(d[13]), "=f"(d[14]), "=f"(d[15]), "=f"(d[16]), "=f"(d[17]), "=f"(d[18]), "=f"(d[19]), "=f"(d[20]), "=f"(d[21]), "=f"(d[22]), "=f"(d[23]), "=f"(d[24]), "=f"(d[25]), "=f"(d[26]), "=f"(d[27]), "=f"(d[28]), "=f"(d[29]), "=f"(d[30]), "=f"(d[31]), "=f"(d[32]), "=f"(d[33]), "=f"(d[34]), "=f"(d[35]), "=f"(d[36]), "=f"(d[37]), "=f"(d[38]), "=f"(d[39]), "=f"(d[40]), "=f"(d[41]), "=f"(d[42]), "=f"(d[43]), "=f"(d[44]), "=f"(d[45]), "=f"(d[46]), "=f"(d[47]), "=f"(d[48]), "=f"(d[49]), "=f"(d[50]), "=f"(d[51]), "=f"(d[52]), "=f"(d[53]), "=f"(d[54]), "=f"(d[55]), "=f"(d[56]), "=f"(d[57]), "=f"(d[58]), "=f"(d[59]), "=f"(d[60]), "=f"(d[61]), "=f"(d[62]), "=f"(d[63]), "=f"(d[64]), "=f"(d[65]), "=f"(d[66]), "=f"(d[67]), "=f"(d[68]), "=f"(d[69]), "=f"(d[70]), "=f"(d[71]), "=f"(d[72]), "=f"(d[73]), "=f"(d[74]), "=f"(d[75]), "=f"(d[76]), "=f"(d[77]), "=f"(d[78]), "=f"(d[79]), "=f"(d[80]), "=f"(d[81]), "=f"(d[82]), "=f"(d[83]), "=f"(d[84]), "=f"(d[85]), "=f"(d[86]), "=f"(d[87]), "=f"(d[88]), "=f"(d[89]), "=f"(d[90]), "=f"(d[91]), "=f"(d[92]), "=f"(d[93]), "=f"(d[94]), "=f"(d[95]), "=f"(d[96]), "=f"(d[97]), "=f"(d[98]), "=f"(d[99]), "=f"(d[100]), "=f"(d[101]), "=f"(d[102]), "=f"(d[103]), "=f"(d[104]), "=f"(d[105]), "=f"(d[106]), "=f"(d[107]), "=f"(d[108]), "=f"(d[109]), "=f"(d[110]), "=f"(d[111]), "=f"(d[112]), "=f"(d[113]), "=f"(d[114]), "=f"(d[115]), "=f"(d[116]), "=f"(d[117]), "=f"(d[118]), "=f"(d[119]), "=f"(d[120]), "=f"(d[121]), "=f"(d[122]), "=f"(d[123]), "=f"(d[124]), "=f"(d[125]), "=f"(d[126]), "=f"(d[127])
    : "r"(a), "r"(b), "n"(0x40000040) : "memory");
}
__device__ __forceinline__ void kstep(float (&d)[128], uint32_t a, uint32_t b) {
  asm volatile("{\n.reg .u32 t;\n.reg .u64 da, db;\nwgmma.fence.sync.aligned;\n"
    "add.u32 t, %128, 0;\nmov.b64 da, {t, %130};\nadd.u32 t, %129, 0;\nmov.b64 db, {t, %130};\n"
    "wgmma.mma_async.sync.aligned.m64n256k16.f32.bf16.bf16 {%0, %1, %2, %3, %4, %5, %6, %7, %8, %9, %10, %11, %12, %13, %14, %15, %16, %17, %18, %19, %20, %21, %22, %23, %24, %25, %26, %27, %28, %29, %30, %31, %32, %33, %34, %35, %36, %37, %38, %39, %40, %41, %42, %43, %44, %45, %46, %47, %48, %49, %50, %51, %52, %53, %54, %55, %56, %57, %58, %59, %60, %61, %62, %63, %64, %65, %66, %67, %68, %69, %70, %71, %72, %73, %74, %75, %76, %77, %78, %79, %80, %81, %82, %83, %84, %85, %86, %87, %88, %89, %90, %91, %92, %93, %94, %95, %96, %97, %98, %99, %100, %101, %102, %103, %104, %105, %106, %107, %108, %109, %110, %111, %112, %113, %114, %115, %116, %117, %118, %119, %120, %121, %122, %123, %124, %125, %126, %127}, da, db, 1, 1, 1, 0, 1;\nwgmma.commit_group.sync.aligned;\n"
    "add.u32 t, %128, 2;\nmov.b64 da, {t, %130};\nadd.u32 t, %129, 128;\nmov.b64 db, {t, %130};\n"
    "wgmma.mma_async.sync.aligned.m64n256k16.f32.bf16.bf16 {%0, %1, %2, %3, %4, %5, %6, %7, %8, %9, %10, %11, %12, %13, %14, %15, %16, %17, %18, %19, %20, %21, %22, %23, %24, %25, %26, %27, %28, %29, %30, %31, %32, %33, %34, %35, %36, %37, %38, %39, %40, %41, %42, %43, %44, %45, %46, %47, %48, %49, %50, %51, %52, %53, %54, %55, %56, %57, %58, %59, %60, %61, %62, %63, %64, %65, %66, %67, %68, %69, %70, %71, %72, %73, %74, %75, %76, %77, %78, %79, %80, %81, %82, %83, %84, %85, %86, %87, %88, %89, %90, %91, %92, %93, %94, %95, %96, %97, %98, %99, %100, %101, %102, %103, %104, %105, %106, %107, %108, %109, %110, %111, %112, %113, %114, %115, %116, %117, %118, %119, %120, %121, %122, %123, %124, %125, %126, %127}, da, db, 1, 1, 1, 0, 1;\n"
    "add.u32 t, %128, 4;\nmov.b64 da, {t, %130};\nadd.u32 t, %129, 1024;\nmov.b64 db, {t, %130};\n"
    "wgmma.mma_async.sync.aligned.m64n256k16.f32.bf16.bf16 {%0, %1, %2, %3, %4, %5, %6, %7, %8, %9, %10, %11, %12, %13, %14, %15, %16, %17, %18, %19, %20, %21, %22, %23, %24, %25, %26, %27, %28, %29, %30, %31, %32, %33, %34, %35, %36, %37, %38, %39, %40, %41, %42, %43, %44, %45, %46, %47, %48, %49, %50, %51, %52, %53, %54, %55, %56, %57, %58, %59, %60, %61, %62, %63, %64, %65, %66, %67, %68, %69, %70, %71, %72, %73, %74, %75, %76, %77, %78, %79, %80, %81, %82, %83, %84, %85, %86, %87, %88, %89, %90, %91, %92, %93, %94, %95, %96, %97, %98, %99, %100, %101, %102, %103, %104, %105, %106, %107, %108, %109, %110, %111, %112, %113, %114, %115, %116, %117, %118, %119, %120, %121, %122, %123, %124, %125, %126, %127}, da, db, 1, 1, 1, 0, 1;\n"
    "add.u32 t, %128, 6;\nmov.b64 da, {t, %130};\nadd.u32 t, %129, 1152;\nmov.b64 db, {t, %130};\n"
    "wgmma.mma_async.sync.aligned.m64n256k16.f32.bf16.bf16 {%0, %1, %2, %3, %4, %5, %6, %7, %8, %9, %10, %11, %12, %13, %14, %15, %16, %17, %18, %19, %20, %21, %22, %23, %24, %25, %26, %27, %28, %29, %30, %31, %32, %33, %34, %35, %36, %37, %38, %39, %40, %41, %42, %43, %44, %45, %46, %47, %48, %49, %50, %51, %52, %53, %54, %55, %56, %57, %58, %59, %60, %61, %62, %63, %64, %65, %66, %67, %68, %69, %70, %71, %72, %73, %74, %75, %76, %77, %78, %79, %80, %81, %82, %83, %84, %85, %86, %87, %88, %89, %90, %91, %92, %93, %94, %95, %96, %97, %98, %99, %100, %101, %102, %103, %104, %105, %106, %107, %108, %109, %110, %111, %112, %113, %114, %115, %116, %117, %118, %119, %120, %121, %122, %123, %124, %125, %126, %127}, da, db, 1, 1, 1, 0, 1;\nwgmma.commit_group.sync.aligned;\n"
    "}\n"
    : "+f"(d[0]), "+f"(d[1]), "+f"(d[2]), "+f"(d[3]), "+f"(d[4]), "+f"(d[5]), "+f"(d[6]), "+f"(d[7]), "+f"(d[8]), "+f"(d[9]), "+f"(d[10]), "+f"(d[11]), "+f"(d[12]), "+f"(d[13]), "+f"(d[14]), "+f"(d[15]), "+f"(d[16]), "+f"(d[17]), "+f"(d[18]), "+f"(d[19]), "+f"(d[20]), "+f"(d[21]), "+f"(d[22]), "+f"(d[23]), "+f"(d[24]), "+f"(d[25]), "+f"(d[26]), "+f"(d[27]), "+f"(d[28]), "+f"(d[29]), "+f"(d[30]), "+f"(d[31]), "+f"(d[32]), "+f"(d[33]), "+f"(d[34]), "+f"(d[35]), "+f"(d[36]), "+f"(d[37]), "+f"(d[38]), "+f"(d[39]), "+f"(d[40]), "+f"(d[41]), "+f"(d[42]), "+f"(d[43]), "+f"(d[44]), "+f"(d[45]), "+f"(d[46]), "+f"(d[47]), "+f"(d[48]), "+f"(d[49]), "+f"(d[50]), "+f"(d[51]), "+f"(d[52]), "+f"(d[53]), "+f"(d[54]), "+f"(d[55]), "+f"(d[56]), "+f"(d[57]), "+f"(d[58]), "+f"(d[59]), "+f"(d[60]), "+f"(d[61]), "+f"(d[62]), "+f"(d[63]), "+f"(d[64]), "+f"(d[65]), "+f"(d[66]), "+f"(d[67]), "+f"(d[68]), "+f"(d[69]), "+f"(d[70]), "+f"(d[71]), "+f"(d[72]), "+f"(d[73]), "+f"(d[74]), "+f"(d[75]), "+f"(d[76]), "+f"(d[77]), "+f"(d[78]), "+f"(d[79]), "+f"(d[80]), "+f"(d[81]), "+f"(d[82]), "+f"(d[83]), "+f"(d[84]), "+f"(d[85]), "+f"(d[86]), "+f"(d[87]), "+f"(d[88]), "+f"(d[89]), "+f"(d[90]), "+f"(d[91]), "+f"(d[92]), "+f"(d[93]), "+f"(d[94]), "+f"(d[95]), "+f"(d[96]), "+f"(d[97]), "+f"(d[98]), "+f"(d[99]), "+f"(d[100]), "+f"(d[101]), "+f"(d[102]), "+f"(d[103]), "+f"(d[104]), "+f"(d[105]), "+f"(d[106]), "+f"(d[107]), "+f"(d[108]), "+f"(d[109]), "+f"(d[110]), "+f"(d[111]), "+f"(d[112]), "+f"(d[113]), "+f"(d[114]), "+f"(d[115]), "+f"(d[116]), "+f"(d[117]), "+f"(d[118]), "+f"(d[119]), "+f"(d[120]), "+f"(d[121]), "+f"(d[122]), "+f"(d[123]), "+f"(d[124]), "+f"(d[125]), "+f"(d[126]), "+f"(d[127])
    : "r"(a), "r"(b), "n"(0x40000040) : "memory");
}
__device__ __forceinline__ void first_kstep(float (&d)[96], uint32_t a, uint32_t b) {
  asm volatile("{\n.reg .u32 t;\n.reg .u64 da, db;\nwgmma.fence.sync.aligned;\n"
    "add.u32 t, %96, 0;\nmov.b64 da, {t, %98};\nadd.u32 t, %97, 0;\nmov.b64 db, {t, %98};\n"
    "wgmma.mma_async.sync.aligned.m64n192k16.f32.bf16.bf16 {%0, %1, %2, %3, %4, %5, %6, %7, %8, %9, %10, %11, %12, %13, %14, %15, %16, %17, %18, %19, %20, %21, %22, %23, %24, %25, %26, %27, %28, %29, %30, %31, %32, %33, %34, %35, %36, %37, %38, %39, %40, %41, %42, %43, %44, %45, %46, %47, %48, %49, %50, %51, %52, %53, %54, %55, %56, %57, %58, %59, %60, %61, %62, %63, %64, %65, %66, %67, %68, %69, %70, %71, %72, %73, %74, %75, %76, %77, %78, %79, %80, %81, %82, %83, %84, %85, %86, %87, %88, %89, %90, %91, %92, %93, %94, %95}, da, db, 0, 1, 1, 0, 1;\nwgmma.commit_group.sync.aligned;\n"
    "add.u32 t, %96, 2;\nmov.b64 da, {t, %98};\nadd.u32 t, %97, 128;\nmov.b64 db, {t, %98};\n"
    "wgmma.mma_async.sync.aligned.m64n192k16.f32.bf16.bf16 {%0, %1, %2, %3, %4, %5, %6, %7, %8, %9, %10, %11, %12, %13, %14, %15, %16, %17, %18, %19, %20, %21, %22, %23, %24, %25, %26, %27, %28, %29, %30, %31, %32, %33, %34, %35, %36, %37, %38, %39, %40, %41, %42, %43, %44, %45, %46, %47, %48, %49, %50, %51, %52, %53, %54, %55, %56, %57, %58, %59, %60, %61, %62, %63, %64, %65, %66, %67, %68, %69, %70, %71, %72, %73, %74, %75, %76, %77, %78, %79, %80, %81, %82, %83, %84, %85, %86, %87, %88, %89, %90, %91, %92, %93, %94, %95}, da, db, 1, 1, 1, 0, 1;\n"
    "add.u32 t, %96, 4;\nmov.b64 da, {t, %98};\nadd.u32 t, %97, 1024;\nmov.b64 db, {t, %98};\n"
    "wgmma.mma_async.sync.aligned.m64n192k16.f32.bf16.bf16 {%0, %1, %2, %3, %4, %5, %6, %7, %8, %9, %10, %11, %12, %13, %14, %15, %16, %17, %18, %19, %20, %21, %22, %23, %24, %25, %26, %27, %28, %29, %30, %31, %32, %33, %34, %35, %36, %37, %38, %39, %40, %41, %42, %43, %44, %45, %46, %47, %48, %49, %50, %51, %52, %53, %54, %55, %56, %57, %58, %59, %60, %61, %62, %63, %64, %65, %66, %67, %68, %69, %70, %71, %72, %73, %74, %75, %76, %77, %78, %79, %80, %81, %82, %83, %84, %85, %86, %87, %88, %89, %90, %91, %92, %93, %94, %95}, da, db, 1, 1, 1, 0, 1;\n"
    "add.u32 t, %96, 6;\nmov.b64 da, {t, %98};\nadd.u32 t, %97, 1152;\nmov.b64 db, {t, %98};\n"
    "wgmma.mma_async.sync.aligned.m64n192k16.f32.bf16.bf16 {%0, %1, %2, %3, %4, %5, %6, %7, %8, %9, %10, %11, %12, %13, %14, %15, %16, %17, %18, %19, %20, %21, %22, %23, %24, %25, %26, %27, %28, %29, %30, %31, %32, %33, %34, %35, %36, %37, %38, %39, %40, %41, %42, %43, %44, %45, %46, %47, %48, %49, %50, %51, %52, %53, %54, %55, %56, %57, %58, %59, %60, %61, %62, %63, %64, %65, %66, %67, %68, %69, %70, %71, %72, %73, %74, %75, %76, %77, %78, %79, %80, %81, %82, %83, %84, %85, %86, %87, %88, %89, %90, %91, %92, %93, %94, %95}, da, db, 1, 1, 1, 0, 1;\nwgmma.commit_group.sync.aligned;\n"
    "}\n"
    : "=f"(d[0]), "=f"(d[1]), "=f"(d[2]), "=f"(d[3]), "=f"(d[4]), "=f"(d[5]), "=f"(d[6]), "=f"(d[7]), "=f"(d[8]), "=f"(d[9]), "=f"(d[10]), "=f"(d[11]), "=f"(d[12]), "=f"(d[13]), "=f"(d[14]), "=f"(d[15]), "=f"(d[16]), "=f"(d[17]), "=f"(d[18]), "=f"(d[19]), "=f"(d[20]), "=f"(d[21]), "=f"(d[22]), "=f"(d[23]), "=f"(d[24]), "=f"(d[25]), "=f"(d[26]), "=f"(d[27]), "=f"(d[28]), "=f"(d[29]), "=f"(d[30]), "=f"(d[31]), "=f"(d[32]), "=f"(d[33]), "=f"(d[34]), "=f"(d[35]), "=f"(d[36]), "=f"(d[37]), "=f"(d[38]), "=f"(d[39]), "=f"(d[40]), "=f"(d[41]), "=f"(d[42]), "=f"(d[43]), "=f"(d[44]), "=f"(d[45]), "=f"(d[46]), "=f"(d[47]), "=f"(d[48]), "=f"(d[49]), "=f"(d[50]), "=f"(d[51]), "=f"(d[52]), "=f"(d[53]), "=f"(d[54]), "=f"(d[55]), "=f"(d[56]), "=f"(d[57]), "=f"(d[58]), "=f"(d[59]), "=f"(d[60]), "=f"(d[61]), "=f"(d[62]), "=f"(d[63]), "=f"(d[64]), "=f"(d[65]), "=f"(d[66]), "=f"(d[67]), "=f"(d[68]), "=f"(d[69]), "=f"(d[70]), "=f"(d[71]), "=f"(d[72]), "=f"(d[73]), "=f"(d[74]), "=f"(d[75]), "=f"(d[76]), "=f"(d[77]), "=f"(d[78]), "=f"(d[79]), "=f"(d[80]), "=f"(d[81]), "=f"(d[82]), "=f"(d[83]), "=f"(d[84]), "=f"(d[85]), "=f"(d[86]), "=f"(d[87]), "=f"(d[88]), "=f"(d[89]), "=f"(d[90]), "=f"(d[91]), "=f"(d[92]), "=f"(d[93]), "=f"(d[94]), "=f"(d[95])
    : "r"(a), "r"(b), "n"(0x40000040) : "memory");
}
__device__ __forceinline__ void kstep(float (&d)[96], uint32_t a, uint32_t b) {
  asm volatile("{\n.reg .u32 t;\n.reg .u64 da, db;\nwgmma.fence.sync.aligned;\n"
    "add.u32 t, %96, 0;\nmov.b64 da, {t, %98};\nadd.u32 t, %97, 0;\nmov.b64 db, {t, %98};\n"
    "wgmma.mma_async.sync.aligned.m64n192k16.f32.bf16.bf16 {%0, %1, %2, %3, %4, %5, %6, %7, %8, %9, %10, %11, %12, %13, %14, %15, %16, %17, %18, %19, %20, %21, %22, %23, %24, %25, %26, %27, %28, %29, %30, %31, %32, %33, %34, %35, %36, %37, %38, %39, %40, %41, %42, %43, %44, %45, %46, %47, %48, %49, %50, %51, %52, %53, %54, %55, %56, %57, %58, %59, %60, %61, %62, %63, %64, %65, %66, %67, %68, %69, %70, %71, %72, %73, %74, %75, %76, %77, %78, %79, %80, %81, %82, %83, %84, %85, %86, %87, %88, %89, %90, %91, %92, %93, %94, %95}, da, db, 1, 1, 1, 0, 1;\nwgmma.commit_group.sync.aligned;\n"
    "add.u32 t, %96, 2;\nmov.b64 da, {t, %98};\nadd.u32 t, %97, 128;\nmov.b64 db, {t, %98};\n"
    "wgmma.mma_async.sync.aligned.m64n192k16.f32.bf16.bf16 {%0, %1, %2, %3, %4, %5, %6, %7, %8, %9, %10, %11, %12, %13, %14, %15, %16, %17, %18, %19, %20, %21, %22, %23, %24, %25, %26, %27, %28, %29, %30, %31, %32, %33, %34, %35, %36, %37, %38, %39, %40, %41, %42, %43, %44, %45, %46, %47, %48, %49, %50, %51, %52, %53, %54, %55, %56, %57, %58, %59, %60, %61, %62, %63, %64, %65, %66, %67, %68, %69, %70, %71, %72, %73, %74, %75, %76, %77, %78, %79, %80, %81, %82, %83, %84, %85, %86, %87, %88, %89, %90, %91, %92, %93, %94, %95}, da, db, 1, 1, 1, 0, 1;\n"
    "add.u32 t, %96, 4;\nmov.b64 da, {t, %98};\nadd.u32 t, %97, 1024;\nmov.b64 db, {t, %98};\n"
    "wgmma.mma_async.sync.aligned.m64n192k16.f32.bf16.bf16 {%0, %1, %2, %3, %4, %5, %6, %7, %8, %9, %10, %11, %12, %13, %14, %15, %16, %17, %18, %19, %20, %21, %22, %23, %24, %25, %26, %27, %28, %29, %30, %31, %32, %33, %34, %35, %36, %37, %38, %39, %40, %41, %42, %43, %44, %45, %46, %47, %48, %49, %50, %51, %52, %53, %54, %55, %56, %57, %58, %59, %60, %61, %62, %63, %64, %65, %66, %67, %68, %69, %70, %71, %72, %73, %74, %75, %76, %77, %78, %79, %80, %81, %82, %83, %84, %85, %86, %87, %88, %89, %90, %91, %92, %93, %94, %95}, da, db, 1, 1, 1, 0, 1;\n"
    "add.u32 t, %96, 6;\nmov.b64 da, {t, %98};\nadd.u32 t, %97, 1152;\nmov.b64 db, {t, %98};\n"
    "wgmma.mma_async.sync.aligned.m64n192k16.f32.bf16.bf16 {%0, %1, %2, %3, %4, %5, %6, %7, %8, %9, %10, %11, %12, %13, %14, %15, %16, %17, %18, %19, %20, %21, %22, %23, %24, %25, %26, %27, %28, %29, %30, %31, %32, %33, %34, %35, %36, %37, %38, %39, %40, %41, %42, %43, %44, %45, %46, %47, %48, %49, %50, %51, %52, %53, %54, %55, %56, %57, %58, %59, %60, %61, %62, %63, %64, %65, %66, %67, %68, %69, %70, %71, %72, %73, %74, %75, %76, %77, %78, %79, %80, %81, %82, %83, %84, %85, %86, %87, %88, %89, %90, %91, %92, %93, %94, %95}, da, db, 1, 1, 1, 0, 1;\nwgmma.commit_group.sync.aligned;\n"
    "}\n"
    : "+f"(d[0]), "+f"(d[1]), "+f"(d[2]), "+f"(d[3]), "+f"(d[4]), "+f"(d[5]), "+f"(d[6]), "+f"(d[7]), "+f"(d[8]), "+f"(d[9]), "+f"(d[10]), "+f"(d[11]), "+f"(d[12]), "+f"(d[13]), "+f"(d[14]), "+f"(d[15]), "+f"(d[16]), "+f"(d[17]), "+f"(d[18]), "+f"(d[19]), "+f"(d[20]), "+f"(d[21]), "+f"(d[22]), "+f"(d[23]), "+f"(d[24]), "+f"(d[25]), "+f"(d[26]), "+f"(d[27]), "+f"(d[28]), "+f"(d[29]), "+f"(d[30]), "+f"(d[31]), "+f"(d[32]), "+f"(d[33]), "+f"(d[34]), "+f"(d[35]), "+f"(d[36]), "+f"(d[37]), "+f"(d[38]), "+f"(d[39]), "+f"(d[40]), "+f"(d[41]), "+f"(d[42]), "+f"(d[43]), "+f"(d[44]), "+f"(d[45]), "+f"(d[46]), "+f"(d[47]), "+f"(d[48]), "+f"(d[49]), "+f"(d[50]), "+f"(d[51]), "+f"(d[52]), "+f"(d[53]), "+f"(d[54]), "+f"(d[55]), "+f"(d[56]), "+f"(d[57]), "+f"(d[58]), "+f"(d[59]), "+f"(d[60]), "+f"(d[61]), "+f"(d[62]), "+f"(d[63]), "+f"(d[64]), "+f"(d[65]), "+f"(d[66]), "+f"(d[67]), "+f"(d[68]), "+f"(d[69]), "+f"(d[70]), "+f"(d[71]), "+f"(d[72]), "+f"(d[73]), "+f"(d[74]), "+f"(d[75]), "+f"(d[76]), "+f"(d[77]), "+f"(d[78]), "+f"(d[79]), "+f"(d[80]), "+f"(d[81]), "+f"(d[82]), "+f"(d[83]), "+f"(d[84]), "+f"(d[85]), "+f"(d[86]), "+f"(d[87]), "+f"(d[88]), "+f"(d[89]), "+f"(d[90]), "+f"(d[91]), "+f"(d[92]), "+f"(d[93]), "+f"(d[94]), "+f"(d[95])
    : "r"(a), "r"(b), "n"(0x40000040) : "memory");
}
__device__ __forceinline__ void half_kstep0(float (&d)[64], uint32_t a, uint32_t b) {
  asm volatile("{\n.reg .u32 t;\n.reg .u64 da, db;\nwgmma.fence.sync.aligned;\n"
    "add.u32 t, %64, 0;\nmov.b64 da, {t, %66};\nadd.u32 t, %65, 0;\nmov.b64 db, {t, %66};\n"
    "wgmma.mma_async.sync.aligned.m64n128k16.f32.bf16.bf16 {%0, %1, %2, %3, %4, %5, %6, %7, %8, %9, %10, %11, %12, %13, %14, %15, %16, %17, %18, %19, %20, %21, %22, %23, %24, %25, %26, %27, %28, %29, %30, %31, %32, %33, %34, %35, %36, %37, %38, %39, %40, %41, %42, %43, %44, %45, %46, %47, %48, %49, %50, %51, %52, %53, %54, %55, %56, %57, %58, %59, %60, %61, %62, %63}, da, db, 1, 1, 1, 0, 1;\n"
    "add.u32 t, %64, 2;\nmov.b64 da, {t, %66};\nadd.u32 t, %65, 128;\nmov.b64 db, {t, %66};\n"
    "wgmma.mma_async.sync.aligned.m64n128k16.f32.bf16.bf16 {%0, %1, %2, %3, %4, %5, %6, %7, %8, %9, %10, %11, %12, %13, %14, %15, %16, %17, %18, %19, %20, %21, %22, %23, %24, %25, %26, %27, %28, %29, %30, %31, %32, %33, %34, %35, %36, %37, %38, %39, %40, %41, %42, %43, %44, %45, %46, %47, %48, %49, %50, %51, %52, %53, %54, %55, %56, %57, %58, %59, %60, %61, %62, %63}, da, db, 1, 1, 1, 0, 1;\n"
    "add.u32 t, %64, 4;\nmov.b64 da, {t, %66};\nadd.u32 t, %65, 1024;\nmov.b64 db, {t, %66};\n"
    "wgmma.mma_async.sync.aligned.m64n128k16.f32.bf16.bf16 {%0, %1, %2, %3, %4, %5, %6, %7, %8, %9, %10, %11, %12, %13, %14, %15, %16, %17, %18, %19, %20, %21, %22, %23, %24, %25, %26, %27, %28, %29, %30, %31, %32, %33, %34, %35, %36, %37, %38, %39, %40, %41, %42, %43, %44, %45, %46, %47, %48, %49, %50, %51, %52, %53, %54, %55, %56, %57, %58, %59, %60, %61, %62, %63}, da, db, 1, 1, 1, 0, 1;\n"
    "add.u32 t, %64, 6;\nmov.b64 da, {t, %66};\nadd.u32 t, %65, 1152;\nmov.b64 db, {t, %66};\n"
    "wgmma.mma_async.sync.aligned.m64n128k16.f32.bf16.bf16 {%0, %1, %2, %3, %4, %5, %6, %7, %8, %9, %10, %11, %12, %13, %14, %15, %16, %17, %18, %19, %20, %21, %22, %23, %24, %25, %26, %27, %28, %29, %30, %31, %32, %33, %34, %35, %36, %37, %38, %39, %40, %41, %42, %43, %44, %45, %46, %47, %48, %49, %50, %51, %52, %53, %54, %55, %56, %57, %58, %59, %60, %61, %62, %63}, da, db, 1, 1, 1, 0, 1;\n"
    "wgmma.commit_group.sync.aligned;\n}\n"
    : "+f"(d[0]), "+f"(d[1]), "+f"(d[2]), "+f"(d[3]), "+f"(d[4]), "+f"(d[5]), "+f"(d[6]), "+f"(d[7]), "+f"(d[8]), "+f"(d[9]), "+f"(d[10]), "+f"(d[11]), "+f"(d[12]), "+f"(d[13]), "+f"(d[14]), "+f"(d[15]), "+f"(d[16]), "+f"(d[17]), "+f"(d[18]), "+f"(d[19]), "+f"(d[20]), "+f"(d[21]), "+f"(d[22]), "+f"(d[23]), "+f"(d[24]), "+f"(d[25]), "+f"(d[26]), "+f"(d[27]), "+f"(d[28]), "+f"(d[29]), "+f"(d[30]), "+f"(d[31]), "+f"(d[32]), "+f"(d[33]), "+f"(d[34]), "+f"(d[35]), "+f"(d[36]), "+f"(d[37]), "+f"(d[38]), "+f"(d[39]), "+f"(d[40]), "+f"(d[41]), "+f"(d[42]), "+f"(d[43]), "+f"(d[44]), "+f"(d[45]), "+f"(d[46]), "+f"(d[47]), "+f"(d[48]), "+f"(d[49]), "+f"(d[50]), "+f"(d[51]), "+f"(d[52]), "+f"(d[53]), "+f"(d[54]), "+f"(d[55]), "+f"(d[56]), "+f"(d[57]), "+f"(d[58]), "+f"(d[59]), "+f"(d[60]), "+f"(d[61]), "+f"(d[62]), "+f"(d[63])
    : "r"(a), "r"(b), "n"(0x40000040) : "memory");
}
__device__ __forceinline__ void half_kstep1(float (&d)[64], uint32_t a, uint32_t b) {
  asm volatile("{\n.reg .u32 t;\n.reg .u64 da, db;\nwgmma.fence.sync.aligned;\n"
    "add.u32 t, %64, 0;\nmov.b64 da, {t, %66};\nadd.u32 t, %65, 512;\nmov.b64 db, {t, %66};\n"
    "wgmma.mma_async.sync.aligned.m64n128k16.f32.bf16.bf16 {%0, %1, %2, %3, %4, %5, %6, %7, %8, %9, %10, %11, %12, %13, %14, %15, %16, %17, %18, %19, %20, %21, %22, %23, %24, %25, %26, %27, %28, %29, %30, %31, %32, %33, %34, %35, %36, %37, %38, %39, %40, %41, %42, %43, %44, %45, %46, %47, %48, %49, %50, %51, %52, %53, %54, %55, %56, %57, %58, %59, %60, %61, %62, %63}, da, db, 1, 1, 1, 0, 1;\n"
    "add.u32 t, %64, 2;\nmov.b64 da, {t, %66};\nadd.u32 t, %65, 640;\nmov.b64 db, {t, %66};\n"
    "wgmma.mma_async.sync.aligned.m64n128k16.f32.bf16.bf16 {%0, %1, %2, %3, %4, %5, %6, %7, %8, %9, %10, %11, %12, %13, %14, %15, %16, %17, %18, %19, %20, %21, %22, %23, %24, %25, %26, %27, %28, %29, %30, %31, %32, %33, %34, %35, %36, %37, %38, %39, %40, %41, %42, %43, %44, %45, %46, %47, %48, %49, %50, %51, %52, %53, %54, %55, %56, %57, %58, %59, %60, %61, %62, %63}, da, db, 1, 1, 1, 0, 1;\n"
    "add.u32 t, %64, 4;\nmov.b64 da, {t, %66};\nadd.u32 t, %65, 1536;\nmov.b64 db, {t, %66};\n"
    "wgmma.mma_async.sync.aligned.m64n128k16.f32.bf16.bf16 {%0, %1, %2, %3, %4, %5, %6, %7, %8, %9, %10, %11, %12, %13, %14, %15, %16, %17, %18, %19, %20, %21, %22, %23, %24, %25, %26, %27, %28, %29, %30, %31, %32, %33, %34, %35, %36, %37, %38, %39, %40, %41, %42, %43, %44, %45, %46, %47, %48, %49, %50, %51, %52, %53, %54, %55, %56, %57, %58, %59, %60, %61, %62, %63}, da, db, 1, 1, 1, 0, 1;\n"
    "add.u32 t, %64, 6;\nmov.b64 da, {t, %66};\nadd.u32 t, %65, 1664;\nmov.b64 db, {t, %66};\n"
    "wgmma.mma_async.sync.aligned.m64n128k16.f32.bf16.bf16 {%0, %1, %2, %3, %4, %5, %6, %7, %8, %9, %10, %11, %12, %13, %14, %15, %16, %17, %18, %19, %20, %21, %22, %23, %24, %25, %26, %27, %28, %29, %30, %31, %32, %33, %34, %35, %36, %37, %38, %39, %40, %41, %42, %43, %44, %45, %46, %47, %48, %49, %50, %51, %52, %53, %54, %55, %56, %57, %58, %59, %60, %61, %62, %63}, da, db, 1, 1, 1, 0, 1;\n"
    "wgmma.commit_group.sync.aligned;\n}\n"
    : "+f"(d[0]), "+f"(d[1]), "+f"(d[2]), "+f"(d[3]), "+f"(d[4]), "+f"(d[5]), "+f"(d[6]), "+f"(d[7]), "+f"(d[8]), "+f"(d[9]), "+f"(d[10]), "+f"(d[11]), "+f"(d[12]), "+f"(d[13]), "+f"(d[14]), "+f"(d[15]), "+f"(d[16]), "+f"(d[17]), "+f"(d[18]), "+f"(d[19]), "+f"(d[20]), "+f"(d[21]), "+f"(d[22]), "+f"(d[23]), "+f"(d[24]), "+f"(d[25]), "+f"(d[26]), "+f"(d[27]), "+f"(d[28]), "+f"(d[29]), "+f"(d[30]), "+f"(d[31]), "+f"(d[32]), "+f"(d[33]), "+f"(d[34]), "+f"(d[35]), "+f"(d[36]), "+f"(d[37]), "+f"(d[38]), "+f"(d[39]), "+f"(d[40]), "+f"(d[41]), "+f"(d[42]), "+f"(d[43]), "+f"(d[44]), "+f"(d[45]), "+f"(d[46]), "+f"(d[47]), "+f"(d[48]), "+f"(d[49]), "+f"(d[50]), "+f"(d[51]), "+f"(d[52]), "+f"(d[53]), "+f"(d[54]), "+f"(d[55]), "+f"(d[56]), "+f"(d[57]), "+f"(d[58]), "+f"(d[59]), "+f"(d[60]), "+f"(d[61]), "+f"(d[62]), "+f"(d[63])
    : "r"(a), "r"(b), "n"(0x40000040) : "memory");
}

__device__ __forceinline__ void sum_columns(float (&d)[4], uint32_t a, uint32_t b) {
  asm volatile("{\n.reg .u32 t;\n.reg .u64 da, db;\nmov.b64 db, {%5, 0};\nwgmma.fence.sync.aligned;\n"
               "add.u32 t, %4, 0;\nmov.b64 da, {t, %6};\nwgmma.mma_async.sync.aligned.m64n8k16.f32.bf16.bf16 {%0, %1, %2, %3}, da, db, 1, 1, 1, 1, 0;\n"
               "add.u32 t, %4, 128;\nmov.b64 da, {t, %6};\nwgmma.mma_async.sync.aligned.m64n8k16.f32.bf16.bf16 {%0, %1, %2, %3}, da, db, 1, 1, 1, 1, 0;\n"
               "add.u32 t, %4, 256;\nmov.b64 da, {t, %6};\nwgmma.mma_async.sync.aligned.m64n8k16.f32.bf16.bf16 {%0, %1, %2, %3}, da, db, 1, 1, 1, 1, 0;\n"
               "add.u32 t, %4, 384;\nmov.b64 da, {t, %6};\nwgmma.mma_async.sync.aligned.m64n8k16.f32.bf16.bf16 {%0, %1, %2, %3}, da, db, 1, 1, 1, 1, 0;\n"
               "add.u32 t, %4, 512;\nmov.b64 da, {t, %6};\nwgmma.mma_async.sync.aligned.m64n8k16.f32.bf16.bf16 {%0, %1, %2, %3}, da, db, 1, 1, 1, 1, 0;\n"
               "add.u32 t, %4, 640;\nmov.b64 da, {t, %6};\nwgmma.mma_async.sync.aligned.m64n8k16.f32.bf16.bf16 {%0, %1, %2, %3}, da, db, 1, 1, 1, 1, 0;\n"
               "add.u32 t, %4, 768;\nmov.b64 da, {t, %6};\nwgmma.mma_async.sync.aligned.m64n8k16.f32.bf16.bf16 {%0, %1, %2, %3}, da, db, 1, 1, 1, 1, 0;\n"
               "add.u32 t, %4, 896;\nmov.b64 da, {t, %6};\nwgmma.mma_async.sync.aligned.m64n8k16.f32.bf16.bf16 {%0, %1, %2, %3}, da, db, 1, 1, 1, 1, 0;\n"
               "add.u32 t, %4, 1024;\nmov.b64 da, {t, %6};\nwgmma.mma_async.sync.aligned.m64n8k16.f32.bf16.bf16 {%0, %1, %2, %3}, da, db, 1, 1, 1, 1, 0;\n"
               "add.u32 t, %4, 1152;\nmov.b64 da, {t, %6};\nwgmma.mma_async.sync.aligned.m64n8k16.f32.bf16.bf16 {%0, %1, %2, %3}, da, db, 1, 1, 1, 1, 0;\n"
               "add.u32 t, %4, 1280;\nmov.b64 da, {t, %6};\nwgmma.mma_async.sync.aligned.m64n8k16.f32.bf16.bf16 {%0, %1, %2, %3}, da, db, 1, 1, 1, 1, 0;\n"
               "add.u32 t, %4, 1408;\nmov.b64 da, {t, %6};\nwgmma.mma_async.sync.aligned.m64n8k16.f32.bf16.bf16 {%0, %1, %2, %3}, da, db, 1, 1, 1, 1, 0;\n"
               "add.u32 t, %4, 1536;\nmov.b64 da, {t, %6};\nwgmma.mma_async.sync.aligned.m64n8k16.f32.bf16.bf16 {%0, %1, %2, %3}, da, db, 1, 1, 1, 1, 0;\n"
               "add.u32 t, %4, 1664;\nmov.b64 da, {t, %6};\nwgmma.mma_async.sync.aligned.m64n8k16.f32.bf16.bf16 {%0, %1, %2, %3}, da, db, 1, 1, 1, 1, 0;\n"
               "add.u32 t, %4, 1792;\nmov.b64 da, {t, %6};\nwgmma.mma_async.sync.aligned.m64n8k16.f32.bf16.bf16 {%0, %1, %2, %3}, da, db, 1, 1, 1, 1, 0;\n"
               "add.u32 t, %4, 1920;\nmov.b64 da, {t, %6};\nwgmma.mma_async.sync.aligned.m64n8k16.f32.bf16.bf16 {%0, %1, %2, %3}, da, db, 1, 1, 1, 1, 0;\n"
               "wgmma.commit_group.sync.aligned;\nwgmma.wait_group.sync.aligned 0;\n}"
               : "+f"(d[0]), "+f"(d[1]), "+f"(d[2]), "+f"(d[3]) : "r"(a), "r"(b), "n"(0x40000040) : "memory");
}
struct Job {
  uint32_t type, layer, R, col, nk;
  __device__ __forceinline__ explicit Job(uint32_t j) : type(j & 3), layer((j >> 2) & 1), R((j >> 3) & 7), col((j >> 6) & 63), nk((j >> 12) & 63) {}
  __device__ __forceinline__ uint32_t inst() const { return layer * 2 + (type >> 1); }
};
struct Smem {
  char* scratch;
  uint32_t base;
  __device__ __forceinline__ uint32_t stage(uint32_t s) const { return base + (s & (NSTAGE - 1)) * STAGE; }
  __device__ __forceinline__ uint32_t slot(uint32_t c) const { return base + STG_OFF + c * SLOT; }
  __device__ __forceinline__ uint32_t full(uint32_t s) const { return base + BAR_OFF + (s & (NSTAGE - 1)) * 8; }
  __device__ __forceinline__ uint32_t empty(uint32_t s) const { return base + BAR_OFF + 32 + (s & (NSTAGE - 1)) * 8; }
  __device__ __forceinline__ uint32_t filled(uint32_t u) const { return base + BAR_OFF + 64 + u * 8; }
  __device__ __forceinline__ uint32_t vacant(uint32_t u) const { return base + BAR_OFF + 96 + u * 8; }
  __device__ __forceinline__ uint32_t summed(uint32_t s) const { return base + BAR_OFF + 128 + (s & (NSTAGE - 1)) * 8; }
  __device__ __forceinline__ uint32_t aux_full() const { return base + BAR_OFF + 160; }
  __device__ __forceinline__ uint32_t boot() const { return base + BAR_OFF + 168; }
  __device__ __forceinline__ uint32_t xchg_full() const { return base + BAR_OFF + 176; }
  __device__ __forceinline__ uint32_t wgmma_done() const { return base + BAR_OFF + 184; }
  __device__ __forceinline__ uint32_t mma_done() const { return base + BAR_OFF + 192; }
  __device__ __forceinline__ uint32_t kv_ready(int w) const { return base + BAR_OFF + 208 + w * 8; }
  __device__ __forceinline__ uint32_t pair_id() const { return base + BAR_OFF + 280; }
  __device__ __forceinline__ uint32_t stats() const { return base + AUX_OFF; }
  __device__ __forceinline__ uint32_t sums() const { return base + AUX_OFF + 1088; }
  __device__ __forceinline__ uint32_t xchg() const { return base + AUX_OFF + 1600; }
};
__device__ __forceinline__ uint32_t par(uint32_t s) { return (s / NSTAGE) & 1; }

__device__ __forceinline__ void st_word(u64* p, uint32_t lo, uint32_t hi) {
  asm volatile("st.relaxed.gpu.global.u64 [%0], %1;" ::"l"(p), "l"(((u64)hi << 32) | lo) : "memory");
}
__device__ __forceinline__ uint2 ld_word(const u64* p) {
  u64 v;
  asm volatile("ld.relaxed.gpu.global.u64 %0, [%1];" : "=l"(v) : "l"(p) : "memory");
  return make_uint2((uint32_t)v, (uint32_t)(v >> 32));
}
__device__ __forceinline__ void add_moments(uint4 v, float (&m)[4]) {
  const uint32_t w[4] = {v.x, v.y, v.z, v.w};
#pragma unroll
  for (int c = 0; c < 4; c++) {
    const float lo = bf_lo(w[c]), hi = bf_hi(w[c]);
    m[0] += lo; m[1] += hi; m[2] = fmaf(lo, lo, m[2]); m[3] = fmaf(hi, hi, m[3]);
  }
}
__device__ __forceinline__ void publish_stats(const Smem& sm, float s, float q, uint32_t idx, bool valid, uint32_t e1) {
  const float mean = s * (1.f / D), var = fmaxf(q * (1.f / D) - mean * mean, 0.f);
  const u64 word = ((u64)((__float_as_uint(-bf_round(mean)) & 0xffff0000u) | (e1 & 0xffff)) << 32) | __float_as_uint(rcp(bf_round(sqrt_fast(bf_round(bf_round(var) + 1e-5f)))));
  asm volatile("{\n.reg .pred p;\nsetp.ne.u32 p, %2, 0;\n@p st.relaxed.gpu.global.u64 [%0], %1;\n}" ::"l"(SCR(sm, stats, idx * 8)), "l"(word), "r"((uint32_t)valid) : "memory");
}
__device__ __forceinline__ void stats_task(const Smem& sm, uint32_t jw, int rank, int w, uint32_t e1, const bf16* x) {
  const uint32_t inst = (jw >> 22) & 3, lane = fresh_tid() & 31, steps = (jw >> 31) * 2 + 2;
  uint32_t row = ((jw >> 24) & 127) * 8 + (w - 1) * 4 + (lane >> 3);
  wait_count(counter(C_X + inst * 16 + (row >> 7) * 2 + rank, lane & 7), e1 * (inst & 1 ? 56 : 16));
  const uint4* p = at(reinterpret_cast<const uint4*>(x), (row * 2 + rank) * (D * 2) + (lane & 7) * 16);
  uint4 v[8];
  float m[4] = {0.f, 0.f, 0.f, 0.f};
#pragma unroll
  for (int i = 0; i < 8; i++) v[i] = ldg128(p + i * 8);
#pragma unroll 1
  for (uint32_t it = 1; it <= steps; it++) {
    p = at(p, it & 1 ? 1024 : 8 * D * 4 - 1024);
#pragma unroll
    for (int i = 0; i < 8; i++) {
      add_moments(v[i], m);
      if (it < steps) v[i] = ldg128(p + i * 8);
    }
    if (!(it & 1)) {
      m[0] += m[1]; m[2] += m[3];
#pragma unroll
      for (int o = 1; o <= 4; o <<= 1) { m[0] += __shfl_xor_sync(~0u, m[0], o); m[2] += __shfl_xor_sync(~0u, m[2], o); }
      publish_stats(sm, m[0], m[2], (inst + 1) * S + rank * (S / 2) + row, (lane & 7) == 0, e1);
      m[0] = m[1] = m[2] = m[3] = 0.f;
      row += 8;
    }
  }
}
struct Stager {
  uint2 st[5], cs[4];
  __device__ __forceinline__ void load(const Smem& sm, const Job& J, int rank, int lane, bool sums) {
#pragma unroll
    for (int i = 0; i < 5; i++) st[i] = ld_word(SCR(sm, stats, (J.inst() * S + rank * (S / 2) + J.R * 128 + min(max(lane - 8 + 32 * i, J.R && J.type == T_Q ? -8 : 0), 127)) * 8));
#pragma unroll
    for (int i = 0; i < 4; i++)
      if (sums && (i < 3 || J.type == T_G)) cs[i] = ld_word(SCR(sm, cs, ((J.col + J.type * 8) * 128 + lane) * 8) + i * 32);
  }
  __device__ __forceinline__ void store(const Smem& sm, const Job& J, int rank, int lane, bool sums, uint32_t e1) {
    for (uint32_t n = 0;; n++) {
      uint32_t bad = (st[1].y ^ e1) | (st[2].y ^ e1) | (st[3].y ^ e1);
      bad |= (st[0].y ^ e1) | (st[4].y ^ e1);
      if (sums) bad |= (cs[0].y ^ e1) | (cs[1].y ^ e1) | (cs[2].y ^ e1);
      if (J.type == T_G) bad |= cs[3].y ^ e1;
      if (__all_sync(~0u, (bad & 0xffff) == 0)) break;
      __nanosleep(300);
      if (n > SPIN_LIMIT) __trap();
      load(sm, J, rank, lane, sums);
    }
#pragma unroll
    for (int i = 0; i < 5; i++) {
      if (i < 4 || lane < 8) sts64(sm.stats() + (lane + 32 * i) * 8, st[i]);
      if (i < 4 && sums && (i < 3 || J.type == T_G)) sts32(sm.sums() + (lane + 32 * i) * 4, cs[i].x);
    }
  }
};
__device__ __forceinline__ void add_cols(float (&a)[8], uint4 x, uint4 y) {
  const uint4 t = add8(x, y);
  a[0] += bf_lo(t.x); a[1] += bf_hi(t.x); a[2] += bf_lo(t.y); a[3] += bf_hi(t.y);
  a[4] += bf_lo(t.z); a[5] += bf_hi(t.z); a[6] += bf_lo(t.w); a[7] += bf_hi(t.w);
}
__device__ __forceinline__ void reduce_cols(float (&a)[8], int lane) {
#pragma unroll
  for (int i = 0; i < 4; i++) { const bool up = lane & 16; const float o = __shfl_xor_sync(~0u, up ? a[i] : a[i + 4], 16); a[i] = (up ? a[i + 4] : a[i]) + o; }
#pragma unroll
  for (int i = 0; i < 2; i++) { const bool up = lane & 8; const float o = __shfl_xor_sync(~0u, up ? a[i] : a[i + 2], 8); a[i] = (up ? a[i + 2] : a[i]) + o; }
}
template <class Fn>
__device__ __forceinline__ uint32_t qkv_col_sums(const Smem& sm, int rank, int w, int lane, Fn between) {
  float a[8] = {0.f, 0.f, 0.f, 0.f, 0.f, 0.f, 0.f, 0.f};
#pragma unroll 1
  for (int s = 0; s < D / 64; s++) {
    between(s);
    const uint32_t p = sm.stage(s) + SLOT + rank * SLOT + w * 4096 + (lane >> 3) * 128 + (((lane & 7) ^ (lane >> 3)) << 4);
    uint4 v[8];
    mbar_wait(sm.full(s), par(s));
#pragma unroll
    for (int j = 0; j < 8; j++) v[j] = lds128((p ^ ((j & 1) * 64)) + j * 512);
    __syncwarp();
    mbar_arrive_cl_if(lane < 2, mapa(sm.summed(s), lane & 1));
    add_cols(a, add8(v[0], v[1]), add8(v[2], v[3]));
    add_cols(a, add8(v[4], v[5]), add8(v[6], v[7]));
  }
  reduce_cols(a, lane);
  const uint32_t slot = sm.xchg() + (w * 32 + lane) * 8;
  asm volatile("st.async.weak.shared::cluster.mbarrier::complete_tx::bytes.v2.b32 [%0], {%1, %2}, [%3];"
               ::"r"(mapa(slot, rank ^ 1)), "r"(__float_as_uint(a[0])), "r"(__float_as_uint(a[1])), "r"(mapa(sm.xchg_full(), rank ^ 1)) : "memory");
  mbar_wait(sm.xchg_full(), 0);
  const uint2 o = lds64(slot);
  return pack_bf16(a[0] + __uint_as_float(o.x), a[1] + __uint_as_float(o.y));
}

constexpr float LOGIT_SCALE = 0.17677669529663687f * 1.4426950408889634f;
constexpr float MASKED = -1e30f;
enum { A_CS = 16, A_NM = 40, A_KT = 42, A_KU = 44, A_CT = 46, A_CU = 48, A_BIAS = 50, A_MASK = 52, A_ZERO = 53 };
__device__ __forceinline__ void attention_prepare(uint32_t (&r)[64], const Smem& sm, int W, int lane, bool first) {
  const int i = lane >> 2, c = (lane & 3) * 2;
  r[A_ZERO] = opaque_zero();
  r[A_MASK] = (c > i ? 0xffffu : 0u) | (c + 1 > i ? 0xffff0000u : 0u);
  const uint32_t a = sm.stats() + W * 128;
  const uint2 r0 = lds64(a + 64 + i * 8), r1 = lds64(a + 128 + i * 8);
#pragma unroll
  for (int y = 0; y < 2; y++) {
    const uint32_t k = a + (c + y + (c + y > i ? 0 : 8)) * 8;
    const float kt = lds32f(k), ku = lds32f(k + 64);
    r[A_KT + y] = __float_as_uint(kt); r[A_CT + y] = __float_as_uint(__uint_as_float(r0.x) * LOGIT_SCALE * kt);
    r[A_KU + y] = __float_as_uint(ku); r[A_CU + y] = __float_as_uint(__uint_as_float(r1.x) * LOGIT_SCALE * ku);
    r[A_BIAS + y] = __float_as_uint(first && W == 0 && c + y > i ? MASKED : 0.f);
  }
#pragma unroll
  for (int j = 0; j < 6; j++) {
    const uint4 v = lds128(sm.sums() + c * 48 + j * 16);
    r[A_CS + 4 * j] = v.x; r[A_CS + 4 * j + 1] = v.y; r[A_CS + 4 * j + 2] = v.z; r[A_CS + 4 * j + 3] = v.w;
  }
  r[A_NM] = dup_hi(r0.y); r[A_NM + 1] = dup_hi(r1.y);
}
__device__ __forceinline__ bool attention(const float (&acc)[96], uint32_t (&r)[64], const Smem& sm, int W, int lane, uint32_t t8, uint32_t t16,
                                          bool halo, uint32_t block, uint32_t tag, uint32_t parity, uint32_t next_bar, uint32_t next_parity, int ji) {
#define TRW W
  const uint32_t own = (W >> 2) * SLOT;
  const uint32_t pk = W == 0 ? (halo ? 4096 : 1024) : W == 4 ? 7168 : own - 1024;
  const uint32_t pv = W == 0 && halo ? 6144 : pk + 8192;
  uint32_t x[48];
  auto pack = [&](int j0, int step, int count) {
#pragma unroll
    for (int j = j0; j < j0 + step * count; j += step) x[j] = bf2_fma(r[A_NM + j % 2], r[A_CS + j / 2], pack_bf16(acc[2 * j], acc[2 * j + 1]));
  };
  auto put8 = [&](uint32_t a, int j) {
    stsm4(t8 + a, x[j], x[j + 2], x[j + 4], x[j + 6]);
    stsm4((t8 ^ 64) + a, x[j + 8], x[j + 10], x[j + 12], x[j + 14]);
  };
  uint32_t k0[2][4], v0[2][4], v12[4][4];
  pack(17, 2, 8);
  put8(own + 1024, 17);
  pack(32, 1, 16);
#pragma unroll
  for (int j = 0; j < 4; j++) stsm4((t16 ^ (j << 5)) + (own + 8192), x[32 + 4 * j], x[33 + 4 * j], x[34 + 4 * j], x[35 + 4 * j]);
  mbar_arrive_warp(sm.kv_ready(W));
  pack(16, 2, 8);
  pack(0, 1, 16);
  if (W == 0) {
    put8(0, 16);
#pragma unroll
    for (int j = 0; j < 4; j++) stsm4(lane & 8 ? sm.xchg() : (t16 ^ (j << 5)) + 2048, x[4 * j], x[4 * j + 1], x[4 * j + 2], x[4 * j + 3]);
  }
  mbar_wait(sm.kv_ready(W - 1), parity);
#pragma unroll
  for (int h = 0; h < 2; h++) ldsm4((t8 ^ (h * 64)) + pk, k0[h]);
#pragma unroll
  for (int j = 0; j < 4; j++) ldsm4t((t16 ^ (j << 5)) + (own + 8192), v12[j]);
#pragma unroll
  for (int h = 0; h < 2; h++) ldsm4t((t8 ^ (h * 64)) + pv, v0[h]);
  if (W < 4) mbar_wait(sm.wgmma_done(), parity);
  const bool next_full = mbar_test(next_bar, next_parity);
  TRC(ji, 20);
  float s0[2][4], s1[2][4], s2[2][4];
#pragma unroll
  for (int h = 0; h < 2; h++) {
#pragma unroll
    for (int y = 0; y < 4; y++) s0[h][y] = s1[h][y] = s2[h][y] = 0.f;
  }
#pragma unroll
  for (int ks = 0; ks < 2; ks++)
#pragma unroll
    for (int h = 0; h < 2; h++) {
      const int n = 8 * h + 4 * ks;
      mma16816(s1[h], x[n], x[n + 1], x[n + 2], x[n + 3], x[16 + n], x[18 + n]);
      mma16816(s2[h], x[n], x[n + 1], x[n + 2], x[n + 3], x[17 + n], x[19 + n]);
      mma16816(s0[h], x[n], x[n + 1], x[n + 2], x[n + 3], k0[h][2 * ks], k0[h][2 * ks + 1]);
    }
  const uint32_t mask = r[A_MASK];
  const bool after[2] = {(mask & 1) != 0, (int)mask < 0};
  float lt[2][2], lu[2][2], mt[2], mu[2];
#pragma unroll
  for (int h = 0; h < 2; h++) {
#pragma unroll
    for (int y = 0; y < 2; y++) {
      lt[h][y] = fmaf(after[y] ? s0[h][y] : s1[h][y], __uint_as_float(r[A_CT + y]), __uint_as_float(r[A_BIAS + y]));
      lu[h][y] = (after[y] ? s1[h][2 + y] : s2[h][2 + y]) * __uint_as_float(r[A_CU + y]);
    }
    mt[h] = fmaxf(lt[h][0], lt[h][1]);
    mu[h] = fmaxf(lu[h][0], lu[h][1]);
  }
#pragma unroll
  for (int d = 1; d <= 2; d++)
#pragma unroll
    for (int h = 0; h < 2; h++) {
      mt[h] = fmaxf(mt[h], __shfl_xor_sync(~0u, mt[h], d));
      mu[h] = fmaxf(mu[h], __shfl_xor_sync(~0u, mu[h], d));
    }
  float o[2][4][4];
#pragma unroll
  for (int h = 0; h < 2; h++) {
#pragma unroll
    for (int y = 0; y < 2; y++) { lt[h][y] = ex2(lt[h][y] - mt[h]); lu[h][y] = ex2(lu[h][y] - mu[h]); }
    const uint32_t pt = pack_bf16(lt[h][0] * __uint_as_float(r[A_KT]), lt[h][1] * __uint_as_float(r[A_KT + 1]));
    const uint32_t pu = pack_bf16(lu[h][0] * __uint_as_float(r[A_KU]), lu[h][1] * __uint_as_float(r[A_KU + 1]));
#pragma unroll
    for (int n = 0; n < 4; n++) {
      o[h][n][0] = o[h][n][1] = o[h][n][2] = o[h][n][3] = 0.f;
      mma16816(o[h][n], pt & ~mask, pu & mask, 0u, pu & ~mask, v12[2 * h + n / 2][n % 2 * 2], v12[2 * h + n / 2][n % 2 * 2 + 1]);
    }
#pragma unroll
    for (int n = 0; n < 4; n++) mma1688(o[h][n], pt & mask, 0u, v0[h][n]);
    mt[h] = lt[h][0] + lt[h][1];
    mu[h] = lu[h][0] + lu[h][1];
  }
#pragma unroll
  for (int d = 1; d <= 2; d++)
#pragma unroll
    for (int h = 0; h < 2; h++) {
      mt[h] += __shfl_xor_sync(~0u, mt[h], d);
      mu[h] += __shfl_xor_sync(~0u, mu[h], d);
    }
  uint32_t dep = 0;
#pragma unroll
  for (int n = 0; n < 3; n++) dep |= __float_as_uint(o[n % 2][n / 2][0]);
  mbar_arrive_warp(sm.mma_done() + (dep & r[A_ZERO]));
  TRC(ji, 22);
  if (W == 7) {
    ulonglong2* exp = SCR(sm, halo, (block * 256 + lane) * 16);
#pragma unroll
    for (int m = 0; m < 8; m++)
      asm volatile("st.relaxed.gpu.global.v2.u64 [%0], {%1,%2};" ::"l"(exp + m * 32), "l"(((u64)tag << 32) | x[17 + 4 * m]), "l"(((u64)tag << 32) | x[19 + 4 * m]) : "memory");
  }
#pragma unroll
  for (int h = 0; h < 2; h++) {
    const float rt = rcp(mt[h]), ru = rcp(mu[h]);
#pragma unroll
    for (int n = 0; n < 4; n++) {
      r[8 * h + 2 * n] = pack_bf16(o[h][n][0] * rt, o[h][n][1] * rt);
      r[8 * h + 2 * n + 1] = pack_bf16(o[h][n][2] * ru, o[h][n][3] * ru);
    }
  }
  return next_full;
}
__device__ __forceinline__ void import_halo(const Smem& sm, const ulonglong2* halo, uint32_t tag, int lane) {
  u64 x[16];
  for (uint32_t n = 0;; n++) {
#pragma unroll
    for (int m = 0; m < 8; m++)
      asm volatile("ld.relaxed.gpu.global.v2.u64 {%0,%1}, [%2];" : "=l"(x[2 * m]), "=l"(x[2 * m + 1]) : "l"(halo + m * 32) : "memory");
    uint32_t bad = 0;
#pragma unroll
    for (int m = 0; m < 16; m++) bad |= (uint32_t)(x[m] >> 32) ^ tag;
    if (__all_sync(~0u, bad == 0)) break;
    __nanosleep(300);
    if (n > SPIN_LIMIT) __trap();
  }
  const uint32_t a = sm.slot(0) + 4096 + (lane & 7) * 128 + (((lane >> 3) ^ (lane & 7)) << 4);
#pragma unroll
  for (int m = 0; m < 4; m++) stsm4((a ^ ((m & 1) * 64)) + (m >> 1) * 2048, (uint32_t)x[4 * m], (uint32_t)x[4 * m + 1], (uint32_t)x[4 * m + 2], (uint32_t)x[4 * m + 3]);
}
__device__ __forceinline__ void unpack8(uint4 v, float* f) {
  f[0] = bf_lo(v.x); f[1] = bf_hi(v.x); f[2] = bf_lo(v.y); f[3] = bf_hi(v.y);
  f[4] = bf_lo(v.z); f[5] = bf_hi(v.z); f[6] = bf_lo(v.w); f[7] = bf_hi(v.w);
}
__device__ __forceinline__ void boundary_rows(const Smem& sm, int h, int lane, uint32_t out) {
  const int i = lane >> 2, u = h * 4 + (lane & 3);
  uint4 r[8];
  float x[8], l[8], ik[8];
  unpack8(lds128(sm.slot(0) + 2048 + i * 128 + ((u ^ i) << 4)), x);
#pragma unroll
  for (int j = 0; j < 8; j++) {
    r[j] = lds128(sm.slot(0) + j * 128 + (j > i ? 4096 : 0) + ((u ^ j) << 4));
    ik[j] = lds32f(sm.stats() + j * 8 + (j > i ? 0 : 64));
  }
  const float cq = lds32f(sm.stats() + 64 + i * 8) * LOGIT_SCALE;
#pragma unroll
  for (int j = 0; j < 8; j++) {
    float kf[8];
    unpack8(r[j], kf);
    r[j] = lds128(sm.slot(0) + j * 128 + (j > i ? 6144 : 8192) + ((u ^ j) << 4));
    l[j] = 0.f;
#pragma unroll
    for (int d = 0; d < 8; d++) l[j] = fmaf(x[d], kf[d], l[j]);
  }
#pragma unroll
  for (int d = 1; d <= 2; d++)
#pragma unroll
    for (int j = 0; j < 8; j++) l[j] += __shfl_xor_sync(~0u, l[j], d);
  float m = MASKED, sum = 0.f;
#pragma unroll
  for (int j = 0; j < 8; j++) { l[j] *= cq * ik[j]; m = fmaxf(m, l[j]); }
#pragma unroll
  for (int j = 0; j < 8; j++) { l[j] = ex2(l[j] - m); sum += l[j]; }
  const float rs = rcp(sum);
#pragma unroll
  for (int d = 0; d < 8; d++) x[d] = 0.f;
#pragma unroll
  for (int j = 0; j < 8; j++) {
    const float pw = l[j] * ik[j] * rs;
    float vf[8];
    unpack8(r[j], vf);
#pragma unroll
    for (int d = 0; d < 8; d++) x[d] = fmaf(pw, vf[d], x[d]);
  }
  stg128(SCR(sm, o, out + i * (2 * D) + u * 16), make_uint4(pack_bf16(x[0], x[1]), pack_bf16(x[2], x[3]), pack_bf16(x[4], x[5]), pack_bf16(x[6], x[7])));
}
__device__ __forceinline__ uint32_t swiglu2(uint32_t g, uint32_t u, float hinv, float hinv2) {
  const float a = bf_lo(g) * hinv, b = bf_hi(g) * hinv, a2 = bf_lo(g) * hinv2, b2 = bf_hi(g) * hinv2;
  return bf2_mul(pack_bf16(fmaf(a2, tanh_fast(a), a2), fmaf(b2, tanh_fast(b), b2)), u);
}

__device__ __forceinline__ const uint32_t* dep_counter(const Smem& sm, uint32_t jw, int rank, uint32_t k) {
  const Job J(jw);
  const uint32_t b = J.R * 2 + rank;
  const uint32_t line = J.type == T_O ? C_O + J.layer * 16 + b : J.type == T_D ? C_H + J.layer * 16 + b : C_X + max((int)J.inst() - 1, 0) * 16 + b;
  return counter(line, J.type & 1 ? k >> (J.type >> 1) : (k >> 2) * 2 + (k & 1));
}
__device__ __forceinline__ void producer(const Params& P, const Smem& sm, const uint32_t* jobs, const uint8_t* kseq, int rank, int lane, uint32_t launches) {
  const uint32_t e1 = __shfl_sync(~0u, launches, 0) + 1;
  uint32_t s = (jobs[0] & JOB_C) ? 0 : NSTAGE;
  uint32_t end = 0, poll = 0;
  uint64_t keep, stream;
  asm("createpolicy.fractional.L2::evict_unchanged.b64 %0, 1.0;" : "=l"(keep));
  asm("createpolicy.fractional.L2::evict_first.b64 %0, 1.0;" : "=l"(stream));
  const uint32_t* dep = counter(0, 0);
  const uint32_t summed_end = (jobs[0] & JOB_C) ? 0 : D / 64 + NSTAGE;
  for (int ji = 0;; ji++) {
    const uint32_t jw = jobs[ji];
    const Job J(jw);
    if (J.nk == 0) break;
    const bool isC = jw & JOB_C, isX = isC && (jw & JOB_X);
    const uint32_t target = (jw & 7) == 0 ? 0 : e1 * (J.type == T_Q ? 56 : J.type == T_G ? 16 : 1);
    const uint32_t g = J.col * 2 + rank;
    const CUtensorMap* tmA = &P.a[isC ? 4 + isX : (jw & 7) == 4 ? 2 : J.type];
    const CUtensorMap* tmB = &P.w[J.type];
    const uint32_t bytes = isC ? 32768 : J.type == T_Q ? 40960 : STAGE, bcol = J.col << (J.type == T_Q ? 0 : J.type == T_G ? 1 : 2);
    const uint32_t a0 = isX ? 0 : (g >> 2) * 128 + (g & 1) * 64, a1 = isX ? g * 64 : J.R * 128, ak = isX ? 0 : 256, a2 = isC ? (g >> 1) & 1 : rank;
    end += J.nk;
    uint32_t sa = s, spins = 0;
    auto issue_a = [&](uint32_t k) { TRS(sa, 1); tma3d(sm.stage(sa), tmA, isC ? a0 : (k & 63) * 64, isC ? a1 + k * ak : a1, isX ? k * 4 : a2, sm.full(sa), (k & K_LAST_A) ? stream : keep); };
    auto issue_b = [&](uint32_t k) {
      mbar_expect_tx(sm.full(s), bytes);
      TRS(s, 0);
      if (!isC) tma4d_mc(sm.stage(s) + SLOT + rank * SLOT, tmB, (k & 63) * 64 + rank * 32, bcol, sm.full(s), (k & K_LAST_B) ? stream : keep);
    };
    TRI(lane == 0, ji, 6);
    TRK(lane == 0, ji, 24);
    while (true) {
      const uint32_t missing = __ballot_sync(~0u, (int)(poll - target) < 0 && lane < J.nk);
      uint32_t lim = end;
      if (missing) lim += __ffs(missing) - 1 - J.nk;
      if (lim > sa) {
        fence_acquire();
        fence_proxy_async();
        TRI(sa == end - J.nk && lane == 0, ji, 7);
#pragma unroll 1
        for (; sa < min(lim, s); sa++) {
          const uint32_t k = kseq[sa];
          if (elect()) issue_a(k);
        }
#pragma unroll 1
        for (int phase = 0;; phase++) {
          const uint32_t upto = phase == 2 ? lim : phase == 1 ? lim - LOOK : min((int)lim - LOOK, (int)sa + MID);
#pragma unroll 1
          for (; (int)sa < (int)upto; sa++, s++) {
            const uint32_t k = kseq[s];
            uint32_t stage = sm.stage(s), bar = sm.full(s), c0 = isC ? a0 : (k & 63) * 64, c1 = isC ? a1 + k * ak : a1, kb = (k & 63) * 64 + rank * 32, c2 = isX ? k * 4 : a2;
            uint64_t pa = (k & K_LAST_A) ? stream : keep, pb = (k & K_LAST_B) ? stream : keep;
            asm volatile("" : "+r"(stage), "+r"(bar), "+r"(c0), "+r"(c1), "+r"(kb), "+r"(c2), "+l"(pa), "+l"(pb));
            if (s < summed_end) mbar_wait(sm.summed(s), par(s) ^ 1);
            mbar_wait(bar + 32, par(s) ^ 1);
            TRS(s, 0);
            asm volatile("{\n.reg .pred p, q;\nelect.sync _|p, -1;\nsetp.eq.and.u32 q, %14, 0, p;\n"
                         "@q cp.async.bulk.tensor.4d.shared::cluster.global.mbarrier::complete_tx::bytes.multicast::cluster.L2::cache_hint [%3], [%4, {%5, %6, %7, %5}], [%0], %8, %9;\n"
                         "@p cp.async.bulk.tensor.3d.shared::cluster.global.mbarrier::complete_tx::bytes.L2::cache_hint [%2], [%10, {%11, %12, %13}], [%0], %15;\n"
                         "@p mbarrier.arrive.expect_tx.shared::cta.b64 _, [%0], %1;\n}"
                         ::"r"(bar), "r"(bytes), "r"(stage), "r"(stage + SLOT + rank * SLOT), "l"(tmB), "r"(0), "r"(kb), "r"(bcol), "h"((uint16_t)3), "l"(pb),
                           "l"(tmA), "r"(c0), "r"(c1), "r"(c2), "r"((uint32_t)isC), "l"(pa) : "memory");
            TRS(s, 1);
          }
          if (phase == 2) break;
          if (phase == 1) poll = ld_relaxed(dep);
          else if (lim == end) dep = dep_counter(sm, jobs[ji + 1], rank, (reinterpret_cast<const uint32_t*>(kseq)[(end + lane) >> 2] >> ((end + lane) % 4 * 8)) & 63);
        }
        if (lim == end) break;
      } else {
        if (s < min(end, sa + NSTAGE) && __all_sync(~0u, mbar_test(sm.empty(s), par(s) ^ 1))) {
          const uint32_t k = kseq[s];
          if (s < summed_end) mbar_wait(sm.summed(s), par(s) ^ 1);
          if (elect()) issue_b(k);
          s++;
        }
        poll = ld_relaxed(dep);
        if (++spins > SPIN_LIMIT) __trap();
      }
    }
    TRI(lane == 0, ji, 8);
  }
}

__global__ void __cluster_dims__(2, 1, 1) __launch_bounds__(384, 1) mega_kernel(char* scratch, uint32_t by_place, const __grid_constant__ Params P) {
#undef TRW
#define TRW warp
  extern __shared__ __align__(1024) uint8_t smem_raw[];
  TRX(threadIdx.x == 320, JMAX - 1, 0, 1, "%%globaltimer_lo");
  TRX(threadIdx.x == 320, JMAX - 1, 0, 25, "%%clock");
  TRX(threadIdx.x == 320, JMAX - 1, 0, 28, "%%smid");
  Smem sm;
  sm.scratch = scratch;
  sm.base = smem_u32(smem_raw);
  if ((sm.base & 0x3FFFF) != SMEM_BASE) __trap();
  const int warp = __shfl_sync(~0u, threadIdx.x >> 5, 0);
  const int rank = blockIdx.x & 1;
  uint32_t smid;
  asm("mov.u32 %0, %%smid;" : "=r"(smid));
  const uint32_t pair = !by_place ? blockIdx.x >> 1 : smid < 2 * NPAIR - 8 ? (smid >> 1) + 4 : (smid >> 1) + 4 - NPAIR;
  const uint32_t* jobs = P.jobs[pair];
  const uint32_t launches = ld_relaxed(counter(C_EP, blockIdx.x + threadIdx.y));
  if (warp == 10) {
    if (elect()) {
      for (int i = 0; i < NSTAGE; i++) mbar_init(sm.full(i), 1);
      mbar_init(sm.boot(), 1);
      asm volatile("fence.mbarrier_init.release.cluster;" ::: "memory");
    }
    cluster_arrive();
    const uint32_t first = jobs[0];
    const bool isC = first & JOB_C;
    if (elect()) {
      prefetch_tm(&P.a[0]);
      prefetch_tm(&P.w[0]);
    }
    uint64_t keep;
    asm("createpolicy.fractional.L2::evict_unchanged.b64 %0, 1.0;" : "=l"(keep));
    const Job J(first);
    if (!isC) {
      if (elect()) {
        mbar_expect_tx(sm.full(0), 40960);
        tma3d(sm.stage(0), &P.a[0], 0, J.R * 128, rank, sm.full(0), keep);
        TRS(0, 1);
      }
      TRX(threadIdx.x == 320, JMAX - 1, 0, 26, "%%clock");
      cluster_wait();
      TRX(threadIdx.x == 320, JMAX - 1, 0, 27, "%%clock");
      if (elect()) {
        tma4d_mc(sm.stage(0) + SLOT + rank * SLOT, &P.w[0], rank * 32, J.col, sm.full(0), keep);
        TRS(0, 0);
      }
#pragma unroll 1
      for (int k = 1; k < NSTAGE; k++) {
        if (elect()) {
          tma4d_mc(sm.stage(k) + SLOT + rank * SLOT, &P.w[0], k * 64 + rank * 32, J.col, sm.full(k), keep);
          TRS(k, 0);
          mbar_expect_tx(sm.full(k), 40960);
          tma3d(sm.stage(k), &P.a[0], k * 64, J.R * 128, rank, sm.full(k), keep);
          TRS(k, 1);
        }
      }
    } else {
      cluster_wait();
      if (!(first & JOB_X)) mbar_wait(sm.boot(), 0);
    }
  } else {
    if (warp < 8 && elect()) {
      mbar_init(sm.kv_ready(warp), 1);
      if (warp == 3) {
        mbar_init(sm.aux_full(), 3); mbar_init(sm.wgmma_done(), 4); mbar_init(sm.mma_done(), 8); mbar_init(sm.xchg_full(), 1); mbar_init(sm.kv_ready(-1), 1);
        mbar_expect_tx(sm.xchg_full(), 768);
      } else if (warp > 3) {
        mbar_init(sm.empty(warp), 4); mbar_init(sm.summed(warp), 6); mbar_init(sm.filled(warp - 4), 4); mbar_init(sm.vacant(warp - 4), 3);
      }
      asm volatile("fence.mbarrier_init.release.cluster;" ::: "memory");
    }
    cluster_arrive();
  }
  TRI(threadIdx.x == 0, JMAX - 1, 0);

  if (warp < 8) {
    asm volatile("setmaxnreg.inc.sync.aligned.u32 208;");
    const uint32_t e1 = launches + 1;
    cluster_wait();
    const uint32_t wg = warp >> 2;
    uint32_t rel = (threadIdx.x & 95) == 0 ? mapa(sm.empty(0), (threadIdx.x & 32) ? rank ^ 1 : rank) : 0;
    uint32_t dst = sm.slot(0) + (warp & 3) * 2048 + (threadIdx.x & 15) * 128 + ((((threadIdx.x >> 4) & 1) ^ (threadIdx.x & 7)) << 4);
    uint32_t t8 = sm.slot(0) + (warp & 3) * 2048 + (threadIdx.x & 7) * 128 + ((((threadIdx.x >> 3) & 3) ^ (threadIdx.x & 7)) << 4);
    rel = __shfl_sync(~0u, rel, threadIdx.x);
    dst = __shfl_sync(~0u, dst, threadIdx.x);
    t8 = __shfl_sync(~0u, t8, threadIdx.x);
    const uint32_t da0 = ((SMEM_BASE >> 4) | (1 << 16)) + wg * 512, dba = (255 << 16) + 1024 - wg * 512;
    uint32_t pend[64], todo = 0, pbar = 0, vbar = sm.vacant(0), ppar = 0, poff = 0, direct = 0;
    uint32_t s = 0, na = 0, nb = 0, ready = 0;
    auto release = [&](uint32_t st) { mbar_arrive_cl_if(rel, rel + (st & (NSTAGE - 1)) * 8); };
    auto flush = [&](bool vacant) {
      if (__all_sync(~0u, vacant)) {
        const uint32_t a = dst + poff;
        if (todo & 2) {
#pragma unroll
          for (int j = 0; j < 4; j++) stsm4(a ^ (j << 5), pend[4 * j], pend[4 * j + 1], pend[4 * j + 2], pend[4 * j + 3]);
          if (todo == 2) {
#pragma unroll
            for (int j = 0; j < 4; j++) stsm4((a ^ (j << 5)) + 8192, pend[16 + 4 * j], pend[17 + 4 * j], pend[18 + 4 * j], pend[19 + 4 * j]);
          }
        } else {
#pragma unroll
          for (int j = 0; j < 8; j++) stsm4((a ^ ((j & 3) << 5)) + (j >> 2) * 8192, pend[32 + 4 * j], pend[33 + 4 * j], pend[34 + 4 * j], pend[35 + 4 * j]);
        }
        mbar_arrive_warp(pbar);
        pbar += 16; vbar += 16; ppar = ~nb & 1;
        todo = todo == 2;
      }
    };
    uint32_t jw = jobs[0];
#pragma unroll
    for (int i = 0; i < 64; i++) pend[i] = 0;
    for (int ji = 0;; ji++) {
      const uint32_t cur = jw, nk = (jw >> 12) & 63, isQ = (jw & 3) == T_Q;
      jw = jobs[ji + 1];
      if (__builtin_expect((cur & JOB_C) || !ready, 0)) {
        for (uint32_t spins = 0; todo && ((cur & JOB_C) || !ready);) {
          if (direct && todo == 1) {
            vbar = sm.empty(s); ppar = par(s) ^ 1; poff = sm.stage(s) - sm.slot(0) + wg * SLOT;
          }
          flush(mbar_test(vbar, ppar));
          ready = __all_sync(~0u, mbar_test(sm.full(s), par(s)));
          if (++spins > SPIN_LIMIT) __trap();
        }
        if (cur & JOB_C) {
          if (nk == 0) break;
          TRC(ji, 16);
          constexpr uint32_t ONES = 0x3f803f80;
          const uint32_t lane = fresh_tid() & 31, g = ((cur >> 6) & 63) * 2 + rank;
          if (!(cur & JOB_X)) {
            float d[4] = {0.f, 0.f, 0.f, 0.f};
            sts32(sm.xchg() + 128 + lane * 4, ONES);
            fence_proxy_async_smem();
            bar_sync<9, 256>();
#pragma unroll 1
            for (int i = 0; i < 4; i++, s++) {
              mbar_wait(sm.full(s), par(s));
              if (!wg) sum_columns(d, da0 + (s & (NSTAGE - 1)) * (STAGE / 16), (SMEM_BASE + AUX_OFF + 1600 + 128) >> 4);
              release(s);
            }
            const float c = lane & 1 ? d[2] : d[0], c1 = __shfl_down_sync(~0u, c, 4);
            asm volatile("{\n.reg .pred p;\nsetp.eq.u32 p, %2, 0;\n@p st.relaxed.gpu.global.u64 [%0], %1;\n}"
                         ::"l"(SCR(sm, cs, (16 * 128 + g * 32 + (warp & 3) * 8 + (lane & 1) * 4 + (lane >> 3)) * 8)), "l"(((u64)e1 << 32) | pack_bf16(c, c1)), "r"((lane & 6) | wg) : "memory");
          } else {
            float a[6][4];
#pragma unroll
            for (int n = 0; n < 24; n++) pend[n] = 0;
#pragma unroll 1
            for (int i = 0;; i++) {
              const uint32_t p = dst - sm.slot(0) + sm.stage(s) + wg * SLOT;
              mbar_wait(sm.full(s), par(s));
              uint32_t v[8][4];
#pragma unroll
              for (int n = 0; n < 24; n++) a[n / 4][n % 4] = __uint_as_float(pend[n]);
#pragma unroll
              for (int j = 0; j < 8; j++) ldsm4((p ^ ((j & 3) << 5)) + (j >> 2) * 8192, v[j]);
#pragma unroll
              for (int j = 0; j < 8; j++) {
                mma16816(a[4 + (j & 1)], v[j][0], v[j][1], v[j][2], v[j][3], ONES, ONES);
#pragma unroll
                for (int n = 0; n < 4; n++) mma1688(a[n], v[j][n & 2], v[j][(n & 2) + 1], v[j][n]);
              }
#pragma unroll
              for (int n = 0; n < 24; n++) pend[n] = __float_as_uint(a[n / 4][n % 4]);
              if (i == 3) break;
              bar_sync<9, 256>();
              release(s++);
            }
            const uint32_t part = sm.stage(s) + 2 * SLOT + lane * 8, row = g * 64 + (warp & 3) * 16 + wg * 8 + (lane >> 2);
            const bool odd = lane & 4;
            const float s0 = a[4][0] + a[5][0], q0 = odd ? a[0][1] + a[2][1] : a[0][0] + a[2][0];
            const float s1 = a[4][2] + a[5][2], q1 = odd ? a[1][3] + a[3][3] : a[1][2] + a[3][2];
            sts64(part + warp * 256, make_uint2(__float_as_uint(wg ? s0 : s1), __float_as_uint(wg ? q0 : q1)));
            bar_sync<9, 256>();
            const uint2 o = lds64(part + (warp ^ 4) * 256);
            fence_proxy_async_smem();
            bar_sync<9, 256>();
            release(s++);
            publish_stats(sm, (wg ? s1 : s0) + __uint_as_float(o.x), (wg ? q1 : q0) + __uint_as_float(o.y), (row & 1) * (S / 2) + (row >> 1), (lane & 3) == lane >> 3, e1);
          }
          ready = 0;
          TRC(ji, 18);
          continue;
        }
        if (!ready) mbar_wait(sm.full(s), par(s));
      }
      auto mainloop = [&](auto& acc, uint32_t nk, uint32_t last_lead, auto near_end) {
        const uint32_t lead = (jw >> 12) % 64 == 0 ? min(last_lead, nk - 2) : 2, turn = wg ? lead : nk - 2, hurry = nk - lead - wg;
        uint32_t owed = 0;
        uint32_t da = da0 + (s & (NSTAGE - 1)) * (STAGE / 16);
        if (todo == 3) mbar_wait(vbar, ppar);
        if (wg) bar_sync<13, 256>();
        TRC(ji, 16);
        first_kstep(acc, da, da + dba);
        if (!wg) bar_arrive<13, 256>();
        constexpr uint32_t CLEAR = sizeof(acc) == 96 * 4 ? PREP + 2 : 3;
        for (uint32_t left = nk - 1;; left--) {
          for (uint32_t spins = 0;; spins++) {
            const bool vacant = mbar_test(vbar, ppar), next_full = mbar_test(sm.full(s + 1), par(s + 1));
            wg_wait<2>();
            mbar_arrive_cl_if(owed, owed + ((s - 1) & (NSTAGE - 1)) * 8);
            owed = 0;
            ready = __all_sync(~0u, next_full);
            if (!todo) {
              near_end(left, vacant);
              break;
            }
            const bool go = ready && left >= max(CLEAR, lead + 1);
            if (!(go && spins)) flush(vacant);
            if (go) break;
            if (spins > SPIN_LIMIT) __trap();
          }
          if (left == 0) break;
          if (!ready) mbar_wait(sm.full(s + 1), par(s + 1));
          owed = rel;
          if (left == turn) {
            wg_wait<0>();
            release(s);
            owed = 0;
            if (wg) bar_sync<1, 256>();
          }
          if (left - lead < hurry) wg_wait<1>();
          s++;
          da = da0 + (s & (NSTAGE - 1)) * (STAGE / 16);
          kstep(acc, da, da + dba);
          if (left == 1 + wg * 64) bar_arrive<1, 256>();
        }
      };
      if (isQ) {
        float acc[96];
        const uint32_t lane = (((dst - SMEM_BASE) >> 7) & 15) | ((dst ^ (dst >> 3)) & 16), qpar = (na ^ nb) & 1;
        uint32_t prepare_at = PREP;
        mainloop(acc, nk, LAST_LEAD, [&](uint32_t left, bool aux_full) {
          if (left == PREP + 1) {
            vbar = sm.aux_full(); ppar = qpar;
          } else if (left == prepare_at) {
            if (left == 0) mbar_wait(vbar, ppar);
            if (left == 0 || __all_sync(~0u, aux_full)) attention_prepare(pend, sm, warp, lane, !(cur & 0x38));
            else prepare_at--;
          }
        });
        wg_wait<0>();
        release(s);
        u64 token = 0;
        asm volatile("{\n.reg .pred p;\nsetp.eq.u32 p, %2, 0;\n@p mbarrier.arrive.shared::cta.b64 %0, [%1];\n}" : "+l"(token) : "r"(sm.wgmma_done()), "r"(lane + 1 - wg) : "memory");
        pend[A_NM + 1] |= (uint32_t)token & pend[A_ZERO];
        TRC(ji, 18);
        ready = __all_sync(~0u, attention(acc, pend, sm, warp, lane, t8, dst, cur & JOB_EARLY, (((cur >> 2) & 1) * 16 + ((cur >> 3) & 7) * 2 + rank) * 16 + ((cur >> 6) & 15), e1, qpar,
                                          sm.full(s + 1), par(s + 1), ji));
        todo = 3; pbar = sm.filled(wg); vbar = sm.mma_done(); ppar = qpar; poff = SLOT + wg * 8192;
      } else {
        float acc[128];
        direct = (cur & 1) && (jw >> 12) % 64 == 0;
        const bool split = direct && nk >= SPLIT_MIN;
        mainloop(acc, split ? nk - 4 : nk, split ? 0 : LAST_LEAD, [](uint32_t, bool) {});
        pbar = sm.filled(wg); vbar = pbar + 32; ppar = na & 1; poff = wg * SLOT;
        nb++;
        todo = 2;
        if (__builtin_expect(split, 0)) {
          const uint32_t s0 = s;
          uint32_t d[4];
#pragma unroll
          for (int i = 0; i < 4; i++) d[i] = da0 + ((s0 + 1 + i) & (NSTAGE - 1)) * (STAGE / 16);
          wg_wait<0>();
          release(s0);
          float lo[64], hi[64];
#pragma unroll
          for (int i = 0; i < 64; i++) {
            asm volatile("mov.b32 %0, %1;" : "=f"(lo[i]) : "f"(acc[i]));
            asm volatile("mov.b32 %0, %1;" : "=f"(hi[i]) : "f"(acc[64 + i]));
          }
          if (wg) {
            bar_sync<1, 256>();
            bar_sync<3, 256>();
          }
#pragma unroll
          for (int i = 0; i < 3; i++) {
            mbar_wait(sm.full(s0 + 1 + i), par(s0 + 1 + i));
            half_kstep0(lo, d[i], d[i] + dba);
          }
          half_kstep1(hi, d[0], d[0] + dba);
          half_kstep1(hi, d[1], d[1] + dba);
          mbar_wait(sm.full(s0 + 4), par(s0 + 4));
          half_kstep0(lo, d[3], d[3] + dba);
          half_kstep1(hi, d[2], d[2] + dba);
          half_kstep1(hi, d[3], d[3] + dba);
          if (!wg) bar_arrive<3, 256>();
          s += 4;
          wg_wait<2>();
#pragma unroll
          for (int i = 0; i < 32; i++) pend[i] = pack_bf16(lo[2 * i], lo[2 * i + 1]);
          pbar = sm.filled(2 * wg); vbar = pbar + 32; poff = 0;
          if (wg) ppar = ~nb & 1;
          mbar_wait(vbar, ppar);
          const uint32_t parity = ppar;
          flush(true);
          pbar = sm.filled(2 * wg + 1); vbar = pbar + 32; poff = SLOT; ppar = parity;
          direct = 0;
          wg_wait<0>();
          TRC(ji, 18);
#pragma unroll
          for (int i = 0; i < 32; i++) pend[32 + i] = pack_bf16(hi[2 * i], hi[2 * i + 1]);
        } else {
          wg_wait<0>();
          release(s);
          const bool next_full = mbar_test(sm.full(s + 1), par(s + 1));
          TRC(ji, 18);
#pragma unroll
          for (int i = 0; i < 64; i++) {
            const int j = (i & 15) + (i & 16) * 2 + (i >> 5) * 16;
            pend[i] = pack_bf16(acc[2 * j], acc[2 * j + 1]);
          }
          ready = __all_sync(~0u, next_full);
        }
      }
      na++;
      s++;
    }
  } else {
    asm volatile("setmaxnreg.dec.sync.aligned.u32 88;");
    if (warp == 10) {
      producer(P, sm, jobs, P.kseq[pair], rank, threadIdx.x & 31, launches);
    } else {
      const uint32_t e1 = __shfl_sync(~0u, launches, 0) + 1;
      const int w = min(warp - 8, 2);
      cluster_wait();
      if (w == 1) asm volatile("st.shared::cluster.u32 [%0], %1;" ::"r"(mapa(sm.pair_id(), rank ^ 1)), "r"(pair) : "memory");
      const uint32_t boot = jobs[JMAX - 1] >> 24, pieces = (boot & 127) == 127 ? 0 : 1 + (boot >> 7), piece0 = (boot & 127) * 2 + rank * pieces;
      auto copy_rows = [&](uint32_t step, uint32_t n) {
        constexpr int IN = 2 * SLOT / BOOT_PIECES, OUT = 2 * SLOT / BOOT_OUT;
        const uint32_t rows = (piece0 + n) * 32768;
        if (step == BOOT_STEP) mbar_wait(sm.boot(), n & 1);
        if (elect()) {
          if (step == 0) mbar_expect_tx(sm.boot(), pieces ? 2 * SLOT : 0);
          if (step < BOOT_PIECES && pieces)
            asm volatile("cp.async.bulk.shared::cluster.global.mbarrier::complete_tx::bytes [%0], [%1], %2, [%3];"
                         ::"r"(sm.slot(0) + step * IN), "l"(at(P.x0, rows + step * IN)), "n"(IN), "r"(sm.boot()) : "memory");
          if (step - BOOT_STEP < BOOT_OUT && pieces) {
            asm volatile("cp.async.bulk.global.shared::cta.bulk_group [%0], [%1], %2;"
                         ::"l"(at(P.out, rows + (step - BOOT_STEP) * OUT)), "r"(sm.slot(0) + (step - BOOT_STEP) * OUT), "n"(OUT) : "memory");
            bulk_commit();
          }
        }
        if (step == BOOT_STEP + BOOT_OUT) {
          bulk_wait();
          if (n + 1 >= pieces && elect()) {
            mbar_arrive_n(sm.vacant(0), 3);
            mbar_arrive_n(sm.vacant(1), 3);
          }
        }
      };
      if (jobs[0] & JOB_C) {
        if (w == 2) {
          if (jobs[0] & JOB_X) mbar_wait(sm.full(3), 0);
#pragma unroll 1
          for (uint32_t n = 0; n == 0 || n < pieces; n++) {
#pragma unroll 1
            for (int i = 0; i <= BOOT_STEP + BOOT_OUT; i++) {
              copy_rows(i, n);
              bulk_wait_read<0>();
            }
          }
        }
      } else {
        const int lane = threadIdx.x & 31, word = (lane >> 3) * 24 + w * 8 + (lane & 7);
        Stager st;
        const uint32_t cs = qkv_col_sums(sm, rank, w, lane, [&](int s) {
          if (w == 2) copy_rows(s - 1, 0);
          if (w == 0 && s == ST_STEP) st.load(sm, Job(jobs[0]), rank, lane, false);
          if (w == 0 && s == ST_STEP + 2) st.store(sm, Job(jobs[0]), rank, lane, false, e1);
        });
        sts32(sm.sums() + word * 4, cs);
        mbar_arrive_warp(sm.aux_full());
        if ((jobs[0] & 0x38) == 0 && rank == 0) st_word(SCR(sm, cs, (((jobs[0] >> 6) & 15) * 128 + word) * 8), cs, e1);
      }
      bar_sync<2, 96>();
      if (w == 2 && pieces && elect()) {
        red_release(counter(C_RD + (piece0 >> 4) * 2, 0), pieces);
        red_relaxed(counter(C_RD + (piece0 >> 4) * 2 + 1, 0), pieces);
      }
      uint32_t na = 0, nb = 0, stages = 0;
      for (int ji = 0;; ji++) {
        const uint32_t jw = jobs[ji];
        const Job J(jw);
        if (J.nk == 0) break;
        stages += J.nk;
        if (w != 0 && ((jw >> 22) & 3) != 3) {
          stats_task(sm, jw, rank, w, e1, P.out);
          TRI(threadIdx.x == 11 * 32, ji, 10);
        }
        if (jw & JOB_C) continue;
        const int lane = fresh_tid() & 31;
        const uint32_t b = J.R * 2 + rank;
        if (w == 0 && !(J.type & 1) && ji != 0) {
          Stager st;
          st.load(sm, J, rank, lane, true);
          st.store(sm, J, rank, lane, true, e1);
          TRI(lane == 0, ji, 9);
        }
        if (J.type == T_G) {
          bar_sync<2, 96>();
          constexpr int PER = 16 / NG;
          const uint32_t swap = P.swap, never = jw, ac = sm.sums() + (lane & 7) * 16;
          uint32_t ag[NG], au[NG], as = sm.stats() + 64 + w * NG * 32 + (lane >> 3) * 8;
          uint32_t ho = (rank * (S / 2) + J.R * 128 + w * NG * 4 + (lane >> 3)) * (F * 2) + J.col * 256 + (lane & 7) * 16;
          uint4 cg = lds128(ac + (swap >> 5)), cu = lds128(ac + 256 - (swap >> 5)), g4[NG], u4[NG];
          uint2 st[NG];
          auto load = [&] {
#pragma unroll
            for (int i = 0; i < NG; i++) { st[i] = lds64v(as + i * 32); g4[i] = lds128v(ag[i]); u4[i] = lds128v(au[i]); }
          };
#pragma unroll
          for (int i = 0; i < NG; i++) {
            const uint32_t a = (sm.slot(0) + (w * NG + i) * 512 + (lane >> 3) * 128 + (((lane & 7) ^ (lane >> 3)) << 4)) ^ (((w * NG + i) & 1) << 6);
            ag[i] = a + swap; au[i] = a + (swap ^ 8192);
          }
          mbar_wait(sm.filled(0), na & 1);
          mbar_wait(sm.filled(1), na & 1);
          load();
          if (w == 2 && elect()) red_relaxed(counter(C_RD + J.inst() * 16 + b, 0), 1);
          TRI(threadIdx.x == 11 * 32, ji, 3);
#pragma unroll 1
          for (uint32_t g = w; g < 4 * PER; g += 3) {
            float hinv[NG], hinv2[NG];
            uint4 gc[NG], uc[NG];
            const bool turn = ((g + 3) ^ g) & PER, half = ((g + 3) ^ g) & (2 * PER);
#pragma unroll
            for (int i = 0; i < NG; i++) {
              hinv[i] = 0.5f * __uint_as_float(st[i].x);
              hinv2[i] = hinv[i] * __uint_as_float(st[i].x);
              asm volatile("" : "+f"(hinv[i]), "+f"(hinv2[i]));
              gc[i] = fma8(dup_hi(st[i].y), cg, g4[i]);
              uc[i] = fma8(dup_hi(st[i].y), cu, u4[i]);
              ag[i] = (ag[i] + NG * 1536) ^ ((NG & 1) << 6);
              au[i] = (au[i] + NG * 1536) ^ ((NG & 1) << 6);
            }
            as += NG * 96;
            if (turn) {
              mbar_arrive_warp(sm.vacant((g / PER) ^ 2));
              if (half) {
                cg = lds128(ac + (swap >> 5) + 128); cu = lds128(ac + 384 - (swap >> 5));
                as -= 1024;
              }
#pragma unroll
              for (int i = 0; i < NG; i++) { ag[i] += half ? -3 * 8192 : 8192; au[i] += half ? -3 * 8192 : 8192; }
              TRX(threadIdx.x == 11 * 32 && g < 3 * PER, ji, 25, 25 + g / PER * 2, "%%clock");
              if (g < 3 * PER) mbar_wait(sm.filled(g / PER + 1), (g < PER ? na : nb) & 1);
              TRX(threadIdx.x == 11 * 32 && g < 3 * PER, ji, 25, 26 + g / PER * 2, "%%clock");
            }
            load();
            if (g == never) mbar_wait(sm.boot(), 0);
            bf16* out = SCR(sm, h, ho);
#pragma unroll
            for (int i = 0; i < NG; i++)
              stg128(out + i * 4 * F, make_uint4(swiglu2(gc[i].x, uc[i].x, hinv[i], hinv2[i]), swiglu2(gc[i].y, uc[i].y, hinv[i], hinv2[i]),
                                                 swiglu2(gc[i].z, uc[i].z, hinv[i], hinv2[i]), swiglu2(gc[i].w, uc[i].w, hinv[i], hinv2[i])));
            ho += NG * 12 * F * 2 - (half ? 128 * F * 2 - 128 : 0);
          }
          bar_sync<2, 96>();
          TRI(threadIdx.x == 11 * 32, ji, 4);
          if (w == 2 && elect()) red_release(counter(C_H + J.layer * 16 + b, J.col), 1);
          TRI(threadIdx.x == 11 * 32, ji, 5);
        } else if (J.type == T_Q) {
          const bool late = J.R > 0 && !(jw & JOB_EARLY);
          if (w == 0) {
            __syncwarp();
            if (ji != 0 && elect()) mbar_arrive_n(sm.aux_full(), 3);
#pragma unroll 1
            for (int phase = 0; phase < 2; phase++) {
              if (J.R > 0 && phase == late) import_halo(sm, SCR(sm, halo, (((J.layer * 16 + b - 2) * 16 + J.col) * 256 + lane) * 16), e1, lane);
              if (phase == 0) {
                mbar_arrive_warp(sm.kv_ready(-1));
                TRI(lane == 0, ji, 11);
#pragma unroll 1
                for (int h = 0; h < 2; h++) {
                  mbar_wait(sm.filled(h), na & 1);
                  TRI(lane == 0, ji, 3);
                  fence_proxy_async_smem();
                  bulk_wait_read<0>();
                  if (elect()) {
                    tma3d_store(&P.ow, J.col * 64, J.R * 128 + h * 64, rank, sm.slot(1) + h * 8192);
                    bulk_commit();
                  }
                }
                if (J.layer && elect()) red_relaxed(counter(C_RD + 32 + b, 0), 1);
              }
            }
            bulk_wait();
          }
          if (late && w < 2) {
            bar_sync<7, 64>();
            boundary_rows(sm, w, lane, rank * O_PLANE + J.R * 128 * (D * 2) + J.col * 128);
            bar_sync<7, 64>();
          }
          TRI(threadIdx.x == 256, ji, 4);
          if (w == 0 && elect()) {
            mbar_arrive_n(sm.vacant(0), 3);
            mbar_arrive_n(sm.vacant(1), 3);
            red_release(counter(C_O + J.layer * 16 + b, J.col), 1);
          }
          TRI(threadIdx.x == 256, ji, 5);
        } else if (w == 0) {
          wait_count(counter(C_RD + J.inst() * 16 + b, 0), e1 * (J.type == T_D ? 28 : 16));
          fence_proxy_async();
          const bool last = Job(jobs[ji + 1]).nk == 0, split = last && J.nk >= SPLIT_MIN;
#pragma unroll 1
          for (uint32_t v = 0; v < 4; v++) {
            const uint32_t u = last && !split ? (v >> 1) + (v & 1) * 2 : v;
            mbar_wait(sm.filled(u), (u & 2 ? nb : na) & 1);
            TRI(u == 0 && lane == 0, ji, 3);
            fence_proxy_async_smem();
            const uint32_t src = (last && !split && (u & 2) ? sm.stage(stages) : sm.slot(0)) + (u & 1) * SLOT;
#pragma unroll 1
            for (uint32_t p = 0; p < 16384 / PIECE; p++) {
              if (elect()) {
                tma3d_reduce_add(&P.xr, J.col * 256 + (split ? (u & 1) * 128 + p * PIECE / 8192 * 64 : (u & 2) * 32 + p * PIECE / 8192 * 128),
                                 J.R * 128 + (split ? u >> 1 : u & 1) * 64 + p * PIECE % 8192 / 128, rank, src + p * PIECE);
                bulk_commit();
              }
              if (!last) bulk_wait_read<DEPTH - 1>();
            }
            if (!last) {
              bulk_wait();
              if (elect()) mbar_arrive_n(sm.vacant(u ^ 2), 3);
            } else if (split && (v == 1 || v == 2)) {
              bulk_wait_read<16384 / PIECE>();
              if (elect()) mbar_arrive_n(sm.vacant(v + 1), 3);
            }
            if (u == 1 && J.inst() != 3) bar_arrive<8, 64>();
          }
          bulk_wait();
        }
        if ((J.type & 1) && J.inst() != 3 && w < 2) {
          if (w == 1) bar_sync<8, 64>();
          TRX(lane == 0, ji, 4, w ? 12 : 4, "%%globaltimer_lo");
          if (elect()) red_release(counter(C_X + J.inst() * 16 + b, J.col * 2 + 1 - w), J.nk);
          TRX(lane == 0, ji, 5, w ? 13 : 5, "%%globaltimer_lo");
          if (w == 1) bar_arrive<10, 64>(); else bar_sync<10, 64>();
        }
        na++;
        nb += J.type != T_Q;
      }
      TRI(threadIdx.x == 8 * 32, JMAX - 1, 6);
      TRK(threadIdx.x == 8 * 32, JMAX - 1, 24);
      if (w == 0 && elect()) red_relaxed(counter(C_EP, blockIdx.x), 1);
      if (w == 2 && __float_as_uint(lds32f(sm.pair_id())) != pair) __trap();
    }
  }
  cluster_arrive();
  cluster_wait();
}

typedef CUresult (*EncodeFn)(CUtensorMap*, CUtensorMapDataType, cuuint32_t, void*, const cuuint64_t*, const cuuint64_t*, const cuuint32_t*,
                             const cuuint32_t*, CUtensorMapInterleave, CUtensorMapSwizzle, CUtensorMapL2promotion, CUtensorMapFloatOOBfill);
struct Dim { cuuint64_t size, stride; cuuint32_t box; };
template <int N> void encode(EncodeFn fn, CUtensorMap* m, const void* ptr, const Dim (&d)[N]) {
  cuuint64_t dims[N], strides[N];
  cuuint32_t box[N], es[N];
  for (int i = 0; i < N; i++) { dims[i] = d[i].size; strides[i] = d[i].stride; box[i] = d[i].box; es[i] = 1; }
  fn(m, CU_TENSOR_MAP_DATA_TYPE_BFLOAT16, N, const_cast<void*>(ptr), dims, strides + 1, box, es, CU_TENSOR_MAP_INTERLEAVE_NONE,
     CU_TENSOR_MAP_SWIZZLE_128B, CU_TENSOR_MAP_L2_PROMOTION_L2_128B, CU_TENSOR_MAP_FLOAT_OOB_FILL_NONE);
}

}

extern "C" void kernel_launch(void* const* d_in, const int* in_sizes, int n_in, void* d_out, int out_size) {
  (void)in_sizes; (void)n_in; (void)out_size;
  static EncodeFn fn = nullptr;
  static Scratch* scr;
  static int sms;
  if (!fn) {
    void* p = nullptr;
    cudaDriverEntryPointQueryResult q;
    cudaGetDriverEntryPoint("cuTensorMapEncodeTiled", &p, cudaEnableDefault, &q);
    fn = (EncodeFn)p;
    scr = scratch_base();
    int device = 0;
    cudaGetDevice(&device);
    cudaDeviceGetAttribute(&sms, cudaDevAttrMultiProcessorCount, device);
    cudaFuncSetAttribute(mega_kernel, cudaFuncAttributeMaxDynamicSharedMemorySize, SMEM_BYTES);
  }
  static Params P;
  const char *wg = (const char*)d_in[4], *wu = (const char*)d_in[5], *w0 = wg < wu ? wg : wu;
  const cuuint64_t plane = wg < wu ? wu - wg : wg - wu;
  P.swap = wg < wu ? 0 : 8192;
  encode(fn, &P.a[0], d_in[0], {{D, 2, 64}, {S / 2, D * 4, 128}, {2, D * 2, 1}});
  encode(fn, &P.a[1], scr->o, {{D, 2, 64}, {S / 2, D * 2, 128}, {2, O_PLANE, 1}});
  encode(fn, &P.ow, scr->o, {{D, 2, 64}, {S / 2, D * 2, 64}, {2, O_PLANE, 1}});
  encode(fn, &P.a[2], d_out, {{D, 2, 64}, {S / 2, D * 4, 128}, {2, D * 2, 1}});
  encode(fn, &P.a[3], scr->h, {{F, 2, 64}, {S / 2, F * 2, 128}, {2, (cuuint64_t)F * S, 1}});
  encode(fn, &P.a[4], w0, {{F, 2, 64}, {D, F * 2, 256}, {2, plane, 1}});
  encode(fn, &P.a[5], d_in[0], {{64, 2, 64}, {S, D * 2, 64}, {16, 128, 4}});
  encode(fn, &P.w[T_Q], d_in[1], {{64, 2, 64}, {D, 3 * D * 2, 32}, {16, 128, 1}, {3, D * 2, 3}});
  encode(fn, &P.w[T_O], d_in[2], {{64, 2, 64}, {D, D * 2, 32}, {16, 128, 4}, {1, (cuuint64_t)D * D * 2, 1}});
  encode(fn, &P.w[T_G], w0, {{64, 2, 64}, {D, F * 2, 32}, {F / 64, 128, 2}, {2, plane, 2}});
  encode(fn, &P.w[T_D], d_in[6], {{64, 2, 64}, {F, D * 2, 32}, {16, 128, 4}, {1, (cuuint64_t)F * D * 2, 1}});
  encode(fn, &P.xr, d_out, {{D, 2, 64}, {S / 2, D * 4, PIECE / 128}, {2, D * 2, 1}});
  memcpy(P.jobs, kJobs, sizeof(kJobs));
  memcpy(P.kseq, kSeq, sizeof(kSeq));
  P.x0 = (const bf16*)d_in[0];
  P.wqkv = (const bf16*)d_in[1];
  P.out = (bf16*)d_out;
  mega_kernel<<<2 * NPAIR, 384, SMEM_BYTES>>>((char*)scr, sms == 2 * NPAIR, P);
}
```

```cpp
#include <cuda_runtime.h>
#include <cuda_bf16.h>
#include <cuda.h>
#include <stddef.h>
#include <stdint.h>
#include <string.h>

namespace {

typedef __nv_bfloat16 bf16;
typedef unsigned long long u64;
constexpr int S = 2048, D = 1024, F = 3584;
constexpr int STAGE = 49152, NSTAGE = 4, SLOT = 16384;
constexpr int STG_OFF = NSTAGE * STAGE, BAR_OFF = STG_OFF + 2 * SLOT, AUX_OFF = BAR_OFF + 336;
constexpr int SMEM_BYTES = AUX_OFF + 2736;
constexpr int SMEM_BASE = 1024;
constexpr int NPAIR = 66, JMAX = 24, KMAX = 296;
constexpr int T_Q = 0, T_O = 1, T_G = 2, T_D = 3;
constexpr uint32_t JOB_C = 1u << 18;
constexpr uint32_t K_LAST_A = 64, K_LAST_B = 128;
constexpr uint32_t JOB_EARLY = 1u << 21;
constexpr uint32_t JOB_X = JOB_EARLY;
constexpr int BOOT_PIECES = 4, BOOT_OUT = 8, BOOT_STEP = 5, ST_STEP = 9;
constexpr int HEAD_START = 500;
constexpr int SPLIT_MIN = 7;
constexpr int PREP = 3, LAST_LEAD = 3;
constexpr int LOOK = 2, MID = 7;
constexpr int NG = 2, PIECE = 8192, DEPTH = 2;
constexpr uint32_t SPIN_LIMIT = 1u << 21;

constexpr int C_X = 0;
constexpr int C_O = C_X + 48;
constexpr int C_H = C_O + 32;
constexpr int C_RD = C_H + 32;
constexpr int C_EP = C_RD + 64;
constexpr int C_LINES = C_EP + 5;

struct Scratch {
  bf16 h[S * F];
  uint32_t cnt[256 * 32];
  bf16 o[S / 2 * D];
  u64 stats[4 * S];
  bf16 o1[S / 2 * D];
  u64 cs[44 * 128];
  ulonglong2 halo[2 * 16 * 16 * 8 * 32];
};
constexpr uint32_t O_PLANE = offsetof(Scratch, o1) - offsetof(Scratch, o);
static_assert(C_LINES <= 256, "");
constexpr size_t PAGE = 2 << 20;
__device__ __align__(1024) char g_scratch[sizeof(Scratch) + PAGE];
Scratch* scratch_base() {
  char* p;
  cudaGetSymbolAddress((void**)&p, g_scratch);
  return (Scratch*)(p + (-(size_t)p & (PAGE - 1)));
}

uint32_t kJobs[NPAIR][JMAX] = {
  {0xe44200,0xc10020,0xc44040,0xc08009,0xc10082,0x4101001a,0xc10022,0xc1800b,0x184170b3,0x46610054,0x5b610034,0x7d41000e,0xc1001e,0xc10076,0xc10096,0xc14037,0xc40000,0xc40000,0xc40000,0xc40000,0xc40000,0xc40000,0xc40000,0x80c40000},
  {0xe44000,0xc10018,0xc44080,0xc08009,0xc10021,0x22010052,0xc10092,0xc100aa,0xc09013,0x16410004,0x2d61004c,0x3461002c,0x4e410086,0xc10056,0x618100ae,0xc100b6,0xc1b02f,0xc40000,0xc40000,0xc40000,0xc40000,0xc40000,0xc40000,0x82c40000},
  {0xc10000,0xc44140,0xc04001,0xc10042,0x3a01004a,0xc1006a,0xc100b2,0xc1201b,0x26413033,0x6440b00d,0x681001d,0x3281002d,0xd48100a6,0xc101be,0xc1e007,0xc40000,0xc40000,0xc40000,0xc40000,0xc40000,0xc40000,0xc40000,0xc40000,0x7fc40000},
  {0xc10010,0xc440c0,0xc04001,0xc10002,0x3b01008a,0xc1019a,0xc101aa,0xc0800b,0x1a40d01b,0xc10014,0x66410064,0x2810006,0xc1008e,0xc10066,0xc1007e,0xc0e087,0xc1003f,0xc40000,0xc40000,0xc40000,0xc40000,0xc40000,0xc40000,0x7fc40000},
  {0xc10048,0xe10058,0xe10070,0xc05039,0x21010012,0x7a01b003,0xc1003a,0x29410044,0x3561001c,0x4f61005c,0x5761003c,0x7e41004e,0x6081009e,0xc100be,0xc1c00f,0xc40000,0xc40000,0xc40000,0xc40000,0xc40000,0xc40000,0xc40000,0xc40000,0x7fc40000},
  {0xe44240,0xc443c0,0xe10158,0xc10130,0xc040e1,0x170101ca,0x620101da,0xc101f2,0x641905b,0xc07063,0x324100c5,0x7a61016c,0x12a1013c,0x288101d6,0xc101ee,0xc10236,0xc1a04f,0xc40000,0xc40000,0xc40000,0xc40000,0xc40000,0xc40000,0x84c40000},
  {0xe44280,0xc44780,0xc10228,0x1f044840,0xe10270,0xc103ca,0x5e01039a,0xc103b2,0xc1042a,0xc103ba,0x6d4180bb,0x8810506,0xc100b5,0xd2810426,0xc103be,0xc1f097,0xc40000,0xc40000,0xc40000,0xc40000,0xc40000,0xc40000,0xc40000,0x86c40000},
  {0xe44380,0xc102d0,0xc040c1,0xc10091,0x1101044a,0x67010452,0xc1046a,0xc104f2,0x2c4170ab,0x5240e0bb,0x5810486,0xc104ce,0xc10466,0xc1047e,0xc1f09f,0xc40000,0xc40000,0xc40000,0xc40000,0xc40000,0xc40000,0xc40000,0xc40000,0x88c40000},
  {0xe442c0,0xc10320,0xc040c1,0x1d210338,0xc1054a,0x610105e2,0x7301e0cb,0xc10344,0xc1030c,0xc040bb,0x6041036c,0x1ca1033c,0x29810596,0x6c8105a6,0xc106f6,0xc1d0df,0xc40000,0xc40000,0xc40000,0xc40000,0xc40000,0xc40000,0xc40000,0x8ac40000},
  {0xe443c0,0xc10390,0xc44d80,0xc100d1,0x1501060a,0x64010612,0x720180c3,0x24106ba,0xc1038c,0x404103dc,0xc103f4,0x2c80c0e5,0x4d810656,0xc1066e,0xc1069e,0xc1a0ef,0xc40000,0xc40000,0xc40000,0xc40000,0xc40000,0xc40000,0xc40000,0x8cc40000},
  {0xc10088,0xe100e0,0xc10011,0x270100ca,0x6c01015a,0x7c01800b,0xc0d023,0x2140f0b3,0x516100dc,0xc10106,0xc1010e,0xc10166,0xc1013e,0xc1f017,0xc40000,0xc40000,0xc40000,0xc40000,0xc40000,0xc40000,0xc40000,0xc40000,0xc40000,0xec40000},
  {0xc10198,0xc101b0,0x1b0445c0,0xc44600,0xc446c0,0xc1030a,0x5d010322,0xc102f2,0xc0e04b,0xc101c4,0xc1707b,0x79410055,0xc07065,0xb0810075,0xd0810326,0xc10336,0xc1d05f,0xc40000,0xc40000,0xc40000,0xc40000,0xc40000,0xc40000,0xfc40000},
  {0xc10050,0xc10060,0xc10038,0x29210078,0x3e010062,0xc10032,0x441901b,0x2461000c,0x36610024,0x5d410074,0x228100ad,0x5b810026,0xc1006e,0xc1005e,0xc1203f,0xc40000,0xc40000,0xc40000,0xc40000,0xc40000,0xc40000,0xc40000,0xc40000,0x10c40000},
  {0xe44040,0xc444c0,0xc10168,0xc10049,0x1601024a,0x63010252,0xc10262,0xc1027a,0xc18073,0x55410045,0x48101c6,0xc1034e,0xc1035e,0xc1023e,0xc1e04f,0xc40000,0xc40000,0xc40000,0xc40000,0xc40000,0xc40000,0xc40000,0xc40000,0x91c40000},
  {0xe44080,0xc44700,0xe10220,0xc09089,0xc103c2,0x5a010412,0xc10512,0xc103f2,0x1e41c0a3,0x4961021c,0x58410234,0x36a1027c,0x4881041e,0x7281051e,0xc10436,0xc1909f,0xc40000,0xc40000,0xc40000,0xc40000,0xc40000,0xc40000,0xc40000,0x93c40000},
  {0xe44180,0xc44880,0xe102a0,0xc04081,0x1c2102f8,0xc104ca,0x66010462,0xc104ea,0xc104ba,0xc104fa,0xc102d4,0xc102ac,0x1d8104c6,0xc104d6,0x6d8104a6,0xc1053e,0xc0f087,0xc0c0b7,0xc40000,0xc40000,0xc40000,0xc40000,0xc40000,0x95c40000},
  {0xe440c0,0xc44ac0,0xc10328,0xc07041,0xc080c9,0xc0c0e1,0xb2010592,0xc105aa,0xc106e2,0x1d4130db,0xc090e3,0x484100fb,0xc810546,0x3f81054e,0x5d810566,0xc1057e,0xc200c7,0xc40000,0xc40000,0xc40000,0xc40000,0xc40000,0xc40000,0x97c40000},
  {0xe441c0,0xc44c40,0xc10398,0xc44d40,0xe103f0,0xc100f1,0xd0010692,0xc10632,0xc10672,0xc1067a,0x6f6103cc,0x736103a4,0x13810606,0xc1064e,0xc10626,0xc1067e,0xc0f0e7,0xc0e0ff,0xc40000,0xc40000,0xc40000,0xc40000,0xc40000,0x99c40000},
  {0xe44300,0xc100a0,0xc04001,0xc100c2,0x3c010112,0x7b01d003,0x741013a,0x234100c4,0x374100d4,0xc100ac,0x39a100fc,0xc10156,0x6981012e,0xc1019e,0xc1b01f,0xc40000,0xc40000,0xc40000,0xc40000,0xc40000,0xc40000,0xc40000,0xc40000,0x9bc40000},
  {0xe44340,0xc101d8,0xc09041,0xc10051,0x24010352,0xc1032a,0xc1b053,0x12410073,0xe101dc,0xe101ac,0xc10286,0x40810296,0x758102a6,0xc102e6,0xc19057,0xc40000,0xc40000,0xc40000,0xc40000,0xc40000,0xc40000,0xc40000,0xc40000,0x9dc40000},
  {0xc10008,0xc44000,0xc44100,0xe10068,0xc10029,0x3601009a,0xc1002a,0xc100a2,0xc1007a,0x3041803b,0xc0b095,0x10810046,0x41810016,0x7881002e,0xc1003e,0xc19037,0xc40000,0xc40000,0xc40000,0xc40000,0xc40000,0xc40000,0xc40000,0x1fc40000},
  {0xc10110,0xc44440,0xe10160,0xc101c2,0x4201021a,0xc10222,0xc10272,0xc101fa,0x3f410104,0x5e610114,0xc100dd,0x2081024e,0x5c8101e6,0xc101fe,0xc10047,0xc1007f,0xc40000,0xc40000,0xc40000,0xc40000,0xc40000,0xc40000,0xc40000,0x20c40000},
  {0xc10200,0xc44a00,0xc10260,0x3010402,0x4301050a,0xc10422,0xc0808b,0xc10432,0xc10244,0xe10214,0xc0b08d,0x7810386,0xc1050e,0x5f8103e6,0xc103fe,0xc1f0a7,0xc40000,0xc40000,0xc40000,0xc40000,0xc40000,0xc40000,0xc40000,0x7fc40000},
  {0xc102c0,0xc44900,0xc102b0,0x40449c0,0x120100b1,0x3801045a,0xc10472,0xa41a093,0x3d8102c4,0x4fa10294,0xe102e4,0xe102bc,0xc10516,0xc104e6,0xc104fe,0xc1b08f,0xc40000,0xc40000,0xc40000,0xc40000,0xc40000,0xc40000,0xc40000,0x7fc40000},
  {0xc10308,0xe10350,0xc44b00,0xe10378,0xc070f9,0x3f01059a,0xc105f2,0xc105ba,0x134105fa,0xe1034c,0xe10364,0xc106c6,0xc10556,0xc1055e,0xc105f6,0xc1e0ef,0xc40000,0xc40000,0xc40000,0xc40000,0xc40000,0xc40000,0xc40000,0x21c40000},
  {0xc10388,0xe103e0,0xc44d00,0xc10682,0x5801065a,0xc106aa,0xc41b0d3,0xc110eb,0x4a4130fb,0x3810686,0xc106ce,0xc106ee,0xc106a6,0xc1e0d7,0xc40000,0xc40000,0xc40000,0xc40000,0xc40000,0xc40000,0xc40000,0xc40000,0xc40000,0x22c40000},
  {0xe44100,0xc44180,0xe100d8,0xc44280,0xc10019,0x1001010a,0xc0b039,0xc10172,0xc1016a,0x1441a02b,0x4241009c,0xb8100f4,0x24810146,0x5981003d,0xf08100f6,0xc19017,0xc0c03f,0xc40000,0xc40000,0xc40000,0xc40000,0xc40000,0xc40000,0xa3c40000},
  {0xe44140,0xc101a0,0xc44640,0xc10059,0x1301028a,0x6501029a,0xc08079,0x71014053,0xc180e3,0xc0e07b,0xc101b4,0x37a101bc,0x4981007d,0x668102b6,0xc1033e,0xc1806f,0xc40000,0xc40000,0xc40000,0xc40000,0xc40000,0xc40000,0xc40000,0xa5c40000},
  {0x2e010040,0xe10028,0xe10030,0xc1000a,0x6801005a,0xc10072,0x40f013,0x104100ba,0x56410005,0x7161006c,0x14a1007c,0x2a810035,0x68810036,0xc1018e,0xc18027,0xc40000,0xc40000,0xc40000,0xc40000,0xc40000,0xc40000,0xc40000,0xc40000,0x7fc40000},
  {0xc10150,0xe10118,0xc44680,0xc10069,0x2f0101d2,0x7701c043,0x541023a,0x2241006b,0x4741011c,0xc10174,0x2f81020e,0xc1025e,0x7a8101f6,0xc10256,0xc0c05f,0xc0a077,0xc40000,0xc40000,0xc40000,0xc40000,0xc40000,0xc40000,0xc40000,0x27c40000},
  {0xc10208,0xc44740,0xc447c0,0xc04081,0xc07089,0x100a9,0xb00103da,0x7501d083,0x34103fa,0xe1020c,0xe10254,0xe1022c,0xc1038e,0xc1039e,0x768103b6,0xc1d08f,0xc0a0bf,0xc40000,0xc40000,0xc40000,0xc40000,0xc40000,0xc40000,0x28c40000},
  {0xc10290,0xc44940,0xc102f0,0x5010099,0x200080b9,0xd201049a,0xc104a2,0xc1047a,0xc0e09b,0x3e6102cc,0x5f40707b,0xc102f4,0x2b81048e,0xc1049e,0x7b8104b6,0xc104de,0xc160b7,0xc40000,0xc40000,0xc40000,0xc40000,0xc40000,0xc40000,0x29c40000},
  {0xc10318,0xc10358,0xc44b80,0xc10542,0x59010552,0xc1056a,0xc10572,0xc1c0eb,0x4b610314,0x59610374,0x7f61037c,0x158100fd,0x648105ae,0xc105e6,0xc180c7,0xc40000,0xc40000,0xc40000,0xc40000,0xc40000,0xc40000,0xc40000,0xc40000,0x2ac40000},
  {0xc103c0,0xc44c00,0xc103e8,0x6010602,0x4401061a,0xc090f9,0x7401a0cb,0xc170e3,0xc0d0fb,0xc103ec,0xc040e5,0x2e81068e,0xc1065e,0x7e8106b6,0xc1b0df,0xc0a0ff,0xc40000,0xc40000,0xc40000,0xc40000,0xc40000,0xc40000,0xc40000,0x7fc40000},
  {0xc100c8,0xc44240,0xc100b0,0x7010102,0x450100da,0xc1012a,0xc100f2,0xc100fa,0xe1008c,0xe10094,0xc0500d,0x1810186,0xc10196,0x6781016e,0xc100fe,0xc1d02f,0xc40000,0xc40000,0xc40000,0xc40000,0xc40000,0xc40000,0xc40000,0x2bc40000},
  {0xc101d0,0xe101e0,0xc100a1,0x250102ca,0x6e01031a,0x7e0102b2,0xc102ba,0xc0a06b,0x3161018c,0x676101ec,0x744102c6,0xc102d6,0x6f8102ae,0xc1032e,0xc1b067,0xc40000,0xc40000,0xc40000,0xc40000,0xc40000,0xc40000,0xc40000,0xc40000,0x2cc40000},
  {0xc10108,0xe10170,0xe10138,0xc08079,0x3701025a,0xc10232,0xc1404b,0x1b410144,0x2e610154,0x38610164,0x68410206,0xc101ce,0xc10226,0xc1037e,0xc1d067,0xc40000,0xc40000,0xc40000,0xc40000,0xc40000,0xc40000,0xc40000,0xc40000,0x2dc40000},
  {0xc10218,0xc10258,0xc10278,0x2a01040a,0xc080b9,0xc103ea,0xc1308b,0x1f41053a,0xc10085,0x7c61026c,0x16810406,0x478103d6,0x738103ae,0xc1042e,0xc19097,0xc40000,0xc40000,0xc40000,0xc40000,0xc40000,0xc40000,0xc40000,0xc40000,0x2ec40000},
  {0xc102c8,0xe102a8,0xc04081,0x1010482,0x5b010492,0x7601b083,0x941809b,0xe1028c,0xe102a4,0xc05095,0x11810446,0x42810496,0xc1046e,0xc104be,0xc190a7,0xc40000,0xc40000,0xc40000,0xc40000,0xc40000,0xc40000,0xc40000,0xc40000,0x2fc40000},
  {0xc10348,0xc44bc0,0xc10370,0x80105c2,0x4601058a,0x790200c3,0x14160db,0x3c410354,0x61610324,0x754105c6,0xc105d6,0x658106e6,0xc105fe,0xc1d0cf,0xc40000,0xc40000,0xc40000,0xc40000,0xc40000,0xc40000,0xc40000,0xc40000,0xc40000,0x30c40000},
  {0xc103d0,0xc103a8,0xc103f8,0x2b01064a,0x6901062a,0xc1069a,0xc106b2,0x27410384,0x394103d4,0x7b6103e4,0x17810646,0x448106d6,0xc106ae,0xc106be,0xc1a0e7,0xc40000,0xc40000,0xc40000,0xc40000,0xc40000,0xc40000,0xc40000,0xc40000,0x31c40000},
  {0xc100d0,0xe100a8,0xc100d9,0x2801018a,0x6d010132,0x7d010162,0xc1017a,0xc1102b,0x4140d03b,0xfa100ec,0x1b8100ce,0xc1015e,0x7d810136,0xc1a007,0xc0b037,0xc40000,0xc40000,0xc40000,0xc40000,0xc40000,0xc40000,0xc40000,0xc40000,0x32c40000},
  {0xc10190,0xc44580,0xc101f0,0x9010282,0x47010292,0xc102da,0xc102e2,0xc1033a,0xc10073,0x536101e4,0xc10306,0xc10356,0xc1029e,0xc102be,0xc1f057,0xc40000,0xc40000,0xc40000,0xc40000,0xc40000,0xc40000,0xc40000,0xc40000,0x33c40000},
  {0xc10148,0xc44400,0xc10128,0xa010202,0x4801020a,0xc101ea,0xc1604b,0x1c41037a,0x6e61010c,0x76610124,0x18810246,0xc10216,0x63810266,0xc1027e,0xc13047,0xc0a0bf,0xc40000,0xc40000,0xc40000,0xc40000,0xc40000,0xc40000,0xc40000,0x34c40000},
  {0xc10248,0xc44a40,0xc10268,0xb010382,0x490103d2,0xc103aa,0xc10532,0xc1043a,0xc120b3,0x50410264,0x8103c6,0xc10396,0xc103a6,0xc1043e,0xc1e0af,0xc40000,0xc40000,0xc40000,0xc40000,0xc40000,0xc40000,0xc40000,0xc40000,0x35c40000},
  {0xc10288,0x2c2102d8,0xe102b8,0xc1048a,0x6a0104d2,0xc104aa,0xc1052a,0x284150ab,0x5440e0bb,0xa81009d,0x34a102fc,0x4a81045e,0xc10476,0xc104ee,0xc110bf,0xc40000,0xc40000,0xc40000,0xc40000,0xc40000,0xc40000,0xc40000,0xc40000,0x36c40000},
  {0xc10340,0xc44a80,0xc10368,0xc010582,0x4a0106da,0xc105d2,0xc105ea,0xc106fa,0xc130f3,0x654100cd,0x1f810586,0xc105ce,0x6e8105ee,0xc105be,0xc0f0e7,0xc0c0f7,0xc40000,0xc40000,0xc40000,0xc40000,0xc40000,0xc40000,0xc40000,0x7fc40000},
  {0xc103d8,0xc44cc0,0xc040c1,0xc103b8,0x140106ca,0x5f010662,0xc106a2,0xc106ea,0xc1d0f3,0xc080fb,0xe8100d5,0x2381060e,0x5881061e,0xc10636,0xc106fe,0xc120ff,0xc40000,0xc40000,0xc40000,0xc40000,0xc40000,0xc40000,0xc40000,0x37c40000},
  {0xc10080,0xc441c0,0xc04001,0xc10142,0x3d0100d2,0xc101a2,0xc101ba,0xc12023,0x2540d02b,0x4340c03b,0x72410015,0x2681014e,0xc1011e,0xc100ee,0xc101a6,0xc0a027,0xc0a03f,0xc40000,0xc40000,0xc40000,0xc40000,0xc40000,0xc40000,0x7fc40000},
  {0xc10180,0xc44500,0xc101f8,0xd010302,0x4b0102d2,0x7801c043,0x8420063,0xc080f3,0x6241004d,0x1e809065,0x218100f5,0xd6810366,0xc102f6,0xc2006f,0xc40000,0xc40000,0xc40000,0xc40000,0xc40000,0xc40000,0xc40000,0xc40000,0xc40000,0x7fc40000},
  {0xc10140,0xc44380,0xc10120,0xe010342,0x4c01035a,0xc1022a,0xc1026a,0xc1e06b,0x4540c07b,0xc10134,0x3581006d,0x458101de,0x7c810276,0xc10376,0xc15077,0xc40000,0xc40000,0xc40000,0xc40000,0xc40000,0xc40000,0xc40000,0xc40000,0x7fc40000},
  {0xc10240,0xc44800,0xe10230,0xc10502,0x4d010392,0xc1041a,0xc103a2,0xc1209b,0x2040c0ab,0x4441025c,0xd810274,0x2581040e,0xc103de,0x7f8103f6,0xc10526,0xc130bf,0xc40000,0xc40000,0xc40000,0xc40000,0xc40000,0xc40000,0xc40000,0x7fc40000},
  {0xc10298,0xc448c0,0xc102e8,0xf010442,0x4e0104da,0xc10522,0xc104b2,0xc1c0a3,0x4c41029c,0x706102b4,0x1981044e,0x5a8100bd,0x6a810536,0xc1052e,0xc160b7,0xc40000,0xc40000,0xc40000,0xc40000,0xc40000,0xc40000,0xc40000,0xc40000,0x38c40000},
  {0xc10300,0xe10330,0xc44dc0,0xc100e9,0xb401055a,0xc105a2,0xc105b2,0xc106f2,0xc0b0eb,0x4d61035c,0x5a61032c,0xc1058e,0xc1059e,0x7781056e,0xc105de,0xc170f7,0xc40000,0xc40000,0xc40000,0xc40000,0xc40000,0xc40000,0xc40000,0x7fc40000},
  {0xc103c8,0xe103a0,0xc04081,0x2010642,0x5c010652,0xc10622,0xb41d0d3,0x3c8103c4,0x4ba1039c,0xe103b4,0xe103bc,0xc10616,0xc1062e,0xc1063e,0xc1a0d7,0xc40000,0xc40000,0xc40000,0xc40000,0xc40000,0xc40000,0xc40000,0xc40000,0x39c40000},
  {0xc100c0,0xc442c0,0xc100b8,0x192100f8,0x2301014a,0xc100e2,0xc100ea,0xc19023,0x336100cc,0x694100e4,0x3aa100bc,0xc10116,0xc101ae,0xc1017e,0xc1d01f,0xc40000,0xc40000,0xc40000,0xc40000,0xc40000,0xc40000,0xc40000,0xc40000,0x7fc40000},
  {0xc10188,0xe101a8,0xc080c9,0x18010071,0x400102a2,0xc102ea,0xc10332,0x11410184,0x2f6101d4,0x3a6101a4,0x6a410346,0xc102ce,0xc102de,0xc1036e,0xc15047,0xc0a07f,0xc40000,0xc40000,0xc40000,0xc40000,0xc40000,0xc40000,0xc40000,0x3ac40000},
  {0xc10100,0xc44480,0xc10178,0xc10242,0x4f010212,0xc101e2,0xe41f05b,0x2b61014c,0x3b61015c,0x6b61012c,0x7761017c,0x1a81021e,0x7481022e,0xc1026e,0xc19077,0xc40000,0xc40000,0xc40000,0xc40000,0xc40000,0xc40000,0xc40000,0xc40000,0x7fc40000},
  {0xc10210,0x2d210250,0xe10238,0xc1038a,0x6b0103e2,0x7001d08b,0x19410204,0xe1024c,0xe10224,0xe1023c,0xc040a5,0x4e8103ce,0xc103ee,0xc10416,0xc1a0af,0xc40000,0xc40000,0xc40000,0xc40000,0xc40000,0xc40000,0xc40000,0xc40000,0x3bc40000},
  {0xc10280,0xc44980,0xc102e0,0xc104c2,0x5401051a,0xc104e2,0xd41e093,0xc10284,0xc102dc,0xc102ec,0xc0c0a5,0x3e810456,0x6b8104ae,0xc104f6,0xc1b087,0xc40000,0xc40000,0xc40000,0xc40000,0xc40000,0xc40000,0xc40000,0xc40000,0x7fc40000},
  {0xc10310,0xc44b40,0xc10360,0xc106c2,0x550105ca,0xc10562,0xc105da,0xc1057a,0xc10304,0xc1031c,0xc10334,0x278100ed,0x438106de,0xc10576,0xc105b6,0xc150f7,0xc40000,0xc40000,0xc40000,0xc40000,0xc40000,0xc40000,0xc40000,0x3cc40000},
  {0xc10380,0xc44c80,0xc040c1,0x1e2103b0,0xc1068a,0x600106d2,0xc1066a,0xc1063a,0xc0f0db,0x3d610394,0x6c4103ac,0x3ba103fc,0xc10696,0xc10666,0xc10676,0xc0f0cf,0xc0e0ff,0xc40000,0xc40000,0xc40000,0xc40000,0xc40000,0xc40000,0x7fc40000},
  {0xc10090,0xc44200,0xc100e8,0x1a044340,0xc10031,0x39010152,0xc10122,0xc101b2,0x17410084,0xc11033,0x5c40703b,0xc100b4,0x2d810025,0x468100de,0x79810176,0xc101b6,0xc16027,0xc40000,0xc40000,0xc40000,0xc40000,0xc40000,0xc40000,0x3dc40000},
  {0xc101c8,0xc101e8,0xc10061,0x2601034a,0x6f0102aa,0x7f01036a,0xc102fa,0xe101cc,0xc1019c,0xc101f4,0x38a101fc,0x4c810316,0xc102ee,0xc1030e,0xc0c0cf,0xc0e07f,0xc40000,0xc40000,0xc40000,0xc40000,0xc40000,0xc40000,0xc40000,0x3ec40000},
  {0xc10098,0xc44300,0xc100f0,0xc10182,0x56010192,0xc1011a,0xf420013,0x2a414033,0x636100a4,0x784100c6,0xc100d6,0x628100e6,0xc10126,0xc1c00f,0xc40000,0xc40000,0xc40000,0xc40000,0xc40000,0xc40000,0xc40000,0xc40000,0xc40000,0x3fc40000},
  {0xc101c0,0xc44540,0xc101b8,0xc102c2,0x57010312,0xc10362,0xc10372,0xc09053,0x15411063,0xc10194,0xc0508d,0x981005d,0x3381028e,0x5e81031e,0xc102fe,0xc0f05f,0xc1007f,0xc40000,0xc40000,0xc40000,0xc40000,0xc40000,0xc40000,0x7fc40000},
};
uint8_t kSeq[NPAIR][KMAX] = {
  {0,1,2,3,0,1,2,3,4,5,6,7,8,9,10,11,12,13,14,15,0,1,2,3,64,67,72,78,76,70,66,74,64,66,76,78,65,67,77,79,68,70,69,71,72,74,73,75,4,6,0,2,5,7,1,3,12,14,8,10,13,15,9,11,4,6,8,10,0,2,5,7,9,11,12,14,1,3,13,15,88,89,94,95,116,117,118,119,106,107,78,79,82,83,112,113,84,85,102,103,98,99,72,73,72,73,80,81,98,99,74,75,110,111,112,113,86,87,92,93,78,79,64,65,66,67,84,68,70,69,71,76,78,72,74,64,66,77,79,73,75,65,67,68,70,72,74,69,71,64,66,76,78,73,75,65,67,77,79,8,10,0,2,9,11,12,14,1,3,4,6,13,15,5,7,12,14,8,10,4,6,0,2,13,15,9,11,5,7,1,3,12,14,8,10,13,15,4,6,9,11,5,7,0,2,1,3,200,202,73,75,196,198,192,194,204,206,197,199,193,195,205,207,71,66,67,112,113,98,99,86,87,110,111,114,115,88,89,118,119,196,197,230,0,0,0,0,0,0,0,0,0,0,0,0,0,0,0,0,0,0,0,0,0,0,0,0,0,0,0,0,0,0,0,0,0,0,0,0,0,0,0,0,0,0,0,0,0,0,0,0,0,0,0,0,0},
  {0,1,2,3,0,1,2,3,4,5,6,7,8,9,10,11,12,13,14,15,0,1,2,3,77,69,73,79,65,68,75,71,70,64,76,66,74,72,79,71,78,67,69,65,75,77,68,73,12,14,8,10,13,15,9,11,0,2,4,6,1,3,5,7,76,78,72,74,77,79,73,75,64,66,68,70,65,67,69,71,4,6,12,14,8,10,0,2,5,7,13,15,9,11,1,3,114,115,100,101,74,75,116,117,118,0,2,4,6,8,10,1,3,5,7,12,14,9,11,13,15,76,78,68,70,77,79,64,66,72,74,69,71,65,67,73,75,12,14,4,6,0,2,13,15,5,7,8,10,1,3,9,11,8,10,12,14,0,2,9,11,13,15,1,3,4,6,5,7,8,10,9,11,4,6,0,2,12,14,5,7,1,3,13,15,4,6,12,14,8,10,5,7,13,15,9,11,0,2,1,3,12,14,8,10,13,15,4,6,9,11,5,7,128,130,1,3,99,64,65,80,81,92,93,108,109,106,107,70,71,66,67,90,91,88,89,82,83,224,225,232,233,230,231,0,0,0,0,0,0,0,0,0,0,0,0,0,0,0,0,0,0,0,0,0,0,0,0,0,0,0,0,0,0,0,0,0,0,0,0,0,0,0,0,0,0,0,0,0,0,0,0,0,0,0,0},
  {64,65,66,67,68,69,70,71,72,73,74,75,76,77,78,79,0,1,2,3,79,75,77,73,0,2,12,14,1,3,13,15,4,6,5,7,8,10,9,11,64,66,72,74,65,67,73,75,76,78,68,70,77,79,69,71,4,6,12,14,8,10,0,2,5,7,13,15,9,11,1,3,0,2,8,10,4,6,12,14,1,3,9,11,5,7,13,15,83,98,99,108,109,92,93,78,79,84,85,100,101,66,67,74,75,88,66,67,84,85,68,69,90,91,104,105,70,71,210,211,228,229,106,107,222,71,72,69,66,64,78,74,77,76,75,73,64,71,78,77,69,72,75,70,74,79,76,73,68,67,66,65,64,71,78,74,77,70,73,69,66,72,76,79,68,65,67,75,4,6,5,7,8,10,12,14,9,11,13,15,0,2,1,3,4,6,12,14,8,10,5,7,13,15,0,2,9,11,1,3,106,107,104,105,92,93,88,89,72,73,90,91,100,101,78,79,116,117,64,65,118,119,208,209,94,95,76,77,240,241,0,0,0,0,0,0,0,0,0,0,0,0,0,0,0,0,0,0,0,0,0,0,0,0,0,0,0,0,0,0,0,0,0,0,0,0,0,0,0,0,0,0,0,0,0,0,0,0,0,0,0,0,0,0,0,0,0,0,0,0,0,0,0,0,0,0},
  {0,1,2,3,4,5,6,7,8,9,10,11,12,13,14,15,0,1,2,3,66,74,68,64,0,2,12,14,1,3,13,15,4,6,5,7,8,10,9,11,64,66,72,74,65,67,73,75,76,78,68,70,77,79,69,71,4,6,0,2,5,7,1,3,12,14,8,10,13,15,9,11,4,6,12,14,8,10,128,130,5,7,13,15,9,11,129,131,92,93,64,65,100,101,96,97,89,76,77,96,97,86,87,72,73,116,117,110,111,4,6,5,7,12,14,8,10,0,2,13,15,9,11,1,3,0,2,1,3,4,6,8,10,12,14,5,7,9,11,13,15,8,10,12,14,0,2,9,11,13,15,1,3,4,6,5,7,8,10,0,2,9,11,12,14,1,3,4,6,13,15,5,7,4,6,5,7,8,10,12,14,9,11,13,15,0,2,1,3,4,6,12,14,8,10,5,7,13,15,0,2,9,11,1,3,77,112,113,110,111,82,83,70,71,68,69,102,103,108,80,81,66,67,90,91,96,97,242,243,202,203,70,199,238,239,0,0,0,0,0,0,0,0,0,0,0,0,0,0,0,0,0,0,0,0,0,0,0,0,0,0,0,0,0,0,0,0,0,0,0,0,0,0,0,0,0,0,0,0,0,0,0,0,0,0,0,0,0,0,0,0,0,0,0,0,0},
  {64,65,66,67,68,69,70,71,72,73,74,75,76,77,78,79,64,65,66,67,68,69,70,71,72,73,74,75,76,77,78,79,64,65,66,67,68,69,70,71,72,73,74,75,76,77,78,79,198,69,194,199,204,12,14,8,10,13,15,9,11,0,2,4,6,1,3,5,7,70,71,64,65,98,99,92,93,78,79,112,113,94,95,72,73,80,81,84,85,114,115,116,117,106,107,66,136,138,128,130,137,139,129,131,140,142,141,143,132,134,133,135,0,2,4,6,8,10,1,3,5,7,12,14,9,11,13,15,4,6,5,7,0,2,8,10,12,14,1,3,9,11,13,15,68,70,69,71,64,66,72,74,76,78,65,67,73,75,77,79,132,134,128,130,133,135,129,131,136,138,140,142,137,139,141,143,8,10,0,2,9,11,12,14,1,3,4,6,13,15,5,7,12,14,8,10,4,6,0,2,13,15,9,11,5,7,1,3,4,6,12,14,8,10,5,7,13,15,0,2,137,139,1,3,92,93,108,109,98,99,80,81,100,101,70,71,116,117,96,97,74,75,64,65,112,113,82,83,234,235,212,213,0,0,0,0,0,0,0,0,0,0,0,0,0,0,0,0,0,0,0,0,0,0,0,0,0,0,0,0,0,0,0,0,0,0,0,0,0,0,0,0,0,0,0,0},
  {0,1,2,3,0,1,2,3,0,1,2,3,4,5,6,7,8,9,10,11,12,13,14,15,0,1,2,3,4,5,6,7,8,9,10,11,12,13,14,15,70,64,76,66,0,2,8,10,1,3,9,11,12,14,4,6,13,15,5,7,4,6,0,2,5,7,1,3,12,14,8,10,13,15,9,11,0,2,8,10,4,6,12,14,1,3,9,11,5,7,13,15,93,78,79,84,85,100,101,66,67,74,75,88,89,76,77,96,97,86,87,72,73,116,117,110,111,84,85,88,89,114,115,110,66,71,70,77,69,73,72,64,65,78,67,75,79,74,76,68,12,14,4,6,0,2,13,15,5,7,8,10,1,3,9,11,132,134,128,130,133,135,129,131,136,138,140,142,137,139,141,143,8,10,9,11,4,6,0,2,12,14,5,7,1,3,13,15,4,6,12,14,8,10,5,7,13,15,9,11,0,2,1,3,140,142,136,138,141,143,132,134,137,139,133,135,128,130,129,131,72,73,86,87,102,103,90,91,118,119,68,69,206,207,114,115,66,67,110,111,94,95,88,217,204,205,0,0,0,0,0,0,0,0,0,0,0,0,0,0,0,0,0,0,0,0,0,0,0,0,0,0,0,0,0,0,0,0,0,0,0,0,0,0,0,0,0,0,0,0,0,0,0,0,0,0},
  {0,1,2,3,0,1,2,3,0,1,2,3,4,5,6,7,8,9,10,11,12,13,14,15,0,1,2,3,0,1,2,3,4,5,6,7,8,9,10,11,12,13,14,15,0,2,8,10,1,3,9,11,12,14,4,6,13,15,5,7,4,6,0,2,5,7,1,3,12,14,8,10,13,15,9,11,0,2,8,10,4,6,12,14,1,3,9,11,5,7,13,15,4,6,12,14,8,10,0,2,5,7,13,15,137,11,1,3,136,138,128,130,137,139,129,131,140,142,141,143,132,134,133,135,204,205,236,237,240,241,210,211,226,227,228,229,192,193,200,201,208,209,202,203,212,213,214,215,8,10,12,14,0,2,9,11,13,15,1,3,4,6,5,7,78,74,77,71,70,64,66,69,79,200,75,68,204,73,195,65,4,6,5,7,8,10,12,14,9,11,13,15,0,2,1,3,132,134,140,142,136,138,133,135,141,143,128,130,137,139,129,131,99,102,103,86,87,104,105,78,79,118,119,114,115,88,89,112,113,100,101,64,65,84,85,94,95,224,225,82,83,196,197,0,0,0,0,0,0,0,0,0,0,0,0,0,0,0,0,0,0,0,0,0,0,0,0,0,0,0,0,0,0,0,0,0,0,0,0,0,0,0,0,0,0,0,0,0,0,0,0,0,0,0,0,0},
  {0,1,2,3,0,1,2,3,4,5,6,7,8,9,10,11,12,13,14,15,66,74,68,64,64,74,76,66,68,70,65,72,79,67,69,71,78,75,77,73,0,2,8,10,1,3,9,11,12,14,4,6,13,15,5,7,12,14,8,10,13,15,9,11,0,2,4,6,1,3,5,7,4,6,12,14,8,10,0,2,5,7,13,15,9,11,1,3,0,2,8,10,4,6,12,14,1,3,9,11,5,7,13,15,99,100,101,90,91,70,71,76,77,68,69,110,111,82,83,74,75,96,97,118,119,104,105,238,239,242,243,232,233,218,219,220,221,230,231,196,197,8,10,12,14,0,2,9,11,13,15,1,3,4,6,5,7,8,10,0,2,9,11,12,14,1,3,4,6,13,15,5,7,4,6,5,7,8,10,12,14,9,11,13,15,0,2,1,3,4,6,140,142,136,138,133,135,141,143,128,130,137,139,129,131,80,81,96,97,92,93,108,109,70,71,82,83,100,101,78,79,74,75,114,115,94,95,118,119,200,201,192,193,240,241,226,0,0,0,0,0,0,0,0,0,0,0,0,0,0,0,0,0,0,0,0,0,0,0,0,0,0,0,0,0,0,0,0,0,0,0,0,0,0,0,0,0,0,0,0,0,0,0,0,0,0,0,0,0,0,0,0,0,0,0,0},
  {0,1,2,3,0,1,2,3,4,5,6,7,8,9,10,11,12,13,14,15,69,76,67,65,0,1,2,3,4,5,6,7,8,9,10,11,12,13,14,15,0,2,8,10,1,3,9,11,12,14,4,6,13,15,5,7,4,6,8,10,0,2,5,7,9,11,12,14,1,3,13,15,88,89,94,95,116,117,118,119,106,107,78,79,82,83,112,113,84,85,102,103,98,99,72,73,92,93,64,65,100,101,0,2,4,6,8,10,1,3,5,7,12,14,9,11,13,15,12,14,4,6,13,15,0,2,8,10,5,7,1,3,9,11,222,223,244,245,12,14,4,6,0,2,13,15,5,7,8,10,1,3,9,11,132,134,128,130,133,135,129,131,136,138,140,142,137,139,141,143,8,10,9,11,4,6,0,2,12,14,5,7,1,3,13,15,4,6,5,7,8,10,12,14,9,11,13,15,0,2,1,3,12,14,8,10,13,15,4,6,9,11,5,7,0,2,1,3,65,112,113,98,99,88,89,86,87,84,85,90,91,106,235,68,69,104,105,76,77,116,117,110,111,102,103,194,195,0,0,0,0,0,0,0,0,0,0,0,0,0,0,0,0,0,0,0,0,0,0,0,0,0,0,0,0,0,0,0,0,0,0,0,0,0,0,0,0,0,0,0,0,0,0,0,0,0},
  {0,1,2,3,0,1,2,3,4,5,6,7,8,9,10,11,12,13,14,15,0,1,2,3,64,74,76,66,68,70,65,72,79,67,69,71,78,75,77,73,0,2,8,10,1,3,9,11,12,14,4,6,13,15,5,7,12,14,8,10,13,15,9,11,0,2,4,6,1,3,5,7,96,97,82,83,74,75,110,111,76,77,88,89,118,119,68,69,100,101,104,105,102,103,90,91,136,138,128,130,9,11,129,131,140,142,141,143,132,134,133,135,12,14,4,6,13,15,0,2,8,10,5,7,1,3,9,11,4,6,5,7,0,2,8,10,12,14,1,3,9,11,13,15,4,6,8,10,5,7,0,2,12,14,9,11,1,3,13,15,77,69,78,72,76,68,66,73,79,67,75,65,8,10,9,11,4,6,0,2,12,14,5,7,1,3,13,15,4,6,12,14,8,10,5,7,13,15,9,11,0,2,1,3,12,14,8,10,132,134,0,2,141,143,9,11,133,135,129,131,64,65,80,81,92,93,108,109,106,107,70,71,66,67,90,91,88,89,82,83,96,97,232,233,230,231,0,0,0,0,0,0,0,0,0,0,0,0,0,0,0,0,0,0,0,0,0,0,0,0,0,0,0,0,0,0,0,0,0,0,0,0,0,0,0,0,0,0,0,0,0,0,0,0,0,0},
  {64,65,66,67,68,69,70,71,72,73,74,75,76,77,78,79,0,1,2,3,4,5,6,7,8,9,10,11,12,13,14,15,64,74,76,66,68,70,65,72,79,67,69,71,78,75,77,73,0,2,8,10,1,3,9,11,12,14,4,6,13,15,5,7,4,6,0,2,5,7,1,3,12,14,8,10,13,15,9,11,114,115,76,77,70,71,86,87,90,91,74,75,66,67,68,69,80,81,108,109,110,111,104,105,84,85,88,89,114,115,110,111,98,99,66,67,94,85,68,69,90,91,104,105,70,71,210,211,100,101,234,235,4,6,5,7,0,2,8,10,12,14,1,3,9,11,13,15,8,10,12,14,0,2,9,11,13,15,1,3,4,6,5,7,8,10,0,2,9,11,12,14,1,3,4,6,13,15,5,7,4,6,5,7,8,10,12,14,9,11,13,15,0,2,1,3,4,6,12,14,8,10,133,135,13,15,0,2,137,139,1,3,99,102,103,86,87,104,105,78,79,118,119,114,115,88,89,112,113,100,101,64,65,84,85,94,95,224,225,210,211,196,197,0,0,0,0,0,0,0,0,0,0,0,0,0,0,0,0,0,0,0,0,0,0,0,0,0,0,0,0,0,0,0,0,0,0,0,0,0,0,0,0,0,0,0,0,0,0,0,0,0,0,0,0,0},
  {0,1,2,3,4,5,6,7,8,9,10,11,12,13,14,15,0,1,2,3,4,5,6,7,8,9,10,11,12,13,14,15,0,1,2,3,0,1,2,3,0,1,2,3,0,2,8,10,1,3,9,11,12,14,4,6,13,15,5,7,4,6,8,10,0,2,5,7,9,11,12,14,1,3,13,15,0,2,8,10,4,6,12,14,1,3,9,11,5,7,13,15,72,73,92,93,64,65,100,101,96,97,114,115,76,77,0,2,4,6,8,10,1,3,5,7,12,14,9,11,13,15,204,205,108,109,112,113,210,211,226,227,228,229,192,193,200,201,208,209,202,203,212,213,214,71,69,72,78,64,77,75,74,79,73,67,76,70,68,66,65,68,66,73,79,67,75,65,78,74,77,71,70,64,194,69,207,200,75,196,204,73,195,65,4,6,5,7,8,10,12,14,9,11,13,15,0,2,1,3,12,14,8,10,13,15,4,6,9,11,5,7,0,2,1,3,65,112,113,98,99,88,89,86,87,84,85,90,91,106,107,68,69,104,105,76,77,116,117,238,239,102,103,194,195,0,0,0,0,0,0,0,0,0,0,0,0,0,0,0,0,0,0,0,0,0,0,0,0,0,0,0,0,0,0,0,0,0,0,0,0,0,0,0,0,0,0,0,0,0,0,0,0,0,0,0},
  {0,1,2,3,4,5,6,7,8,9,10,11,12,13,14,15,0,1,2,3,4,5,6,7,8,9,10,11,12,13,14,15,0,1,2,3,4,5,6,7,8,9,10,11,12,13,14,15,64,65,66,67,68,69,70,71,72,73,74,75,76,77,78,79,4,6,8,10,0,2,5,7,9,11,12,14,1,3,13,15,0,2,8,10,4,6,12,14,1,3,9,11,5,7,13,15,64,65,70,71,80,81,112,113,90,91,102,103,118,119,104,105,114,115,106,107,94,95,68,69,82,12,14,4,6,13,15,0,2,8,10,5,7,1,3,9,11,0,2,1,3,4,6,8,10,12,14,5,7,9,11,13,15,68,70,72,74,69,71,64,66,76,78,73,75,65,67,77,79,64,71,78,74,77,70,73,69,66,72,76,79,68,65,67,75,4,6,5,7,8,10,12,14,9,11,13,15,0,2,1,3,4,6,12,14,8,10,5,7,13,15,9,11,0,2,1,3,204,206,200,202,196,198,192,194,205,207,201,203,197,199,193,195,78,79,106,107,86,87,94,95,76,77,220,221,72,73,98,227,212,213,0,0,0,0,0,0,0,0,0,0,0,0,0,0,0,0,0,0,0,0,0,0,0,0,0,0,0,0,0,0,0,0,0,0,0,0,0,0,0,0,0,0,0,0,0},
  {0,1,2,3,0,1,2,3,0,1,2,3,4,5,6,7,8,9,10,11,12,13,14,15,64,67,72,77,69,73,78,76,70,66,74,79,65,68,75,71,0,2,8,10,1,3,9,11,12,14,4,6,13,15,5,7,12,14,8,10,13,15,9,11,0,2,4,6,1,3,5,7,4,6,8,10,0,2,5,7,9,11,12,14,1,3,13,15,136,138,128,130,137,139,129,131,140,142,141,143,132,134,133,135,78,79,64,65,66,67,84,85,68,69,90,91,104,105,70,71,210,211,100,101,106,107,222,223,66,71,70,77,69,73,72,64,65,78,67,75,79,74,76,68,8,10,12,14,0,2,9,11,13,15,1,3,4,6,5,7,8,10,0,2,9,11,12,14,1,3,4,6,13,15,5,7,12,14,8,10,4,6,0,2,13,15,9,11,5,7,1,3,4,6,12,14,8,10,5,7,141,143,0,2,137,139,1,3,92,93,108,109,98,99,80,81,100,101,70,71,116,117,96,97,74,75,64,65,112,113,82,83,106,107,212,213,232,233,0,0,0,0,0,0,0,0,0,0,0,0,0,0,0,0,0,0,0,0,0,0,0,0,0,0,0,0,0,0,0,0,0,0,0,0,0,0,0,0,0,0,0,0,0,0,0,0,0,0,0,0,0,0,0,0,0,0},
  {0,1,2,3,0,1,2,3,0,1,2,3,4,5,6,7,8,9,10,11,12,13,14,15,64,67,72,77,69,73,78,76,70,64,66,76,78,65,67,77,79,68,70,69,71,72,74,73,75,12,14,8,10,13,15,9,11,0,2,4,6,1,3,5,7,76,78,72,74,77,79,73,75,64,66,68,70,65,67,69,71,0,2,8,10,4,6,12,14,1,3,9,11,5,7,13,15,84,85,88,89,114,115,110,111,98,99,66,67,94,95,70,71,76,77,106,107,96,97,64,65,78,79,90,91,4,6,5,7,0,2,8,10,12,14,1,3,9,11,13,15,4,6,8,10,5,7,0,2,12,14,9,11,1,3,13,15,132,134,128,130,133,135,129,131,136,138,140,142,137,139,141,143,12,14,8,10,4,6,0,2,13,15,9,11,5,7,1,3,12,14,8,10,4,6,0,2,13,15,9,11,5,7,1,3,12,14,8,10,13,15,132,134,9,11,133,135,128,130,129,131,99,88,89,86,87,84,85,90,91,234,235,68,69,104,105,76,77,116,117,110,111,102,103,194,195,0,0,0,0,0,0,0,0,0,0,0,0,0,0,0,0,0,0,0,0,0,0,0,0,0,0,0,0,0,0,0,0,0,0,0,0,0,0,0,0,0,0,0,0,0,0,0,0,0,0},
  {0,1,2,3,0,1,2,3,0,1,2,3,4,5,6,7,8,9,10,11,12,13,14,15,79,75,77,73,0,1,2,3,4,5,6,7,8,9,10,11,12,13,14,15,0,2,8,10,1,3,9,11,12,14,4,6,13,15,5,7,4,6,8,10,0,2,5,7,9,11,12,14,1,3,13,15,4,6,12,14,8,10,0,2,5,7,13,15,9,11,1,3,136,138,128,130,137,139,129,131,140,142,141,143,132,134,133,135,136,138,128,130,137,139,129,131,140,142,141,143,132,134,133,135,4,6,5,7,12,14,8,10,0,2,13,15,9,11,1,3,12,14,4,6,0,2,13,15,5,7,8,10,1,3,9,11,8,10,12,14,0,2,9,11,13,15,1,3,4,6,5,7,8,10,9,11,4,6,0,2,12,14,5,7,1,3,13,15,4,6,5,7,8,10,12,14,9,11,13,15,0,2,1,3,4,6,12,14,8,10,5,7,13,15,0,2,9,11,1,3,109,86,87,114,115,98,99,66,67,84,85,96,97,74,75,102,103,80,81,96,97,76,77,218,219,236,237,0,0,0,0,0,0,0,0,0,0,0,0,0,0,0,0,0,0,0,0,0,0,0,0,0,0,0,0,0,0,0,0,0,0,0,0,0,0,0,0,0,0,0,0,0,0,0,0,0},
  {0,1,2,3,0,1,2,3,0,1,2,3,4,5,6,7,8,9,10,11,12,13,14,15,72,78,70,71,66,74,68,70,66,74,79,65,68,75,71,74,72,79,71,78,67,69,65,75,77,68,73,12,14,8,10,13,15,9,11,0,2,4,6,1,3,5,7,4,6,12,14,8,10,0,2,5,7,13,15,9,11,1,3,4,6,8,10,0,2,5,7,9,11,12,14,1,3,13,15,68,69,82,83,98,99,108,109,92,93,78,79,84,85,100,101,66,67,74,75,86,87,92,93,118,119,68,69,216,217,198,199,206,207,246,247,194,195,238,239,242,243,232,233,8,10,12,14,0,2,9,11,13,15,1,3,4,6,5,7,8,10,0,2,9,11,12,14,1,3,4,6,13,15,5,7,4,6,5,7,8,10,12,14,9,11,13,15,0,2,1,3,132,134,140,142,136,138,133,135,141,143,128,130,137,139,129,131,106,107,104,105,92,93,88,89,72,73,90,91,100,101,78,79,116,117,64,65,118,119,208,209,94,95,76,77,240,241,238,239,0,0,0,0,0,0,0,0,0,0,0,0,0,0,0,0,0,0,0,0,0,0,0,0,0,0,0,0,0,0,0,0,0,0,0,0,0,0,0,0,0,0,0,0,0,0,0,0,0,0,0,0,0,0,0,0,0},
  {0,1,2,3,0,1,2,3,0,1,2,3,4,5,6,7,8,9,10,11,12,13,14,15,0,1,2,3,0,1,2,3,4,5,6,7,8,9,10,11,12,13,14,15,76,69,70,72,74,66,71,75,67,77,68,73,79,206,64,65,12,14,8,10,13,15,9,11,0,2,4,6,1,3,5,7,0,2,8,10,4,6,12,14,1,3,9,11,5,7,13,15,0,2,8,10,4,6,12,14,1,3,9,11,5,7,13,15,136,138,128,130,137,139,129,131,140,142,141,143,132,134,133,135,12,14,4,6,13,15,0,2,8,10,5,7,1,3,9,11,0,2,1,3,4,6,8,10,12,14,5,7,9,11,13,15,8,10,12,14,0,2,9,11,13,15,1,3,4,6,5,7,8,10,0,2,9,11,12,14,1,3,4,6,13,15,5,7,4,6,5,7,8,10,12,14,9,11,13,15,0,2,1,3,4,6,140,142,136,138,5,7,141,143,0,2,137,139,129,131,75,98,99,66,67,80,81,92,93,114,115,112,113,88,89,110,111,82,83,68,69,104,105,108,109,102,103,244,245,0,0,0,0,0,0,0,0,0,0,0,0,0,0,0,0,0,0,0,0,0,0,0,0,0,0,0,0,0,0,0,0,0,0,0,0,0,0,0,0,0,0,0,0,0,0,0},
  {0,1,2,3,0,1,2,3,4,5,6,7,8,9,10,11,12,13,14,15,69,76,67,65,0,2,12,14,1,3,13,15,4,6,5,7,8,10,9,11,12,14,8,10,13,15,9,11,0,2,4,6,1,3,5,7,67,108,109,86,87,96,97,82,83,74,75,110,111,76,77,88,89,118,119,68,69,100,101,104,105,102,103,90,91,136,138,128,130,137,139,129,131,140,142,141,143,132,134,133,135,0,2,4,6,8,10,1,3,5,7,12,14,9,11,13,15,4,6,5,7,12,14,8,10,0,2,13,15,9,11,1,3,12,14,4,6,0,2,13,15,5,7,8,10,1,3,9,11,132,134,128,130,133,135,129,131,136,138,140,142,137,139,141,143,8,10,9,11,4,6,0,2,12,14,5,7,1,3,13,15,4,6,12,14,8,10,5,7,13,15,9,11,0,2,1,3,12,14,8,10,4,6,0,2,13,15,9,11,5,7,1,3,80,81,96,97,92,93,108,109,70,71,82,83,100,101,206,207,74,75,114,115,94,95,118,119,200,201,192,0,0,0,0,0,0,0,0,0,0,0,0,0,0,0,0,0,0,0,0,0,0,0,0,0,0,0,0,0,0,0,0,0,0,0,0,0,0,0,0,0,0,0,0,0,0,0,0,0,0,0,0,0,0,0,0},
  {0,1,2,3,0,1,2,3,4,5,6,7,8,9,10,11,12,13,14,15,64,79,75,77,73,69,76,67,65,64,74,76,66,68,70,65,72,79,67,69,71,78,75,77,73,12,14,8,10,13,15,9,11,0,2,4,6,1,3,5,7,4,6,12,14,8,10,0,2,5,7,13,15,9,11,1,3,76,77,88,89,106,107,78,79,96,97,108,109,114,115,100,101,74,75,116,117,118,119,82,83,112,113,98,72,73,80,81,98,99,74,75,110,111,112,113,86,87,92,93,4,6,5,7,0,2,8,10,12,14,1,3,9,11,13,15,12,14,4,6,0,2,13,15,5,7,8,10,1,3,9,11,8,10,12,14,0,2,9,11,13,15,1,3,4,6,5,7,8,10,9,11,4,6,0,2,12,14,5,7,1,3,13,15,4,6,5,7,8,10,12,14,9,11,13,15,0,2,1,3,132,134,133,135,136,138,140,142,137,139,141,143,128,130,129,131,90,91,106,107,92,93,116,117,72,73,76,77,108,109,110,111,208,209,70,71,66,67,202,203,226,0,0,0,0,0,0,0,0,0,0,0,0,0,0,0,0,0,0,0,0,0,0,0,0,0,0,0,0,0,0,0,0,0,0,0,0,0,0,0,0,0,0,0,0,0,0,0,0,0,0,0,0,0,0,0},
  {64,65,66,67,68,69,70,71,72,73,74,75,76,77,78,79,0,1,2,3,0,1,2,3,64,65,66,67,68,69,70,71,72,73,74,75,76,77,78,79,72,76,64,70,66,74,71,78,67,79,65,197,75,68,73,77,4,6,0,2,5,7,1,3,12,14,8,10,13,15,9,11,4,6,12,14,8,10,0,2,5,7,13,15,9,11,1,3,68,70,72,74,64,66,69,71,73,75,76,78,65,67,77,79,136,138,128,130,137,139,129,131,140,142,141,143,132,134,133,135,76,77,108,109,112,113,82,83,226,227,100,101,64,65,200,201,208,209,202,203,212,213,214,215,71,69,72,78,64,77,75,74,79,73,67,8,10,12,14,0,2,9,11,13,15,1,3,4,6,5,7,8,10,9,11,4,6,0,2,12,14,5,7,1,3,13,15,4,6,12,14,8,10,5,7,13,15,9,11,0,2,1,3,132,134,140,142,136,138,133,135,141,143,128,130,137,139,129,131,64,65,84,85,92,93,104,105,74,75,78,79,100,101,82,83,72,73,116,117,222,223,234,235,198,0,0,0,0,0,0,0,0,0,0,0,0,0,0,0,0,0,0,0,0,0,0,0,0,0,0,0,0,0,0,0,0,0,0,0,0,0,0,0,0,0,0,0,0,0,0,0,0,0,0,0,0},
  {0,1,2,3,4,5,6,7,8,9,10,11,12,13,14,15,0,1,2,3,64,65,66,67,68,69,70,71,72,73,74,75,76,77,78,79,64,66,76,78,65,67,77,79,68,70,69,71,72,74,73,75,4,6,0,2,5,7,1,3,12,14,8,10,13,15,9,11,4,6,8,10,0,2,5,7,9,11,12,14,1,3,13,15,0,2,8,10,4,6,12,14,1,3,9,11,5,7,13,15,136,138,128,130,137,139,129,131,140,142,141,143,132,134,133,135,64,66,68,70,72,74,65,67,69,71,76,78,73,75,77,79,68,70,69,71,76,78,72,74,64,66,77,79,73,75,65,67,64,71,78,77,69,72,75,70,74,79,76,73,68,67,66,65,8,10,0,2,9,11,12,14,1,3,4,6,13,15,5,7,4,6,5,7,8,10,12,14,9,11,13,15,0,2,1,3,132,134,140,142,136,138,133,135,141,143,128,130,137,139,129,131,106,107,104,105,92,93,88,89,72,73,90,91,100,101,78,79,84,85,80,81,66,67,90,91,96,97,242,243,202,203,198,199,0,0,0,0,0,0,0,0,0,0,0,0,0,0,0,0,0,0,0,0,0,0,0,0,0,0,0,0,0,0,0,0,0,0,0,0,0,0,0,0,0,0,0,0,0,0,0,0,0,0,0,0},
  {64,65,66,67,68,69,70,71,72,73,74,75,76,77,78,79,0,1,2,3,64,65,66,67,68,69,70,71,72,73,74,75,76,77,78,79,64,66,76,78,65,67,77,79,68,70,69,71,72,74,73,75,64,66,72,74,65,67,73,75,76,78,68,70,77,79,69,71,4,6,8,10,0,2,5,7,9,11,12,14,1,3,13,15,80,81,108,109,110,111,104,105,0,2,8,10,4,6,12,14,1,3,9,11,5,7,13,15,0,2,4,6,8,10,1,3,5,7,12,14,9,11,13,15,4,6,5,7,12,14,8,10,0,2,13,15,9,11,1,3,71,72,69,66,64,78,74,77,76,75,73,8,10,12,14,0,2,9,11,13,15,1,3,4,6,5,7,8,10,0,2,9,11,12,14,1,3,4,6,13,15,5,7,4,6,5,7,8,10,12,14,9,11,13,15,0,2,1,3,132,134,140,142,136,138,133,135,141,143,128,130,137,139,129,131,64,65,78,79,90,91,106,107,94,95,68,69,96,97,74,75,98,99,66,67,80,81,220,221,242,243,112,113,216,217,236,0,0,0,0,0,0,0,0,0,0,0,0,0,0,0,0,0,0,0,0,0,0,0,0,0,0,0,0,0,0,0,0,0,0,0,0,0,0,0,0,0,0,0,0,0,0,0,0,0,0},
  {64,65,66,67,68,69,70,71,72,73,74,75,76,77,78,79,0,1,2,3,0,1,2,3,4,5,6,7,8,9,10,11,12,13,14,15,0,1,2,3,76,69,70,72,74,66,71,75,67,77,68,73,79,78,64,65,4,6,0,2,5,7,1,3,12,14,8,10,13,15,9,11,0,2,8,10,4,6,12,14,1,3,9,11,5,7,13,15,108,109,114,115,100,101,74,75,116,117,118,119,82,83,112,113,98,99,102,103,68,69,110,111,104,105,0,2,4,6,8,10,1,3,5,7,12,14,9,11,13,15,4,6,5,7,12,14,8,10,0,2,13,15,9,11,1,3,64,66,65,67,68,70,72,74,76,78,69,71,73,75,77,79,132,134,128,130,133,135,129,131,136,138,140,142,137,139,141,143,8,10,9,11,4,6,0,2,12,14,5,7,1,3,13,15,4,6,5,7,8,10,12,14,9,11,13,15,0,2,1,3,4,6,12,14,8,10,5,7,13,15,0,2,9,11,1,3,105,72,73,86,87,102,103,90,91,118,119,68,69,78,79,114,115,66,67,110,111,94,95,216,217,204,205,0,0,0,0,0,0,0,0,0,0,0,0,0,0,0,0,0,0,0,0,0,0,0,0,0,0,0,0,0,0,0,0,0,0,0,0,0,0,0,0,0,0,0},
  {64,65,66,67,68,69,70,71,72,73,74,75,76,77,78,79,64,65,66,67,68,69,70,71,72,73,74,75,76,77,78,79,0,1,2,3,0,1,2,3,4,5,6,7,8,9,10,11,12,13,14,15,198,197,194,199,204,203,206,4,6,0,2,5,7,1,3,12,14,8,10,13,15,9,11,0,2,8,10,4,6,12,14,1,3,9,11,5,7,13,15,136,138,128,130,9,11,129,131,140,142,141,143,132,134,133,135,136,138,128,130,137,139,129,131,140,142,141,143,132,134,133,135,12,14,4,6,13,15,0,2,8,10,5,7,1,3,9,11,0,2,1,3,4,6,8,10,12,14,5,7,9,11,13,15,8,10,12,14,0,2,9,11,13,15,1,3,4,6,5,7,8,10,9,11,4,6,0,2,12,14,5,7,1,3,13,15,12,14,8,10,4,6,0,2,13,15,9,11,5,7,1,3,12,14,8,10,13,15,4,6,9,11,5,7,0,2,1,3,118,119,76,77,74,75,68,69,72,73,100,101,110,111,84,85,206,207,116,117,94,95,242,243,86,87,240,241,226,227,0,0,0,0,0,0,0,0,0,0,0,0,0,0,0,0,0,0,0,0,0,0,0,0,0,0,0,0,0,0,0,0,0,0,0,0,0,0,0,0,0,0,0,0,0,0,0},
  {64,65,66,67,68,69,70,71,72,73,74,75,76,77,78,79,0,1,2,3,4,5,6,7,8,9,10,11,12,13,14,15,0,1,2,3,64,66,76,78,65,67,77,79,68,70,69,71,72,74,73,75,4,6,0,2,5,7,1,3,12,14,8,10,13,15,9,11,4,6,12,14,8,10,0,2,5,7,13,15,9,11,1,3,97,108,109,114,115,100,101,74,75,116,117,118,119,82,83,112,113,98,99,102,103,68,69,110,111,104,105,114,115,102,103,98,99,100,101,90,91,70,71,76,77,68,69,110,193,200,201,208,209,202,203,212,213,214,215,222,223,244,245,234,235,224,225,8,10,12,14,0,2,9,11,13,15,1,3,4,6,5,7,8,10,0,2,9,11,12,14,1,3,4,6,13,15,5,7,4,6,12,14,8,10,5,7,13,15,9,11,0,2,1,3,4,6,5,7,8,10,140,142,9,11,13,15,0,2,1,3,90,91,106,107,92,93,116,117,72,73,76,77,108,109,110,111,80,81,70,71,66,67,74,75,98,99,102,103,214,215,0,0,0,0,0,0,0,0,0,0,0,0,0,0,0,0,0,0,0,0,0,0,0,0,0,0,0,0,0,0,0,0,0,0,0,0,0,0,0,0,0,0,0,0,0,0,0,0,0,0,0,0,0,0,0},
  {0,1,2,3,0,1,2,3,0,1,2,3,4,5,6,7,8,9,10,11,12,13,14,15,0,1,2,3,74,66,76,79,70,72,64,67,71,69,78,68,75,65,77,73,0,2,8,10,1,3,9,11,12,14,4,6,13,15,5,7,203,206,200,202,196,201,207,205,195,192,193,0,2,8,10,4,6,12,14,1,3,9,11,5,7,13,15,4,6,12,14,8,10,0,2,5,7,13,15,137,139,129,131,112,113,84,85,88,89,66,67,78,79,92,93,72,73,80,81,106,107,116,117,236,237,64,65,94,95,4,6,5,7,0,2,8,10,12,14,1,3,9,11,13,15,4,6,8,10,5,7,0,2,12,14,9,11,1,3,13,15,72,74,76,78,64,66,73,75,77,79,65,67,68,70,69,71,72,79,194,76,192,67,202,196,199,206,198,197,205,201,193,203,12,14,8,10,13,15,4,6,9,11,5,7,0,2,1,3,90,91,106,107,92,93,116,117,72,73,76,77,108,109,110,111,80,81,70,71,66,67,74,75,98,82,83,68,69,104,105,108,109,102,103,244,245,0,0,0,0,0,0,0,0,0,0,0,0,0,0,0,0,0,0,0,0,0,0,0,0,0,0,0,0,0,0,0,0,0,0,0,0,0,0,0,0,0,0,0,0,0,0,0,0,0,0},
  {0,1,2,3,0,1,2,3,4,5,6,7,8,9,10,11,12,13,14,15,0,1,2,3,74,66,76,79,70,72,64,67,71,69,78,68,75,65,77,73,0,2,8,10,1,3,9,11,12,14,4,6,13,15,5,7,4,6,0,2,5,7,1,3,12,14,8,10,13,15,9,11,202,196,201,207,205,195,192,193,90,91,70,71,72,73,66,67,64,65,84,85,92,93,80,81,86,87,94,95,84,85,88,89,114,115,110,111,98,99,66,67,94,95,70,71,76,77,106,107,96,97,64,65,215,222,223,244,245,234,235,224,225,216,217,198,199,206,4,6,8,10,5,7,0,2,12,14,9,11,1,3,13,15,132,134,128,130,133,135,129,131,136,138,140,142,137,139,141,143,72,79,194,76,192,67,202,196,199,206,198,197,205,201,193,203,12,14,8,10,13,15,4,6,9,11,5,7,0,2,1,3,4,6,12,14,136,138,5,7,13,15,128,130,137,139,129,131,80,81,92,93,108,109,106,107,70,71,66,67,90,91,88,89,82,83,224,225,232,233,230,231,0,0,0,0,0,0,0,0,0,0,0,0,0,0,0,0,0,0,0,0,0,0,0,0,0,0,0,0,0,0,0,0,0,0,0,0,0,0,0,0,0,0,0,0,0,0,0,0,0,0,0,0,0,0},
  {64,65,66,67,68,69,70,71,72,73,74,75,76,77,78,79,0,1,2,3,4,5,6,7,8,9,10,11,12,13,14,15,64,65,66,67,68,69,70,71,72,73,74,75,76,77,78,79,0,2,8,10,1,3,9,11,12,14,4,6,13,15,5,7,4,6,0,2,5,7,1,3,12,14,8,10,13,15,9,11,0,2,8,10,4,6,12,14,1,3,9,11,5,7,13,15,119,82,83,112,113,98,99,102,103,68,69,110,111,104,105,200,202,192,194,201,203,193,195,204,206,205,207,196,198,197,199,66,71,70,77,69,73,72,64,65,78,67,75,79,74,76,68,76,78,68,70,64,66,77,79,69,71,72,74,65,67,73,75,132,134,128,130,133,135,129,131,136,138,140,142,137,139,141,143,78,74,77,71,70,64,194,69,207,200,75,196,204,73,195,65,12,14,8,10,13,15,4,6,9,11,5,7,0,2,1,3,72,74,64,66,73,75,76,78,65,67,196,198,77,79,197,199,68,69,96,97,74,75,98,99,66,67,80,81,92,93,114,115,112,113,88,89,108,109,246,247,0,0,0,0,0,0,0,0,0,0,0,0,0,0,0,0,0,0,0,0,0,0,0,0,0,0,0,0,0,0,0,0,0,0,0,0,0,0,0,0,0,0,0,0,0,0,0,0,0},
  {0,1,2,3,4,5,6,7,8,9,10,11,12,13,14,15,64,65,66,67,68,69,70,71,72,73,74,75,76,77,78,79,0,1,2,3,72,76,64,70,66,74,71,78,67,79,65,197,75,68,73,77,12,14,8,10,13,15,9,11,0,2,4,6,1,3,5,7,108,109,86,87,96,97,82,83,74,75,110,111,76,77,88,89,118,119,68,69,100,101,104,105,102,103,90,91,136,138,128,130,137,139,129,131,140,142,141,143,132,134,133,135,76,77,68,69,110,111,82,83,74,75,96,97,118,119,104,105,4,6,5,7,0,2,8,10,12,14,1,3,9,11,13,15,4,6,8,10,5,7,0,2,12,14,9,11,1,3,13,15,8,10,0,2,9,11,12,14,1,3,4,6,13,15,5,7,12,14,8,10,4,6,0,2,13,15,9,11,5,7,1,3,12,14,8,10,13,15,132,134,9,11,5,7,0,2,1,3,136,138,9,11,132,134,0,2,140,142,133,135,129,131,141,143,79,74,75,114,115,94,95,118,119,72,73,64,208,209,96,97,76,77,218,219,236,237,0,0,0,0,0,0,0,0,0,0,0,0,0,0,0,0,0,0,0,0,0,0,0,0,0,0,0,0,0,0,0,0,0,0,0,0,0,0,0,0,0,0,0,0,0,0,0,0,0,0},
  {64,65,66,67,68,69,70,71,72,73,74,75,76,77,78,79,0,1,2,3,0,1,2,3,66,74,68,64,66,74,79,65,68,75,71,72,76,64,70,66,74,71,78,67,79,65,69,75,68,73,77,4,6,0,2,5,7,1,3,12,14,8,10,13,15,9,11,70,71,64,65,98,99,92,93,78,79,112,113,94,95,72,73,80,81,84,85,114,115,116,117,106,107,66,67,108,136,138,128,130,137,139,129,131,140,142,141,143,132,134,133,135,12,14,4,6,13,15,0,2,8,10,5,7,1,3,9,11,4,6,5,7,12,14,8,10,0,2,13,15,9,11,1,3,76,78,4,6,0,2,13,15,5,7,8,10,1,3,9,11,8,10,0,2,9,11,12,14,1,3,4,6,13,15,5,7,12,14,8,10,4,6,0,2,13,15,9,11,5,7,1,3,12,14,8,10,13,15,4,6,9,11,5,7,0,2,1,3,92,93,108,109,98,99,80,81,100,101,70,71,116,117,96,97,74,75,64,65,112,113,82,83,234,235,84,85,104,112,113,228,229,192,193,216,217,246,247,0,0,0,0,0,0,0,0,0,0,0,0,0,0,0,0,0,0,0,0,0,0,0,0,0,0,0,0,0,0,0,0,0,0,0,0,0,0,0,0,0,0,0,0,0,0,0,0,0},
  {0,1,2,3,4,5,6,7,8,9,10,11,12,13,14,15,0,1,2,3,0,1,2,3,4,5,6,7,8,9,10,11,12,13,14,15,74,66,76,79,70,72,64,67,71,69,78,68,75,65,77,73,198,194,204,206,200,202,196,192,4,6,0,2,5,7,1,3,12,14,8,10,13,15,9,11,4,6,8,10,0,2,5,7,9,11,12,14,1,3,13,15,136,138,128,130,137,139,129,131,140,142,141,143,132,134,133,135,88,89,76,77,96,97,86,87,72,73,116,117,110,111,12,14,4,6,13,15,0,2,8,10,5,7,1,3,9,11,219,220,221,230,231,196,197,4,6,8,10,5,7,0,2,12,14,9,11,1,3,13,15,8,10,0,2,9,11,12,14,1,3,4,6,13,15,5,7,12,14,8,10,4,6,0,2,13,15,9,11,5,7,1,3,12,14,8,10,13,15,4,6,9,11,5,7,0,2,1,3,12,14,8,10,132,134,0,2,13,15,9,11,133,135,1,3,64,65,84,85,92,93,104,105,74,75,206,207,100,101,82,83,200,201,116,117,222,223,0,0,0,0,0,0,0,0,0,0,0,0,0,0,0,0,0,0,0,0,0,0,0,0,0,0,0,0,0,0,0,0,0,0,0,0,0,0,0,0,0,0,0,0,0,0,0,0,0},
  {0,1,2,3,4,5,6,7,8,9,10,11,12,13,14,15,64,65,66,67,68,69,70,71,72,73,74,75,76,77,78,79,0,1,2,3,64,66,76,78,65,67,77,79,68,70,69,71,72,74,73,75,12,14,8,10,13,15,9,11,0,2,4,6,1,3,5,7,4,6,12,14,8,10,0,2,5,7,13,15,9,11,1,3,0,2,8,10,4,6,12,14,1,3,9,11,5,7,13,15,112,113,84,85,88,89,66,67,78,79,92,93,72,73,80,81,106,107,116,117,108,109,64,65,94,95,86,87,4,6,5,7,12,14,8,10,0,2,13,15,9,11,1,3,4,6,8,10,5,7,0,2,12,14,9,11,1,3,13,15,132,134,128,130,133,135,129,131,136,138,140,142,137,139,141,143,200,207,194,204,192,195,202,196,199,206,198,197,205,201,193,203,4,6,12,14,8,10,5,7,13,15,9,11,0,2,1,3,4,6,5,7,136,138,140,142,9,11,141,143,128,130,129,131,82,83,70,71,68,69,102,103,108,109,86,87,114,115,98,99,66,67,84,85,224,225,202,203,0,0,0,0,0,0,0,0,0,0,0,0,0,0,0,0,0,0,0,0,0,0,0,0,0,0,0,0,0,0,0,0,0,0,0,0,0,0,0,0,0,0,0,0,0,0,0,0},
  {64,65,66,67,68,69,70,71,72,73,74,75,76,77,78,79,0,1,2,3,0,1,2,3,4,5,6,7,8,9,10,11,12,13,14,15,64,66,76,78,65,67,77,79,68,70,69,71,72,74,73,75,4,6,0,2,5,7,1,3,12,14,8,10,13,15,9,11,200,202,196,201,207,205,195,192,193,96,97,114,115,76,77,70,71,86,87,90,91,74,75,66,67,68,69,80,81,108,109,110,111,104,105,78,79,90,91,80,81,102,103,104,105,108,109,112,113,72,73,116,117,82,83,100,101,74,204,205,236,237,240,241,210,211,226,227,228,229,192,12,14,4,6,0,2,13,15,5,7,8,10,1,3,9,11,64,71,70,74,8,10,0,2,9,11,12,14,1,3,4,6,13,15,5,7,12,14,8,10,4,6,0,2,13,15,9,11,5,7,1,3,12,14,8,10,13,15,4,6,9,11,5,7,0,2,1,3,80,81,96,97,92,93,108,109,70,71,82,83,100,101,78,79,74,75,114,115,94,95,118,119,72,73,64,112,113,228,229,192,193,216,217,246,247,0,0,0,0,0,0,0,0,0,0,0,0,0,0,0,0,0,0,0,0,0,0,0,0,0,0,0,0,0,0,0,0,0,0,0,0,0,0,0,0,0,0,0,0,0,0,0,0,0,0,0,0},
  {64,65,66,67,68,69,70,71,72,73,74,75,76,77,78,79,0,1,2,3,0,1,2,3,4,5,6,7,8,9,10,11,12,13,14,15,64,66,76,78,65,67,77,79,68,70,69,71,72,74,73,75,4,6,0,2,5,7,1,3,12,14,8,10,13,15,9,11,4,6,12,14,8,10,0,2,5,7,13,15,9,11,1,3,0,2,8,10,4,6,12,14,1,3,9,11,5,7,13,15,136,138,128,130,137,139,129,131,140,142,141,143,132,134,133,135,12,14,4,6,13,15,0,2,8,10,5,7,1,3,9,11,68,70,69,71,76,78,72,74,64,66,77,79,73,75,65,67,79,68,65,67,70,8,10,12,14,0,2,9,11,13,15,1,3,4,6,5,7,8,10,9,11,4,6,0,2,12,14,5,7,1,3,13,15,4,6,12,14,8,10,5,7,13,15,9,11,0,2,1,3,132,134,140,142,136,138,133,135,141,143,128,130,137,139,129,131,118,119,76,77,74,75,68,69,72,73,100,101,110,111,84,85,206,207,116,117,94,95,242,243,214,215,240,241,226,0,0,0,0,0,0,0,0,0,0,0,0,0,0,0,0,0,0,0,0,0,0,0,0,0,0,0,0,0,0,0,0,0,0,0,0,0,0,0,0,0,0,0,0,0,0,0,0,0,0},
  {0,1,2,3,4,5,6,7,8,9,10,11,12,13,14,15,0,1,2,3,4,5,6,7,8,9,10,11,12,13,14,15,70,64,76,66,74,72,79,71,78,67,69,65,75,77,68,73,0,2,8,10,1,3,9,11,12,14,4,6,13,15,5,7,4,6,0,2,5,7,1,3,12,14,8,10,13,15,9,11,0,2,8,10,4,6,12,14,1,3,9,11,5,7,13,15,136,138,128,130,137,139,129,131,140,142,141,143,132,134,133,135,112,113,84,85,88,89,66,67,78,79,76,78,68,70,77,79,64,66,72,74,69,71,65,67,73,75,12,14,4,6,0,2,13,15,5,7,8,10,1,3,9,11,8,10,12,14,0,2,9,11,13,15,1,3,4,6,5,7,8,10,9,11,4,6,0,2,12,14,5,7,1,3,13,15,4,6,12,14,8,10,5,7,13,15,9,11,0,2,1,3,4,6,12,14,8,10,5,7,13,15,9,11,128,130,1,3,89,108,109,118,119,82,83,70,71,100,101,102,103,84,85,116,117,72,73,214,215,238,239,232,233,204,205,0,0,0,0,0,0,0,0,0,0,0,0,0,0,0,0,0,0,0,0,0,0,0,0,0,0,0,0,0,0,0,0,0,0,0,0,0,0,0,0,0,0,0,0,0,0,0,0,0,0,0},
  {64,65,66,67,68,69,70,71,72,73,74,75,76,77,78,79,0,1,2,3,4,5,6,7,8,9,10,11,12,13,14,15,0,1,2,3,4,5,6,7,8,9,10,11,12,13,14,15,198,197,194,199,204,203,206,200,4,6,0,2,5,7,1,3,12,14,8,10,13,15,9,11,0,2,8,10,4,6,12,14,1,3,9,11,5,7,13,15,70,71,86,87,90,91,74,75,66,67,68,69,80,81,108,109,110,111,104,105,0,2,4,6,8,10,1,3,5,7,12,14,9,11,13,15,4,6,5,7,12,14,8,10,0,2,13,15,9,11,1,3,0,2,1,3,4,6,8,10,12,14,5,7,9,11,13,15,8,10,12,14,0,2,9,11,13,15,1,3,4,6,5,7,8,10,0,2,9,11,12,14,1,3,4,6,13,15,5,7,4,6,5,7,8,10,12,14,9,11,13,15,0,2,1,3,4,6,12,14,8,10,5,7,13,15,0,2,9,11,1,3,64,65,78,79,90,91,106,107,94,95,68,69,96,97,74,75,98,99,66,67,208,209,92,93,242,243,240,241,216,0,0,0,0,0,0,0,0,0,0,0,0,0,0,0,0,0,0,0,0,0,0,0,0,0,0,0,0,0,0,0,0,0,0,0,0,0,0,0,0,0,0,0,0,0,0,0},
  {0,1,2,3,4,5,6,7,8,9,10,11,12,13,14,15,64,65,66,67,68,69,70,71,72,73,74,75,76,77,78,79,0,1,2,3,4,5,6,7,8,9,10,11,12,13,14,15,0,2,8,10,1,3,9,11,12,14,4,6,13,15,5,7,197,199,203,201,207,205,195,193,4,6,12,14,8,10,0,2,5,7,13,15,9,11,1,3,88,89,94,95,116,117,118,119,106,107,78,79,82,83,112,113,84,85,102,136,138,128,130,137,139,129,131,140,142,141,143,132,134,133,135,66,71,70,77,69,73,72,64,65,78,67,75,79,74,76,68,12,14,4,6,0,2,13,15,5,7,8,10,1,3,9,11,8,10,12,14,0,2,9,11,13,15,1,3,4,6,5,7,8,10,9,11,4,6,0,2,12,14,5,7,1,3,13,15,4,6,12,14,8,10,5,7,13,15,9,11,0,2,1,3,4,6,12,14,136,138,5,7,13,15,137,139,128,130,129,131,90,91,106,107,92,93,116,117,72,73,76,77,108,109,110,111,80,81,198,199,66,67,202,203,226,0,0,0,0,0,0,0,0,0,0,0,0,0,0,0,0,0,0,0,0,0,0,0,0,0,0,0,0,0,0,0,0,0,0,0,0,0,0,0,0,0,0,0,0,0,0,0,0,0,0,0,0},
  {64,65,66,67,68,69,70,71,72,73,74,75,76,77,78,79,0,1,2,3,4,5,6,7,8,9,10,11,12,13,14,15,72,78,70,71,64,66,76,78,65,67,77,79,68,70,69,71,72,74,73,75,12,14,8,10,13,15,9,11,0,2,4,6,1,3,5,7,109,86,87,96,97,82,83,74,75,110,111,76,77,88,89,118,119,68,69,100,101,104,105,102,103,90,91,64,65,70,71,80,81,112,113,90,91,102,103,118,119,104,105,114,115,106,107,94,95,68,69,12,14,4,6,13,15,0,2,8,10,5,7,1,3,9,11,0,2,1,3,4,6,8,10,12,14,5,7,9,11,13,15,76,70,68,66,65,8,10,12,14,0,2,9,11,13,15,1,3,4,6,5,7,8,10,9,11,4,6,0,2,12,14,5,7,1,3,13,15,4,6,12,14,8,10,5,7,13,15,9,11,0,2,1,3,132,134,140,142,136,138,133,135,141,143,128,130,137,139,129,131,109,118,119,82,83,70,71,100,101,102,103,84,85,116,117,72,73,86,87,110,111,232,233,204,205,0,0,0,0,0,0,0,0,0,0,0,0,0,0,0,0,0,0,0,0,0,0,0,0,0,0,0,0,0,0,0,0,0,0,0,0,0,0,0,0,0,0,0,0,0,0,0,0,0,0,0},
  {64,65,66,67,68,69,70,71,72,73,74,75,76,77,78,79,0,1,2,3,0,1,2,3,4,5,6,7,8,9,10,11,12,13,14,15,64,66,76,78,65,67,77,79,68,70,69,71,72,74,73,75,64,66,72,74,65,67,73,75,76,78,68,70,77,79,69,71,70,71,64,65,98,99,92,93,78,79,112,113,94,95,72,73,80,81,84,85,114,115,116,117,106,107,66,67,108,109,86,87,64,65,70,71,80,81,112,113,90,91,102,103,118,119,104,105,114,115,106,107,94,95,4,6,5,7,12,14,8,10,0,2,13,15,9,11,1,3,0,2,1,3,4,6,8,10,12,14,5,7,9,11,13,15,8,10,12,14,0,2,9,11,13,15,1,3,4,6,5,7,8,10,9,11,4,6,0,2,12,14,5,7,1,3,13,15,4,6,5,7,8,10,12,14,9,11,13,15,0,2,1,3,4,6,12,14,8,10,5,7,13,15,0,2,9,11,1,3,85,104,105,72,73,86,87,102,103,90,91,118,119,68,69,206,207,114,115,66,67,110,111,94,95,216,217,204,205,0,0,0,0,0,0,0,0,0,0,0,0,0,0,0,0,0,0,0,0,0,0,0,0,0,0,0,0,0,0,0,0,0,0,0,0,0,0,0,0,0,0,0,0,0,0,0,0,0},
  {0,1,2,3,4,5,6,7,8,9,10,11,12,13,14,15,0,1,2,3,4,5,6,7,8,9,10,11,12,13,14,15,0,1,2,3,4,5,6,7,8,9,10,11,12,13,14,15,0,2,8,10,1,3,9,11,12,14,4,6,13,15,5,7,4,6,12,14,8,10,0,2,5,7,13,15,9,11,1,3,4,6,0,2,5,7,1,3,12,14,8,10,13,15,9,11,0,2,8,10,4,6,12,14,1,3,137,139,5,7,141,143,0,2,4,6,8,10,1,3,5,7,12,14,9,11,13,15,4,6,5,7,12,14,8,10,0,2,13,15,9,11,1,3,0,2,1,3,4,6,8,10,12,14,5,7,9,11,13,15,8,10,12,14,0,2,9,11,13,15,1,3,4,6,5,7,8,10,9,11,4,6,0,2,12,14,5,7,1,3,13,15,4,6,12,14,8,10,5,7,13,15,9,11,0,2,1,3,4,6,140,142,136,138,5,7,141,143,128,130,137,139,129,131,108,109,118,119,82,83,70,71,100,101,102,103,84,85,116,117,72,73,86,87,110,111,232,233,204,205,0,0,0,0,0,0,0,0,0,0,0,0,0,0,0,0,0,0,0,0,0,0,0,0,0,0,0,0,0,0,0,0,0,0,0,0,0,0,0,0,0,0,0,0,0,0},
  {0,1,2,3,4,5,6,7,8,9,10,11,12,13,14,15,0,1,2,3,4,5,6,7,8,9,10,11,12,13,14,15,74,66,76,79,70,72,64,67,71,69,78,68,75,65,77,73,0,2,8,10,1,3,9,11,12,14,4,6,13,15,5,7,0,2,8,10,4,6,12,14,1,3,9,11,5,7,13,15,4,6,8,10,0,2,5,7,9,11,12,14,1,3,13,15,136,138,128,130,137,139,129,131,140,142,141,143,132,134,133,135,86,87,114,115,102,103,98,99,100,101,90,91,70,71,204,205,68,206,207,246,247,194,195,238,239,242,243,232,233,218,76,78,68,70,64,66,77,79,69,71,72,74,65,67,73,75,8,10,0,2,9,11,12,14,1,3,4,6,13,15,5,7,12,14,8,10,4,6,0,2,13,15,9,11,5,7,1,3,12,14,8,10,13,15,4,6,9,11,5,7,0,2,1,3,110,111,82,83,70,71,68,69,102,103,108,109,86,87,114,115,98,99,66,67,84,85,96,97,74,75,103,208,209,96,97,76,77,218,219,236,237,0,0,0,0,0,0,0,0,0,0,0,0,0,0,0,0,0,0,0,0,0,0,0,0,0,0,0,0,0,0,0,0,0,0,0,0,0,0,0,0,0,0,0,0,0,0,0,0,0,0,0,0,0},
  {0,1,2,3,4,5,6,7,8,9,10,11,12,13,14,15,0,1,2,3,0,1,2,3,4,5,6,7,8,9,10,11,12,13,14,15,64,66,76,78,65,67,77,79,68,70,69,71,72,74,73,75,12,14,8,10,13,15,9,11,0,2,4,6,1,3,5,7,4,6,0,2,5,7,1,3,12,14,8,10,13,15,9,11,4,6,8,10,0,2,5,7,9,11,12,14,1,3,13,15,136,138,128,130,137,139,129,131,140,142,141,143,132,134,133,135,108,109,204,205,88,89,114,115,96,97,102,103,116,117,246,247,0,2,1,3,4,6,8,10,12,14,5,7,9,11,13,15,8,10,12,14,0,2,9,11,13,15,1,3,4,6,5,7,8,10,9,11,4,6,0,2,12,14,5,7,1,3,13,15,12,14,8,10,4,6,0,2,13,15,9,11,5,7,1,3,132,134,140,142,136,138,133,135,141,143,128,130,137,139,129,131,99,102,103,86,87,104,105,78,79,118,119,114,115,88,89,112,113,100,101,64,65,84,85,94,95,224,225,210,211,196,197,0,0,0,0,0,0,0,0,0,0,0,0,0,0,0,0,0,0,0,0,0,0,0,0,0,0,0,0,0,0,0,0,0,0,0,0,0,0,0,0,0,0,0,0,0,0,0,0,0,0,0,0,0},
  {64,65,66,67,68,69,70,71,72,73,74,75,76,77,78,79,0,1,2,3,0,1,2,3,4,5,6,7,8,9,10,11,12,13,14,15,64,66,76,78,65,67,77,79,68,70,69,71,72,74,73,75,64,66,72,74,65,67,73,75,76,78,68,70,77,79,69,71,4,6,12,14,8,10,0,2,5,7,13,15,9,11,1,3,88,89,94,95,116,117,118,119,106,107,78,79,82,83,112,113,84,85,102,103,98,99,136,138,128,130,137,139,129,131,140,142,141,143,132,134,133,135,12,14,4,6,13,15,0,2,8,10,5,7,1,3,9,11,0,2,1,3,4,6,8,10,12,14,5,7,9,11,13,15,8,10,12,14,0,2,9,11,13,15,1,3,4,6,5,7,8,10,9,11,4,6,0,2,12,14,5,7,1,3,13,15,4,6,5,7,8,10,12,14,9,11,13,15,0,2,1,3,4,6,12,14,8,10,5,7,13,15,0,2,9,11,1,3,69,102,103,108,109,86,87,114,115,98,99,66,67,84,85,96,97,74,75,68,69,104,105,108,109,102,103,244,245,0,0,0,0,0,0,0,0,0,0,0,0,0,0,0,0,0,0,0,0,0,0,0,0,0,0,0,0,0,0,0,0,0,0,0,0,0,0,0,0,0,0,0,0,0,0,0,0,0},
  {64,65,66,67,68,69,70,71,72,73,74,75,76,77,78,79,0,1,2,3,0,1,2,3,4,5,6,7,8,9,10,11,12,13,14,15,64,66,76,78,65,67,77,79,68,70,69,71,72,74,73,75,12,14,8,10,13,15,9,11,0,2,4,6,1,3,5,7,4,6,12,14,8,10,0,2,5,7,13,15,9,11,1,3,0,2,8,10,4,6,12,14,1,3,9,11,5,7,13,15,136,138,128,130,137,139,129,131,140,142,141,143,132,134,133,135,94,95,108,109,76,77,88,89,114,115,96,97,102,103,116,117,118,119,0,2,1,3,4,6,8,10,12,14,5,7,9,11,13,15,8,10,12,14,0,2,9,11,13,15,1,3,4,6,5,7,8,10,9,11,4,6,0,2,12,14,5,7,1,3,13,15,4,6,5,7,8,10,12,14,9,11,13,15,0,2,1,3,4,6,12,14,8,10,5,7,13,15,0,2,9,11,1,3,118,119,76,77,74,75,68,69,72,73,100,101,110,111,84,85,78,79,116,117,94,95,242,243,214,215,240,241,226,227,0,0,0,0,0,0,0,0,0,0,0,0,0,0,0,0,0,0,0,0,0,0,0,0,0,0,0,0,0,0,0,0,0,0,0,0,0,0,0,0,0,0,0,0,0,0,0,0,0,0,0,0},
  {64,65,66,67,68,69,70,71,72,73,74,75,76,77,78,79,64,65,66,67,68,69,70,71,72,73,74,75,76,77,78,79,0,1,2,3,4,5,6,7,8,9,10,11,12,13,14,15,0,2,8,10,1,3,9,11,12,14,4,6,13,15,5,7,12,14,8,10,13,15,9,11,0,2,4,6,1,3,5,7,4,6,12,14,8,10,0,2,5,7,13,15,9,11,1,3,68,70,76,78,72,74,64,66,69,71,77,79,73,75,65,67,72,73,80,81,106,107,116,117,108,109,64,65,94,95,86,87,114,115,102,103,226,234,235,224,225,216,217,198,199,206,207,246,247,194,195,64,71,78,77,69,72,75,70,74,79,76,73,68,67,66,65,196,198,192,194,197,199,193,195,200,202,204,206,201,203,205,207,12,14,8,10,4,6,0,2,13,15,9,11,5,7,1,3,12,14,8,10,13,15,132,134,9,11,133,135,128,130,1,3,196,198,204,206,200,202,69,71,205,207,201,203,192,194,193,195,81,66,67,90,91,96,97,114,115,74,75,198,199,238,239,210,211,0,0,0,0,0,0,0,0,0,0,0,0,0,0,0,0,0,0,0,0,0,0,0,0,0,0,0,0,0,0,0,0,0,0,0,0,0,0,0,0,0,0,0,0,0,0,0,0,0,0,0,0},
  {64,65,66,67,68,69,70,71,72,73,74,75,76,77,78,79,0,1,2,3,0,1,2,3,4,5,6,7,8,9,10,11,12,13,14,15,64,66,76,78,65,67,77,79,68,70,69,71,72,74,73,75,4,6,0,2,5,7,1,3,12,14,8,10,13,15,9,11,76,78,72,74,77,79,73,75,64,66,68,70,65,67,69,71,4,6,12,14,8,10,0,2,5,7,13,15,9,11,1,3,8,10,128,130,9,11,1,3,140,142,13,15,132,134,133,135,107,94,95,108,109,76,77,88,89,114,115,96,97,102,103,116,117,118,119,71,72,69,66,64,78,74,77,76,75,73,79,68,65,67,70,8,10,12,14,0,2,9,11,13,15,1,3,4,6,5,7,8,10,0,2,9,11,12,14,1,3,4,6,13,15,5,7,4,6,12,14,8,10,5,7,13,15,9,11,0,2,1,3,4,6,12,14,8,10,5,7,13,15,0,2,9,11,1,3,64,65,78,79,90,91,106,107,94,95,68,69,96,97,74,102,103,208,209,96,97,76,77,218,219,236,237,0,0,0,0,0,0,0,0,0,0,0,0,0,0,0,0,0,0,0,0,0,0,0,0,0,0,0,0,0,0,0,0,0,0,0,0,0,0,0,0,0,0,0,0,0,0,0,0,0,0,0,0,0,0},
  {0,1,2,3,4,5,6,7,8,9,10,11,12,13,14,15,0,1,2,3,79,75,77,73,0,1,2,3,4,5,6,7,8,9,10,11,12,13,14,15,0,2,8,10,1,3,9,11,12,14,4,6,13,15,5,7,4,6,8,10,0,2,5,7,9,11,12,14,1,3,13,15,4,6,8,10,0,2,5,7,9,11,12,14,1,3,13,15,4,6,12,14,8,10,0,2,5,7,13,15,9,11,1,3,72,73,80,81,98,99,74,75,110,111,112,113,86,87,92,93,78,79,64,65,66,67,84,85,68,69,90,91,104,218,219,220,221,230,231,196,197,71,69,72,78,64,77,75,74,79,73,67,76,70,68,66,65,8,10,0,2,9,11,12,14,1,3,4,6,13,15,5,7,12,14,8,10,4,6,0,2,13,15,9,11,5,7,1,3,12,14,8,10,13,15,4,6,9,11,5,7,0,2,1,3,196,198,204,206,200,202,197,199,205,207,192,194,201,203,193,195,78,79,106,235,86,87,94,95,76,77,220,221,200,201,98,99,212,213,0,0,0,0,0,0,0,0,0,0,0,0,0,0,0,0,0,0,0,0,0,0,0,0,0,0,0,0,0,0,0,0,0,0,0,0,0,0,0,0,0,0,0,0,0,0,0,0,0,0,0,0,0,0,0,0,0},
  {64,65,66,67,68,69,70,71,72,73,74,75,76,77,78,79,0,1,2,3,72,78,70,71,0,2,12,14,1,3,13,15,4,6,5,7,8,10,9,11,12,14,8,10,13,15,9,11,0,2,4,6,1,3,5,7,4,6,8,10,0,2,5,7,9,11,12,14,1,3,13,15,8,10,0,2,9,11,1,3,12,14,13,15,132,134,5,7,95,70,71,76,77,106,107,96,97,64,65,78,79,90,91,80,81,102,69,110,111,82,83,74,75,96,97,118,119,104,105,94,223,244,245,234,235,224,225,216,217,198,199,71,69,72,78,64,77,75,74,79,73,67,76,70,68,66,65,8,10,0,2,9,11,12,14,1,3,4,6,13,15,5,7,12,14,8,10,4,6,0,2,13,15,9,11,5,7,1,3,4,6,12,14,8,10,5,7,13,15,9,11,0,2,1,3,68,70,69,71,200,202,204,206,201,203,205,207,192,194,193,195,64,65,78,79,90,91,106,107,94,95,112,113,228,229,64,193,216,217,246,247,0,0,0,0,0,0,0,0,0,0,0,0,0,0,0,0,0,0,0,0,0,0,0,0,0,0,0,0,0,0,0,0,0,0,0,0,0,0,0,0,0,0,0,0,0,0,0,0,0,0,0,0,0,0,0,0,0,0,0,0,0,0,0,0,0},
  {64,65,66,67,68,69,70,71,72,73,74,75,76,77,78,79,0,1,2,3,0,1,2,3,4,5,6,7,8,9,10,11,12,13,14,15,64,66,76,78,65,67,77,79,68,70,69,71,72,74,73,75,12,14,8,10,13,15,9,11,0,2,4,6,1,3,5,7,70,71,64,65,98,99,92,93,78,79,112,113,94,95,72,73,80,81,84,85,114,115,116,117,106,107,66,67,111,98,99,66,67,94,95,70,71,76,77,106,107,96,97,64,65,78,79,90,91,80,81,102,103,104,105,236,237,240,241,72,105,70,71,210,211,100,101,106,71,72,69,66,64,78,74,77,76,75,73,79,68,65,67,70,64,71,70,74,77,69,78,72,76,78,74,77,71,70,64,66,69,207,200,75,68,204,73,195,65,4,6,5,7,8,10,12,14,9,11,13,15,0,2,1,3,12,14,8,10,13,15,132,134,9,11,133,135,0,2,1,3,118,119,76,77,74,75,68,69,72,73,100,101,110,111,84,85,206,207,116,117,94,95,114,115,214,215,112,113,98,99,192,193,0,0,0,0,0,0,0,0,0,0,0,0,0,0,0,0,0,0,0,0,0,0,0,0,0,0,0,0,0,0,0,0,0,0,0,0,0,0,0,0,0,0,0,0,0,0,0,0,0,0,0,0,0,0,0},
  {64,65,66,67,68,69,70,71,72,73,74,75,76,77,78,79,0,1,2,3,64,65,66,67,68,69,70,71,72,73,74,75,76,77,78,79,64,66,76,78,65,67,77,79,68,70,69,71,72,74,73,75,4,6,0,2,5,7,1,3,12,14,8,10,13,15,9,11,4,6,12,14,8,10,0,2,5,7,13,15,9,11,1,3,4,6,12,14,8,10,0,2,5,7,13,15,137,139,129,131,92,93,72,73,80,81,106,107,116,117,108,109,64,65,94,95,86,87,114,115,102,103,98,99,100,101,90,91,70,71,207,246,247,194,195,238,239,242,243,232,233,218,4,6,8,10,5,7,0,2,12,14,9,11,1,3,13,15,64,71,78,74,77,70,73,69,66,72,76,79,68,65,67,75,12,14,8,10,4,6,0,2,13,15,9,11,5,7,1,3,12,14,8,10,13,15,4,6,9,11,5,7,0,2,1,3,204,206,200,202,205,207,196,198,201,203,197,199,192,194,193,195,71,66,67,112,113,98,99,86,87,110,111,114,115,88,89,118,119,68,69,230,231,0,0,0,0,0,0,0,0,0,0,0,0,0,0,0,0,0,0,0,0,0,0,0,0,0,0,0,0,0,0,0,0,0,0,0,0,0,0,0,0,0,0,0,0,0,0,0,0,0,0,0,0,0},
  {64,65,66,67,68,69,70,71,72,73,74,75,76,77,78,79,0,1,2,3,0,1,2,3,4,5,6,7,8,9,10,11,12,13,14,15,64,66,76,78,65,67,77,79,68,70,69,71,72,74,73,75,12,14,8,10,13,15,9,11,0,2,4,6,1,3,5,7,4,6,0,2,5,7,1,3,12,14,8,10,13,15,9,11,4,6,8,10,0,2,5,7,9,11,12,14,1,3,13,15,82,83,98,99,108,109,92,93,78,79,84,85,100,101,66,67,74,75,112,113,84,85,88,89,66,67,78,79,92,93,4,6,5,7,0,2,8,10,12,14,1,3,9,11,13,15,4,6,8,10,5,7,0,2,12,14,9,11,1,3,13,15,8,10,0,2,9,11,12,14,1,3,4,6,13,15,5,7,12,14,8,10,4,6,0,2,13,15,9,11,5,7,1,3,12,14,8,10,13,15,132,134,9,11,5,7,0,2,1,3,196,198,69,71,200,202,204,206,201,203,205,207,192,194,193,195,78,79,106,107,86,87,94,95,76,77,220,221,200,201,98,99,212,213,208,0,0,0,0,0,0,0,0,0,0,0,0,0,0,0,0,0,0,0,0,0,0,0,0,0,0,0,0,0,0,0,0,0,0,0,0,0,0,0,0,0,0,0,0,0,0,0,0,0,0,0},
  {0,1,2,3,4,5,6,7,8,9,10,11,12,13,14,15,0,1,2,3,0,1,2,3,4,5,6,7,8,9,10,11,12,13,14,15,64,66,76,78,65,67,77,79,68,70,69,71,72,74,73,75,4,6,0,2,5,7,1,3,12,14,8,10,13,15,9,11,4,6,8,10,0,2,5,7,9,11,12,14,1,3,13,15,0,2,8,10,4,6,12,14,1,3,137,139,5,7,13,15,80,81,102,103,104,105,108,109,112,113,72,73,116,117,82,83,100,101,74,75,86,87,92,93,118,119,68,69,4,6,5,7,0,2,8,10,12,14,1,3,9,11,13,15,4,6,8,10,5,7,0,2,12,14,9,11,1,3,13,15,8,10,0,2,9,11,12,14,1,3,4,6,13,15,5,7,200,207,194,204,192,195,202,196,199,206,198,197,205,201,193,203,12,14,8,10,13,15,4,6,9,11,5,7,0,2,1,3,132,134,12,14,136,138,133,135,13,15,137,139,128,130,129,131,106,107,70,71,66,67,112,113,98,99,86,87,110,111,242,243,88,89,118,119,196,197,0,0,0,0,0,0,0,0,0,0,0,0,0,0,0,0,0,0,0,0,0,0,0,0,0,0,0,0,0,0,0,0,0,0,0,0,0,0,0,0,0,0,0,0,0,0,0,0,0,0},
  {64,65,66,67,68,69,70,71,72,73,74,75,76,77,78,79,0,1,2,3,4,5,6,7,8,9,10,11,12,13,14,15,0,1,2,3,72,76,64,70,66,74,71,78,67,79,65,69,75,68,73,77,4,6,0,2,5,7,1,3,12,14,8,10,13,15,9,11,4,6,8,10,0,2,5,7,9,11,12,14,1,3,13,15,0,2,8,10,4,6,12,14,1,3,137,139,5,7,141,143,192,194,200,202,68,70,204,206,193,195,201,203,197,199,205,207,111,82,83,74,75,96,97,118,119,104,105,4,6,5,7,0,2,8,10,12,14,1,3,9,11,13,15,76,78,68,70,0,2,13,15,5,7,8,10,1,3,9,11,8,10,0,2,9,11,12,14,1,3,4,6,13,15,5,7,12,14,8,10,4,6,0,2,13,15,9,11,5,7,1,3,4,6,12,14,8,10,5,7,13,15,9,11,0,2,1,3,12,14,136,138,132,134,0,2,141,143,137,139,133,135,129,131,64,65,84,85,92,93,104,105,74,75,206,207,100,101,82,83,200,201,116,117,222,223,234,0,0,0,0,0,0,0,0,0,0,0,0,0,0,0,0,0,0,0,0,0,0,0,0,0,0,0,0,0,0,0,0,0,0,0,0,0,0,0,0,0,0,0,0,0,0,0,0,0,0},
  {64,65,66,67,68,69,70,71,72,73,74,75,76,77,78,79,0,1,2,3,4,5,6,7,8,9,10,11,12,13,14,15,69,76,67,65,64,66,76,78,65,67,77,79,68,70,69,71,72,74,73,75,12,14,8,10,13,15,9,11,0,2,4,6,1,3,5,7,4,6,8,10,0,2,5,7,9,11,12,14,1,3,13,15,90,91,70,71,72,73,66,67,64,65,84,85,92,93,80,81,86,87,94,95,76,77,88,89,106,107,78,79,96,0,2,4,6,8,10,1,3,5,7,12,14,9,11,13,15,4,6,5,7,0,2,8,10,12,14,1,3,9,11,13,15,4,6,8,10,5,7,0,2,12,14,9,11,1,3,13,15,132,134,128,130,133,135,129,131,136,138,140,142,137,139,141,143,8,10,9,11,4,6,0,2,12,14,5,7,1,3,13,15,4,6,12,14,8,10,5,7,13,15,9,11,0,2,1,3,132,134,140,142,136,138,133,135,141,143,128,130,137,139,129,131,104,105,78,79,118,119,114,115,88,89,112,113,100,101,64,65,84,85,94,95,96,97,210,211,196,197,0,0,0,0,0,0,0,0,0,0,0,0,0,0,0,0,0,0,0,0,0,0,0,0,0,0,0,0,0,0,0,0,0,0,0,0,0,0,0,0,0,0,0,0,0},
  {64,65,66,67,68,69,70,71,72,73,74,75,76,77,78,79,0,1,2,3,0,1,2,3,4,5,6,7,8,9,10,11,12,13,14,15,0,1,2,3,4,5,6,7,8,9,10,11,12,13,14,15,0,2,8,10,1,3,9,11,12,14,4,6,13,15,5,7,4,6,8,10,0,2,5,7,9,11,12,14,1,3,13,15,4,6,12,14,8,10,0,2,5,7,13,15,9,11,1,3,103,104,105,108,109,112,113,72,73,116,117,82,83,100,101,74,75,86,87,92,93,118,119,68,69,76,78,68,70,77,79,64,66,72,74,69,71,65,67,73,75,0,2,1,3,4,6,8,10,12,14,5,7,9,11,13,15,132,134,128,130,133,135,129,131,136,138,140,142,137,139,141,143,8,10,9,11,4,6,0,2,12,14,5,7,1,3,13,15,4,6,12,14,8,10,5,7,13,15,9,11,0,2,1,3,132,134,140,142,136,138,133,135,141,143,128,130,137,139,129,131,65,112,113,98,99,88,89,86,87,84,85,90,91,106,107,68,69,104,105,76,77,116,117,110,111,102,103,194,195,0,0,0,0,0,0,0,0,0,0,0,0,0,0,0,0,0,0,0,0,0,0,0,0,0,0,0,0,0,0,0,0,0,0,0,0,0,0,0,0,0,0,0,0,0,0},
  {64,65,66,67,68,69,70,71,72,73,74,75,76,77,78,79,0,1,2,3,4,5,6,7,8,9,10,11,12,13,14,15,64,67,72,77,69,73,78,76,76,69,70,72,74,66,71,75,67,77,68,73,79,206,64,65,4,6,8,10,0,2,5,7,9,11,12,14,1,3,13,15,4,6,12,14,8,10,0,2,5,7,13,15,9,11,1,3,0,2,8,10,4,6,12,14,1,3,9,11,5,7,13,15,0,2,4,6,8,10,1,3,5,7,12,14,9,11,13,15,4,6,5,7,12,14,8,10,0,2,13,15,9,11,1,3,0,2,1,3,4,6,8,10,12,14,5,7,9,11,13,15,8,10,12,14,0,2,9,11,13,15,1,3,4,6,5,7,8,10,0,2,9,11,12,14,1,3,4,6,13,15,5,7,12,14,8,10,4,6,0,2,13,15,9,11,5,7,1,3,4,6,12,14,8,10,5,7,13,15,9,11,0,2,1,3,116,117,64,65,118,119,80,81,94,95,76,77,112,113,110,111,82,83,70,71,68,112,113,228,229,64,65,88,217,246,247,0,0,0,0,0,0,0,0,0,0,0,0,0,0,0,0,0,0,0,0,0,0,0,0,0,0,0,0,0,0,0,0,0,0,0,0,0,0,0,0,0,0,0,0,0,0,0,0,0},
  {64,65,66,67,68,69,70,71,72,73,74,75,76,77,78,79,0,1,2,3,0,1,2,3,4,5,6,7,8,9,10,11,12,13,14,15,64,66,76,78,65,67,77,79,68,70,69,71,72,74,73,75,12,14,8,10,13,15,9,11,0,2,4,6,1,3,5,7,4,6,8,10,0,2,5,7,9,11,12,14,1,3,13,15,64,65,70,71,80,81,112,113,90,91,102,103,118,119,104,105,114,115,106,107,94,95,68,69,82,83,98,99,108,109,92,12,14,4,6,13,15,0,2,8,10,5,7,1,3,9,11,4,6,5,7,0,2,8,10,12,14,1,3,9,11,13,15,76,78,68,70,64,66,77,79,69,71,72,74,65,67,73,75,132,134,128,130,133,135,129,131,136,138,140,142,137,139,141,143,12,14,8,10,4,6,0,2,13,15,9,11,5,7,1,3,4,6,12,14,8,10,5,7,13,15,9,11,0,2,1,3,4,6,12,14,136,138,5,7,13,15,137,139,128,130,129,131,64,65,84,85,92,93,104,105,74,75,206,207,100,101,82,83,72,73,116,117,222,223,234,235,198,0,0,0,0,0,0,0,0,0,0,0,0,0,0,0,0,0,0,0,0,0,0,0,0,0,0,0,0,0,0,0,0,0,0,0,0,0,0,0,0,0,0,0,0},
  {0,1,2,3,4,5,6,7,8,9,10,11,12,13,14,15,64,65,66,67,68,69,70,71,72,73,74,75,76,77,78,79,0,1,2,3,4,5,6,7,8,9,10,11,12,13,14,15,0,2,8,10,1,3,9,11,12,14,4,6,13,15,5,7,4,6,8,10,0,2,5,7,9,11,12,14,1,3,13,15,103,98,99,72,73,92,93,64,65,100,101,96,97,114,115,76,77,70,71,86,87,90,91,74,75,66,67,68,69,0,2,4,6,8,10,1,3,5,7,12,14,9,11,13,15,12,14,4,6,13,15,0,2,8,10,5,7,1,3,9,11,0,2,1,3,4,6,8,10,12,14,5,7,9,11,13,15,132,134,128,130,133,135,129,131,136,138,140,142,137,139,141,143,79,67,75,65,8,10,0,2,9,11,12,14,1,3,4,6,13,15,5,7,4,6,12,14,8,10,5,7,13,15,9,11,0,2,1,3,8,10,9,11,4,6,0,2,140,142,133,135,1,3,141,143,64,65,80,81,92,93,108,109,106,107,70,71,66,67,90,91,88,89,82,83,224,225,232,233,230,231,0,0,0,0,0,0,0,0,0,0,0,0,0,0,0,0,0,0,0,0,0,0,0,0,0,0,0,0,0,0,0,0,0,0,0,0,0,0,0,0,0,0,0,0,0},
  {64,65,66,67,68,69,70,71,72,73,74,75,76,77,78,79,0,1,2,3,64,65,66,67,68,69,70,71,72,73,74,75,76,77,78,79,64,66,76,78,65,67,77,79,68,70,69,71,72,74,73,75,4,6,0,2,5,7,1,3,12,14,8,10,13,15,9,11,4,6,8,10,0,2,5,7,9,11,12,14,1,3,13,15,90,91,70,71,72,73,66,67,64,65,84,85,92,93,80,81,86,87,94,95,76,77,88,89,106,107,78,79,96,97,0,2,4,6,8,10,1,3,5,7,12,14,9,11,13,15,4,6,5,7,0,2,8,10,12,14,1,3,9,11,13,15,12,14,4,6,0,2,13,15,5,7,8,10,1,3,9,11,64,71,70,74,77,69,78,72,76,68,66,73,8,10,9,11,4,6,0,2,12,14,5,7,1,3,13,15,4,6,12,14,8,10,5,7,13,15,9,11,0,2,1,3,12,14,8,10,13,15,4,6,9,11,5,7,0,2,1,3,106,107,104,105,92,93,88,89,72,73,90,91,100,101,206,207,116,117,64,65,118,119,80,209,222,223,204,0,0,0,0,0,0,0,0,0,0,0,0,0,0,0,0,0,0,0,0,0,0,0,0,0,0,0,0,0,0,0,0,0,0,0,0,0,0,0,0,0,0,0,0,0,0,0},
  {0,1,2,3,4,5,6,7,8,9,10,11,12,13,14,15,0,1,2,3,64,65,66,67,68,69,70,71,72,73,74,75,76,77,78,79,64,66,76,78,65,67,77,79,68,70,69,71,72,74,73,75,64,66,72,74,65,67,73,75,76,78,68,70,77,79,69,71,4,6,8,10,0,2,5,7,9,11,12,14,1,3,13,15,68,70,64,66,69,71,65,67,76,78,72,74,77,79,73,75,136,138,128,130,137,139,129,131,140,142,141,143,132,134,133,135,64,66,68,70,72,74,65,67,69,71,76,78,73,75,77,79,4,6,5,7,0,2,8,10,12,14,1,3,9,11,13,15,4,6,8,10,5,7,0,2,12,14,9,11,1,3,13,15,64,71,78,74,77,70,73,69,66,72,76,79,68,65,67,75,12,14,8,10,4,6,0,2,13,15,9,11,5,7,1,3,12,14,8,10,13,15,132,134,9,11,133,135,0,2,1,3,204,206,200,202,205,207,196,198,201,203,197,199,192,194,193,195,107,70,71,66,67,112,113,98,99,86,87,110,111,242,243,88,89,118,119,196,197,0,0,0,0,0,0,0,0,0,0,0,0,0,0,0,0,0,0,0,0,0,0,0,0,0,0,0,0,0,0,0,0,0,0,0,0,0,0,0,0,0,0,0,0,0,0,0},
  {64,65,66,67,68,69,70,71,72,73,74,75,76,77,78,79,0,1,2,3,72,78,70,71,0,1,2,3,4,5,6,7,8,9,10,11,12,13,14,15,0,2,8,10,1,3,9,11,12,14,4,6,13,15,5,7,12,14,8,10,13,15,9,11,0,2,4,6,1,3,5,7,4,6,12,14,8,10,0,2,5,7,13,15,9,11,1,3,136,138,128,130,137,139,129,131,140,142,141,143,132,134,133,135,75,88,89,76,77,96,97,86,87,72,73,116,117,110,111,4,6,5,7,12,14,8,10,0,2,13,15,9,11,1,3,12,14,4,6,0,2,13,15,5,7,8,10,1,3,9,11,132,134,128,130,133,135,129,131,136,138,140,142,137,139,141,143,8,10,9,11,4,6,0,2,12,14,5,7,1,3,13,15,4,6,5,7,8,10,12,14,9,11,13,15,0,2,1,3,12,14,8,10,13,15,132,134,9,11,133,135,128,130,129,131,116,117,96,97,74,75,64,65,112,113,82,83,106,107,84,80,81,66,67,90,91,96,97,242,243,74,75,198,199,0,0,0,0,0,0,0,0,0,0,0,0,0,0,0,0,0,0,0,0,0,0,0,0,0,0,0,0,0,0,0,0,0,0,0,0,0,0,0,0,0,0,0,0,0,0,0,0,0,0,0,0},
  {0,1,2,3,4,5,6,7,8,9,10,11,12,13,14,15,0,1,2,3,0,1,2,3,4,5,6,7,8,9,10,11,12,13,14,15,0,1,2,3,76,69,70,72,74,66,71,75,67,77,68,73,79,78,64,65,12,14,8,10,13,15,9,11,0,2,4,6,1,3,5,7,4,6,8,10,0,2,5,7,9,11,12,14,1,3,13,15,128,130,136,138,4,6,140,142,129,131,137,139,133,135,141,143,0,2,4,6,8,10,1,3,5,7,12,14,9,11,13,15,95,108,109,76,77,88,89,114,115,96,97,102,103,244,245,246,247,219,220,221,230,231,196,197,4,6,8,10,5,7,0,2,12,14,9,11,1,3,13,15,64,71,70,74,77,69,78,72,76,68,66,73,79,67,75,65,12,14,8,10,4,6,0,2,13,15,9,11,5,7,1,3,12,14,8,10,13,15,4,6,9,11,5,7,0,2,1,3,76,78,72,74,77,79,68,70,73,75,69,71,64,66,65,67,82,83,70,71,100,101,102,103,84,85,116,117,72,73,86,87,110,111,232,233,204,205,0,0,0,0,0,0,0,0,0,0,0,0,0,0,0,0,0,0,0,0,0,0,0,0,0,0,0,0,0,0,0,0,0,0,0,0,0,0,0,0,0,0,0,0,0,0,0,0,0,0},
  {64,65,66,67,68,69,70,71,72,73,74,75,76,77,78,79,0,1,2,3,4,5,6,7,8,9,10,11,12,13,14,15,70,64,76,66,74,72,79,71,78,67,69,65,75,77,68,73,0,2,8,10,1,3,9,11,12,14,4,6,13,15,5,7,4,6,12,14,8,10,0,2,5,7,13,15,9,11,1,3,4,6,12,14,8,10,0,2,5,7,13,15,9,11,1,3,136,138,128,130,137,139,129,131,140,142,141,143,132,134,133,135,12,14,4,6,13,15,0,2,8,10,5,7,1,3,9,11,4,6,5,7,0,2,8,10,12,14,1,3,9,11,13,15,4,6,8,10,5,7,0,2,12,14,9,11,1,3,13,15,132,134,128,130,133,135,129,131,136,138,140,142,137,139,141,143,8,10,9,11,4,6,0,2,12,14,5,7,1,3,13,15,4,6,12,14,8,10,5,7,13,15,9,11,0,2,1,3,8,10,0,2,9,11,140,142,1,3,132,134,141,143,133,135,92,93,108,109,98,99,80,81,100,101,70,71,110,111,82,83,68,69,104,105,108,109,102,103,244,245,0,0,0,0,0,0,0,0,0,0,0,0,0,0,0,0,0,0,0,0,0,0,0,0,0,0,0,0,0,0,0,0,0,0,0,0,0,0,0,0,0,0,0,0,0,0},
  {0,1,2,3,4,5,6,7,8,9,10,11,12,13,14,15,0,1,2,3,0,1,2,3,4,5,6,7,8,9,10,11,12,13,14,15,64,66,76,78,65,67,77,79,68,70,69,71,72,74,73,75,12,14,8,10,13,15,9,11,0,2,4,6,1,3,5,7,4,6,0,2,5,7,1,3,12,14,8,10,13,15,9,11,90,91,70,71,72,73,66,67,64,65,84,85,92,93,80,81,86,87,94,95,76,77,88,89,106,107,78,79,96,97,108,109,72,73,80,81,98,99,74,75,110,111,240,241,86,87,92,93,206,207,192,193,0,2,1,3,4,6,8,10,12,14,5,7,9,11,13,15,8,10,12,14,0,2,9,11,13,15,1,3,4,6,5,7,8,10,9,11,4,6,0,2,12,14,5,7,1,3,13,15,4,6,5,7,8,10,12,14,9,11,13,15,0,2,1,3,132,134,5,7,136,138,140,142,9,11,141,143,128,130,129,131,104,105,72,73,86,87,102,103,90,91,118,119,68,69,206,207,114,115,66,67,110,111,222,223,216,217,204,205,0,0,0,0,0,0,0,0,0,0,0,0,0,0,0,0,0,0,0,0,0,0,0,0,0,0,0,0,0,0,0,0,0,0,0,0,0,0,0,0,0,0,0,0,0,0,0,0,0,0,0,0},
  {64,65,66,67,68,69,70,71,72,73,74,75,76,77,78,79,0,1,2,3,0,1,2,3,4,5,6,7,8,9,10,11,12,13,14,15,64,66,76,78,65,67,77,79,68,70,69,71,72,74,73,75,12,14,8,10,13,15,9,11,0,2,4,6,1,3,5,7,4,6,8,10,0,2,5,7,9,11,12,14,1,3,13,15,0,2,8,10,4,6,12,14,1,3,9,11,5,7,13,15,99,102,103,68,69,110,111,104,105,73,116,117,82,83,100,101,74,75,86,87,92,93,118,119,68,69,4,6,5,7,12,14,8,10,0,2,13,15,9,11,1,3,79,68,65,67,70,64,71,78,77,69,72,75,70,74,79,76,73,68,67,66,65,8,10,0,2,9,11,12,14,1,3,4,6,13,15,5,7,12,14,8,10,4,6,0,2,13,15,9,11,5,7,1,3,4,6,12,14,8,10,5,7,13,15,0,2,9,11,1,3,80,81,96,97,92,93,108,109,70,71,82,83,100,101,78,206,207,106,107,86,87,94,95,76,77,220,221,200,201,226,227,0,0,0,0,0,0,0,0,0,0,0,0,0,0,0,0,0,0,0,0,0,0,0,0,0,0,0,0,0,0,0,0,0,0,0,0,0,0,0,0,0,0,0,0,0,0,0,0,0,0,0,0,0,0},
};

struct alignas(64) Params {
  CUtensorMap a[6];
  CUtensorMap w[4];
  CUtensorMap ow;
  CUtensorMap xr;
  const bf16 *x0, *wqkv;
  bf16* out;
  uint32_t swap;
  uint32_t jobs[NPAIR][JMAX];
  uint8_t kseq[NPAIR][KMAX];
};

template <class T> __device__ __forceinline__ T* at(T* base, uint32_t bytes) {
  T* r;
  asm("{\n.reg .u32 lo, hi;\nmov.b64 {lo, hi}, %1;\nadd.cc.u32 lo, lo, %2;\naddc.u32 hi, hi, 0;\nmov.b64 %0, {lo, hi};\n}" : "=l"(r) : "l"(base), "r"(bytes));
  return r;
}
#define SCR(sm, member, bytes) reinterpret_cast<decltype(&scratch_base()->member[0])>(at((sm).scratch, offsetof(Scratch, member) + (bytes)))
#define counter(line, word) SCR(sm, cnt, (line) * 128 + (word) * 4)
#define TRS(st, slot) do {} while (0)
#define TRX(cond, job, bit, slot, reg) do {} while (0)
#define TR(job, slot) do {} while (0)
#define TRI(cond, job, slot) do {} while (0)
#define TRK(cond, job, slot) do {} while (0)
#define TRC(job, slot) do {} while (0)

__device__ __forceinline__ uint32_t smem_u32(const void* p) { return (uint32_t)__cvta_generic_to_shared(p); }
__device__ __forceinline__ void mbar_init(uint32_t bar, uint32_t cnt) { asm volatile("mbarrier.init.shared::cta.b64 [%0], %1;" ::"r"(bar), "r"(cnt) : "memory"); }
__device__ __forceinline__ void mbar_expect_tx(uint32_t bar, uint32_t bytes) { asm volatile("mbarrier.arrive.expect_tx.shared::cta.b64 _, [%0], %1;" ::"r"(bar), "r"(bytes) : "memory"); }
__device__ __forceinline__ void mbar_arrive_n(uint32_t bar, uint32_t cnt) { asm volatile("mbarrier.arrive.shared::cta.b64 _, [%0], %1;" ::"r"(bar), "r"(cnt) : "memory"); }
__device__ __forceinline__ void mbar_arrive_cl_if(uint32_t cond, uint32_t bar) {
  asm volatile("{\n.reg .pred p;\nsetp.ne.u32 p, %1, 0;\n@p mbarrier.arrive.shared::cluster.b64 _, [%0];\n}" ::"r"(bar), "r"(cond) : "memory");
}
__device__ __forceinline__ void mbar_arrive_warp(uint32_t bar) {
  asm volatile("{\n.reg .pred p;\nbar.warp.sync -1;\nelect.sync _|p, -1;\n@p mbarrier.arrive.shared::cta.b64 _, [%0];\n}" ::"r"(bar) : "memory");
}
__device__ __forceinline__ uint32_t mapa(uint32_t addr, uint32_t cta) { uint32_t r; asm("mapa.shared::cluster.u32 %0, %1, %2;" : "=r"(r) : "r"(addr), "r"(cta)); return r; }
__device__ __forceinline__ bool mbar_test(uint32_t bar, uint32_t parity) {
  uint32_t ok;
  asm volatile("{\n.reg .pred p;\nmbarrier.test_wait.parity.shared::cta.b64 p, [%1], %2;\nselp.u32 %0, 1, 0, p;\n}\n" : "=r"(ok) : "r"(bar), "r"(parity) : "memory");
  return ok;
}
__device__ __forceinline__ void mbar_wait(uint32_t bar, uint32_t parity) {
  asm volatile(
      "{\n.reg .pred p;\n.reg .u32 n;\nmov.u32 n, 0;\n"
      "WAIT:\nmbarrier.try_wait.parity.shared::cta.b64 p, [%0], %1;\n@p bra DONE;\n"
      "add.u32 n, n, 1;\nsetp.lt.u32 p, n, %2;\n@p bra WAIT;\ntrap;\nDONE:\n}\n" ::"r"(bar), "r"(parity), "n"(SPIN_LIMIT) : "memory");
}
template <int ID, int N> __device__ __forceinline__ void bar_sync() { asm volatile("bar.sync %0, %1;" ::"n"(ID), "n"(N) : "memory"); }
template <int ID, int N> __device__ __forceinline__ void bar_arrive() { asm volatile("bar.arrive %0, %1;" ::"n"(ID), "n"(N) : "memory"); }
__device__ __forceinline__ uint32_t ld_relaxed(const uint32_t* p) { uint32_t v; asm volatile("ld.relaxed.gpu.global.u32 %0, [%1];" : "=r"(v) : "l"(p) : "memory"); return v; }
__device__ __forceinline__ void red_relaxed(uint32_t* p, uint32_t v) { asm volatile("red.relaxed.gpu.global.add.u32 [%0], %1;" ::"l"(p), "r"(v) : "memory"); }
__device__ __forceinline__ void red_release(uint32_t* p, uint32_t v) {
  asm volatile("fence.release.gpu;\nred.relaxed.gpu.global.add.u32 [%0], %1;" ::"l"(p), "r"(v) : "memory");
}
__device__ __forceinline__ bool elect() {
  uint32_t p;
  asm volatile("{\n.reg .pred P;\nelect.sync _|P, 0xffffffff;\nselp.u32 %0, 1, 0, P;\n}\n" : "=r"(p));
  return p;
}
__device__ __forceinline__ void fence_acquire() { asm volatile("fence.acquire.gpu;" ::: "memory"); }
__device__ __forceinline__ void wait_count(const uint32_t* p, uint32_t target) {
  for (uint32_t n = 0; !__all_sync(~0u, (int)(ld_relaxed(p) - target) >= 0); n++) {
    __nanosleep(200);
    if (n > SPIN_LIMIT) __trap();
  }
  fence_acquire();
}
__device__ __forceinline__ void fence_proxy_async() { asm volatile("fence.proxy.async.global;" ::: "memory"); }
__device__ __forceinline__ void fence_proxy_async_smem() { asm volatile("fence.proxy.async.shared::cta;" ::: "memory"); }
__device__ __forceinline__ void tma4d_mc(uint32_t dst, const CUtensorMap* tm, int c1, int c2, uint32_t bar, uint64_t pol) {
  asm volatile("cp.async.bulk.tensor.4d.shared::cluster.global.mbarrier::complete_tx::bytes.multicast::cluster.L2::cache_hint [%0], [%1, {%3, %4, %5, %3}], [%2], %6, %7;"
               ::"r"(dst), "l"(tm), "r"(bar), "r"(0), "r"(c1), "r"(c2), "h"((uint16_t)3), "l"(pol) : "memory");
}
__device__ __forceinline__ void tma3d(uint32_t dst, const CUtensorMap* tm, int c0, int c1, int c2, uint32_t bar, uint64_t pol) {
  asm volatile("cp.async.bulk.tensor.3d.shared::cluster.global.mbarrier::complete_tx::bytes.L2::cache_hint [%0], [%1, {%3, %4, %5}], [%2], %6;"
               ::"r"(dst), "l"(tm), "r"(bar), "r"(c0), "r"(c1), "r"(c2), "l"(pol) : "memory");
}
__device__ __forceinline__ void tma3d_reduce_add(const CUtensorMap* tm, int c0, int c1, int c2, uint32_t src) {
  asm volatile("cp.reduce.async.bulk.tensor.3d.global.shared::cta.add.tile.bulk_group [%0, {%2, %3, %4}], [%1];"
               ::"l"(tm), "r"(src), "r"(c0), "r"(c1), "r"(c2) : "memory");
}
__device__ __forceinline__ void tma3d_store(const CUtensorMap* tm, int c0, int c1, int c2, uint32_t src) {
  asm volatile("cp.async.bulk.tensor.3d.global.shared::cta.tile.bulk_group [%0, {%2, %3, %4}], [%1];"
               ::"l"(tm), "r"(src), "r"(c0), "r"(c1), "r"(c2) : "memory");
}
__device__ __forceinline__ void bulk_commit() { asm volatile("cp.async.bulk.commit_group;" ::: "memory"); }
template <int N> __device__ __forceinline__ void bulk_wait_read() { asm volatile("cp.async.bulk.wait_group.read %0;" ::"n"(N) : "memory"); }
__device__ __forceinline__ void bulk_wait() { asm volatile("cp.async.bulk.wait_group 0;" ::: "memory"); }
__device__ __forceinline__ uint2 lds64(uint32_t a) { uint2 v; asm volatile("ld.shared.v2.u32 {%0,%1}, [%2];" : "=r"(v.x), "=r"(v.y) : "r"(a) : "memory"); return v; }
__device__ __forceinline__ float lds32f(uint32_t a) { float v; asm volatile("ld.shared.f32 %0, [%1];" : "=f"(v) : "r"(a) : "memory"); return v; }
__device__ __forceinline__ uint4 lds128(uint32_t a) { uint4 v; asm volatile("ld.shared.v4.u32 {%0,%1,%2,%3}, [%4];" : "=r"(v.x), "=r"(v.y), "=r"(v.z), "=r"(v.w) : "r"(a) : "memory"); return v; }
__device__ __forceinline__ uint2 lds64v(uint32_t a) { uint2 v; asm volatile("ld.volatile.shared.v2.u32 {%0,%1}, [%2];" : "=r"(v.x), "=r"(v.y) : "r"(a) : "memory"); return v; }
__device__ __forceinline__ uint4 lds128v(uint32_t a) { uint4 v; asm volatile("ld.volatile.shared.v4.u32 {%0,%1,%2,%3}, [%4];" : "=r"(v.x), "=r"(v.y), "=r"(v.z), "=r"(v.w) : "r"(a) : "memory"); return v; }
__device__ __forceinline__ void sts32(uint32_t a, uint32_t v) { asm volatile("st.shared.u32 [%0], %1;" ::"r"(a), "r"(v) : "memory"); }
__device__ __forceinline__ void sts64(uint32_t a, uint2 v) { asm volatile("st.shared.v2.u32 [%0], {%1,%2};" ::"r"(a), "r"(v.x), "r"(v.y) : "memory"); }
__device__ __forceinline__ void stg128(void* p, uint4 v) { asm volatile("st.global.L1::no_allocate.v4.u32 [%0], {%1,%2,%3,%4};" ::"l"(p), "r"(v.x), "r"(v.y), "r"(v.z), "r"(v.w) : "memory"); }
__device__ __forceinline__ uint4 ldg128(const void* p) { uint4 v; asm volatile("ld.relaxed.gpu.global.v4.u32 {%0,%1,%2,%3}, [%4];" : "=r"(v.x), "=r"(v.y), "=r"(v.z), "=r"(v.w) : "l"(p) : "memory"); return v; }
__device__ __forceinline__ void prefetch_tm(const CUtensorMap* tm) { asm volatile("prefetch.tensormap [%0];" ::"l"(tm) : "memory"); }
template <int N> __device__ __forceinline__ void wg_wait() { asm volatile("wgmma.wait_group.sync.aligned %0;" ::"n"(N) : "memory"); }
__device__ __forceinline__ void cluster_arrive() { asm volatile("barrier.cluster.arrive.relaxed.aligned;" ::: "memory"); }
__device__ __forceinline__ void cluster_wait() { asm volatile("barrier.cluster.wait.acquire.aligned;" ::: "memory"); }
__device__ __forceinline__ uint32_t pack_bf16(float lo, float hi) { uint32_t r; asm("cvt.rn.bf16x2.f32 %0, %1, %2;" : "=r"(r) : "f"(hi), "f"(lo)); return r; }
__device__ __forceinline__ float bf_lo(uint32_t v) { return __uint_as_float(v << 16); }
__device__ __forceinline__ float bf_hi(uint32_t v) { return __uint_as_float(v & 0xffff0000u); }
__device__ __forceinline__ uint32_t dup_hi(uint32_t v) { return __byte_perm(v, 0, 0x3232); }
__device__ __forceinline__ float bf_round(float x) { return __bfloat162float(__float2bfloat16_rn(x)); }
__device__ __forceinline__ uint32_t bf2_add(uint32_t a, uint32_t b) { uint32_t r; asm("add.rn.bf16x2 %0, %1, %2;" : "=r"(r) : "r"(a), "r"(b)); return r; }
__device__ __forceinline__ uint32_t bf2_mul(uint32_t a, uint32_t b) { uint32_t r; asm("mul.rn.bf16x2 %0, %1, %2;" : "=r"(r) : "r"(a), "r"(b)); return r; }
__device__ __forceinline__ uint32_t bf2_fma(uint32_t a, uint32_t b, uint32_t c) { uint32_t r; asm("fma.rn.bf16x2 %0, %1, %2, %3;" : "=r"(r) : "r"(a), "r"(b), "r"(c)); return r; }
__device__ __forceinline__ uint4 add8(uint4 a, uint4 b) { return make_uint4(bf2_add(a.x, b.x), bf2_add(a.y, b.y), bf2_add(a.z, b.z), bf2_add(a.w, b.w)); }
__device__ __forceinline__ uint4 fma8(uint32_t a, uint4 b, uint4 c) { return make_uint4(bf2_fma(a, b.x, c.x), bf2_fma(a, b.y, c.y), bf2_fma(a, b.z, c.z), bf2_fma(a, b.w, c.w)); }
__device__ __forceinline__ void stsm4(uint32_t a, uint32_t r0, uint32_t r1, uint32_t r2, uint32_t r3) {
  asm volatile("stmatrix.sync.aligned.m8n8.x4.shared.b16 [%0], {%1,%2,%3,%4};" ::"r"(a), "r"(r0), "r"(r1), "r"(r2), "r"(r3) : "memory");
}
__device__ __forceinline__ void ldsm4(uint32_t a, uint32_t (&r)[4]) {
  asm volatile("ldmatrix.sync.aligned.m8n8.x4.shared.b16 {%0,%1,%2,%3}, [%4];" : "=r"(r[0]), "=r"(r[1]), "=r"(r[2]), "=r"(r[3]) : "r"(a) : "memory");
}
__device__ __forceinline__ void ldsm4t(uint32_t a, uint32_t (&r)[4]) {
  asm volatile("ldmatrix.sync.aligned.m8n8.x4.trans.shared.b16 {%0,%1,%2,%3}, [%4];" : "=r"(r[0]), "=r"(r[1]), "=r"(r[2]), "=r"(r[3]) : "r"(a) : "memory");
}
__device__ __forceinline__ void mma16816(float (&c)[4], uint32_t a0, uint32_t a1, uint32_t a2, uint32_t a3, uint32_t b0, uint32_t b1) {
  asm volatile("mma.sync.aligned.m16n8k16.row.col.f32.bf16.bf16.f32 {%0,%1,%2,%3}, {%4,%5,%6,%7}, {%8,%9}, {%0,%1,%2,%3};"
               : "+f"(c[0]), "+f"(c[1]), "+f"(c[2]), "+f"(c[3]) : "r"(a0), "r"(a1), "r"(a2), "r"(a3), "r"(b0), "r"(b1));
}
__device__ __forceinline__ void mma1688(float (&c)[4], uint32_t a0, uint32_t a1, uint32_t b0) {
  asm volatile("mma.sync.aligned.m16n8k8.row.col.f32.bf16.bf16.f32 {%0,%1,%2,%3}, {%4,%5}, {%6}, {%0,%1,%2,%3};"
               : "+f"(c[0]), "+f"(c[1]), "+f"(c[2]), "+f"(c[3]) : "r"(a0), "r"(a1), "r"(b0));
}
__device__ __forceinline__ float ex2(float x) { float y; asm("ex2.approx.ftz.f32 %0, %1;" : "=f"(y) : "f"(x)); return y; }
__device__ __forceinline__ float sqrt_fast(float x) { float y; asm("sqrt.approx.f32 %0, %1;" : "=f"(y) : "f"(x)); return y; }
__device__ __forceinline__ float tanh_fast(float x) { float y; asm("tanh.approx.f32 %0, %1;" : "=f"(y) : "f"(x)); return y; }
__device__ __forceinline__ float rcp(float x) { float y; asm("rcp.approx.ftz.f32 %0, %1;" : "=f"(y) : "f"(x)); return y; }
__device__ __forceinline__ uint32_t opaque_zero() { uint32_t z; asm volatile("mov.u32 %0, %%ctaid.y;" : "=r"(z)); return z; }
__device__ __forceinline__ uint32_t clock32() { uint32_t t; asm volatile("mov.u32 %0, %%clock;" : "=r"(t)::"memory"); return t; }
__device__ __forceinline__ void delay(uint32_t n) { for (const uint32_t t0 = clock32(); clock32() - t0 < n;) {} }
__device__ __forceinline__ int fresh_tid() { int t; asm volatile("mov.u32 %0, %%tid.x;" : "=r"(t)); return t; }

__device__ __forceinline__ void first_kstep(float (&d)[128], uint32_t a, uint32_t b) {
  asm volatile("{\n.reg .u32 t;\n.reg .u64 da, db;\nwgmma.fence.sync.aligned;\n"
    "add.u32 t, %128, 0;\nmov.b64 da, {t, %130};\nadd.u32 t, %129, 0;\nmov.b64 db, {t, %130};\n"
    "wgmma.mma_async.sync.aligned.m64n256k16.f32.bf16.bf16 {%0, %1, %2, %3, %4, %5, %6, %7, %8, %9, %10, %11, %12, %13, %14, %15, %16, %17, %18, %19, %20, %21, %22, %23, %24, %25, %26, %27, %28, %29, %30, %31, %32, %33, %34, %35, %36, %37, %38, %39, %40, %41, %42, %43, %44, %45, %46, %47, %48, %49, %50, %51, %52, %53, %54, %55, %56, %57, %58, %59, %60, %61, %62, %63, %64, %65, %66, %67, %68, %69, %70, %71, %72, %73, %74, %75, %76, %77, %78, %79, %80, %81, %82, %83, %84, %85, %86, %87, %88, %89, %90, %91, %92, %93, %94, %95, %96, %97, %98, %99, %100, %101, %102, %103, %104, %105, %106, %107, %108, %109, %110, %111, %112, %113, %114, %115, %116, %117, %118, %119, %120, %121, %122, %123, %124, %125, %126, %127}, da, db, 0, 1, 1, 0, 1;\nwgmma.commit_group.sync.aligned;\n"
    "add.u32 t, %128, 2;\nmov.b64 da, {t, %130};\nadd.u32 t, %129, 128;\nmov.b64 db, {t, %130};\n"
    "wgmma.mma_async.sync.aligned.m64n256k16.f32.bf16.bf16 {%0, %1, %2, %3, %4, %5, %6, %7, %8, %9, %10, %11, %12, %13, %14, %15, %16, %17, %18, %19, %20, %21, %22, %23, %24, %25, %26, %27, %28, %29, %30, %31, %32, %33, %34, %35, %36, %37, %38, %39, %40, %41, %42, %43, %44, %45, %46, %47, %48, %49, %50, %51, %52, %53, %54, %55, %56, %57, %58, %59, %60, %61, %62, %63, %64, %65, %66, %67, %68, %69, %70, %71, %72, %73, %74, %75, %76, %77, %78, %79, %80, %81, %82, %83, %84, %85, %86, %87, %88, %89, %90, %91, %92, %93, %94, %95, %96, %97, %98, %99, %100, %101, %102, %103, %104, %105, %106, %107, %108, %109, %110, %111, %112, %113, %114, %115, %116, %117, %118, %119, %120, %121, %122, %123, %124, %125, %126, %127}, da, db, 1, 1, 1, 0, 1;\n"
    "add.u32 t, %128, 4;\nmov.b64 da, {t, %130};\nadd.u32 t, %129, 1024;\nmov.b64 db, {t, %130};\n"
    "wgmma.mma_async.sync.aligned.m64n256k16.f32.bf16.bf16 {%0, %1, %2, %3, %4, %5, %6, %7, %8, %9, %10, %11, %12, %13, %14, %15, %16, %17, %18, %19, %20, %21, %22, %23, %24, %25, %26, %27, %28, %29, %30, %31, %32, %33, %34, %35, %36, %37, %38, %39, %40, %41, %42, %43, %44, %45, %46, %47, %48, %49, %50, %51, %52, %53, %54, %55, %56, %57, %58, %59, %60, %61, %62, %63, %64, %65, %66, %67, %68, %69, %70, %71, %72, %73, %74, %75, %76, %77, %78, %79, %80, %81, %82, %83, %84, %85, %86, %87, %88, %89, %90, %91, %92, %93, %94, %95, %96, %97, %98, %99, %100, %101, %102, %103, %104, %105, %106, %107, %108, %109, %110, %111, %112, %113, %114, %115, %116, %117, %118, %119, %120, %121, %122, %123, %124, %125, %126, %127}, da, db, 1, 1, 1, 0, 1;\n"
    "add.u32 t, %128, 6;\nmov.b64 da, {t, %130};\nadd.u32 t, %129, 1152;\nmov.b64 db, {t, %130};\n"
    "wgmma.mma_async.sync.aligned.m64n256k16.f32.bf16.bf16 {%0, %1, %2, %3, %4, %5, %6, %7, %8, %9, %10, %11, %12, %13, %14, %15, %16, %17, %18, %19, %20, %21, %22, %23, %24, %25, %26, %27, %28, %29, %30, %31, %32, %33, %34, %35, %36, %37, %38, %39, %40, %41, %42, %43, %44, %45, %46, %47, %48, %49, %50, %51, %52, %53, %54, %55, %56, %57, %58, %59, %60, %61, %62, %63, %64, %65, %66, %67, %68, %69, %70, %71, %72, %73, %74, %75, %76, %77, %78, %79, %80, %81, %82, %83, %84, %85, %86, %87, %88, %89, %90, %91, %92, %93, %94, %95, %96, %97, %98, %99, %100, %101, %102, %103, %104, %105, %106, %107, %108, %109, %110, %111, %112, %113, %114, %115, %116, %117, %118, %119, %120, %121, %122, %123, %124, %125, %126, %127}, da, db, 1, 1, 1, 0, 1;\nwgmma.commit_group.sync.aligned;\n"
    "}\n"
    : "=f"(d[0]), "=f"(d[1]), "=f"(d[2]), "=f"(d[3]), "=f"(d[4]), "=f"(d[5]), "=f"(d[6]), "=f"(d[7]), "=f"(d[8]), "=f"(d[9]), "=f"(d[10]), "=f"(d[11]), "=f"(d[12]), "=f"(d[13]), "=f"(d[14]), "=f"(d[15]), "=f"(d[16]), "=f"(d[17]), "=f"(d[18]), "=f"(d[19]), "=f"(d[20]), "=f"(d[21]), "=f"(d[22]), "=f"(d[23]), "=f"(d[24]), "=f"(d[25]), "=f"(d[26]), "=f"(d[27]), "=f"(d[28]), "=f"(d[29]), "=f"(d[30]), "=f"(d[31]), "=f"(d[32]), "=f"(d[33]), "=f"(d[34]), "=f"(d[35]), "=f"(d[36]), "=f"(d[37]), "=f"(d[38]), "=f"(d[39]), "=f"(d[40]), "=f"(d[41]), "=f"(d[42]), "=f"(d[43]), "=f"(d[44]), "=f"(d[45]), "=f"(d[46]), "=f"(d[47]), "=f"(d[48]), "=f"(d[49]), "=f"(d[50]), "=f"(d[51]), "=f"(d[52]), "=f"(d[53]), "=f"(d[54]), "=f"(d[55]), "=f"(d[56]), "=f"(d[57]), "=f"(d[58]), "=f"(d[59]), "=f"(d[60]), "=f"(d[61]), "=f"(d[62]), "=f"(d[63]), "=f"(d[64]), "=f"(d[65]), "=f"(d[66]), "=f"(d[67]), "=f"(d[68]), "=f"(d[69]), "=f"(d[70]), "=f"(d[71]), "=f"(d[72]), "=f"(d[73]), "=f"(d[74]), "=f"(d[75]), "=f"(d[76]), "=f"(d[77]), "=f"(d[78]), "=f"(d[79]), "=f"(d[80]), "=f"(d[81]), "=f"(d[82]), "=f"(d[83]), "=f"(d[84]), "=f"(d[85]), "=f"(d[86]), "=f"(d[87]), "=f"(d[88]), "=f"(d[89]), "=f"(d[90]), "=f"(d[91]), "=f"(d[92]), "=f"(d[93]), "=f"(d[94]), "=f"(d[95]), "=f"(d[96]), "=f"(d[97]), "=f"(d[98]), "=f"(d[99]), "=f"(d[100]), "=f"(d[101]), "=f"(d[102]), "=f"(d[103]), "=f"(d[104]), "=f"(d[105]), "=f"(d[106]), "=f"(d[107]), "=f"(d[108]), "=f"(d[109]), "=f"(d[110]), "=f"(d[111]), "=f"(d[112]), "=f"(d[113]), "=f"(d[114]), "=f"(d[115]), "=f"(d[116]), "=f"(d[117]), "=f"(d[118]), "=f"(d[119]), "=f"(d[120]), "=f"(d[121]), "=f"(d[122]), "=f"(d[123]), "=f"(d[124]), "=f"(d[125]), "=f"(d[126]), "=f"(d[127])
    : "r"(a), "r"(b), "n"(0x40000040) : "memory");
}
__device__ __forceinline__ void kstep(float (&d)[128], uint32_t a, uint32_t b) {
  asm volatile("{\n.reg .u32 t;\n.reg .u64 da, db;\nwgmma.fence.sync.aligned;\n"
    "add.u32 t, %128, 0;\nmov.b64 da, {t, %130};\nadd.u32 t, %129, 0;\nmov.b64 db, {t, %130};\n"
    "wgmma.mma_async.sync.aligned.m64n256k16.f32.bf16.bf16 {%0, %1, %2, %3, %4, %5, %6, %7, %8, %9, %10, %11, %12, %13, %14, %15, %16, %17, %18, %19, %20, %21, %22, %23, %24, %25, %26, %27, %28, %29, %30, %31, %32, %33, %34, %35, %36, %37, %38, %39, %40, %41, %42, %43, %44, %45, %46, %47, %48, %49, %50, %51, %52, %53, %54, %55, %56, %57, %58, %59, %60, %61, %62, %63, %64, %65, %66, %67, %68, %69, %70, %71, %72, %73, %74, %75, %76, %77, %78, %79, %80, %81, %82, %83, %84, %85, %86, %87, %88, %89, %90, %91, %92, %93, %94, %95, %96, %97, %98, %99, %100, %101, %102, %103, %104, %105, %106, %107, %108, %109, %110, %111, %112, %113, %114, %115, %116, %117, %118, %119, %120, %121, %122, %123, %124, %125, %126, %127}, da, db, 1, 1, 1, 0, 1;\nwgmma.commit_group.sync.aligned;\n"
    "add.u32 t, %128, 2;\nmov.b64 da, {t, %130};\nadd.u32 t, %129, 128;\nmov.b64 db, {t, %130};\n"
    "wgmma.mma_async.sync.aligned.m64n256k16.f32.bf16.bf16 {%0, %1, %2, %3, %4, %5, %6, %7, %8, %9, %10, %11, %12, %13, %14, %15, %16, %17, %18, %19, %20, %21, %22, %23, %24, %25, %26, %27, %28, %29, %30, %31, %32, %33, %34, %35, %36, %37, %38, %39, %40, %41, %42, %43, %44, %45, %46, %47, %48, %49, %50, %51, %52, %53, %54, %55, %56, %57, %58, %59, %60, %61, %62, %63, %64, %65, %66, %67, %68, %69, %70, %71, %72, %73, %74, %75, %76, %77, %78, %79, %80, %81, %82, %83, %84, %85, %86, %87, %88, %89, %90, %91, %92, %93, %94, %95, %96, %97, %98, %99, %100, %101, %102, %103, %104, %105, %106, %107, %108, %109, %110, %111, %112, %113, %114, %115, %116, %117, %118, %119, %120, %121, %122, %123, %124, %125, %126, %127}, da, db, 1, 1, 1, 0, 1;\n"
    "add.u32 t, %128, 4;\nmov.b64 da, {t, %130};\nadd.u32 t, %129, 1024;\nmov.b64 db, {t, %130};\n"
    "wgmma.mma_async.sync.aligned.m64n256k16.f32.bf16.bf16 {%0, %1, %2, %3, %4, %5, %6, %7, %8, %9, %10, %11, %12, %13, %14, %15, %16, %17, %18, %19, %20, %21, %22, %23, %24, %25, %26, %27, %28, %29, %30, %31, %32, %33, %34, %35, %36, %37, %38, %39, %40, %41, %42, %43, %44, %45, %46, %47, %48, %49, %50, %51, %52, %53, %54, %55, %56, %57, %58, %59, %60, %61, %62, %63, %64, %65, %66, %67, %68, %69, %70, %71, %72, %73, %74, %75, %76, %77, %78, %79, %80, %81, %82, %83, %84, %85, %86, %87, %88, %89, %90, %91, %92, %93, %94, %95, %96, %97, %98, %99, %100, %101, %102, %103, %104, %105, %106, %107, %108, %109, %110, %111, %112, %113, %114, %115, %116, %117, %118, %119, %120, %121, %122, %123, %124, %125, %126, %127}, da, db, 1, 1, 1, 0, 1;\n"
    "add.u32 t, %128, 6;\nmov.b64 da, {t, %130};\nadd.u32 t, %129, 1152;\nmov.b64 db, {t, %130};\n"
    "wgmma.mma_async.sync.aligned.m64n256k16.f32.bf16.bf16 {%0, %1, %2, %3, %4, %5, %6, %7, %8, %9, %10, %11, %12, %13, %14, %15, %16, %17, %18, %19, %20, %21, %22, %23, %24, %25, %26, %27, %28, %29, %30, %31, %32, %33, %34, %35, %36, %37, %38, %39, %40, %41, %42, %43, %44, %45, %46, %47, %48, %49, %50, %51, %52, %53, %54, %55, %56, %57, %58, %59, %60, %61, %62, %63, %64, %65, %66, %67, %68, %69, %70, %71, %72, %73, %74, %75, %76, %77, %78, %79, %80, %81, %82, %83, %84, %85, %86, %87, %88, %89, %90, %91, %92, %93, %94, %95, %96, %97, %98, %99, %100, %101, %102, %103, %104, %105, %106, %107, %108, %109, %110, %111, %112, %113, %114, %115, %116, %117, %118, %119, %120, %121, %122, %123, %124, %125, %126, %127}, da, db, 1, 1, 1, 0, 1;\nwgmma.commit_group.sync.aligned;\n"
    "}\n"
    : "+f"(d[0]), "+f"(d[1]), "+f"(d[2]), "+f"(d[3]), "+f"(d[4]), "+f"(d[5]), "+f"(d[6]), "+f"(d[7]), "+f"(d[8]), "+f"(d[9]), "+f"(d[10]), "+f"(d[11]), "+f"(d[12]), "+f"(d[13]), "+f"(d[14]), "+f"(d[15]), "+f"(d[16]), "+f"(d[17]), "+f"(d[18]), "+f"(d[19]), "+f"(d[20]), "+f"(d[21]), "+f"(d[22]), "+f"(d[23]), "+f"(d[24]), "+f"(d[25]), "+f"(d[26]), "+f"(d[27]), "+f"(d[28]), "+f"(d[29]), "+f"(d[30]), "+f"(d[31]), "+f"(d[32]), "+f"(d[33]), "+f"(d[34]), "+f"(d[35]), "+f"(d[36]), "+f"(d[37]), "+f"(d[38]), "+f"(d[39]), "+f"(d[40]), "+f"(d[41]), "+f"(d[42]), "+f"(d[43]), "+f"(d[44]), "+f"(d[45]), "+f"(d[46]), "+f"(d[47]), "+f"(d[48]), "+f"(d[49]), "+f"(d[50]), "+f"(d[51]), "+f"(d[52]), "+f"(d[53]), "+f"(d[54]), "+f"(d[55]), "+f"(d[56]), "+f"(d[57]), "+f"(d[58]), "+f"(d[59]), "+f"(d[60]), "+f"(d[61]), "+f"(d[62]), "+f"(d[63]), "+f"(d[64]), "+f"(d[65]), "+f"(d[66]), "+f"(d[67]), "+f"(d[68]), "+f"(d[69]), "+f"(d[70]), "+f"(d[71]), "+f"(d[72]), "+f"(d[73]), "+f"(d[74]), "+f"(d[75]), "+f"(d[76]), "+f"(d[77]), "+f"(d[78]), "+f"(d[79]), "+f"(d[80]), "+f"(d[81]), "+f"(d[82]), "+f"(d[83]), "+f"(d[84]), "+f"(d[85]), "+f"(d[86]), "+f"(d[87]), "+f"(d[88]), "+f"(d[89]), "+f"(d[90]), "+f"(d[91]), "+f"(d[92]), "+f"(d[93]), "+f"(d[94]), "+f"(d[95]), "+f"(d[96]), "+f"(d[97]), "+f"(d[98]), "+f"(d[99]), "+f"(d[100]), "+f"(d[101]), "+f"(d[102]), "+f"(d[103]), "+f"(d[104]), "+f"(d[105]), "+f"(d[106]), "+f"(d[107]), "+f"(d[108]), "+f"(d[109]), "+f"(d[110]), "+f"(d[111]), "+f"(d[112]), "+f"(d[113]), "+f"(d[114]), "+f"(d[115]), "+f"(d[116]), "+f"(d[117]), "+f"(d[118]), "+f"(d[119]), "+f"(d[120]), "+f"(d[121]), "+f"(d[122]), "+f"(d[123]), "+f"(d[124]), "+f"(d[125]), "+f"(d[126]), "+f"(d[127])
    : "r"(a), "r"(b), "n"(0x40000040) : "memory");
}
__device__ __forceinline__ void first_kstep(float (&d)[96], uint32_t a, uint32_t b) {
  asm volatile("{\n.reg .u32 t;\n.reg .u64 da, db;\nwgmma.fence.sync.aligned;\n"
    "add.u32 t, %96, 0;\nmov.b64 da, {t, %98};\nadd.u32 t, %97, 0;\nmov.b64 db, {t, %98};\n"
    "wgmma.mma_async.sync.aligned.m64n192k16.f32.bf16.bf16 {%0, %1, %2, %3, %4, %5, %6, %7, %8, %9, %10, %11, %12, %13, %14, %15, %16, %17, %18, %19, %20, %21, %22, %23, %24, %25, %26, %27, %28, %29, %30, %31, %32, %33, %34, %35, %36, %37, %38, %39, %40, %41, %42, %43, %44, %45, %46, %47, %48, %49, %50, %51, %52, %53, %54, %55, %56, %57, %58, %59, %60, %61, %62, %63, %64, %65, %66, %67, %68, %69, %70, %71, %72, %73, %74, %75, %76, %77, %78, %79, %80, %81, %82, %83, %84, %85, %86, %87, %88, %89, %90, %91, %92, %93, %94, %95}, da, db, 0, 1, 1, 0, 1;\nwgmma.commit_group.sync.aligned;\n"
    "add.u32 t, %96, 2;\nmov.b64 da, {t, %98};\nadd.u32 t, %97, 128;\nmov.b64 db, {t, %98};\n"
    "wgmma.mma_async.sync.aligned.m64n192k16.f32.bf16.bf16 {%0, %1, %2, %3, %4, %5, %6, %7, %8, %9, %10, %11, %12, %13, %14, %15, %16, %17, %18, %19, %20, %21, %22, %23, %24, %25, %26, %27, %28, %29, %30, %31, %32, %33, %34, %35, %36, %37, %38, %39, %40, %41, %42, %43, %44, %45, %46, %47, %48, %49, %50, %51, %52, %53, %54, %55, %56, %57, %58, %59, %60, %61, %62, %63, %64, %65, %66, %67, %68, %69, %70, %71, %72, %73, %74, %75, %76, %77, %78, %79, %80, %81, %82, %83, %84, %85, %86, %87, %88, %89, %90, %91, %92, %93, %94, %95}, da, db, 1, 1, 1, 0, 1;\n"
    "add.u32 t, %96, 4;\nmov.b64 da, {t, %98};\nadd.u32 t, %97, 1024;\nmov.b64 db, {t, %98};\n"
    "wgmma.mma_async.sync.aligned.m64n192k16.f32.bf16.bf16 {%0, %1, %2, %3, %4, %5, %6, %7, %8, %9, %10, %11, %12, %13, %14, %15, %16, %17, %18, %19, %20, %21, %22, %23, %24, %25, %26, %27, %28, %29, %30, %31, %32, %33, %34, %35, %36, %37, %38, %39, %40, %41, %42, %43, %44, %45, %46, %47, %48, %49, %50, %51, %52, %53, %54, %55, %56, %57, %58, %59, %60, %61, %62, %63, %64, %65, %66, %67, %68, %69, %70, %71, %72, %73, %74, %75, %76, %77, %78, %79, %80, %81, %82, %83, %84, %85, %86, %87, %88, %89, %90, %91, %92, %93, %94, %95}, da, db, 1, 1, 1, 0, 1;\n"
    "add.u32 t, %96, 6;\nmov.b64 da, {t, %98};\nadd.u32 t, %97, 1152;\nmov.b64 db, {t, %98};\n"
    "wgmma.mma_async.sync.aligned.m64n192k16.f32.bf16.bf16 {%0, %1, %2, %3, %4, %5, %6, %7, %8, %9, %10, %11, %12, %13, %14, %15, %16, %17, %18, %19, %20, %21, %22, %23, %24, %25, %26, %27, %28, %29, %30, %31, %32, %33, %34, %35, %36, %37, %38, %39, %40, %41, %42, %43, %44, %45, %46, %47, %48, %49, %50, %51, %52, %53, %54, %55, %56, %57, %58, %59, %60, %61, %62, %63, %64, %65, %66, %67, %68, %69, %70, %71, %72, %73, %74, %75, %76, %77, %78, %79, %80, %81, %82, %83, %84, %85, %86, %87, %88, %89, %90, %91, %92, %93, %94, %95}, da, db, 1, 1, 1, 0, 1;\nwgmma.commit_group.sync.aligned;\n"
    "}\n"
    : "=f"(d[0]), "=f"(d[1]), "=f"(d[2]), "=f"(d[3]), "=f"(d[4]), "=f"(d[5]), "=f"(d[6]), "=f"(d[7]), "=f"(d[8]), "=f"(d[9]), "=f"(d[10]), "=f"(d[11]), "=f"(d[12]), "=f"(d[13]), "=f"(d[14]), "=f"(d[15]), "=f"(d[16]), "=f"(d[17]), "=f"(d[18]), "=f"(d[19]), "=f"(d[20]), "=f"(d[21]), "=f"(d[22]), "=f"(d[23]), "=f"(d[24]), "=f"(d[25]), "=f"(d[26]), "=f"(d[27]), "=f"(d[28]), "=f"(d[29]), "=f"(d[30]), "=f"(d[31]), "=f"(d[32]), "=f"(d[33]), "=f"(d[34]), "=f"(d[35]), "=f"(d[36]), "=f"(d[37]), "=f"(d[38]), "=f"(d[39]), "=f"(d[40]), "=f"(d[41]), "=f"(d[42]), "=f"(d[43]), "=f"(d[44]), "=f"(d[45]), "=f"(d[46]), "=f"(d[47]), "=f"(d[48]), "=f"(d[49]), "=f"(d[50]), "=f"(d[51]), "=f"(d[52]), "=f"(d[53]), "=f"(d[54]), "=f"(d[55]), "=f"(d[56]), "=f"(d[57]), "=f"(d[58]), "=f"(d[59]), "=f"(d[60]), "=f"(d[61]), "=f"(d[62]), "=f"(d[63]), "=f"(d[64]), "=f"(d[65]), "=f"(d[66]), "=f"(d[67]), "=f"(d[68]), "=f"(d[69]), "=f"(d[70]), "=f"(d[71]), "=f"(d[72]), "=f"(d[73]), "=f"(d[74]), "=f"(d[75]), "=f"(d[76]), "=f"(d[77]), "=f"(d[78]), "=f"(d[79]), "=f"(d[80]), "=f"(d[81]), "=f"(d[82]), "=f"(d[83]), "=f"(d[84]), "=f"(d[85]), "=f"(d[86]), "=f"(d[87]), "=f"(d[88]), "=f"(d[89]), "=f"(d[90]), "=f"(d[91]), "=f"(d[92]), "=f"(d[93]), "=f"(d[94]), "=f"(d[95])
    : "r"(a), "r"(b), "n"(0x40000040) : "memory");
}
__device__ __forceinline__ void kstep(float (&d)[96], uint32_t a, uint32_t b) {
  asm volatile("{\n.reg .u32 t;\n.reg .u64 da, db;\nwgmma.fence.sync.aligned;\n"
    "add.u32 t, %96, 0;\nmov.b64 da, {t, %98};\nadd.u32 t, %97, 0;\nmov.b64 db, {t, %98};\n"
    "wgmma.mma_async.sync.aligned.m64n192k16.f32.bf16.bf16 {%0, %1, %2, %3, %4, %5, %6, %7, %8, %9, %10, %11, %12, %13, %14, %15, %16, %17, %18, %19, %20, %21, %22, %23, %24, %25, %26, %27, %28, %29, %30, %31, %32, %33, %34, %35, %36, %37, %38, %39, %40, %41, %42, %43, %44, %45, %46, %47, %48, %49, %50, %51, %52, %53, %54, %55, %56, %57, %58, %59, %60, %61, %62, %63, %64, %65, %66, %67, %68, %69, %70, %71, %72, %73, %74, %75, %76, %77, %78, %79, %80, %81, %82, %83, %84, %85, %86, %87, %88, %89, %90, %91, %92, %93, %94, %95}, da, db, 1, 1, 1, 0, 1;\nwgmma.commit_group.sync.aligned;\n"
    "add.u32 t, %96, 2;\nmov.b64 da, {t, %98};\nadd.u32 t, %97, 128;\nmov.b64 db, {t, %98};\n"
    "wgmma.mma_async.sync.aligned.m64n192k16.f32.bf16.bf16 {%0, %1, %2, %3, %4, %5, %6, %7, %8, %9, %10, %11, %12, %13, %14, %15, %16, %17, %18, %19, %20, %21, %22, %23, %24, %25, %26, %27, %28, %29, %30, %31, %32, %33, %34, %35, %36, %37, %38, %39, %40, %41, %42, %43, %44, %45, %46, %47, %48, %49, %50, %51, %52, %53, %54, %55, %56, %57, %58, %59, %60, %61, %62, %63, %64, %65, %66, %67, %68, %69, %70, %71, %72, %73, %74, %75, %76, %77, %78, %79, %80, %81, %82, %83, %84, %85, %86, %87, %88, %89, %90, %91, %92, %93, %94, %95}, da, db, 1, 1, 1, 0, 1;\n"
    "add.u32 t, %96, 4;\nmov.b64 da, {t, %98};\nadd.u32 t, %97, 1024;\nmov.b64 db, {t, %98};\n"
    "wgmma.mma_async.sync.aligned.m64n192k16.f32.bf16.bf16 {%0, %1, %2, %3, %4, %5, %6, %7, %8, %9, %10, %11, %12, %13, %14, %15, %16, %17, %18, %19, %20, %21, %22, %23, %24, %25, %26, %27, %28, %29, %30, %31, %32, %33, %34, %35, %36, %37, %38, %39, %40, %41, %42, %43, %44, %45, %46, %47, %48, %49, %50, %51, %52, %53, %54, %55, %56, %57, %58, %59, %60, %61, %62, %63, %64, %65, %66, %67, %68, %69, %70, %71, %72, %73, %74, %75, %76, %77, %78, %79, %80, %81, %82, %83, %84, %85, %86, %87, %88, %89, %90, %91, %92, %93, %94, %95}, da, db, 1, 1, 1, 0, 1;\n"
    "add.u32 t, %96, 6;\nmov.b64 da, {t, %98};\nadd.u32 t, %97, 1152;\nmov.b64 db, {t, %98};\n"
    "wgmma.mma_async.sync.aligned.m64n192k16.f32.bf16.bf16 {%0, %1, %2, %3, %4, %5, %6, %7, %8, %9, %10, %11, %12, %13, %14, %15, %16, %17, %18, %19, %20, %21, %22, %23, %24, %25, %26, %27, %28, %29, %30, %31, %32, %33, %34, %35, %36, %37, %38, %39, %40, %41, %42, %43, %44, %45, %46, %47, %48, %49, %50, %51, %52, %53, %54, %55, %56, %57, %58, %59, %60, %61, %62, %63, %64, %65, %66, %67, %68, %69, %70, %71, %72, %73, %74, %75, %76, %77, %78, %79, %80, %81, %82, %83, %84, %85, %86, %87, %88, %89, %90, %91, %92, %93, %94, %95}, da, db, 1, 1, 1, 0, 1;\nwgmma.commit_group.sync.aligned;\n"
    "}\n"
    : "+f"(d[0]), "+f"(d[1]), "+f"(d[2]), "+f"(d[3]), "+f"(d[4]), "+f"(d[5]), "+f"(d[6]), "+f"(d[7]), "+f"(d[8]), "+f"(d[9]), "+f"(d[10]), "+f"(d[11]), "+f"(d[12]), "+f"(d[13]), "+f"(d[14]), "+f"(d[15]), "+f"(d[16]), "+f"(d[17]), "+f"(d[18]), "+f"(d[19]), "+f"(d[20]), "+f"(d[21]), "+f"(d[22]), "+f"(d[23]), "+f"(d[24]), "+f"(d[25]), "+f"(d[26]), "+f"(d[27]), "+f"(d[28]), "+f"(d[29]), "+f"(d[30]), "+f"(d[31]), "+f"(d[32]), "+f"(d[33]), "+f"(d[34]), "+f"(d[35]), "+f"(d[36]), "+f"(d[37]), "+f"(d[38]), "+f"(d[39]), "+f"(d[40]), "+f"(d[41]), "+f"(d[42]), "+f"(d[43]), "+f"(d[44]), "+f"(d[45]), "+f"(d[46]), "+f"(d[47]), "+f"(d[48]), "+f"(d[49]), "+f"(d[50]), "+f"(d[51]), "+f"(d[52]), "+f"(d[53]), "+f"(d[54]), "+f"(d[55]), "+f"(d[56]), "+f"(d[57]), "+f"(d[58]), "+f"(d[59]), "+f"(d[60]), "+f"(d[61]), "+f"(d[62]), "+f"(d[63]), "+f"(d[64]), "+f"(d[65]), "+f"(d[66]), "+f"(d[67]), "+f"(d[68]), "+f"(d[69]), "+f"(d[70]), "+f"(d[71]), "+f"(d[72]), "+f"(d[73]), "+f"(d[74]), "+f"(d[75]), "+f"(d[76]), "+f"(d[77]), "+f"(d[78]), "+f"(d[79]), "+f"(d[80]), "+f"(d[81]), "+f"(d[82]), "+f"(d[83]), "+f"(d[84]), "+f"(d[85]), "+f"(d[86]), "+f"(d[87]), "+f"(d[88]), "+f"(d[89]), "+f"(d[90]), "+f"(d[91]), "+f"(d[92]), "+f"(d[93]), "+f"(d[94]), "+f"(d[95])
    : "r"(a), "r"(b), "n"(0x40000040) : "memory");
}
__device__ __forceinline__ void half_kstep0(float (&d)[64], uint32_t a, uint32_t b) {
  asm volatile("{\n.reg .u32 t;\n.reg .u64 da, db;\nwgmma.fence.sync.aligned;\n"
    "add.u32 t, %64, 0;\nmov.b64 da, {t, %66};\nadd.u32 t, %65, 0;\nmov.b64 db, {t, %66};\n"
    "wgmma.mma_async.sync.aligned.m64n128k16.f32.bf16.bf16 {%0, %1, %2, %3, %4, %5, %6, %7, %8, %9, %10, %11, %12, %13, %14, %15, %16, %17, %18, %19, %20, %21, %22, %23, %24, %25, %26, %27, %28, %29, %30, %31, %32, %33, %34, %35, %36, %37, %38, %39, %40, %41, %42, %43, %44, %45, %46, %47, %48, %49, %50, %51, %52, %53, %54, %55, %56, %57, %58, %59, %60, %61, %62, %63}, da, db, 1, 1, 1, 0, 1;\n"
    "add.u32 t, %64, 2;\nmov.b64 da, {t, %66};\nadd.u32 t, %65, 128;\nmov.b64 db, {t, %66};\n"
    "wgmma.mma_async.sync.aligned.m64n128k16.f32.bf16.bf16 {%0, %1, %2, %3, %4, %5, %6, %7, %8, %9, %10, %11, %12, %13, %14, %15, %16, %17, %18, %19, %20, %21, %22, %23, %24, %25, %26, %27, %28, %29, %30, %31, %32, %33, %34, %35, %36, %37, %38, %39, %40, %41, %42, %43, %44, %45, %46, %47, %48, %49, %50, %51, %52, %53, %54, %55, %56, %57, %58, %59, %60, %61, %62, %63}, da, db, 1, 1, 1, 0, 1;\n"
    "add.u32 t, %64, 4;\nmov.b64 da, {t, %66};\nadd.u32 t, %65, 1024;\nmov.b64 db, {t, %66};\n"
    "wgmma.mma_async.sync.aligned.m64n128k16.f32.bf16.bf16 {%0, %1, %2, %3, %4, %5, %6, %7, %8, %9, %10, %11, %12, %13, %14, %15, %16, %17, %18, %19, %20, %21, %22, %23, %24, %25, %26, %27, %28, %29, %30, %31, %32, %33, %34, %35, %36, %37, %38, %39, %40, %41, %42, %43, %44, %45, %46, %47, %48, %49, %50, %51, %52, %53, %54, %55, %56, %57, %58, %59, %60, %61, %62, %63}, da, db, 1, 1, 1, 0, 1;\n"
    "add.u32 t, %64, 6;\nmov.b64 da, {t, %66};\nadd.u32 t, %65, 1152;\nmov.b64 db, {t, %66};\n"
    "wgmma.mma_async.sync.aligned.m64n128k16.f32.bf16.bf16 {%0, %1, %2, %3, %4, %5, %6, %7, %8, %9, %10, %11, %12, %13, %14, %15, %16, %17, %18, %19, %20, %21, %22, %23, %24, %25, %26, %27, %28, %29, %30, %31, %32, %33, %34, %35, %36, %37, %38, %39, %40, %41, %42, %43, %44, %45, %46, %47, %48, %49, %50, %51, %52, %53, %54, %55, %56, %57, %58, %59, %60, %61, %62, %63}, da, db, 1, 1, 1, 0, 1;\n"
    "wgmma.commit_group.sync.aligned;\n}\n"
    : "+f"(d[0]), "+f"(d[1]), "+f"(d[2]), "+f"(d[3]), "+f"(d[4]), "+f"(d[5]), "+f"(d[6]), "+f"(d[7]), "+f"(d[8]), "+f"(d[9]), "+f"(d[10]), "+f"(d[11]), "+f"(d[12]), "+f"(d[13]), "+f"(d[14]), "+f"(d[15]), "+f"(d[16]), "+f"(d[17]), "+f"(d[18]), "+f"(d[19]), "+f"(d[20]), "+f"(d[21]), "+f"(d[22]), "+f"(d[23]), "+f"(d[24]), "+f"(d[25]), "+f"(d[26]), "+f"(d[27]), "+f"(d[28]), "+f"(d[29]), "+f"(d[30]), "+f"(d[31]), "+f"(d[32]), "+f"(d[33]), "+f"(d[34]), "+f"(d[35]), "+f"(d[36]), "+f"(d[37]), "+f"(d[38]), "+f"(d[39]), "+f"(d[40]), "+f"(d[41]), "+f"(d[42]), "+f"(d[43]), "+f"(d[44]), "+f"(d[45]), "+f"(d[46]), "+f"(d[47]), "+f"(d[48]), "+f"(d[49]), "+f"(d[50]), "+f"(d[51]), "+f"(d[52]), "+f"(d[53]), "+f"(d[54]), "+f"(d[55]), "+f"(d[56]), "+f"(d[57]), "+f"(d[58]), "+f"(d[59]), "+f"(d[60]), "+f"(d[61]), "+f"(d[62]), "+f"(d[63])
    : "r"(a), "r"(b), "n"(0x40000040) : "memory");
}
__device__ __forceinline__ void half_kstep1(float (&d)[64], uint32_t a, uint32_t b) {
  asm volatile("{\n.reg .u32 t;\n.reg .u64 da, db;\nwgmma.fence.sync.aligned;\n"
    "add.u32 t, %64, 0;\nmov.b64 da, {t, %66};\nadd.u32 t, %65, 512;\nmov.b64 db, {t, %66};\n"
    "wgmma.mma_async.sync.aligned.m64n128k16.f32.bf16.bf16 {%0, %1, %2, %3, %4, %5, %6, %7, %8, %9, %10, %11, %12, %13, %14, %15, %16, %17, %18, %19, %20, %21, %22, %23, %24, %25, %26, %27, %28, %29, %30, %31, %32, %33, %34, %35, %36, %37, %38, %39, %40, %41, %42, %43, %44, %45, %46, %47, %48, %49, %50, %51, %52, %53, %54, %55, %56, %57, %58, %59, %60, %61, %62, %63}, da, db, 1, 1, 1, 0, 1;\n"
    "add.u32 t, %64, 2;\nmov.b64 da, {t, %66};\nadd.u32 t, %65, 640;\nmov.b64 db, {t, %66};\n"
    "wgmma.mma_async.sync.aligned.m64n128k16.f32.bf16.bf16 {%0, %1, %2, %3, %4, %5, %6, %7, %8, %9, %10, %11, %12, %13, %14, %15, %16, %17, %18, %19, %20, %21, %22, %23, %24, %25, %26, %27, %28, %29, %30, %31, %32, %33, %34, %35, %36, %37, %38, %39, %40, %41, %42, %43, %44, %45, %46, %47, %48, %49, %50, %51, %52, %53, %54, %55, %56, %57, %58, %59, %60, %61, %62, %63}, da, db, 1, 1, 1, 0, 1;\n"
    "add.u32 t, %64, 4;\nmov.b64 da, {t, %66};\nadd.u32 t, %65, 1536;\nmov.b64 db, {t, %66};\n"
    "wgmma.mma_async.sync.aligned.m64n128k16.f32.bf16.bf16 {%0, %1, %2, %3, %4, %5, %6, %7, %8, %9, %10, %11, %12, %13, %14, %15, %16, %17, %18, %19, %20, %21, %22, %23, %24, %25, %26, %27, %28, %29, %30, %31, %32, %33, %34, %35, %36, %37, %38, %39, %40, %41, %42, %43, %44, %45, %46, %47, %48, %49, %50, %51, %52, %53, %54, %55, %56, %57, %58, %59, %60, %61, %62, %63}, da, db, 1, 1, 1, 0, 1;\n"
    "add.u32 t, %64, 6;\nmov.b64 da, {t, %66};\nadd.u32 t, %65, 1664;\nmov.b64 db, {t, %66};\n"
    "wgmma.mma_async.sync.aligned.m64n128k16.f32.bf16.bf16 {%0, %1, %2, %3, %4, %5, %6, %7, %8, %9, %10, %11, %12, %13, %14, %15, %16, %17, %18, %19, %20, %21, %22, %23, %24, %25, %26, %27, %28, %29, %30, %31, %32, %33, %34, %35, %36, %37, %38, %39, %40, %41, %42, %43, %44, %45, %46, %47, %48, %49, %50, %51, %52, %53, %54, %55, %56, %57, %58, %59, %60, %61, %62, %63}, da, db, 1, 1, 1, 0, 1;\n"
    "wgmma.commit_group.sync.aligned;\n}\n"
    : "+f"(d[0]), "+f"(d[1]), "+f"(d[2]), "+f"(d[3]), "+f"(d[4]), "+f"(d[5]), "+f"(d[6]), "+f"(d[7]), "+f"(d[8]), "+f"(d[9]), "+f"(d[10]), "+f"(d[11]), "+f"(d[12]), "+f"(d[13]), "+f"(d[14]), "+f"(d[15]), "+f"(d[16]), "+f"(d[17]), "+f"(d[18]), "+f"(d[19]), "+f"(d[20]), "+f"(d[21]), "+f"(d[22]), "+f"(d[23]), "+f"(d[24]), "+f"(d[25]), "+f"(d[26]), "+f"(d[27]), "+f"(d[28]), "+f"(d[29]), "+f"(d[30]), "+f"(d[31]), "+f"(d[32]), "+f"(d[33]), "+f"(d[34]), "+f"(d[35]), "+f"(d[36]), "+f"(d[37]), "+f"(d[38]), "+f"(d[39]), "+f"(d[40]), "+f"(d[41]), "+f"(d[42]), "+f"(d[43]), "+f"(d[44]), "+f"(d[45]), "+f"(d[46]), "+f"(d[47]), "+f"(d[48]), "+f"(d[49]), "+f"(d[50]), "+f"(d[51]), "+f"(d[52]), "+f"(d[53]), "+f"(d[54]), "+f"(d[55]), "+f"(d[56]), "+f"(d[57]), "+f"(d[58]), "+f"(d[59]), "+f"(d[60]), "+f"(d[61]), "+f"(d[62]), "+f"(d[63])
    : "r"(a), "r"(b), "n"(0x40000040) : "memory");
}

__device__ __forceinline__ void sum_columns(float (&d)[4], uint32_t a, uint32_t b) {
  asm volatile("{\n.reg .u32 t;\n.reg .u64 da, db;\nmov.b64 db, {%5, 0};\nwgmma.fence.sync.aligned;\n"
               "add.u32 t, %4, 0;\nmov.b64 da, {t, %6};\nwgmma.mma_async.sync.aligned.m64n8k16.f32.bf16.bf16 {%0, %1, %2, %3}, da, db, 1, 1, 1, 1, 0;\n"
               "add.u32 t, %4, 128;\nmov.b64 da, {t, %6};\nwgmma.mma_async.sync.aligned.m64n8k16.f32.bf16.bf16 {%0, %1, %2, %3}, da, db, 1, 1, 1, 1, 0;\n"
               "add.u32 t, %4, 256;\nmov.b64 da, {t, %6};\nwgmma.mma_async.sync.aligned.m64n8k16.f32.bf16.bf16 {%0, %1, %2, %3}, da, db, 1, 1, 1, 1, 0;\n"
               "add.u32 t, %4, 384;\nmov.b64 da, {t, %6};\nwgmma.mma_async.sync.aligned.m64n8k16.f32.bf16.bf16 {%0, %1, %2, %3}, da, db, 1, 1, 1, 1, 0;\n"
               "add.u32 t, %4, 512;\nmov.b64 da, {t, %6};\nwgmma.mma_async.sync.aligned.m64n8k16.f32.bf16.bf16 {%0, %1, %2, %3}, da, db, 1, 1, 1, 1, 0;\n"
               "add.u32 t, %4, 640;\nmov.b64 da, {t, %6};\nwgmma.mma_async.sync.aligned.m64n8k16.f32.bf16.bf16 {%0, %1, %2, %3}, da, db, 1, 1, 1, 1, 0;\n"
               "add.u32 t, %4, 768;\nmov.b64 da, {t, %6};\nwgmma.mma_async.sync.aligned.m64n8k16.f32.bf16.bf16 {%0, %1, %2, %3}, da, db, 1, 1, 1, 1, 0;\n"
               "add.u32 t, %4, 896;\nmov.b64 da, {t, %6};\nwgmma.mma_async.sync.aligned.m64n8k16.f32.bf16.bf16 {%0, %1, %2, %3}, da, db, 1, 1, 1, 1, 0;\n"
               "add.u32 t, %4, 1024;\nmov.b64 da, {t, %6};\nwgmma.mma_async.sync.aligned.m64n8k16.f32.bf16.bf16 {%0, %1, %2, %3}, da, db, 1, 1, 1, 1, 0;\n"
               "add.u32 t, %4, 1152;\nmov.b64 da, {t, %6};\nwgmma.mma_async.sync.aligned.m64n8k16.f32.bf16.bf16 {%0, %1, %2, %3}, da, db, 1, 1, 1, 1, 0;\n"
               "add.u32 t, %4, 1280;\nmov.b64 da, {t, %6};\nwgmma.mma_async.sync.aligned.m64n8k16.f32.bf16.bf16 {%0, %1, %2, %3}, da, db, 1, 1, 1, 1, 0;\n"
               "add.u32 t, %4, 1408;\nmov.b64 da, {t, %6};\nwgmma.mma_async.sync.aligned.m64n8k16.f32.bf16.bf16 {%0, %1, %2, %3}, da, db, 1, 1, 1, 1, 0;\n"
               "add.u32 t, %4, 1536;\nmov.b64 da, {t, %6};\nwgmma.mma_async.sync.aligned.m64n8k16.f32.bf16.bf16 {%0, %1, %2, %3}, da, db, 1, 1, 1, 1, 0;\n"
               "add.u32 t, %4, 1664;\nmov.b64 da, {t, %6};\nwgmma.mma_async.sync.aligned.m64n8k16.f32.bf16.bf16 {%0, %1, %2, %3}, da, db, 1, 1, 1, 1, 0;\n"
               "add.u32 t, %4, 1792;\nmov.b64 da, {t, %6};\nwgmma.mma_async.sync.aligned.m64n8k16.f32.bf16.bf16 {%0, %1, %2, %3}, da, db, 1, 1, 1, 1, 0;\n"
               "add.u32 t, %4, 1920;\nmov.b64 da, {t, %6};\nwgmma.mma_async.sync.aligned.m64n8k16.f32.bf16.bf16 {%0, %1, %2, %3}, da, db, 1, 1, 1, 1, 0;\n"
               "wgmma.commit_group.sync.aligned;\nwgmma.wait_group.sync.aligned 0;\n}"
               : "+f"(d[0]), "+f"(d[1]), "+f"(d[2]), "+f"(d[3]) : "r"(a), "r"(b), "n"(0x40000040) : "memory");
}
struct Job {
  uint32_t type, layer, R, col, nk;
  __device__ __forceinline__ explicit Job(uint32_t j) : type(j & 3), layer((j >> 2) & 1), R((j >> 3) & 7), col((j >> 6) & 63), nk((j >> 12) & 63) {}
  __device__ __forceinline__ uint32_t inst() const { return layer * 2 + (type >> 1); }
};
struct Smem {
  char* scratch;
  uint32_t base;
  __device__ __forceinline__ uint32_t stage(uint32_t s) const { return base + (s & (NSTAGE - 1)) * STAGE; }
  __device__ __forceinline__ uint32_t slot(uint32_t c) const { return base + STG_OFF + c * SLOT; }
  __device__ __forceinline__ uint32_t full(uint32_t s) const { return base + BAR_OFF + (s & (NSTAGE - 1)) * 8; }
  __device__ __forceinline__ uint32_t empty(uint32_t s) const { return base + BAR_OFF + 32 + (s & (NSTAGE - 1)) * 8; }
  __device__ __forceinline__ uint32_t filled(uint32_t u) const { return base + BAR_OFF + 64 + u * 8; }
  __device__ __forceinline__ uint32_t vacant(uint32_t u) const { return base + BAR_OFF + 96 + u * 8; }
  __device__ __forceinline__ uint32_t summed(uint32_t s) const { return base + BAR_OFF + 128 + (s & (NSTAGE - 1)) * 8; }
  __device__ __forceinline__ uint32_t aux_full() const { return base + BAR_OFF + 160; }
  __device__ __forceinline__ uint32_t boot() const { return base + BAR_OFF + 168; }
  __device__ __forceinline__ uint32_t xchg_full() const { return base + BAR_OFF + 176; }
  __device__ __forceinline__ uint32_t wgmma_done() const { return base + BAR_OFF + 184; }
  __device__ __forceinline__ uint32_t mma_done() const { return base + BAR_OFF + 192; }
  __device__ __forceinline__ uint32_t kv_ready(int w) const { return base + BAR_OFF + 208 + w * 8; }
  __device__ __forceinline__ uint32_t pair_id() const { return base + BAR_OFF + 280; }
  __device__ __forceinline__ uint32_t stats() const { return base + AUX_OFF; }
  __device__ __forceinline__ uint32_t sums() const { return base + AUX_OFF + 1088; }
  __device__ __forceinline__ uint32_t xchg() const { return base + AUX_OFF + 1600; }
};
__device__ __forceinline__ uint32_t par(uint32_t s) { return (s / NSTAGE) & 1; }

__device__ __forceinline__ void st_word(u64* p, uint32_t lo, uint32_t hi) {
  asm volatile("st.relaxed.gpu.global.u64 [%0], %1;" ::"l"(p), "l"(((u64)hi << 32) | lo) : "memory");
}
__device__ __forceinline__ uint2 ld_word(const u64* p) {
  u64 v;
  asm volatile("ld.relaxed.gpu.global.u64 %0, [%1];" : "=l"(v) : "l"(p) : "memory");
  return make_uint2((uint32_t)v, (uint32_t)(v >> 32));
}
__device__ __forceinline__ void add_moments(uint4 v, float (&m)[4]) {
  const uint32_t w[4] = {v.x, v.y, v.z, v.w};
#pragma unroll
  for (int c = 0; c < 4; c++) {
    const float lo = bf_lo(w[c]), hi = bf_hi(w[c]);
    m[0] += lo; m[1] += hi; m[2] = fmaf(lo, lo, m[2]); m[3] = fmaf(hi, hi, m[3]);
  }
}
__device__ __forceinline__ void publish_stats(const Smem& sm, float s, float q, uint32_t idx, bool valid, uint32_t e1) {
  const float mean = s * (1.f / D), var = fmaxf(q * (1.f / D) - mean * mean, 0.f);
  const u64 word = ((u64)((__float_as_uint(-bf_round(mean)) & 0xffff0000u) | (e1 & 0xffff)) << 32) | __float_as_uint(rcp(bf_round(sqrt_fast(bf_round(bf_round(var) + 1e-5f)))));
  asm volatile("{\n.reg .pred p;\nsetp.ne.u32 p, %2, 0;\n@p st.relaxed.gpu.global.u64 [%0], %1;\n}" ::"l"(SCR(sm, stats, idx * 8)), "l"(word), "r"((uint32_t)valid) : "memory");
}
__device__ __forceinline__ void stats_task(const Smem& sm, uint32_t jw, int rank, int w, uint32_t e1, const bf16* x) {
  const uint32_t inst = (jw >> 22) & 3, lane = fresh_tid() & 31, steps = (jw >> 31) * 2 + 2;
  uint32_t row = ((jw >> 24) & 127) * 8 + (w - 1) * 4 + (lane >> 3);
  wait_count(counter(C_X + inst * 16 + (row >> 7) * 2 + rank, lane & 7), e1 * (inst & 1 ? 56 : 16));
  const uint4* p = at(reinterpret_cast<const uint4*>(x), (row * 2 + rank) * (D * 2) + (lane & 7) * 16);
  uint4 v[8];
  float m[4] = {0.f, 0.f, 0.f, 0.f};
#pragma unroll
  for (int i = 0; i < 8; i++) v[i] = ldg128(p + i * 8);
#pragma unroll 1
  for (uint32_t it = 1; it <= steps; it++) {
    p = at(p, it & 1 ? 1024 : 8 * D * 4 - 1024);
#pragma unroll
    for (int i = 0; i < 8; i++) {
      add_moments(v[i], m);
      if (it < steps) v[i] = ldg128(p + i * 8);
    }
    if (!(it & 1)) {
      m[0] += m[1]; m[2] += m[3];
#pragma unroll
      for (int o = 1; o <= 4; o <<= 1) { m[0] += __shfl_xor_sync(~0u, m[0], o); m[2] += __shfl_xor_sync(~0u, m[2], o); }
      publish_stats(sm, m[0], m[2], (inst + 1) * S + rank * (S / 2) + row, (lane & 7) == 0, e1);
      m[0] = m[1] = m[2] = m[3] = 0.f;
      row += 8;
    }
  }
}
struct Stager {
  uint2 st[5], cs[4];
  __device__ __forceinline__ void load(const Smem& sm, const Job& J, int rank, int lane, bool sums) {
#pragma unroll
    for (int i = 0; i < 5; i++) st[i] = ld_word(SCR(sm, stats, (J.inst() * S + rank * (S / 2) + J.R * 128 + min(max(lane - 8 + 32 * i, J.R && J.type == T_Q ? -8 : 0), 127)) * 8));
#pragma unroll
    for (int i = 0; i < 4; i++)
      if (sums && (i < 3 || J.type == T_G)) cs[i] = ld_word(SCR(sm, cs, ((J.col + J.type * 8) * 128 + lane) * 8) + i * 32);
  }
  __device__ __forceinline__ void store(const Smem& sm, const Job& J, int rank, int lane, bool sums, uint32_t e1) {
    for (uint32_t n = 0;; n++) {
      uint32_t bad = (st[1].y ^ e1) | (st[2].y ^ e1) | (st[3].y ^ e1);
      bad |= (st[0].y ^ e1) | (st[4].y ^ e1);
      if (sums) bad |= (cs[0].y ^ e1) | (cs[1].y ^ e1) | (cs[2].y ^ e1);
      if (J.type == T_G) bad |= cs[3].y ^ e1;
      if (__all_sync(~0u, (bad & 0xffff) == 0)) break;
      __nanosleep(300);
      if (n > SPIN_LIMIT) __trap();
      load(sm, J, rank, lane, sums);
    }
#pragma unroll
    for (int i = 0; i < 5; i++) {
      if (i < 4 || lane < 8) sts64(sm.stats() + (lane + 32 * i) * 8, st[i]);
      if (i < 4 && sums && (i < 3 || J.type == T_G)) sts32(sm.sums() + (lane + 32 * i) * 4, cs[i].x);
    }
  }
};
__device__ __forceinline__ void add_cols(float (&a)[8], uint4 x, uint4 y) {
  const uint4 t = add8(x, y);
  a[0] += bf_lo(t.x); a[1] += bf_hi(t.x); a[2] += bf_lo(t.y); a[3] += bf_hi(t.y);
  a[4] += bf_lo(t.z); a[5] += bf_hi(t.z); a[6] += bf_lo(t.w); a[7] += bf_hi(t.w);
}
__device__ __forceinline__ void reduce_cols(float (&a)[8], int lane) {
#pragma unroll
  for (int i = 0; i < 4; i++) { const bool up = lane & 16; const float o = __shfl_xor_sync(~0u, up ? a[i] : a[i + 4], 16); a[i] = (up ? a[i + 4] : a[i]) + o; }
#pragma unroll
  for (int i = 0; i < 2; i++) { const bool up = lane & 8; const float o = __shfl_xor_sync(~0u, up ? a[i] : a[i + 2], 8); a[i] = (up ? a[i + 2] : a[i]) + o; }
}
template <class Fn>
__device__ __forceinline__ uint32_t qkv_col_sums(const Smem& sm, int rank, int w, int lane, Fn between) {
  float a[8] = {0.f, 0.f, 0.f, 0.f, 0.f, 0.f, 0.f, 0.f};
#pragma unroll 1
  for (int s = 0; s < D / 64; s++) {
    between(s);
    const uint32_t p = sm.stage(s) + SLOT + rank * SLOT + w * 4096 + (lane >> 3) * 128 + (((lane & 7) ^ (lane >> 3)) << 4);
    uint4 v[8];
    mbar_wait(sm.full(s), par(s));
#pragma unroll
    for (int j = 0; j < 8; j++) v[j] = lds128((p ^ ((j & 1) * 64)) + j * 512);
    __syncwarp();
    mbar_arrive_cl_if(lane < 2, mapa(sm.summed(s), lane & 1));
    add_cols(a, add8(v[0], v[1]), add8(v[2], v[3]));
    add_cols(a, add8(v[4], v[5]), add8(v[6], v[7]));
  }
  reduce_cols(a, lane);
  const uint32_t slot = sm.xchg() + (w * 32 + lane) * 8;
  asm volatile("st.async.weak.shared::cluster.mbarrier::complete_tx::bytes.v2.b32 [%0], {%1, %2}, [%3];"
               ::"r"(mapa(slot, rank ^ 1)), "r"(__float_as_uint(a[0])), "r"(__float_as_uint(a[1])), "r"(mapa(sm.xchg_full(), rank ^ 1)) : "memory");
  mbar_wait(sm.xchg_full(), 0);
  const uint2 o = lds64(slot);
  return pack_bf16(a[0] + __uint_as_float(o.x), a[1] + __uint_as_float(o.y));
}

constexpr float LOGIT_SCALE = 0.17677669529663687f * 1.4426950408889634f;
constexpr float MASKED = -1e30f;
enum { A_CS = 16, A_NM = 40, A_KT = 42, A_KU = 44, A_CT = 46, A_CU = 48, A_BIAS = 50, A_MASK = 52, A_ZERO = 53 };
__device__ __forceinline__ void attention_prepare(uint32_t (&r)[64], const Smem& sm, int W, int lane, bool first) {
  const int i = lane >> 2, c = (lane & 3) * 2;
  r[A_ZERO] = opaque_zero();
  r[A_MASK] = (c > i ? 0xffffu : 0u) | (c + 1 > i ? 0xffff0000u : 0u);
  const uint32_t a = sm.stats() + W * 128;
  const uint2 r0 = lds64(a + 64 + i * 8), r1 = lds64(a + 128 + i * 8);
#pragma unroll
  for (int y = 0; y < 2; y++) {
    const uint32_t k = a + (c + y + (c + y > i ? 0 : 8)) * 8;
    const float kt = lds32f(k), ku = lds32f(k + 64);
    r[A_KT + y] = __float_as_uint(kt); r[A_CT + y] = __float_as_uint(__uint_as_float(r0.x) * LOGIT_SCALE * kt);
    r[A_KU + y] = __float_as_uint(ku); r[A_CU + y] = __float_as_uint(__uint_as_float(r1.x) * LOGIT_SCALE * ku);
    r[A_BIAS + y] = __float_as_uint(first && W == 0 && c + y > i ? MASKED : 0.f);
  }
#pragma unroll
  for (int j = 0; j < 6; j++) {
    const uint4 v = lds128(sm.sums() + c * 48 + j * 16);
    r[A_CS + 4 * j] = v.x; r[A_CS + 4 * j + 1] = v.y; r[A_CS + 4 * j + 2] = v.z; r[A_CS + 4 * j + 3] = v.w;
  }
  r[A_NM] = dup_hi(r0.y); r[A_NM + 1] = dup_hi(r1.y);
}
__device__ __forceinline__ bool attention(const float (&acc)[96], uint32_t (&r)[64], const Smem& sm, int W, int lane, uint32_t t8, uint32_t t16,
                                          bool halo, uint32_t block, uint32_t tag, uint32_t parity, uint32_t next_bar, uint32_t next_parity, int ji) {
#define TRW W
  const uint32_t own = (W >> 2) * SLOT;
  const uint32_t pk = W == 0 ? (halo ? 4096 : 1024) : W == 4 ? 7168 : own - 1024;
  const uint32_t pv = W == 0 && halo ? 6144 : pk + 8192;
  uint32_t x[48];
  auto pack = [&](int j0, int step, int count) {
#pragma unroll
    for (int j = j0; j < j0 + step * count; j += step) x[j] = bf2_fma(r[A_NM + j % 2], r[A_CS + j / 2], pack_bf16(acc[2 * j], acc[2 * j + 1]));
  };
  auto put8 = [&](uint32_t a, int j) {
    stsm4(t8 + a, x[j], x[j + 2], x[j + 4], x[j + 6]);
    stsm4((t8 ^ 64) + a, x[j + 8], x[j + 10], x[j + 12], x[j + 14]);
  };
  uint32_t k0[2][4], v0[2][4], v12[4][4];
  pack(17, 2, 8);
  put8(own + 1024, 17);
  pack(32, 1, 16);
#pragma unroll
  for (int j = 0; j < 4; j++) stsm4((t16 ^ (j << 5)) + (own + 8192), x[32 + 4 * j], x[33 + 4 * j], x[34 + 4 * j], x[35 + 4 * j]);
  mbar_arrive_warp(sm.kv_ready(W));
  pack(16, 2, 8);
  pack(0, 1, 16);
  if (W == 0) {
    put8(0, 16);
#pragma unroll
    for (int j = 0; j < 4; j++) stsm4(lane & 8 ? sm.xchg() : (t16 ^ (j << 5)) + 2048, x[4 * j], x[4 * j + 1], x[4 * j + 2], x[4 * j + 3]);
  }
  mbar_wait(sm.kv_ready(W - 1), parity);
#pragma unroll
  for (int h = 0; h < 2; h++) ldsm4((t8 ^ (h * 64)) + pk, k0[h]);
#pragma unroll
  for (int j = 0; j < 4; j++) ldsm4t((t16 ^ (j << 5)) + (own + 8192), v12[j]);
#pragma unroll
  for (int h = 0; h < 2; h++) ldsm4t((t8 ^ (h * 64)) + pv, v0[h]);
  if (W < 4) mbar_wait(sm.wgmma_done(), parity);
  const bool next_full = mbar_test(next_bar, next_parity);
  TRC(ji, 20);
  float s0[2][4], s1[2][4], s2[2][4];
#pragma unroll
  for (int h = 0; h < 2; h++) {
#pragma unroll
    for (int y = 0; y < 4; y++) s0[h][y] = s1[h][y] = s2[h][y] = 0.f;
  }
#pragma unroll
  for (int ks = 0; ks < 2; ks++)
#pragma unroll
    for (int h = 0; h < 2; h++) {
      const int n = 8 * h + 4 * ks;
      mma16816(s1[h], x[n], x[n + 1], x[n + 2], x[n + 3], x[16 + n], x[18 + n]);
      mma16816(s2[h], x[n], x[n + 1], x[n + 2], x[n + 3], x[17 + n], x[19 + n]);
      mma16816(s0[h], x[n], x[n + 1], x[n + 2], x[n + 3], k0[h][2 * ks], k0[h][2 * ks + 1]);
    }
  const uint32_t mask = r[A_MASK];
  const bool after[2] = {(mask & 1) != 0, (int)mask < 0};
  float lt[2][2], lu[2][2], mt[2], mu[2];
#pragma unroll
  for (int h = 0; h < 2; h++) {
#pragma unroll
    for (int y = 0; y < 2; y++) {
      lt[h][y] = fmaf(after[y] ? s0[h][y] : s1[h][y], __uint_as_float(r[A_CT + y]), __uint_as_float(r[A_BIAS + y]));
      lu[h][y] = (after[y] ? s1[h][2 + y] : s2[h][2 + y]) * __uint_as_float(r[A_CU + y]);
    }
    mt[h] = fmaxf(lt[h][0], lt[h][1]);
    mu[h] = fmaxf(lu[h][0], lu[h][1]);
  }
#pragma unroll
  for (int d = 1; d <= 2; d++)
#pragma unroll
    for (int h = 0; h < 2; h++) {
      mt[h] = fmaxf(mt[h], __shfl_xor_sync(~0u, mt[h], d));
      mu[h] = fmaxf(mu[h], __shfl_xor_sync(~0u, mu[h], d));
    }
  float o[2][4][4];
#pragma unroll
  for (int h = 0; h < 2; h++) {
#pragma unroll
    for (int y = 0; y < 2; y++) { lt[h][y] = ex2(lt[h][y] - mt[h]); lu[h][y] = ex2(lu[h][y] - mu[h]); }
    const uint32_t pt = pack_bf16(lt[h][0] * __uint_as_float(r[A_KT]), lt[h][1] * __uint_as_float(r[A_KT + 1]));
    const uint32_t pu = pack_bf16(lu[h][0] * __uint_as_float(r[A_KU]), lu[h][1] * __uint_as_float(r[A_KU + 1]));
#pragma unroll
    for (int n = 0; n < 4; n++) {
      o[h][n][0] = o[h][n][1] = o[h][n][2] = o[h][n][3] = 0.f;
      mma16816(o[h][n], pt & ~mask, pu & mask, 0u, pu & ~mask, v12[2 * h + n / 2][n % 2 * 2], v12[2 * h + n / 2][n % 2 * 2 + 1]);
    }
#pragma unroll
    for (int n = 0; n < 4; n++) mma1688(o[h][n], pt & mask, 0u, v0[h][n]);
    mt[h] = lt[h][0] + lt[h][1];
    mu[h] = lu[h][0] + lu[h][1];
  }
#pragma unroll
  for (int d = 1; d <= 2; d++)
#pragma unroll
    for (int h = 0; h < 2; h++) {
      mt[h] += __shfl_xor_sync(~0u, mt[h], d);
      mu[h] += __shfl_xor_sync(~0u, mu[h], d);
    }
  uint32_t dep = 0;
#pragma unroll
  for (int n = 0; n < 3; n++) dep |= __float_as_uint(o[n % 2][n / 2][0]);
  mbar_arrive_warp(sm.mma_done() + (dep & r[A_ZERO]));
  TRC(ji, 22);
  if (W == 7) {
    ulonglong2* exp = SCR(sm, halo, (block * 256 + lane) * 16);
#pragma unroll
    for (int m = 0; m < 8; m++)
      asm volatile("st.relaxed.gpu.global.v2.u64 [%0], {%1,%2};" ::"l"(exp + m * 32), "l"(((u64)tag << 32) | x[17 + 4 * m]), "l"(((u64)tag << 32) | x[19 + 4 * m]) : "memory");
  }
#pragma unroll
  for (int h = 0; h < 2; h++) {
    const float rt = rcp(mt[h]), ru = rcp(mu[h]);
#pragma unroll
    for (int n = 0; n < 4; n++) {
      r[8 * h + 2 * n] = pack_bf16(o[h][n][0] * rt, o[h][n][1] * rt);
      r[8 * h + 2 * n + 1] = pack_bf16(o[h][n][2] * ru, o[h][n][3] * ru);
    }
  }
  return next_full;
}
__device__ __forceinline__ void import_halo(const Smem& sm, const ulonglong2* halo, uint32_t tag, int lane) {
  u64 x[16];
  for (uint32_t n = 0;; n++) {
#pragma unroll
    for (int m = 0; m < 8; m++)
      asm volatile("ld.relaxed.gpu.global.v2.u64 {%0,%1}, [%2];" : "=l"(x[2 * m]), "=l"(x[2 * m + 1]) : "l"(halo + m * 32) : "memory");
    uint32_t bad = 0;
#pragma unroll
    for (int m = 0; m < 16; m++) bad |= (uint32_t)(x[m] >> 32) ^ tag;
    if (__all_sync(~0u, bad == 0)) break;
    __nanosleep(300);
    if (n > SPIN_LIMIT) __trap();
  }
  const uint32_t a = sm.slot(0) + 4096 + (lane & 7) * 128 + (((lane >> 3) ^ (lane & 7)) << 4);
#pragma unroll
  for (int m = 0; m < 4; m++) stsm4((a ^ ((m & 1) * 64)) + (m >> 1) * 2048, (uint32_t)x[4 * m], (uint32_t)x[4 * m + 1], (uint32_t)x[4 * m + 2], (uint32_t)x[4 * m + 3]);
}
__device__ __forceinline__ void unpack8(uint4 v, float* f) {
  f[0] = bf_lo(v.x); f[1] = bf_hi(v.x); f[2] = bf_lo(v.y); f[3] = bf_hi(v.y);
  f[4] = bf_lo(v.z); f[5] = bf_hi(v.z); f[6] = bf_lo(v.w); f[7] = bf_hi(v.w);
}
__device__ __forceinline__ void boundary_rows(const Smem& sm, int h, int lane, uint32_t out) {
  const int i = lane >> 2, u = h * 4 + (lane & 3);
  uint4 r[8];
  float x[8], l[8], ik[8];
  unpack8(lds128(sm.slot(0) + 2048 + i * 128 + ((u ^ i) << 4)), x);
#pragma unroll
  for (int j = 0; j < 8; j++) {
    r[j] = lds128(sm.slot(0) + j * 128 + (j > i ? 4096 : 0) + ((u ^ j) << 4));
    ik[j] = lds32f(sm.stats() + j * 8 + (j > i ? 0 : 64));
  }
  const float cq = lds32f(sm.stats() + 64 + i * 8) * LOGIT_SCALE;
#pragma unroll
  for (int j = 0; j < 8; j++) {
    float kf[8];
    unpack8(r[j], kf);
    r[j] = lds128(sm.slot(0) + j * 128 + (j > i ? 6144 : 8192) + ((u ^ j) << 4));
    l[j] = 0.f;
#pragma unroll
    for (int d = 0; d < 8; d++) l[j] = fmaf(x[d], kf[d], l[j]);
  }
#pragma unroll
  for (int d = 1; d <= 2; d++)
#pragma unroll
    for (int j = 0; j < 8; j++) l[j] += __shfl_xor_sync(~0u, l[j], d);
  float m = MASKED, sum = 0.f;
#pragma unroll
  for (int j = 0; j < 8; j++) { l[j] *= cq * ik[j]; m = fmaxf(m, l[j]); }
#pragma unroll
  for (int j = 0; j < 8; j++) { l[j] = ex2(l[j] - m); sum += l[j]; }
  const float rs = rcp(sum);
#pragma unroll
  for (int d = 0; d < 8; d++) x[d] = 0.f;
#pragma unroll
  for (int j = 0; j < 8; j++) {
    const float pw = l[j] * ik[j] * rs;
    float vf[8];
    unpack8(r[j], vf);
#pragma unroll
    for (int d = 0; d < 8; d++) x[d] = fmaf(pw, vf[d], x[d]);
  }
  stg128(SCR(sm, o, out + i * (2 * D) + u * 16), make_uint4(pack_bf16(x[0], x[1]), pack_bf16(x[2], x[3]), pack_bf16(x[4], x[5]), pack_bf16(x[6], x[7])));
}
__device__ __forceinline__ uint32_t swiglu2(uint32_t g, uint32_t u, float hinv, float hinv2) {
  const float a = bf_lo(g) * hinv, b = bf_hi(g) * hinv, a2 = bf_lo(g) * hinv2, b2 = bf_hi(g) * hinv2;
  return bf2_mul(pack_bf16(fmaf(a2, tanh_fast(a), a2), fmaf(b2, tanh_fast(b), b2)), u);
}

__device__ __forceinline__ const uint32_t* dep_counter(const Smem& sm, uint32_t jw, int rank, uint32_t k) {
  const Job J(jw);
  const uint32_t b = J.R * 2 + rank;
  const uint32_t line = J.type == T_O ? C_O + J.layer * 16 + b : J.type == T_D ? C_H + J.layer * 16 + b : C_X + max((int)J.inst() - 1, 0) * 16 + b;
  return counter(line, J.type & 1 ? k >> (J.type >> 1) : (k >> 2) * 2 + (k & 1));
}
__device__ __forceinline__ void producer(const Params& P, const Smem& sm, const uint32_t* jobs, const uint8_t* kseq, int rank, int lane, uint32_t launches) {
  const uint32_t e1 = __shfl_sync(~0u, launches, 0) + 1;
  uint32_t s = (jobs[0] & JOB_C) ? 0 : NSTAGE;
  uint32_t end = 0, poll = 0;
  uint64_t keep, stream;
  asm("createpolicy.fractional.L2::evict_unchanged.b64 %0, 1.0;" : "=l"(keep));
  asm("createpolicy.fractional.L2::evict_first.b64 %0, 1.0;" : "=l"(stream));
  const uint32_t* dep = counter(0, 0);
  const uint32_t summed_end = (jobs[0] & JOB_C) ? 0 : D / 64 + NSTAGE;
  for (int ji = 0;; ji++) {
    const uint32_t jw = jobs[ji];
    const Job J(jw);
    if (J.nk == 0) break;
    const bool isC = jw & JOB_C, isX = isC && (jw & JOB_X);
    const uint32_t target = (jw & 7) == 0 ? 0 : e1 * (J.type == T_Q ? 56 : J.type == T_G ? 16 : 1);
    const uint32_t g = J.col * 2 + rank;
    const CUtensorMap* tmA = &P.a[isC ? 4 + isX : (jw & 7) == 4 ? 2 : J.type];
    const CUtensorMap* tmB = &P.w[J.type];
    const uint32_t bytes = isC ? 32768 : J.type == T_Q ? 40960 : STAGE, bcol = J.col << (J.type == T_Q ? 0 : J.type == T_G ? 1 : 2);
    const uint32_t a0 = isX ? 0 : (g >> 2) * 128 + (g & 1) * 64, a1 = isX ? g * 64 : J.R * 128, ak = isX ? 0 : 256, a2 = isC ? (g >> 1) & 1 : rank;
    end += J.nk;
    uint32_t sa = s, spins = 0;
    auto issue_a = [&](uint32_t k) { TRS(sa, 1); tma3d(sm.stage(sa), tmA, isC ? a0 : (k & 63) * 64, isC ? a1 + k * ak : a1, isX ? k * 4 : a2, sm.full(sa), (k & K_LAST_A) ? stream : keep); };
    auto issue_b = [&](uint32_t k) {
      mbar_expect_tx(sm.full(s), bytes);
      TRS(s, 0);
      if (!isC) tma4d_mc(sm.stage(s) + SLOT + rank * SLOT, tmB, (k & 63) * 64 + rank * 32, bcol, sm.full(s), (k & K_LAST_B) ? stream : keep);
    };
    TRI(lane == 0, ji, 6);
    TRK(lane == 0, ji, 24);
    while (true) {
      const uint32_t missing = __ballot_sync(~0u, (int)(poll - target) < 0 && lane < J.nk);
      uint32_t lim = end;
      if (missing) lim += __ffs(missing) - 1 - J.nk;
      if (lim > sa) {
        fence_acquire();
        fence_proxy_async();
        TRI(sa == end - J.nk && lane == 0, ji, 7);
#pragma unroll 1
        for (; sa < min(lim, s); sa++) {
          const uint32_t k = kseq[sa];
          if (elect()) issue_a(k);
        }
#pragma unroll 1
        for (int phase = 0;; phase++) {
          const uint32_t upto = phase == 2 ? lim : phase == 1 ? lim - LOOK : min((int)lim - LOOK, (int)sa + MID);
#pragma unroll 1
          for (; (int)sa < (int)upto; sa++, s++) {
            const uint32_t k = kseq[s];
            uint32_t stage = sm.stage(s), bar = sm.full(s), c0 = isC ? a0 : (k & 63) * 64, c1 = isC ? a1 + k * ak : a1, kb = (k & 63) * 64 + rank * 32, c2 = isX ? k * 4 : a2;
            uint64_t pa = (k & K_LAST_A) ? stream : keep, pb = (k & K_LAST_B) ? stream : keep;
            asm volatile("" : "+r"(stage), "+r"(bar), "+r"(c0), "+r"(c1), "+r"(kb), "+r"(c2), "+l"(pa), "+l"(pb));
            if (s < summed_end) mbar_wait(sm.summed(s), par(s) ^ 1);
            mbar_wait(bar + 32, par(s) ^ 1);
            TRS(s, 0);
            asm volatile("{\n.reg .pred p, q;\nelect.sync _|p, -1;\nsetp.eq.and.u32 q, %14, 0, p;\n"
                         "@q cp.async.bulk.tensor.4d.shared::cluster.global.mbarrier::complete_tx::bytes.multicast::cluster.L2::cache_hint [%3], [%4, {%5, %6, %7, %5}], [%0], %8, %9;\n"
                         "@p cp.async.bulk.tensor.3d.shared::cluster.global.mbarrier::complete_tx::bytes.L2::cache_hint [%2], [%10, {%11, %12, %13}], [%0], %15;\n"
                         "@p mbarrier.arrive.expect_tx.shared::cta.b64 _, [%0], %1;\n}"
                         ::"r"(bar), "r"(bytes), "r"(stage), "r"(stage + SLOT + rank * SLOT), "l"(tmB), "r"(0), "r"(kb), "r"(bcol), "h"((uint16_t)3), "l"(pb),
                           "l"(tmA), "r"(c0), "r"(c1), "r"(c2), "r"((uint32_t)isC), "l"(pa) : "memory");
            TRS(s, 1);
          }
          if (phase == 2) break;
          if (phase == 1) poll = ld_relaxed(dep);
          else if (lim == end) dep = dep_counter(sm, jobs[ji + 1], rank, (reinterpret_cast<const uint32_t*>(kseq)[(end + lane) >> 2] >> ((end + lane) % 4 * 8)) & 63);
        }
        if (lim == end) break;
      } else {
        if (s < min(end, sa + NSTAGE) && __all_sync(~0u, mbar_test(sm.empty(s), par(s) ^ 1))) {
          const uint32_t k = kseq[s];
          if (s < summed_end) mbar_wait(sm.summed(s), par(s) ^ 1);
          if (elect()) issue_b(k);
          s++;
        }
        poll = ld_relaxed(dep);
        if (++spins > SPIN_LIMIT) __trap();
      }
    }
    TRI(lane == 0, ji, 8);
  }
}

__global__ void __cluster_dims__(2, 1, 1) __launch_bounds__(384, 1) mega_kernel(char* scratch, uint32_t by_place, const __grid_constant__ Params P) {
#undef TRW
#define TRW warp
  extern __shared__ __align__(1024) uint8_t smem_raw[];
  TRX(threadIdx.x == 320, JMAX - 1, 0, 1, "%%globaltimer_lo");
  TRX(threadIdx.x == 320, JMAX - 1, 0, 25, "%%clock");
  TRX(threadIdx.x == 320, JMAX - 1, 0, 28, "%%smid");
  Smem sm;
  sm.scratch = scratch;
  sm.base = smem_u32(smem_raw);
  if ((sm.base & 0x3FFFF) != SMEM_BASE) __trap();
  const int warp = __shfl_sync(~0u, threadIdx.x >> 5, 0);
  const int rank = blockIdx.x & 1;
  uint32_t smid;
  asm("mov.u32 %0, %%smid;" : "=r"(smid));
  const uint32_t pair = !by_place ? blockIdx.x >> 1 : smid < 2 * NPAIR - 8 ? (smid >> 1) + 4 : (smid >> 1) + 4 - NPAIR;
  const uint32_t* jobs = P.jobs[pair];
  const uint32_t launches = ld_relaxed(counter(C_EP, blockIdx.x + threadIdx.y));
  if (warp == 10) {
    if (elect()) {
      for (int i = 0; i < NSTAGE; i++) mbar_init(sm.full(i), 1);
      mbar_init(sm.boot(), 1);
      asm volatile("fence.mbarrier_init.release.cluster;" ::: "memory");
    }
    cluster_arrive();
    const uint32_t first = jobs[0];
    const bool isC = first & JOB_C;
    if (elect()) {
      prefetch_tm(&P.a[0]);
      prefetch_tm(&P.w[0]);
    }
    uint64_t keep;
    asm("createpolicy.fractional.L2::evict_unchanged.b64 %0, 1.0;" : "=l"(keep));
    const Job J(first);
    if (!isC) {
      if (elect()) {
        mbar_expect_tx(sm.full(0), 40960);
        tma3d(sm.stage(0), &P.a[0], 0, J.R * 128, rank, sm.full(0), keep);
        TRS(0, 1);
      }
      TRX(threadIdx.x == 320, JMAX - 1, 0, 26, "%%clock");
      cluster_wait();
      TRX(threadIdx.x == 320, JMAX - 1, 0, 27, "%%clock");
      if (elect()) {
        tma4d_mc(sm.stage(0) + SLOT + rank * SLOT, &P.w[0], rank * 32, J.col, sm.full(0), keep);
        TRS(0, 0);
      }
      delay(HEAD_START);
#pragma unroll 1
      for (int k = 1; k < NSTAGE; k++) {
        if (elect()) {
          tma4d_mc(sm.stage(k) + SLOT + rank * SLOT, &P.w[0], k * 64 + rank * 32, J.col, sm.full(k), keep);
          TRS(k, 0);
          mbar_expect_tx(sm.full(k), 40960);
          tma3d(sm.stage(k), &P.a[0], k * 64, J.R * 128, rank, sm.full(k), keep);
          TRS(k, 1);
        }
      }
    } else {
      cluster_wait();
      if (!(first & JOB_X)) mbar_wait(sm.boot(), 0);
    }
  } else {
    if (warp < 8 && elect()) {
      mbar_init(sm.kv_ready(warp), 1);
      if (warp == 3) {
        mbar_init(sm.aux_full(), 3); mbar_init(sm.wgmma_done(), 4); mbar_init(sm.mma_done(), 8); mbar_init(sm.xchg_full(), 1); mbar_init(sm.kv_ready(-1), 1);
        mbar_expect_tx(sm.xchg_full(), 768);
      } else if (warp > 3) {
        mbar_init(sm.empty(warp), 4); mbar_init(sm.summed(warp), 6); mbar_init(sm.filled(warp - 4), 4); mbar_init(sm.vacant(warp - 4), 3);
      }
      asm volatile("fence.mbarrier_init.release.cluster;" ::: "memory");
    }
    cluster_arrive();
  }
  TRI(threadIdx.x == 0, JMAX - 1, 0);

  if (warp < 8) {
    asm volatile("setmaxnreg.inc.sync.aligned.u32 208;");
    const uint32_t e1 = launches + 1;
    cluster_wait();
    const uint32_t wg = warp >> 2;
    uint32_t rel = (threadIdx.x & 95) == 0 ? mapa(sm.empty(0), (threadIdx.x & 32) ? rank ^ 1 : rank) : 0;
    uint32_t dst = sm.slot(0) + (warp & 3) * 2048 + (threadIdx.x & 15) * 128 + ((((threadIdx.x >> 4) & 1) ^ (threadIdx.x & 7)) << 4);
    uint32_t t8 = sm.slot(0) + (warp & 3) * 2048 + (threadIdx.x & 7) * 128 + ((((threadIdx.x >> 3) & 3) ^ (threadIdx.x & 7)) << 4);
    rel = __shfl_sync(~0u, rel, threadIdx.x);
    dst = __shfl_sync(~0u, dst, threadIdx.x);
    t8 = __shfl_sync(~0u, t8, threadIdx.x);
    const uint32_t da0 = ((SMEM_BASE >> 4) | (1 << 16)) + wg * 512, dba = (255 << 16) + 1024 - wg * 512;
    uint32_t pend[64], todo = 0, pbar = 0, vbar = sm.vacant(0), ppar = 0, poff = 0, direct = 0;
    uint32_t s = 0, na = 0, nb = 0, ready = 0;
    auto release = [&](uint32_t st) { mbar_arrive_cl_if(rel, rel + (st & (NSTAGE - 1)) * 8); };
    auto flush = [&](bool vacant) {
      if (__all_sync(~0u, vacant)) {
        const uint32_t a = dst + poff;
        if (todo & 2) {
#pragma unroll
          for (int j = 0; j < 4; j++) stsm4(a ^ (j << 5), pend[4 * j], pend[4 * j + 1], pend[4 * j + 2], pend[4 * j + 3]);
          if (todo == 2) {
#pragma unroll
            for (int j = 0; j < 4; j++) stsm4((a ^ (j << 5)) + 8192, pend[16 + 4 * j], pend[17 + 4 * j], pend[18 + 4 * j], pend[19 + 4 * j]);
          }
        } else {
#pragma unroll
          for (int j = 0; j < 8; j++) stsm4((a ^ ((j & 3) << 5)) + (j >> 2) * 8192, pend[32 + 4 * j], pend[33 + 4 * j], pend[34 + 4 * j], pend[35 + 4 * j]);
        }
        mbar_arrive_warp(pbar);
        pbar += 16; vbar += 16; ppar = ~nb & 1;
        todo = todo == 2;
      }
    };
    uint32_t jw = jobs[0];
#pragma unroll
    for (int i = 0; i < 64; i++) pend[i] = 0;
    for (int ji = 0;; ji++) {
      const uint32_t cur = jw, nk = (jw >> 12) & 63, isQ = (jw & 3) == T_Q;
      jw = jobs[ji + 1];
      if (__builtin_expect((cur & JOB_C) || !ready, 0)) {
        for (uint32_t spins = 0; todo && ((cur & JOB_C) || !ready);) {
          if (direct && todo == 1) {
            vbar = sm.empty(s); ppar = par(s) ^ 1; poff = sm.stage(s) - sm.slot(0) + wg * SLOT;
          }
          flush(mbar_test(vbar, ppar));
          ready = __all_sync(~0u, mbar_test(sm.full(s), par(s)));
          if (++spins > SPIN_LIMIT) __trap();
        }
        if (cur & JOB_C) {
          if (nk == 0) break;
          TRC(ji, 16);
          constexpr uint32_t ONES = 0x3f803f80;
          const uint32_t lane = fresh_tid() & 31, g = ((cur >> 6) & 63) * 2 + rank;
          if (!(cur & JOB_X)) {
            float d[4] = {0.f, 0.f, 0.f, 0.f};
            sts32(sm.xchg() + 128 + lane * 4, ONES);
            fence_proxy_async_smem();
            bar_sync<9, 256>();
#pragma unroll 1
            for (int i = 0; i < 4; i++, s++) {
              mbar_wait(sm.full(s), par(s));
              if (!wg) sum_columns(d, da0 + (s & (NSTAGE - 1)) * (STAGE / 16), (SMEM_BASE + AUX_OFF + 1600 + 128) >> 4);
              release(s);
            }
            const float c = lane & 1 ? d[2] : d[0], c1 = __shfl_down_sync(~0u, c, 4);
            asm volatile("{\n.reg .pred p;\nsetp.eq.u32 p, %2, 0;\n@p st.relaxed.gpu.global.u64 [%0], %1;\n}"
                         ::"l"(SCR(sm, cs, (16 * 128 + g * 32 + (warp & 3) * 8 + (lane & 1) * 4 + (lane >> 3)) * 8)), "l"(((u64)e1 << 32) | pack_bf16(c, c1)), "r"((lane & 6) | wg) : "memory");
          } else {
            float a[6][4];
#pragma unroll
            for (int n = 0; n < 24; n++) pend[n] = 0;
#pragma unroll 1
            for (int i = 0;; i++) {
              const uint32_t p = dst - sm.slot(0) + sm.stage(s) + wg * SLOT;
              mbar_wait(sm.full(s), par(s));
              uint32_t v[8][4];
#pragma unroll
              for (int n = 0; n < 24; n++) a[n / 4][n % 4] = __uint_as_float(pend[n]);
#pragma unroll
              for (int j = 0; j < 8; j++) ldsm4((p ^ ((j & 3) << 5)) + (j >> 2) * 8192, v[j]);
#pragma unroll
              for (int j = 0; j < 8; j++) {
                mma16816(a[4 + (j & 1)], v[j][0], v[j][1], v[j][2], v[j][3], ONES, ONES);
#pragma unroll
                for (int n = 0; n < 4; n++) mma1688(a[n], v[j][n & 2], v[j][(n & 2) + 1], v[j][n]);
              }
#pragma unroll
              for (int n = 0; n < 24; n++) pend[n] = __float_as_uint(a[n / 4][n % 4]);
              if (i == 3) break;
              bar_sync<9, 256>();
              release(s++);
            }
            const uint32_t part = sm.stage(s) + 2 * SLOT + lane * 8, row = g * 64 + (warp & 3) * 16 + wg * 8 + (lane >> 2);
            const bool odd = lane & 4;
            const float s0 = a[4][0] + a[5][0], q0 = odd ? a[0][1] + a[2][1] : a[0][0] + a[2][0];
            const float s1 = a[4][2] + a[5][2], q1 = odd ? a[1][3] + a[3][3] : a[1][2] + a[3][2];
            sts64(part + warp * 256, make_uint2(__float_as_uint(wg ? s0 : s1), __float_as_uint(wg ? q0 : q1)));
            bar_sync<9, 256>();
            const uint2 o = lds64(part + (warp ^ 4) * 256);
            fence_proxy_async_smem();
            bar_sync<9, 256>();
            release(s++);
            publish_stats(sm, (wg ? s1 : s0) + __uint_as_float(o.x), (wg ? q1 : q0) + __uint_as_float(o.y), (row & 1) * (S / 2) + (row >> 1), (lane & 3) == lane >> 3, e1);
          }
          ready = 0;
          TRC(ji, 18);
          continue;
        }
        if (!ready) mbar_wait(sm.full(s), par(s));
      }
      auto mainloop = [&](auto& acc, uint32_t nk, uint32_t last_lead, auto near_end) {
        const uint32_t lead = (jw >> 12) % 64 == 0 ? min(last_lead, nk - 2) : 2, turn = wg ? lead : nk - 2, hurry = nk - lead - wg;
        uint32_t owed = 0;
        uint32_t da = da0 + (s & (NSTAGE - 1)) * (STAGE / 16);
        if (todo == 3) mbar_wait(vbar, ppar);
        if (wg) bar_sync<13, 256>();
        TRC(ji, 16);
        first_kstep(acc, da, da + dba);
        if (!wg) bar_arrive<13, 256>();
        constexpr uint32_t CLEAR = sizeof(acc) == 96 * 4 ? PREP + 2 : 3;
        for (uint32_t left = nk - 1;; left--) {
          for (uint32_t spins = 0;; spins++) {
            const bool vacant = mbar_test(vbar, ppar), next_full = mbar_test(sm.full(s + 1), par(s + 1));
            wg_wait<2>();
            mbar_arrive_cl_if(owed, owed + ((s - 1) & (NSTAGE - 1)) * 8);
            owed = 0;
            ready = __all_sync(~0u, next_full);
            if (!todo) {
              near_end(left, vacant);
              break;
            }
            const bool go = ready && left >= max(CLEAR, lead + 1);
            if (!(go && spins)) flush(vacant);
            if (go) break;
            if (spins > SPIN_LIMIT) __trap();
          }
          if (left == 0) break;
          if (!ready) mbar_wait(sm.full(s + 1), par(s + 1));
          owed = rel;
          if (left == turn) {
            wg_wait<0>();
            release(s);
            owed = 0;
            if (wg) bar_sync<1, 256>();
          }
          if (left - lead < hurry) wg_wait<1>();
          s++;
          da = da0 + (s & (NSTAGE - 1)) * (STAGE / 16);
          kstep(acc, da, da + dba);
          if (left == 1 + wg * 64) bar_arrive<1, 256>();
        }
      };
      if (isQ) {
        float acc[96];
        const uint32_t lane = (((dst - SMEM_BASE) >> 7) & 15) | ((dst ^ (dst >> 3)) & 16), qpar = (na ^ nb) & 1;
        uint32_t prepare_at = PREP;
        mainloop(acc, nk, LAST_LEAD, [&](uint32_t left, bool aux_full) {
          if (left == PREP + 1) {
            vbar = sm.aux_full(); ppar = qpar;
          } else if (left == prepare_at) {
            if (left == 0) mbar_wait(vbar, ppar);
            if (left == 0 || __all_sync(~0u, aux_full)) attention_prepare(pend, sm, warp, lane, !(cur & 0x38));
            else prepare_at--;
          }
        });
        wg_wait<0>();
        release(s);
        u64 token = 0;
        asm volatile("{\n.reg .pred p;\nsetp.eq.u32 p, %2, 0;\n@p mbarrier.arrive.shared::cta.b64 %0, [%1];\n}" : "+l"(token) : "r"(sm.wgmma_done()), "r"(lane + 1 - wg) : "memory");
        pend[A_NM + 1] |= (uint32_t)token & pend[A_ZERO];
        TRC(ji, 18);
        ready = __all_sync(~0u, attention(acc, pend, sm, warp, lane, t8, dst, cur & JOB_EARLY, (((cur >> 2) & 1) * 16 + ((cur >> 3) & 7) * 2 + rank) * 16 + ((cur >> 6) & 15), e1, qpar,
                                          sm.full(s + 1), par(s + 1), ji));
        todo = 3; pbar = sm.filled(wg); vbar = sm.mma_done(); ppar = qpar; poff = SLOT + wg * 8192;
      } else {
        float acc[128];
        direct = (cur & 1) && (jw >> 12) % 64 == 0;
        const bool split = direct && nk >= SPLIT_MIN;
        mainloop(acc, split ? nk - 4 : nk, split ? 0 : LAST_LEAD, [](uint32_t, bool) {});
        pbar = sm.filled(wg); vbar = pbar + 32; ppar = na & 1; poff = wg * SLOT;
        nb++;
        todo = 2;
        if (__builtin_expect(split, 0)) {
          const uint32_t s0 = s;
          uint32_t d[4];
#pragma unroll
          for (int i = 0; i < 4; i++) d[i] = da0 + ((s0 + 1 + i) & (NSTAGE - 1)) * (STAGE / 16);
          wg_wait<0>();
          release(s0);
          float lo[64], hi[64];
#pragma unroll
          for (int i = 0; i < 64; i++) {
            asm volatile("mov.b32 %0, %1;" : "=f"(lo[i]) : "f"(acc[i]));
            asm volatile("mov.b32 %0, %1;" : "=f"(hi[i]) : "f"(acc[64 + i]));
          }
          if (wg) {
            bar_sync<1, 256>();
            bar_sync<3, 256>();
          }
#pragma unroll
          for (int i = 0; i < 3; i++) {
            mbar_wait(sm.full(s0 + 1 + i), par(s0 + 1 + i));
            half_kstep0(lo, d[i], d[i] + dba);
          }
          half_kstep1(hi, d[0], d[0] + dba);
          half_kstep1(hi, d[1], d[1] + dba);
          mbar_wait(sm.full(s0 + 4), par(s0 + 4));
          half_kstep0(lo, d[3], d[3] + dba);
          half_kstep1(hi, d[2], d[2] + dba);
          half_kstep1(hi, d[3], d[3] + dba);
          if (!wg) bar_arrive<3, 256>();
          s += 4;
          wg_wait<2>();
#pragma unroll
          for (int i = 0; i < 32; i++) pend[i] = pack_bf16(lo[2 * i], lo[2 * i + 1]);
          pbar = sm.filled(2 * wg); vbar = pbar + 32; poff = 0;
          if (wg) ppar = ~nb & 1;
          mbar_wait(vbar, ppar);
          const uint32_t parity = ppar;
          flush(true);
          pbar = sm.filled(2 * wg + 1); vbar = pbar + 32; poff = SLOT; ppar = parity;
          direct = 0;
          wg_wait<0>();
          TRC(ji, 18);
#pragma unroll
          for (int i = 0; i < 32; i++) pend[32 + i] = pack_bf16(hi[2 * i], hi[2 * i + 1]);
        } else {
          wg_wait<0>();
          release(s);
          const bool next_full = mbar_test(sm.full(s + 1), par(s + 1));
          TRC(ji, 18);
#pragma unroll
          for (int i = 0; i < 64; i++) {
            const int j = (i & 15) + (i & 16) * 2 + (i >> 5) * 16;
            pend[i] = pack_bf16(acc[2 * j], acc[2 * j + 1]);
          }
          ready = __all_sync(~0u, next_full);
        }
      }
      na++;
      s++;
    }
  } else {
    asm volatile("setmaxnreg.dec.sync.aligned.u32 88;");
    if (warp == 10) {
      producer(P, sm, jobs, P.kseq[pair], rank, threadIdx.x & 31, launches);
    } else {
      const uint32_t e1 = __shfl_sync(~0u, launches, 0) + 1;
      const int w = min(warp - 8, 2);
      cluster_wait();
      if (w == 1) asm volatile("st.shared::cluster.u32 [%0], %1;" ::"r"(mapa(sm.pair_id(), rank ^ 1)), "r"(pair) : "memory");
      const uint32_t boot = jobs[JMAX - 1] >> 24, pieces = (boot & 127) == 127 ? 0 : 1 + (boot >> 7), piece0 = (boot & 127) * 2 + rank * pieces;
      auto copy_rows = [&](uint32_t step, uint32_t n) {
        constexpr int IN = 2 * SLOT / BOOT_PIECES, OUT = 2 * SLOT / BOOT_OUT;
        const uint32_t rows = (piece0 + n) * 32768;
        if (step == BOOT_STEP) mbar_wait(sm.boot(), n & 1);
        if (elect()) {
          if (step == 0) mbar_expect_tx(sm.boot(), pieces ? 2 * SLOT : 0);
          if (step < BOOT_PIECES && pieces)
            asm volatile("cp.async.bulk.shared::cluster.global.mbarrier::complete_tx::bytes [%0], [%1], %2, [%3];"
                         ::"r"(sm.slot(0) + step * IN), "l"(at(P.x0, rows + step * IN)), "n"(IN), "r"(sm.boot()) : "memory");
          if (step - BOOT_STEP < BOOT_OUT && pieces) {
            asm volatile("cp.async.bulk.global.shared::cta.bulk_group [%0], [%1], %2;"
                         ::"l"(at(P.out, rows + (step - BOOT_STEP) * OUT)), "r"(sm.slot(0) + (step - BOOT_STEP) * OUT), "n"(OUT) : "memory");
            bulk_commit();
          }
        }
        if (step == BOOT_STEP + BOOT_OUT) {
          bulk_wait();
          if (n + 1 >= pieces && elect()) {
            mbar_arrive_n(sm.vacant(0), 3);
            mbar_arrive_n(sm.vacant(1), 3);
          }
        }
      };
      if (jobs[0] & JOB_C) {
        if (w == 2) {
          if (jobs[0] & JOB_X) mbar_wait(sm.full(3), 0);
#pragma unroll 1
          for (uint32_t n = 0; n == 0 || n < pieces; n++) {
#pragma unroll 1
            for (int i = 0; i <= BOOT_STEP + BOOT_OUT; i++) {
              copy_rows(i, n);
              bulk_wait_read<0>();
            }
          }
        }
      } else {
        const int lane = threadIdx.x & 31, word = (lane >> 3) * 24 + w * 8 + (lane & 7);
        Stager st;
        const uint32_t cs = qkv_col_sums(sm, rank, w, lane, [&](int s) {
          if (w == 2) copy_rows(s - 1, 0);
          if (w == 0 && s == ST_STEP) st.load(sm, Job(jobs[0]), rank, lane, false);
          if (w == 0 && s == ST_STEP + 2) st.store(sm, Job(jobs[0]), rank, lane, false, e1);
        });
        sts32(sm.sums() + word * 4, cs);
        mbar_arrive_warp(sm.aux_full());
        if ((jobs[0] & 0x38) == 0 && rank == 0) st_word(SCR(sm, cs, (((jobs[0] >> 6) & 15) * 128 + word) * 8), cs, e1);
      }
      bar_sync<2, 96>();
      if (w == 2 && pieces && elect()) {
        red_release(counter(C_RD + (piece0 >> 4) * 2, 0), pieces);
        red_relaxed(counter(C_RD + (piece0 >> 4) * 2 + 1, 0), pieces);
      }
      uint32_t na = 0, nb = 0, stages = 0;
      for (int ji = 0;; ji++) {
        const uint32_t jw = jobs[ji];
        const Job J(jw);
        if (J.nk == 0) break;
        stages += J.nk;
        if (w != 0 && ((jw >> 22) & 3) != 3) {
          stats_task(sm, jw, rank, w, e1, P.out);
          TRI(threadIdx.x == 11 * 32, ji, 10);
        }
        if (jw & JOB_C) continue;
        const int lane = fresh_tid() & 31;
        const uint32_t b = J.R * 2 + rank;
        if (w == 0 && !(J.type & 1) && ji != 0) {
          Stager st;
          st.load(sm, J, rank, lane, true);
          st.store(sm, J, rank, lane, true, e1);
          TRI(lane == 0, ji, 9);
        }
        if (J.type == T_G) {
          bar_sync<2, 96>();
          constexpr int PER = 16 / NG;
          const uint32_t swap = P.swap, never = jw, ac = sm.sums() + (lane & 7) * 16;
          uint32_t ag[NG], au[NG], as = sm.stats() + 64 + w * NG * 32 + (lane >> 3) * 8;
          uint32_t ho = (rank * (S / 2) + J.R * 128 + w * NG * 4 + (lane >> 3)) * (F * 2) + J.col * 256 + (lane & 7) * 16;
          uint4 cg = lds128(ac + (swap >> 5)), cu = lds128(ac + 256 - (swap >> 5)), g4[NG], u4[NG];
          uint2 st[NG];
          auto load = [&] {
#pragma unroll
            for (int i = 0; i < NG; i++) { st[i] = lds64v(as + i * 32); g4[i] = lds128v(ag[i]); u4[i] = lds128v(au[i]); }
          };
#pragma unroll
          for (int i = 0; i < NG; i++) {
            const uint32_t a = (sm.slot(0) + (w * NG + i) * 512 + (lane >> 3) * 128 + (((lane & 7) ^ (lane >> 3)) << 4)) ^ (((w * NG + i) & 1) << 6);
            ag[i] = a + swap; au[i] = a + (swap ^ 8192);
          }
          mbar_wait(sm.filled(0), na & 1);
          mbar_wait(sm.filled(1), na & 1);
          load();
          if (w == 2 && elect()) red_relaxed(counter(C_RD + J.inst() * 16 + b, 0), 1);
          TRI(threadIdx.x == 11 * 32, ji, 3);
#pragma unroll 1
          for (uint32_t g = w; g < 4 * PER; g += 3) {
            float hinv[NG], hinv2[NG];
            uint4 gc[NG], uc[NG];
            const bool turn = ((g + 3) ^ g) & PER, half = ((g + 3) ^ g) & (2 * PER);
#pragma unroll
            for (int i = 0; i < NG; i++) {
              hinv[i] = 0.5f * __uint_as_float(st[i].x);
              hinv2[i] = hinv[i] * __uint_as_float(st[i].x);
              asm volatile("" : "+f"(hinv[i]), "+f"(hinv2[i]));
              gc[i] = fma8(dup_hi(st[i].y), cg, g4[i]);
              uc[i] = fma8(dup_hi(st[i].y), cu, u4[i]);
              ag[i] = (ag[i] + NG * 1536) ^ ((NG & 1) << 6);
              au[i] = (au[i] + NG * 1536) ^ ((NG & 1) << 6);
            }
            as += NG * 96;
            if (turn) {
              mbar_arrive_warp(sm.vacant((g / PER) ^ 2));
              if (half) {
                cg = lds128(ac + (swap >> 5) + 128); cu = lds128(ac + 384 - (swap >> 5));
                as -= 1024;
              }
#pragma unroll
              for (int i = 0; i < NG; i++) { ag[i] += half ? -3 * 8192 : 8192; au[i] += half ? -3 * 8192 : 8192; }
              TRX(threadIdx.x == 11 * 32 && g < 3 * PER, ji, 25, 25 + g / PER * 2, "%%clock");
              if (g < 3 * PER) mbar_wait(sm.filled(g / PER + 1), (g < PER ? na : nb) & 1);
              TRX(threadIdx.x == 11 * 32 && g < 3 * PER, ji, 25, 26 + g / PER * 2, "%%clock");
            }
            load();
            if (g == never) mbar_wait(sm.boot(), 0);
            bf16* out = SCR(sm, h, ho);
#pragma unroll
            for (int i = 0; i < NG; i++)
              stg128(out + i * 4 * F, make_uint4(swiglu2(gc[i].x, uc[i].x, hinv[i], hinv2[i]), swiglu2(gc[i].y, uc[i].y, hinv[i], hinv2[i]),
                                                 swiglu2(gc[i].z, uc[i].z, hinv[i], hinv2[i]), swiglu2(gc[i].w, uc[i].w, hinv[i], hinv2[i])));
            ho += NG * 12 * F * 2 - (half ? 128 * F * 2 - 128 : 0);
          }
          bar_sync<2, 96>();
          TRI(threadIdx.x == 11 * 32, ji, 4);
          if (w == 2 && elect()) red_release(counter(C_H + J.layer * 16 + b, J.col), 1);
          TRI(threadIdx.x == 11 * 32, ji, 5);
        } else if (J.type == T_Q) {
          const bool late = J.R > 0 && !(jw & JOB_EARLY);
          if (w == 0) {
            __syncwarp();
            if (ji != 0 && elect()) mbar_arrive_n(sm.aux_full(), 3);
#pragma unroll 1
            for (int phase = 0; phase < 2; phase++) {
              if (J.R > 0 && phase == late) import_halo(sm, SCR(sm, halo, (((J.layer * 16 + b - 2) * 16 + J.col) * 256 + lane) * 16), e1, lane);
              if (phase == 0) {
                mbar_arrive_warp(sm.kv_ready(-1));
                TRI(lane == 0, ji, 11);
#pragma unroll 1
                for (int h = 0; h < 2; h++) {
                  mbar_wait(sm.filled(h), na & 1);
                  TRI(lane == 0, ji, 3);
                  fence_proxy_async_smem();
                  bulk_wait_read<0>();
                  if (elect()) {
                    tma3d_store(&P.ow, J.col * 64, J.R * 128 + h * 64, rank, sm.slot(1) + h * 8192);
                    bulk_commit();
                  }
                }
                if (J.layer && elect()) red_relaxed(counter(C_RD + 32 + b, 0), 1);
              }
            }
            bulk_wait();
          }
          if (late && w < 2) {
            bar_sync<7, 64>();
            boundary_rows(sm, w, lane, rank * O_PLANE + J.R * 128 * (D * 2) + J.col * 128);
            bar_sync<7, 64>();
          }
          TRI(threadIdx.x == 256, ji, 4);
          if (w == 0 && elect()) {
            mbar_arrive_n(sm.vacant(0), 3);
            mbar_arrive_n(sm.vacant(1), 3);
            red_release(counter(C_O + J.layer * 16 + b, J.col), 1);
          }
          TRI(threadIdx.x == 256, ji, 5);
        } else if (w == 0) {
          wait_count(counter(C_RD + J.inst() * 16 + b, 0), e1 * (J.type == T_D ? 28 : 16));
          fence_proxy_async();
          const bool last = Job(jobs[ji + 1]).nk == 0, split = last && J.nk >= SPLIT_MIN;
#pragma unroll 1
          for (uint32_t v = 0; v < 4; v++) {
            const uint32_t u = last && !split ? (v >> 1) + (v & 1) * 2 : v;
            mbar_wait(sm.filled(u), (u & 2 ? nb : na) & 1);
            TRI(u == 0 && lane == 0, ji, 3);
            fence_proxy_async_smem();
            const uint32_t src = (last && !split && (u & 2) ? sm.stage(stages) : sm.slot(0)) + (u & 1) * SLOT;
#pragma unroll 1
            for (uint32_t p = 0; p < 16384 / PIECE; p++) {
              if (elect()) {
                tma3d_reduce_add(&P.xr, J.col * 256 + (split ? (u & 1) * 128 + p * PIECE / 8192 * 64 : (u & 2) * 32 + p * PIECE / 8192 * 128),
                                 J.R * 128 + (split ? u >> 1 : u & 1) * 64 + p * PIECE % 8192 / 128, rank, src + p * PIECE);
                bulk_commit();
              }
              if (!last) bulk_wait_read<DEPTH - 1>();
            }
            if (!last) {
              bulk_wait();
              if (elect()) mbar_arrive_n(sm.vacant(u ^ 2), 3);
            } else if (split && (v == 1 || v == 2)) {
              bulk_wait_read<16384 / PIECE>();
              if (elect()) mbar_arrive_n(sm.vacant(v + 1), 3);
            }
            if (u == 1 && J.inst() != 3) bar_arrive<8, 64>();
          }
          bulk_wait();
        }
        if ((J.type & 1) && J.inst() != 3 && w < 2) {
          if (w == 1) bar_sync<8, 64>();
          TRX(lane == 0, ji, 4, w ? 12 : 4, "%%globaltimer_lo");
          if (elect()) red_release(counter(C_X + J.inst() * 16 + b, J.col * 2 + 1 - w), J.nk);
          TRX(lane == 0, ji, 5, w ? 13 : 5, "%%globaltimer_lo");
          if (w == 1) bar_arrive<10, 64>(); else bar_sync<10, 64>();
        }
        na++;
        nb += J.type != T_Q;
      }
      TRI(threadIdx.x == 8 * 32, JMAX - 1, 6);
      TRK(threadIdx.x == 8 * 32, JMAX - 1, 24);
      if (w == 0 && elect()) red_relaxed(counter(C_EP, blockIdx.x), 1);
      if (w == 2 && __float_as_uint(lds32f(sm.pair_id())) != pair) __trap();
    }
  }
  cluster_arrive();
  cluster_wait();
}

typedef CUresult (*EncodeFn)(CUtensorMap*, CUtensorMapDataType, cuuint32_t, void*, const cuuint64_t*, const cuuint64_t*, const cuuint32_t*,
                             const cuuint32_t*, CUtensorMapInterleave, CUtensorMapSwizzle, CUtensorMapL2promotion, CUtensorMapFloatOOBfill);
struct Dim { cuuint64_t size, stride; cuuint32_t box; };
template <int N> void encode(EncodeFn fn, CUtensorMap* m, const void* ptr, const Dim (&d)[N]) {
  cuuint64_t dims[N], strides[N];
  cuuint32_t box[N], es[N];
  for (int i = 0; i < N; i++) { dims[i] = d[i].size; strides[i] = d[i].stride; box[i] = d[i].box; es[i] = 1; }
  fn(m, CU_TENSOR_MAP_DATA_TYPE_BFLOAT16, N, const_cast<void*>(ptr), dims, strides + 1, box, es, CU_TENSOR_MAP_INTERLEAVE_NONE,
     CU_TENSOR_MAP_SWIZZLE_128B, CU_TENSOR_MAP_L2_PROMOTION_L2_128B, CU_TENSOR_MAP_FLOAT_OOB_FILL_NONE);
}

}

extern "C" void kernel_launch(void* const* d_in, const int* in_sizes, int n_in, void* d_out, int out_size) {
  (void)in_sizes; (void)n_in; (void)out_size;
  static EncodeFn fn = nullptr;
  static Scratch* scr;
  static int sms;
  if (!fn) {
    void* p = nullptr;
    cudaDriverEntryPointQueryResult q;
    cudaGetDriverEntryPoint("cuTensorMapEncodeTiled", &p, cudaEnableDefault, &q);
    fn = (EncodeFn)p;
    scr = scratch_base();
    int device = 0;
    cudaGetDevice(&device);
    cudaDeviceGetAttribute(&sms, cudaDevAttrMultiProcessorCount, device);
    cudaFuncSetAttribute(mega_kernel, cudaFuncAttributeMaxDynamicSharedMemorySize, SMEM_BYTES);
  }
  static Params P;
  const char *wg = (const char*)d_in[4], *wu = (const char*)d_in[5], *w0 = wg < wu ? wg : wu;
  const cuuint64_t plane = wg < wu ? wu - wg : wg - wu;
  P.swap = wg < wu ? 0 : 8192;
  encode(fn, &P.a[0], d_in[0], {{D, 2, 64}, {S / 2, D * 4, 128}, {2, D * 2, 1}});
  encode(fn, &P.a[1], scr->o, {{D, 2, 64}, {S / 2, D * 2, 128}, {2, O_PLANE, 1}});
  encode(fn, &P.ow, scr->o, {{D, 2, 64}, {S / 2, D * 2, 64}, {2, O_PLANE, 1}});
  encode(fn, &P.a[2], d_out, {{D, 2, 64}, {S / 2, D * 4, 128}, {2, D * 2, 1}});
  encode(fn, &P.a[3], scr->h, {{F, 2, 64}, {S / 2, F * 2, 128}, {2, (cuuint64_t)F * S, 1}});
  encode(fn, &P.a[4], w0, {{F, 2, 64}, {D, F * 2, 256}, {2, plane, 1}});
  encode(fn, &P.a[5], d_in[0], {{64, 2, 64}, {S, D * 2, 64}, {16, 128, 4}});
  encode(fn, &P.w[T_Q], d_in[1], {{64, 2, 64}, {D, 3 * D * 2, 32}, {16, 128, 1}, {3, D * 2, 3}});
  encode(fn, &P.w[T_O], d_in[2], {{64, 2, 64}, {D, D * 2, 32}, {16, 128, 4}, {1, (cuuint64_t)D * D * 2, 1}});
  encode(fn, &P.w[T_G], w0, {{64, 2, 64}, {D, F * 2, 32}, {F / 64, 128, 2}, {2, plane, 2}});
  encode(fn, &P.w[T_D], d_in[6], {{64, 2, 64}, {F, D * 2, 32}, {16, 128, 4}, {1, (cuuint64_t)F * D * 2, 1}});
  encode(fn, &P.xr, d_out, {{D, 2, 64}, {S / 2, D * 4, PIECE / 128}, {2, D * 2, 1}});
  memcpy(P.jobs, kJobs, sizeof(kJobs));
  memcpy(P.kseq, kSeq, sizeof(kSeq));
  P.x0 = (const bf16*)d_in[0];
  P.wqkv = (const bf16*)d_in[1];
  P.out = (bf16*)d_out;
  mega_kernel<<<2 * NPAIR, 384, SMEM_BYTES>>>((char*)scr, sms == 2 * NPAIR, P);
}
```
